```python
import torch

def _softmax(x, axis=-1):
    return torch.softmax(x, dim=axis)
def _gelu(x):
    return torch.nn.functional.gelu(x, approximate="tanh")
def _silu(x):
    return torch.nn.functional.silu(x)
def _sigmoid(x):
    return torch.sigmoid(x)
def _layernorm(x, axis=-1, eps=1e-5):
    m = x.mean(dim=axis, keepdim=True)
    v = x.var(dim=axis, keepdim=True, unbiased=False)
    return (x - m) / torch.sqrt(v + eps)
def _scatter_add(tgt, idx, src, axis=0):
    return tgt.clone().index_add_(axis, idx, src)
def _segment_sum(src, seg, n):
    out = torch.zeros((n,) + src.shape[1:], dtype=src.dtype)
    return out.index_add_(0, seg, src)
def _pad(x, pw):
    flat = tuple(v for pair in reversed(pw) for v in pair)
    return torch.nn.functional.pad(x, flat)

kernel_name = 'concat_heads__grouped_kv_mqa__linear_attn_block__prompt'

def setup_inputs():

    _w = (lambda a: (lambda t: t.to(torch.bfloat16) if t.is_floating_point() else t)(torch.as_tensor(a)))
    def _A_setup():
        B, S, D, H = 1, 2048, 512, 32
        Dh = D // H
        return {
            "x": _w((lambda *s: torch.randn(*s, dtype=torch.bfloat16) * 0.05)(B, S, D)),
            "wq": _w((lambda *s: torch.randn(*s, dtype=torch.bfloat16) * 1.6)(D, H * Dh)),
            "wk": _w((lambda *s: torch.randn(*s, dtype=torch.bfloat16) * 1.6)(D, Dh)),
            "wv": _w((lambda *s: torch.randn(*s, dtype=torch.bfloat16) * 0.05)(D, Dh)),
            "wo": _w((lambda *s: torch.randn(*s, dtype=torch.bfloat16) * 0.05)(H * Dh, D)),
        }
    _A_in = _A_setup()

    def _B_setup():
        B, S, D = 1, 2048, 512
        return {
            "x": _w((lambda *s: torch.randn(*s, dtype=torch.bfloat16) * 0.05)(B, S, D)),
            "wqkv": _w((lambda *s: torch.randn(*s, dtype=torch.bfloat16) * 0.8)(D, 3 * D)),
            "wo": _w((lambda *s: torch.randn(*s, dtype=torch.bfloat16) * 0.05)(D, D)),
        }
    _B_in = _B_setup()

    return {
        "A_x": _A_in["x"],
        "A_wq": _A_in["wq"],
        "A_wk": _A_in["wk"],
        "A_wv": _A_in["wv"],
        "A_wo": _A_in["wo"],
        "B_x": _B_in["x"],
        "B_wqkv": _B_in["wqkv"],
        "B_wo": _B_in["wo"],
    }

def reference(A_x, A_wq, A_wk, A_wv, A_wo, B_x, B_wqkv, B_wo):
    def _A_ref(x, wq, wk, wv, wo):
        B, S, D = x.shape
        H = 32
        Dh = D // H
        q = (lambda x, *d: x.permute(*d))((x @ wq).reshape(B, S, H, Dh), 0, 2, 1, 3)
        k = x @ wk
        v = x @ wv
        scores = torch.einsum("bhqd,bkd->bhqk", q, k) * (Dh ** -0.5)
        p = _softmax(scores, axis=-1)
        o = torch.einsum("bhqk,bkd->bhqd", p, v)
        return (lambda x, *d: x.permute(*d))(o, 0, 2, 1, 3).reshape(B, S, H * Dh) @ wo

    def _B_ref(x, wqkv, wo):
        B, S, D = x.shape
        H = 32; Dh = D // H
        qkv = (lambda x, *d: x.permute(*d))((x @ wqkv).reshape(B, S, 3, H, Dh), 2, 0, 3, 1, 4)
        q, k, v = qkv[0], qkv[1], qkv[2]
        phi = lambda t: torch.where(t > 0, t + 1, torch.exp(t)) + 1e-6
        pq, pk = phi(q), phi(k)
        kv = torch.einsum("bhsd,bhse->bhde", pk, v)
        z = torch.einsum("bhsd->bhd", pk)
        num = torch.einsum("bhqd,bhde->bhqe", pq, kv)
        den = torch.einsum("bhqd,bhd->bhq", pq, z)[..., None] + 1e-6
        o = num / den
        return (lambda x, *d: x.permute(*d))(o, 0, 2, 1, 3).reshape(B, S, D) @ wo

    a = _A_ref(A_x, A_wq, A_wk, A_wv, A_wo)
    b = _B_ref(B_x, B_wqkv, B_wo)
    return torch.concatenate([a, b], axis=-1)
```

```cpp
#include <cuda_runtime.h>
#include <cuda_bf16.h>
#include <cuda_fp16.h>
#include <cuda.h>
#include <stdint.h>

#define S_TOK 2048
#define D_MOD 512

__device__ __align__(1024) __nv_bfloat16 g_Q[2 * S_TOK * D_MOD];
__device__ __align__(1024) __nv_bfloat16 g_O[2 * S_TOK * D_MOD];
__device__ __align__(1024) uint4 g_KV[6 * S_TOK];
__device__ float g_stats[16 * 2];
__device__ __align__(16) float4 g_kvp[16 * 32 * 3 * 32];

__device__ __forceinline__ uint32_t smem_u32(const void* p) { return (uint32_t)__cvta_generic_to_shared(p); }
__device__ __forceinline__ void mbar_init(uint32_t bar, int cnt) { asm volatile("mbarrier.init.shared::cta.b64 [%0], %1;" :: "r"(bar), "r"(cnt) : "memory"); }
__device__ __forceinline__ void mbar_expect_tx(uint32_t bar, uint32_t bytes) { asm volatile("mbarrier.arrive.expect_tx.shared::cta.b64 _, [%0], %1;" :: "r"(bar), "r"(bytes) : "memory"); }
__device__ __forceinline__ bool mbar_try(uint32_t bar, uint32_t parity) {
  uint32_t ok;
  asm volatile("{\n.reg .pred p;\nmbarrier.try_wait.parity.shared::cta.b64 p, [%1], %2;\nselp.b32 %0, 1, 0, p;\n}\n" : "=r"(ok) : "r"(bar), "r"(parity) : "memory");
  return ok;
}
__device__ __forceinline__ void mbar_wait(uint32_t bar, uint32_t parity) {
  asm volatile("{\n.reg .pred p;\n.reg .u32 c;\nmov.u32 c, 0;\n"
               "LW_%=:\n"
               "mbarrier.try_wait.parity.shared::cta.b64 p, [%0], %1;\n"
               "@p bra LD_%=;\n"
               "add.u32 c, c, 1;\n"
               "setp.lt.u32 p, c, 4000000;\n"
               "@p bra LW_%=;\n"
               "trap;\n"
               "LD_%=:\n}\n" :: "r"(bar), "r"(parity) : "memory");
}
__device__ __forceinline__ void mbar_wait_cluster(uint32_t bar, uint32_t parity) {
  asm volatile("{\n.reg .pred p;\n.reg .u32 c;\nmov.u32 c, 0;\n"
               "LW_%=:\n"
               "mbarrier.try_wait.parity.acquire.cluster.shared::cta.b64 p, [%0], %1;\n"
               "@p bra LD_%=;\n"
               "add.u32 c, c, 1;\n"
               "setp.lt.u32 p, c, 4000000;\n"
               "@p bra LW_%=;\n"
               "trap;\n"
               "LD_%=:\n}\n" :: "r"(bar), "r"(parity) : "memory");
}
__device__ __forceinline__ void mbar_arrive_cta(uint32_t bar, uint32_t cta) {
  asm volatile("{\n.reg .b32 ra;\nmapa.shared::cluster.u32 ra, %0, %1;\nmbarrier.arrive.release.cluster.shared::cluster.b64 _, [ra];\n}\n" :: "r"(bar), "r"(cta) : "memory");
}
__device__ __forceinline__ void cluster_sync() {
  asm volatile("barrier.cluster.arrive.release.aligned;\nbarrier.cluster.wait.acquire.aligned;" ::: "memory");
}
__device__ __forceinline__ void tma2d(uint32_t dst, const CUtensorMap* m, int c0, int c1, uint32_t bar) {
  asm volatile("cp.async.bulk.tensor.2d.shared::cluster.global.mbarrier::complete_tx::bytes [%0], [%1, {%3, %4}], [%2];"
               :: "r"(dst), "l"(m), "r"(bar), "r"(c0), "r"(c1) : "memory");
}
__device__ __forceinline__ void tma2d_mc(uint32_t dst, const CUtensorMap* m, int c0, int c1, uint32_t bar, uint16_t mask) {
  asm volatile("cp.async.bulk.tensor.2d.shared::cluster.global.mbarrier::complete_tx::bytes.multicast::cluster [%0], [%1, {%3, %4}], [%2], %5;"
               :: "r"(dst), "l"(m), "r"(bar), "r"(c0), "r"(c1), "h"(mask) : "memory");
}
__device__ __forceinline__ void tma2d_store(const CUtensorMap* m, uint32_t src, int c0, int c1) {
  asm volatile("cp.async.bulk.tensor.2d.global.shared::cta.bulk_group [%0, {%2, %3}], [%1];"
               :: "l"(m), "r"(src), "r"(c0), "r"(c1) : "memory");
}
__device__ __forceinline__ void bulk_g2s(uint32_t dst, const void* src, uint32_t bytes, uint32_t bar) {
  asm volatile("cp.async.bulk.shared::cluster.global.mbarrier::complete_tx::bytes [%0], [%1], %2, [%3];"
               :: "r"(dst), "l"(src), "r"(bytes), "r"(bar) : "memory");
}
__device__ __forceinline__ void bulk_commit() { asm volatile("cp.async.bulk.commit_group;" ::: "memory"); }
__device__ __forceinline__ void bulk_wait_all() { asm volatile("cp.async.bulk.wait_group 0;" ::: "memory"); }
__device__ __forceinline__ void fence_async() { asm volatile("fence.proxy.async.shared::cta;" ::: "memory"); }
__device__ __forceinline__ void named_bar(int id, int n) { asm volatile("bar.sync %0, %1;" :: "r"(id), "r"(n) : "memory"); }
__device__ __forceinline__ void pdl_launch() { asm volatile("griddepcontrol.launch_dependents;" ::: "memory"); }
__device__ __forceinline__ void pdl_wait() { asm volatile("griddepcontrol.wait;" ::: "memory"); }
__device__ __forceinline__ void wg_fence() { asm volatile("wgmma.fence.sync.aligned;" ::: "memory"); }
__device__ __forceinline__ void wg_commit() { asm volatile("wgmma.commit_group.sync.aligned;" ::: "memory"); }
template <int n> __device__ __forceinline__ void wg_wait() { asm volatile("wgmma.wait_group.sync.aligned %0;" :: "n"(n) : "memory"); }
template <int n> __device__ __forceinline__ void fence_regs(float* r) {
#pragma unroll
  for (int i = 0; i < n; i++) asm volatile("" : "+f"(r[i]) :: "memory");
}
template <int n> __device__ __forceinline__ void fence_regs(uint32_t* r) {
#pragma unroll
  for (int i = 0; i < n; i++) asm volatile("" : "+r"(r[i]) :: "memory");
}
__device__ __forceinline__ uint64_t make_desc(uint32_t addr, uint32_t lbo, uint32_t sbo, uint32_t swz) {
  return (uint64_t)((addr & 0x3FFFF) >> 4) | ((uint64_t)(lbo >> 4) << 16) | ((uint64_t)(sbo >> 4) << 32) | ((uint64_t)swz << 62);
}
__device__ __forceinline__ float ex2f(float x) { float y; asm("ex2.approx.ftz.f32 %0, %1;" : "=f"(y) : "f"(x)); return y; }
__device__ __forceinline__ uint32_t pack_bf16(float lo, float hi) { uint32_t r; asm("cvt.rn.bf16x2.f32 %0, %1, %2;" : "=r"(r) : "f"(hi), "f"(lo)); return r; }
__device__ __forceinline__ uint32_t pack_f16(float lo, float hi) { uint32_t r; asm("cvt.rn.f16x2.f32 %0, %1, %2;" : "=r"(r) : "f"(hi), "f"(lo)); return r; }
__device__ __forceinline__ float bf_lo(uint32_t v) { return __uint_as_float(v << 16); }
__device__ __forceinline__ float bf_hi(uint32_t v) { return __uint_as_float(v & 0xFFFF0000u); }
__device__ __forceinline__ float rbf(float x) { return __bfloat162float(__float2bfloat16_rn(x)); }
__device__ __forceinline__ void stsm4(uint32_t a, uint32_t r0, uint32_t r1, uint32_t r2, uint32_t r3) {
  asm volatile("stmatrix.sync.aligned.m8n8.x4.shared.b16 [%0], {%1,%2,%3,%4};" :: "r"(a), "r"(r0), "r"(r1), "r"(r2), "r"(r3) : "memory");
}
__device__ __forceinline__ void stsm4t(uint32_t a, uint32_t r0, uint32_t r1, uint32_t r2, uint32_t r3) {
  asm volatile("stmatrix.sync.aligned.m8n8.x4.trans.shared.b16 [%0], {%1,%2,%3,%4};" :: "r"(a), "r"(r0), "r"(r1), "r"(r2), "r"(r3) : "memory");
}
__device__ __forceinline__ void mma_bf16(float* d, uint32_t a0, uint32_t a1, uint32_t a2, uint32_t a3, uint32_t b0, uint32_t b1) {
  asm volatile("mma.sync.aligned.m16n8k16.row.col.f32.bf16.bf16.f32 {%0,%1,%2,%3}, {%4,%5,%6,%7}, {%8,%9}, {%0,%1,%2,%3};"
               : "+f"(d[0]), "+f"(d[1]), "+f"(d[2]), "+f"(d[3]) : "r"(a0), "r"(a1), "r"(a2), "r"(a3), "r"(b0), "r"(b1));
}
template<int SD> __device__ __forceinline__ void wg_qk32(float* d, const uint32_t* a, uint64_t desc) {
  asm volatile("wgmma.mma_async.sync.aligned.m64n32k16.f32.f16.f16 {%0,%1,%2,%3,%4,%5,%6,%7,%8,%9,%10,%11,%12,%13,%14,%15}, {%16,%17,%18,%19}, %20, %21, 1, 1, 0;"
   : "+f"(d[0]),"+f"(d[1]),"+f"(d[2]),"+f"(d[3]),"+f"(d[4]),"+f"(d[5]),"+f"(d[6]),"+f"(d[7]),"+f"(d[8]),"+f"(d[9]),"+f"(d[10]),"+f"(d[11]),"+f"(d[12]),"+f"(d[13]),"+f"(d[14]),"+f"(d[15])
   : "r"(a[0]),"r"(a[1]),"r"(a[2]),"r"(a[3]),"l"(desc),"n"(SD));
}
template<int SD> __device__ __forceinline__ void wg_qk64(float* d, const uint32_t* a, uint64_t desc) {
  asm volatile("wgmma.mma_async.sync.aligned.m64n64k16.f32.f16.f16 {%0,%1,%2,%3,%4,%5,%6,%7,%8,%9,%10,%11,%12,%13,%14,%15,%16,%17,%18,%19,%20,%21,%22,%23,%24,%25,%26,%27,%28,%29,%30,%31}, {%32,%33,%34,%35}, %36, %37, 1, 1, 0;"
   : "+f"(d[0]),"+f"(d[1]),"+f"(d[2]),"+f"(d[3]),"+f"(d[4]),"+f"(d[5]),"+f"(d[6]),"+f"(d[7]),"+f"(d[8]),"+f"(d[9]),"+f"(d[10]),"+f"(d[11]),"+f"(d[12]),"+f"(d[13]),"+f"(d[14]),"+f"(d[15]),"+f"(d[16]),"+f"(d[17]),"+f"(d[18]),"+f"(d[19]),"+f"(d[20]),"+f"(d[21]),"+f"(d[22]),"+f"(d[23]),"+f"(d[24]),"+f"(d[25]),"+f"(d[26]),"+f"(d[27]),"+f"(d[28]),"+f"(d[29]),"+f"(d[30]),"+f"(d[31])
   : "r"(a[0]),"r"(a[1]),"r"(a[2]),"r"(a[3]),"l"(desc),"n"(SD));
}
template<int SD> __device__ __forceinline__ void wg_pv24(float* d, const uint32_t* a, uint64_t desc) {
  asm volatile("wgmma.mma_async.sync.aligned.m64n24k16.f32.bf16.bf16 {%0,%1,%2,%3,%4,%5,%6,%7,%8,%9,%10,%11}, {%12,%13,%14,%15}, %16, %17, 1, 1, 1;"
   : "+f"(d[0]),"+f"(d[1]),"+f"(d[2]),"+f"(d[3]),"+f"(d[4]),"+f"(d[5]),"+f"(d[6]),"+f"(d[7]),"+f"(d[8]),"+f"(d[9]),"+f"(d[10]),"+f"(d[11])
   : "r"(a[0]),"r"(a[1]),"r"(a[2]),"r"(a[3]),"l"(desc),"n"(SD));
}
template<int TA, int TB> __device__ __forceinline__ void wg_ss128(float* d, uint64_t da, uint64_t db, int sd) {
  asm volatile("{\n.reg .pred p;\nsetp.ne.b32 p, %66, 0;\n"
   "wgmma.mma_async.sync.aligned.m64n128k16.f32.bf16.bf16 {%0,%1,%2,%3,%4,%5,%6,%7,%8,%9,%10,%11,%12,%13,%14,%15,%16,%17,%18,%19,%20,%21,%22,%23,%24,%25,%26,%27,%28,%29,%30,%31,%32,%33,%34,%35,%36,%37,%38,%39,%40,%41,%42,%43,%44,%45,%46,%47,%48,%49,%50,%51,%52,%53,%54,%55,%56,%57,%58,%59,%60,%61,%62,%63}, %64, %65, p, 1, 1, %67, %68;\n}\n"
   : "+f"(d[0]),"+f"(d[1]),"+f"(d[2]),"+f"(d[3]),"+f"(d[4]),"+f"(d[5]),"+f"(d[6]),"+f"(d[7]),"+f"(d[8]),"+f"(d[9]),"+f"(d[10]),"+f"(d[11]),"+f"(d[12]),"+f"(d[13]),"+f"(d[14]),"+f"(d[15]),"+f"(d[16]),"+f"(d[17]),"+f"(d[18]),"+f"(d[19]),"+f"(d[20]),"+f"(d[21]),"+f"(d[22]),"+f"(d[23]),"+f"(d[24]),"+f"(d[25]),"+f"(d[26]),"+f"(d[27]),"+f"(d[28]),"+f"(d[29]),"+f"(d[30]),"+f"(d[31]),"+f"(d[32]),"+f"(d[33]),"+f"(d[34]),"+f"(d[35]),"+f"(d[36]),"+f"(d[37]),"+f"(d[38]),"+f"(d[39]),"+f"(d[40]),"+f"(d[41]),"+f"(d[42]),"+f"(d[43]),"+f"(d[44]),"+f"(d[45]),"+f"(d[46]),"+f"(d[47]),"+f"(d[48]),"+f"(d[49]),"+f"(d[50]),"+f"(d[51]),"+f"(d[52]),"+f"(d[53]),"+f"(d[54]),"+f"(d[55]),"+f"(d[56]),"+f"(d[57]),"+f"(d[58]),"+f"(d[59]),"+f"(d[60]),"+f"(d[61]),"+f"(d[62]),"+f"(d[63])
   : "l"(da),"l"(db),"r"(sd),"n"(TA),"n"(TB));
}


__device__ __forceinline__ float phi_f(float t) {
  t = rbf(t);
  float r = t > 0.f ? t + 1.f : ex2f(t * 1.4426950408889634f);
  return rbf(r) + 1e-6f;
}

#define NSTEP 22
#define STEPK 96
#define QSCALE 0.36067376022224085f
#define SMAGIC (512.0f + 2.0f * (127.0f - 1.5799993f))

#define K1_STAGE 49152
#define K1_SMEM (4 * K1_STAGE + 32768 + 1024 + 128)
struct K1Params { const __nv_bfloat16* wk; const __nv_bfloat16* wv; };

__global__ void __cluster_dims__(2, 1, 1) __launch_bounds__(384, 1)
k1_proj(const __grid_constant__ CUtensorMap mXA, const __grid_constant__ CUtensorMap mXB,
        const __grid_constant__ CUtensorMap mWq, const __grid_constant__ CUtensorMap mWqkv,
        const __grid_constant__ CUtensorMap mQst, K1Params prm) {
  extern __shared__ uint8_t smem_raw[];
  const uint32_t sWKV = (smem_u32(smem_raw) + 1023u) & ~1023u;
  const uint32_t sb = sWKV + 32768;
  const uint32_t bars = sb + 4 * K1_STAGE;
  const int tid = threadIdx.x, wg = tid >> 7, warp = tid >> 5, lane = tid & 31;
  const int rank = blockIdx.x & 1;
  const int ft = (blockIdx.x >> 1) & 7;
  const int tt = ((blockIdx.x >> 4) << 1) | rank;
  const bool isA = ft < 2;
  const bool doKV = (ft == 0);

  if (tid == 0) {
    for (int s = 0; s < 4; s++) { mbar_init(bars + 8 * s, 1); mbar_init(bars + 32 + 8 * s, doKV ? 6 : 4); }
    asm volatile("fence.mbarrier_init.release.cluster;" ::: "memory");
  }
  cluster_sync();
  pdl_launch();

  if (wg == 2) {
    const CUtensorMap* mX = isA ? &mXA : &mXB;
    const CUtensorMap* mW = isA ? &mWq : &mWqkv;
    int c0, c1;
    if (ft < 4) { c0 = (ft & 1) * 256 + rank * 128; c1 = c0 + 64; }
    else { c0 = 512 + (ft - 4) * 128 + rank * 64; c1 = c0 + 512; }
    auto issue = [&](int kb) {
      const int s = kb & 3;
      const uint32_t st = sb + s * K1_STAGE, fb = bars + 8 * s;
      mbar_expect_tx(fb, K1_STAGE);
      tma2d(st + 32768, mX, kb * 64, tt * 128, fb);
      tma2d_mc(st + rank * 16384, mW, c0, kb * 64, fb, 3);
      tma2d_mc(st + rank * 16384 + 8192, mW, c1, kb * 64, fb, 3);
    };
    if (tid == 256) { for (int kb = 0; kb < 4; kb++) issue(kb); }
    if (doKV) {
      const int t = tid - 256;
#pragma unroll
      for (int i = 0; i < 16; i++) {
        int c = t + i * 128;
        int mat = c >> 10, r = c & 1023;
        const uint4* src = (const uint4*)(mat ? prm.wv : prm.wk);
        uint4 v = __ldg(src + r);
        uint32_t dst = sWKV + (mat * 2 + (r & 1)) * 8192 + (r >> 1) * 16;
        asm volatile("st.shared.v4.b32 [%0], {%1,%2,%3,%4};" :: "r"(dst), "r"(v.x), "r"(v.y), "r"(v.z), "r"(v.w) : "memory");
      }
      fence_async();
      named_bar(3, 128);
      float acc[64];
#pragma unroll
      for (int kb = 0; kb < 8; kb++) {
        const int s = kb & 3;
        mbar_wait(bars + 8 * s, kb >> 2);
        uint64_t da = make_desc(sWKV + kb * 1024, 128, 8192, 0);
        uint64_t db = make_desc(sb + s * K1_STAGE + 32768, 16, 1024, 1);
        wg_fence();
#pragma unroll
        for (int k = 0; k < 4; k++) wg_ss128<1, 0>(acc, da + k * 16, db + k * 2, (kb | k) != 0);
        wg_commit();
        wg_wait<0>();
        fence_regs<64>(acc);
        if (kb < 4) {
          if (tid == 256) {
            mbar_arrive_cta(bars + 32 + 8 * s, 0); mbar_arrive_cta(bars + 32 + 8 * s, 1);
            mbar_wait_cluster(bars + 32 + 8 * s, 0);
            issue(kb + 4);
          }
          __syncwarp();
        }
      }
      named_bar(3, 128);
      const int g = lane >> 2, t4 = lane & 3;
      if (warp < 10) {
        uint32_t pk[32];
        uint32_t pk2[32];
        float stat;
        if (warp == 8) {
          float run0 = 0.f, run1 = 0.f;
          float n2[32];
          uint16_t h0[32], h1[32];
#pragma unroll
          for (int i = 0; i < 32; i++) {
            const int j = i >> 1, e = i & 1;
            float k0 = rbf(acc[4 * j + e]), k1 = rbf(acc[4 * j + 2 + e]);
            acc[4 * j + e] = k0; acc[4 * j + 2 + e] = k1;
            n2[i] = k0 * k0 + k1 * k1;
            if (i < 21) {
              __half d0 = __float2half_rn(2.f * k0 - run0), d1 = __float2half_rn(2.f * k1 - run1);
              run0 += __half2float(d0); run1 += __half2float(d1);
              h0[i] = __half_as_ushort(d0); h1[i] = __half_as_ushort(d1);
            } else {
              h0[i] = __half_as_ushort(__float2half_rn(k0)); h1[i] = __half_as_ushort(__float2half_rn(k1));
            }
          }
          stat = 0.f;
#pragma unroll
          for (int i = 0; i < 32; i++) {
            float v = n2[i];
            v += __shfl_xor_sync(~0u, v, 4); v += __shfl_xor_sync(~0u, v, 8); v += __shfl_xor_sync(~0u, v, 16);
            stat = (v > stat || v != v) ? v : stat;
          }
#pragma unroll
          for (int j = 0; j < 16; j++) {
            pk[2 * j] = (uint32_t)h0[2 * j] | ((uint32_t)h0[2 * j + 1] << 16);
            pk[2 * j + 1] = (uint32_t)h1[2 * j] | ((uint32_t)h1[2 * j + 1] << 16);
            pk2[2 * j] = pack_bf16(acc[4 * j], acc[4 * j + 1]);
            pk2[2 * j + 1] = pack_bf16(acc[4 * j + 2], acc[4 * j + 3]);
          }
        } else {
          stat = 0.f;
#pragma unroll
          for (int j = 0; j < 16; j++) {
            pk[2 * j] = pack_bf16(acc[4 * j], acc[4 * j + 1]);
            pk[2 * j + 1] = pack_bf16(acc[4 * j + 2], acc[4 * j + 3]);
            pk2[2 * j] = 0; pk2[2 * j + 1] = 0;
#pragma unroll
            for (int e = 0; e < 4; e++) { float v = fabsf(rbf(acc[4 * j + e])); stat = (v > stat || v != v) ? v : stat; }
          }
        }
#pragma unroll
        for (int o = 1; o < 32; o <<= 1) { float v = __shfl_xor_sync(~0u, stat, o); stat = (v > stat || v != v) ? v : stat; }
        if (lane == 0) g_stats[tt * 2 + (warp - 8)] = stat;
        const uint32_t stg = sWKV + (warp - 8) * 4096;
        const int m = lane >> 3, r = lane & 7;
#pragma unroll
        for (int j = 0; j < 16; j += 2) {
          uint32_t a = stg + ((j + (m >> 1)) * 8 + r) * 32 + (m & 1) * 16;
          stsm4t(a, pk[2 * j], pk[2 * j + 1], pk[2 * j + 2], pk[2 * j + 3]);
          if (warp == 8) stsm4t(a + 8192, pk2[2 * j], pk2[2 * j + 1], pk2[2 * j + 2], pk2[2 * j + 3]);
        }
      }
      named_bar(3, 128);
      {
        const int tok = tid - 256;
        const int t4k = (tok & 7) >> 1;
        const int i = ((tok >> 3) << 1) | (tok & 1);
        const int ch = tt * 4 + t4k;
        int kap;
        if (i < 21) kap = i * STEPK + 32 + ch;
        else { int idx = ch * 11 + (i - 21); kap = (idx >> 5) * STEPK + (idx & 31); }
#pragma unroll
        for (int a = 0; a < 3; a++) {
#pragma unroll
          for (int h = 0; h < 2; h++) {
            uint4 v;
            asm volatile("ld.shared.v4.b32 {%0,%1,%2,%3}, [%4];" : "=r"(v.x), "=r"(v.y), "=r"(v.z), "=r"(v.w) : "r"(sWKV + a * 4096 + tok * 32 + h * 16));
            g_KV[(a * 2 + h) * S_TOK + kap] = v;
          }
        }
      }
      (void)g; (void)t4;
    } else if (tid == 256) {
      for (int kb = 0; kb < 4; kb++) { mbar_wait_cluster(bars + 32 + 8 * kb, 0); issue(kb + 4); }
    }
  } else {
    float acc0[64], acc1[64];
#pragma unroll
    for (int kb = 0; kb < 8; kb++) {
      const int s = kb & 3;
      mbar_wait(bars + 8 * s, kb >> 2);
      const uint32_t st = sb + s * K1_STAGE;
      uint64_t da0 = make_desc(st + wg * 16384, 8192, 1024, 1);
      uint64_t da1 = make_desc(st + wg * 16384 + 8192, 8192, 1024, 1);
      uint64_t db = make_desc(st + 32768, 16, 1024, 1);
      wg_fence();
#pragma unroll
      for (int k = 0; k < 4; k++) {
        wg_ss128<1, 0>(acc0, da0 + k * 128, db + k * 2, (kb | k) != 0);
        wg_ss128<1, 0>(acc1, da1 + k * 128, db + k * 2, (kb | k) != 0);
      }
      wg_commit();
      if (kb >= 1 && kb <= 4) {
        wg_wait<1>();
        if ((tid & 127) == 0) { mbar_arrive_cta(bars + 32 + 8 * (kb - 1), 0); mbar_arrive_cta(bars + 32 + 8 * (kb - 1), 1); }
        __syncwarp();
      }
    }
    wg_wait<0>();
    fence_regs<64>(acc0); fence_regs<64>(acc1);
    const int w4 = warp & 3;
    if (ft < 4) {
      const int m = lane >> 3, r = lane & 7;
#pragma unroll
      for (int hf = 0; hf < 2; hf++) {
        float* acc = hf ? acc1 : acc0;
        const uint32_t stg = sb + hf * K1_STAGE + wg * 16384;
#pragma unroll
        for (int j = 0; j < 16; j += 2) {
          uint32_t p[4];
#pragma unroll
          for (int u = 0; u < 4; u++) {
            float a = acc[4 * j + 2 * u], b = acc[4 * j + 2 * u + 1];
            if (!isA) { a = phi_f(a); b = phi_f(b); }
            p[u] = pack_bf16(a, b);
          }
          const int tok = (j + (m >> 1)) * 8 + r;
          const int chunk = w4 * 2 + (m & 1);
          stsm4t(stg + tok * 128 + ((chunk ^ r) << 4), p[0], p[1], p[2], p[3]);
        }
      }
      fence_async();
      named_bar(wg + 1, 128);
      if ((tid & 127) == 0) {
        const int col = (ft & 1) * 256 + wg * 128;
        const int row = (isA ? 0 : S_TOK) + tt * 128;
        tma2d_store(&mQst, sb + wg * 16384, col, row);
        tma2d_store(&mQst, sb + K1_STAGE + wg * 16384, col + 64, row);
        bulk_commit();
        bulk_wait_all();
      }
    } else {
      float kv0[4] = {0, 0, 0, 0}, kv1[4] = {0, 0, 0, 0}, z0[4] = {0, 0, 0, 0}, z1[4] = {0, 0, 0, 0};
      const uint32_t one = 0x3F803F80u;
#pragma unroll
      for (int j = 0; j < 16; j += 2) {
        uint32_t b00 = pack_bf16(phi_f(acc0[4 * j]), phi_f(acc0[4 * j + 1]));
        uint32_t b10 = pack_bf16(phi_f(acc0[4 * j + 2]), phi_f(acc0[4 * j + 3]));
        uint32_t b01 = pack_bf16(phi_f(acc0[4 * j + 4]), phi_f(acc0[4 * j + 5]));
        uint32_t b11 = pack_bf16(phi_f(acc0[4 * j + 6]), phi_f(acc0[4 * j + 7]));
        uint32_t a0 = pack_bf16(acc1[4 * j], acc1[4 * j + 1]);
        uint32_t a1 = pack_bf16(acc1[4 * j + 2], acc1[4 * j + 3]);
        uint32_t a2 = pack_bf16(acc1[4 * j + 4], acc1[4 * j + 5]);
        uint32_t a3 = pack_bf16(acc1[4 * j + 6], acc1[4 * j + 7]);
        mma_bf16(kv0, a0, a1, a2, a3, b00, b01);
        mma_bf16(kv1, a0, a1, a2, a3, b10, b11);
        mma_bf16(z0, one, one, one, one, b00, b01);
        mma_bf16(z1, one, one, one, one, b10, b11);
      }
      const int head = (ft - 4) * 8 + wg * 4 + w4;
      float4* dst = g_kvp + ((tt * 32 + head) * 3) * 32 + lane;
      dst[0] = make_float4(kv0[0], kv0[1], kv1[0], kv1[1]);
      dst[32] = make_float4(kv0[2], kv0[3], kv1[2], kv1[3]);
      dst[64] = make_float4(z0[0], z0[1], z1[0], z1[1]);
    }
  }
}

#define K2_SMEM (5 * 32768 + 1024 + 128)

__device__ __forceinline__ uint32_t exp2_pair_fix(float d0, float d1, uint32_t one) {
  uint32_t w, y, r;
  asm("prmt.b32 %0, %1, %2, 0x6521;" : "=r"(w) : "r"(__float_as_uint(d0)), "r"(__float_as_uint(d1)));
  asm("lop3.b32 %0, %1, 0x007F007F, %2, 0xEA;" : "=r"(y) : "r"(w), "r"(one));
  uint32_t s = w | 0x007F007Fu;
  asm("fma.rn.bf16x2 %0, %1, %2, %3;" : "=r"(r) : "r"(w), "r"(y), "r"(s));
  return r;
}

__device__ __noinline__ void attn_slow(int row0, uint32_t sV) {
  const int t = threadIdx.x & 127;
  const int row = row0 + (t >> 1), half = t & 1;
  const uint4* qp = (const uint4*)(g_Q + (size_t)row * 16);
  uint4 qa = qp[0], qb = qp[1];
  float q[16];
  uint32_t qq[8] = {qa.x, qa.y, qa.z, qa.w, qb.x, qb.y, qb.z, qb.w};
#pragma unroll
  for (int i = 0; i < 8; i++) { q[2 * i] = bf_lo(qq[i]); q[2 * i + 1] = bf_hi(qq[i]); }
  float m = -INFINITY, l = 0.f, o[16];
#pragma unroll
  for (int i = 0; i < 16; i++) o[i] = 0.f;
  for (int j = half * 1024; j < half * 1024 + 1024; j++) {
    uint4 ka = g_KV[4 * S_TOK + j], kb = g_KV[5 * S_TOK + j];
    uint32_t kk[8] = {ka.x, ka.y, ka.z, ka.w, kb.x, kb.y, kb.z, kb.w};
    float s = 0.f;
#pragma unroll
    for (int i = 0; i < 8; i++) { s = fmaf(q[2 * i], bf_lo(kk[i]), s); s = fmaf(q[2 * i + 1], bf_hi(kk[i]), s); }
    s = rbf(s) * 0.25f;
    if (s > m) {
      float c = __expf(m - s);
      l *= c;
#pragma unroll
      for (int i = 0; i < 16; i++) o[i] *= c;
      m = s;
    }
    float p = __expf(s - m);
    l += p;
    uint32_t vv[8];
    asm volatile("ld.shared.v4.b32 {%0,%1,%2,%3}, [%4];" : "=r"(vv[0]), "=r"(vv[1]), "=r"(vv[2]), "=r"(vv[3]) : "r"(sV + j * 16));
    asm volatile("ld.shared.v4.b32 {%0,%1,%2,%3}, [%4];" : "=r"(vv[4]), "=r"(vv[5]), "=r"(vv[6]), "=r"(vv[7]) : "r"(sV + 32768 + j * 16));
#pragma unroll
    for (int i = 0; i < 8; i++) { o[2 * i] = fmaf(p, bf_lo(vv[i]), o[2 * i]); o[2 * i + 1] = fmaf(p, bf_hi(vv[i]), o[2 * i + 1]); }
  }
  float m2 = __shfl_xor_sync(~0u, m, 1);
  float mm = fmaxf(m, m2);
  float c = __expf(m - mm);
  l *= c; l += __shfl_xor_sync(~0u, l, 1);
  float inv = 1.f / l;
  uint32_t r[8];
#pragma unroll
  for (int i = 0; i < 16; i++) { o[i] *= c; o[i] += __shfl_xor_sync(~0u, o[i], 1); o[i] *= inv; }
#pragma unroll
  for (int i = 0; i < 8; i++) r[i] = pack_bf16(o[2 * i], o[2 * i + 1]);
  uint4* dst = (uint4*)(g_O + (size_t)row * 16);
  if (half == 0) dst[0] = make_uint4(r[0], r[1], r[2], r[3]); else dst[1] = make_uint4(r[4], r[5], r[6], r[7]);
}

__device__ __forceinline__ void lin_mid(int cta) {
  const int warp = threadIdx.x >> 5, lane = threadIdx.x & 31;
  const int head = cta * 8 + (warp & 7), th = warp >> 3;
  float4 a0 = make_float4(0, 0, 0, 0), a1 = a0, a2 = a0;
#pragma unroll 4
  for (int tt = 0; tt < 16; tt++) {
    const float4* src = g_kvp + ((tt * 32 + head) * 3) * 32 + lane;
    float4 u = src[0], v = src[32], w = src[64];
    a0.x += u.x; a0.y += u.y; a0.z += u.z; a0.w += u.w;
    a1.x += v.x; a1.y += v.y; a1.z += v.z; a1.w += v.w;
    a2.x += w.x; a2.y += w.y; a2.z += w.z; a2.w += w.w;
  }
  const uint32_t b00 = pack_bf16(a0.x, a0.y), b01 = pack_bf16(a0.z, a0.w);
  const uint32_t b10 = pack_bf16(a1.x, a1.y), b11 = pack_bf16(a1.z, a1.w);
  const uint32_t bz0 = pack_bf16(a2.x, a2.y), bz1 = pack_bf16(a2.z, a2.w);
  const int g = lane >> 2, t = lane & 3;
  const uint32_t* pq = (const uint32_t*)(g_Q + (size_t)S_TOK * D_MOD) + head * 8 + t;
  uint32_t* po = (uint32_t*)(g_O + (size_t)S_TOK * D_MOD) + head * 8 + t;
  for (int tb = 0; tb < 64; tb += 8) {
    uint32_t a[8][4];
#pragma unroll
    for (int u = 0; u < 8; u++) {
      const int r = th * 1024 + (tb + u) * 16 + g;
      a[u][0] = pq[r * 256]; a[u][1] = pq[(r + 8) * 256]; a[u][2] = pq[r * 256 + 4]; a[u][3] = pq[(r + 8) * 256 + 4];
    }
#pragma unroll
    for (int u = 0; u < 8; u++) {
      float n0[4] = {0, 0, 0, 0}, n1[4] = {0, 0, 0, 0}, dn[4] = {0, 0, 0, 0};
      mma_bf16(n0, a[u][0], a[u][1], a[u][2], a[u][3], b00, b01);
      mma_bf16(n1, a[u][0], a[u][1], a[u][2], a[u][3], b10, b11);
      mma_bf16(dn, a[u][0], a[u][1], a[u][2], a[u][3], bz0, bz1);
      const float i0 = 1.f / rbf(rbf(dn[0]) + 1e-6f), i1 = 1.f / rbf(rbf(dn[2]) + 1e-6f);
      const int r = th * 1024 + (tb + u) * 16 + g;
      po[r * 256] = pack_bf16(rbf(n0[0]) * i0, rbf(n0[1]) * i0);
      po[(r + 8) * 256] = pack_bf16(rbf(n0[2]) * i1, rbf(n0[3]) * i1);
      po[r * 256 + 4] = pack_bf16(rbf(n1[0]) * i0, rbf(n1[1]) * i0);
      po[(r + 8) * 256 + 4] = pack_bf16(rbf(n1[2]) * i1, rbf(n1[3]) * i1);
    }
  }
}

__global__ void __launch_bounds__(512, 1) k2_attn() {
  extern __shared__ uint8_t smem_raw[];
  const uint32_t sb = (smem_u32(smem_raw) + 1023u) & ~1023u;
  const uint32_t sK = sb, sV = sb + 65536, bars = sb + 5 * 32768;
  const int tid = threadIdx.x, wg = tid >> 7, lane = tid & 31;
  if (blockIdx.x >= 128) {
    pdl_launch();
    pdl_wait();
    lin_mid(blockIdx.x - 128);
    return;
  }
  if (tid == 0) {
    for (int c = 0; c < 4; c++) mbar_init(bars + 8 * c, 1);
    asm volatile("fence.mbarrier_init.release.cluster;" ::: "memory");
  }
#pragma unroll
  for (int i = 0; i < 4; i++)
    asm volatile("st.shared.v4.b32 [%0], {%1,%2,%2,%2};" :: "r"(sV + 65536 + (tid + i * 512) * 16), "r"(0x00003F80u), "r"(0u) : "memory");
  fence_async();
  __syncthreads();
  pdl_launch();
  pdl_wait();
  if (tid == 0) {
    const int kb[5] = {0, 2 * STEPK, 6 * STEPK, 14 * STEPK, S_TOK};
#pragma unroll
    for (int c = 0; c < 4; c++) {
      const uint32_t bytes = (kb[c + 1] - kb[c]) * 16;
      mbar_expect_tx(bars + 8 * c, 4 * bytes);
#pragma unroll
      for (int p = 0; p < 4; p++) bulk_g2s(sb + p * 32768 + kb[c] * 16, g_KV + p * S_TOK + kb[c], bytes, bars + 8 * c);
    }
  }
  float kmax2, vmax;
  {
    float s = g_stats[lane];
#pragma unroll
    for (int o = 2; o < 32; o <<= 1) { float v = __shfl_xor_sync(~0u, s, o); s = (v > s || v != v) ? v : s; }
    kmax2 = __shfl_sync(~0u, s, 0); vmax = __shfl_sync(~0u, s, 1);
  }
  float lim;
  {
    float lv = vmax > 0.f ? __log2f(vmax) : 0.f;
    lim = fminf(90.f, fminf(95.f + lv, 113.f - lv));
    if (!(vmax < 1e30f) || !(kmax2 <= 65536.f) || lim < 0.f) lim = -1.f;
  }
  const int g = lane >> 2, t = lane & 3, w4 = (tid >> 5) & 3;
  const uint32_t one = 0x3F803F80u + (uint32_t)(lim > 1e30f);
  const uint64_t dK0 = make_desc(sK, 32768, 128, 0);
  const uint64_t dV0 = make_desc(sV, 128, 32768, 0);

#pragma unroll 1
  for (int pass = 0; pass < 2; pass++) {
    const int row0 = blockIdx.x * 512 + (pass * 4 + wg) * 64;
    uint32_t q[4];
    bool bad;
    {
      const uint32_t* qp = (const uint32_t*)g_Q + (size_t)(row0 + w4 * 16 + g) * 8 + t;
      uint32_t r[4] = {qp[0], qp[64], qp[4], qp[68]};
      float n0 = 0.f, n1 = 0.f;
#pragma unroll
      for (int i = 0; i < 4; i++) {
        float a = bf_lo(r[i]) * QSCALE, b = bf_hi(r[i]) * QSCALE;
        q[i] = pack_f16(a, b);
        if (i & 1) n1 += a * a + b * b; else n0 += a * a + b * b;
      }
      n0 += __shfl_xor_sync(~0u, n0, 1); n0 += __shfl_xor_sync(~0u, n0, 2);
      n1 += __shfl_xor_sync(~0u, n1, 1); n1 += __shfl_xor_sync(~0u, n1, 2);
      float n = fmaxf(n0, n1);
      bad = !(n0 <= 65536.f && n1 <= 65536.f && lim > 0.f && n * kmax2 * 1.01f <= lim * lim);
    }
    uint32_t anybad;
    asm volatile("{\n.reg .pred p, q;\nsetp.ne.u32 p, %1, 0;\nbarrier.cta.red.or.pred q, %2, 128, p;\nselp.u32 %0, 1, 0, q;\n}\n"
                 : "=r"(anybad) : "r"((uint32_t)bad), "r"(wg + 1) : "memory");
    if (__any_sync(~0u, anybad)) {
      for (int c = 0; c < 4; c++) mbar_wait(bars + 8 * c, 0);
      attn_slow(row0, sV);
      continue;
    }
    float Sm[16], Sp[32], O[12];
    uint32_t P[24];
#pragma unroll
    for (int i = 0; i < 32; i++) Sp[i] = SMAGIC;
#pragma unroll
    for (int i = 0; i < 16; i++) Sm[i] = 0.f;
#pragma unroll
    for (int i = 0; i < 12; i++) O[i] = 0.f;
    fence_regs<16>(Sm); fence_regs<32>(Sp); fence_regs<12>(O); fence_regs<4>(q);
    mbar_wait(bars, 0);
    wg_fence();
    wg_qk32<0>(Sm, q, dK0);
    wg_qk64<1>(Sp, q, dK0 + 32);
    wg_commit();
    wg_wait<0>();
    fence_regs<16>(Sm); fence_regs<32>(Sp);
    uint64_t dK = dK0 + STEPK, dV = dV0;
    int nextw = 1, wb = 1;
#pragma unroll 1
    for (int s = 0; s < 21; s++) {
#pragma unroll
      for (int i = 0; i < 8; i++) P[i] = pack_bf16(ex2f(Sm[2 * i]), ex2f(Sm[2 * i + 1]));
#pragma unroll
      for (int i = 0; i < 16; i++) P[8 + i] = exp2_pair_fix(Sp[2 * i], Sp[2 * i + 1], one);
      fence_regs<24>(P);
      if (s == nextw) { mbar_wait(bars + 8 * wb, 0); nextw = nextw * 2 + 3; wb++; }
      wg_fence();
      wg_qk32<0>(Sm, q, dK);
      wg_qk64<1>(Sp, q, dK + 32);
#pragma unroll
      for (int k = 0; k < 6; k++) wg_pv24<1>(O, &P[4 * k], dV + k * 16);
      wg_commit();
      wg_wait<0>();
      fence_regs<16>(Sm); fence_regs<32>(Sp); fence_regs<12>(O); fence_regs<24>(P);
      dK += STEPK; dV += STEPK;
    }
#pragma unroll
    for (int i = 0; i < 8; i++) P[i] = pack_bf16(ex2f(Sm[2 * i]), ex2f(Sm[2 * i + 1]));
    fence_regs<8>(P);
    wg_fence();
    wg_pv24<1>(O, &P[0], dV);
    wg_pv24<1>(O, &P[4], dV + 16);
    wg_commit();
    wg_wait<0>();
    fence_regs<12>(O);
    const float l0 = __shfl_sync(~0u, O[8], lane & ~3), l1 = __shfl_sync(~0u, O[10], lane & ~3);
    const float i0 = 1.f / l0, i1 = 1.f / l1;
    uint32_t* op = (uint32_t*)g_O + (size_t)(row0 + w4 * 16 + g) * 8 + t;
    op[0] = pack_bf16(O[0] * i0, O[1] * i0);
    op[64] = pack_bf16(O[2] * i1, O[3] * i1);
    op[4] = pack_bf16(O[4] * i0, O[5] * i0);
    op[68] = pack_bf16(O[6] * i1, O[7] * i1);
  }
}

#define K3_SMEM (131072 + 6 * 16384 + 1024 + 256)
__global__ void __cluster_dims__(2, 1, 1) __launch_bounds__(288, 1)
k3_out(const __grid_constant__ CUtensorMap mO, const __grid_constant__ CUtensorMap mWoA,
       const __grid_constant__ CUtensorMap mWoB, const __grid_constant__ CUtensorMap mOut) {
  extern __shared__ uint8_t smem_raw[];
  const uint32_t sb = (smem_u32(smem_raw) + 1023u) & ~1023u;
  const uint32_t sW = sb, sA = sb + 131072, bars = sA + 6 * 16384;
  const int tid = threadIdx.x, wg = tid >> 7, warp = tid >> 5, lane = tid & 31;
  const int rank = blockIdx.x & 1;
  const int nt = (blockIdx.x & 7);
  const int tt = blockIdx.x >> 3;
  const int part = nt >> 2;
  if (tid == 0) {
    for (int s = 0; s < 14; s++) mbar_init(bars + 8 * s, 1);
    mbar_init(bars + 112, 4); mbar_init(bars + 120, 4);
    asm volatile("fence.mbarrier_init.release.cluster;" ::: "memory");
  }
  cluster_sync();
  if (wg == 2) {
    if (lane == 0) {
      const CUtensorMap* mW = part ? &mWoB : &mWoA;
      const int col = (nt & 3) * 128;
      for (int kb = 0; kb < 8; kb++) {
        mbar_expect_tx(bars + 8 * kb, 16384);
        tma2d(sW + kb * 16384, mW, col, kb * 64, bars + 8 * kb);
        tma2d(sW + kb * 16384 + 8192, mW, col + 64, kb * 64, bars + 8 * kb);
      }
      pdl_wait();
      const int row = part * S_TOK + tt * 128 + rank * 64;
      for (int kb = 0; kb < 8; kb++) {
        const int s = kb < 6 ? kb : kb - 6;
        if (kb >= 6) mbar_wait_cluster(bars + 112 + 8 * s, 0);
        mbar_expect_tx(bars + 64 + 8 * s, 16384);
        tma2d_mc(sA + s * 16384 + rank * 8192, &mO, kb * 64, row, bars + 64 + 8 * s, 3);
      }
    }
  } else {
    float acc[64];
#pragma unroll
    for (int kb = 0; kb < 8; kb++) {
      const int s = kb < 6 ? kb : kb - 6;
      mbar_wait(bars + 8 * kb, 0);
      mbar_wait(bars + 64 + 8 * s, kb >= 6);
      uint64_t da = make_desc(sA + s * 16384 + wg * 8192, 16, 1024, 1);
      uint64_t db = make_desc(sW + kb * 16384, 8192, 1024, 1);
      wg_fence();
#pragma unroll
      for (int k = 0; k < 4; k++) wg_ss128<0, 1>(acc, da + k * 2, db + k * 128, (kb | k) != 0);
      wg_commit();
      if (kb == 1 || kb == 2) {
        wg_wait<1>();
        if ((tid & 127) == 0) { mbar_arrive_cta(bars + 112 + 8 * (kb - 1), 0); mbar_arrive_cta(bars + 112 + 8 * (kb - 1), 1); }
        __syncwarp();
      }
    }
    wg_wait<0>();
    fence_regs<64>(acc);
    const int w4 = warp & 3, m = lane >> 3, r = lane & 7;
#pragma unroll
    for (int j = 0; j < 16; j += 2) {
      const uint32_t stg = sA + (2 + (j >> 3)) * 16384 + wg * 8192;
      const int row = w4 * 16 + (m & 1) * 8 + r;
      const int chunk = (j & 7) + (m >> 1);
      stsm4(stg + row * 128 + ((chunk ^ r) << 4),
            pack_bf16(acc[4 * j], acc[4 * j + 1]), pack_bf16(acc[4 * j + 2], acc[4 * j + 3]),
            pack_bf16(acc[4 * j + 4], acc[4 * j + 5]), pack_bf16(acc[4 * j + 6], acc[4 * j + 7]));
    }
    fence_async();
    named_bar(wg + 1, 128);
    if ((tid & 127) == 0) {
      tma2d_store(&mOut, sA + 2 * 16384 + wg * 8192, nt * 128, tt * 128 + wg * 64);
      tma2d_store(&mOut, sA + 3 * 16384 + wg * 8192, nt * 128 + 64, tt * 128 + wg * 64);
      bulk_commit();
      bulk_wait_all();
    }
  }
}

typedef CUresult (*EncodeFn)(CUtensorMap*, CUtensorMapDataType, cuuint32_t, void*, const cuuint64_t*, const cuuint64_t*,
                             const cuuint32_t*, const cuuint32_t*, CUtensorMapInterleave, CUtensorMapSwizzle,
                             CUtensorMapL2promotion, CUtensorMapFloatOOBfill);

static void make_map(EncodeFn enc, CUtensorMap* m, const void* ptr, uint64_t cols, uint64_t rows, uint32_t bc, uint32_t br) {
  cuuint64_t dims[2] = {cols, rows};
  cuuint64_t strides[1] = {cols * 2};
  cuuint32_t box[2] = {bc, br};
  cuuint32_t es[2] = {1, 1};
  enc(m, CU_TENSOR_MAP_DATA_TYPE_BFLOAT16, 2, (void*)ptr, dims, strides, box, es, CU_TENSOR_MAP_INTERLEAVE_NONE,
      CU_TENSOR_MAP_SWIZZLE_128B, CU_TENSOR_MAP_L2_PROMOTION_L2_256B, CU_TENSOR_MAP_FLOAT_OOB_FILL_NONE);
}

extern "C" void kernel_launch(void* const* d_in, const int* in_sizes, int n_in, void* d_out, int out_size) {
  (void)in_sizes; (void)n_in; (void)out_size;
  static EncodeFn enc = nullptr;
  static void* pQ = nullptr; static void* pO = nullptr;
  if (!enc) {
    void* fn = nullptr; cudaDriverEntryPointQueryResult qr;
    cudaGetDriverEntryPoint("cuTensorMapEncodeTiled", &fn, cudaEnableDefault, &qr);
    enc = (EncodeFn)fn;
    cudaGetSymbolAddress(&pQ, g_Q);
    cudaGetSymbolAddress(&pO, g_O);
    cudaFuncSetAttribute(k1_proj, cudaFuncAttributeMaxDynamicSharedMemorySize, K1_SMEM);
    cudaFuncSetAttribute(k2_attn, cudaFuncAttributeMaxDynamicSharedMemorySize, K2_SMEM);
    cudaFuncSetAttribute(k3_out, cudaFuncAttributeMaxDynamicSharedMemorySize, K3_SMEM);
  }
  CUtensorMap mXA, mXB, mWq, mWqkv, mQst, mO, mWoA, mWoB, mOut;
  make_map(enc, &mXA, d_in[0], 512, 2048, 64, 128);
  make_map(enc, &mWq, d_in[1], 512, 512, 64, 64);
  make_map(enc, &mWoA, d_in[4], 512, 512, 64, 64);
  make_map(enc, &mXB, d_in[5], 512, 2048, 64, 128);
  make_map(enc, &mWqkv, d_in[6], 1536, 512, 64, 64);
  make_map(enc, &mWoB, d_in[7], 512, 512, 64, 64);
  make_map(enc, &mQst, pQ, 512, 4096, 64, 128);
  make_map(enc, &mO, pO, 512, 4096, 64, 64);
  make_map(enc, &mOut, d_out, 1024, 2048, 64, 64);
  K1Params prm{(const __nv_bfloat16*)d_in[2], (const __nv_bfloat16*)d_in[3]};

  cudaStream_t st = cudaStreamPerThread;
  cudaLaunchAttribute at[1];
  at[0].id = cudaLaunchAttributeProgrammaticStreamSerialization;
  at[0].val.programmaticStreamSerializationAllowed = 1;
  cudaLaunchConfig_t cfg = {};
  cfg.stream = st;
  cfg.gridDim = dim3(128); cfg.blockDim = dim3(384); cfg.dynamicSmemBytes = K1_SMEM; cfg.attrs = at; cfg.numAttrs = 0;
  cudaLaunchKernelEx(&cfg, k1_proj, mXA, mXB, mWq, mWqkv, mQst, prm);
  cfg.gridDim = dim3(132); cfg.blockDim = dim3(512); cfg.dynamicSmemBytes = K2_SMEM; cfg.numAttrs = 1;
  cudaLaunchKernelEx(&cfg, k2_attn);
  cfg.gridDim = dim3(128); cfg.blockDim = dim3(288); cfg.dynamicSmemBytes = K3_SMEM; cfg.numAttrs = 1;
  cudaLaunchKernelEx(&cfg, k3_out, mO, mWoA, mWoB, mOut);
}
```

```cpp
#include <cuda_runtime.h>
#include <cuda_bf16.h>
#include <cuda_fp16.h>
#include <cuda.h>
#include <stdint.h>

#define S_TOK 2048
#define D_MOD 512

__device__ __align__(1024) __nv_bfloat16 g_Q[2 * S_TOK * D_MOD];
__device__ __align__(1024) __nv_bfloat16 g_O[2 * S_TOK * D_MOD];
__device__ __align__(1024) uint4 g_KV[6 * S_TOK];
__device__ uint2 g_stats[64];
__device__ __align__(16) float4 g_kvp[16 * 32 * 3 * 32];

#define TS(k, i) do {} while (0)
__device__ __forceinline__ uint32_t smem_u32(const void* p) { return (uint32_t)__cvta_generic_to_shared(p); }
__device__ __forceinline__ void mbar_init(uint32_t bar, int cnt) { asm volatile("mbarrier.init.shared::cta.b64 [%0], %1;" :: "r"(bar), "r"(cnt) : "memory"); }
__device__ __forceinline__ void mbar_expect_tx(uint32_t bar, uint32_t bytes) { asm volatile("mbarrier.arrive.expect_tx.shared::cta.b64 _, [%0], %1;" :: "r"(bar), "r"(bytes) : "memory"); }
__device__ __forceinline__ bool mbar_try(uint32_t bar, uint32_t parity) {
  uint32_t ok;
  asm volatile("{\n.reg .pred p;\nmbarrier.try_wait.parity.shared::cta.b64 p, [%1], %2;\nselp.b32 %0, 1, 0, p;\n}\n" : "=r"(ok) : "r"(bar), "r"(parity) : "memory");
  return ok;
}
__device__ __forceinline__ void mbar_wait(uint32_t bar, uint32_t parity) {
  asm volatile("{\n.reg .pred p;\n.reg .u32 c;\nmov.u32 c, 0;\n"
               "LW_%=:\n"
               "mbarrier.try_wait.parity.shared::cta.b64 p, [%0], %1;\n"
               "@p bra LD_%=;\n"
               "add.u32 c, c, 1;\n"
               "setp.lt.u32 p, c, 4000000;\n"
               "@p bra LW_%=;\n"
               "trap;\n"
               "LD_%=:\n}\n" :: "r"(bar), "r"(parity) : "memory");
}
__device__ __forceinline__ void mbar_arrive_cta(uint32_t bar, uint32_t cta) {
  asm volatile("{\n.reg .b32 ra;\nmapa.shared::cluster.u32 ra, %0, %1;\nmbarrier.arrive.shared::cluster.b64 _, [ra];\n}\n" :: "r"(bar), "r"(cta) : "memory");
}
__device__ __forceinline__ void cluster_sync() {
  asm volatile("barrier.cluster.arrive.relaxed.aligned;\nbarrier.cluster.wait.aligned;" ::: "memory");
}
__device__ __forceinline__ void tma2d(uint32_t dst, const CUtensorMap* m, int c0, int c1, uint32_t bar) {
  asm volatile("cp.async.bulk.tensor.2d.shared::cluster.global.mbarrier::complete_tx::bytes [%0], [%1, {%3, %4}], [%2];"
               :: "r"(dst), "l"(m), "r"(bar), "r"(c0), "r"(c1) : "memory");
}
__device__ __forceinline__ void tma2d_mc(uint32_t dst, const CUtensorMap* m, int c0, int c1, uint32_t bar, uint16_t mask) {
  asm volatile("cp.async.bulk.tensor.2d.shared::cluster.global.mbarrier::complete_tx::bytes.multicast::cluster [%0], [%1, {%3, %4}], [%2], %5;"
               :: "r"(dst), "l"(m), "r"(bar), "r"(c0), "r"(c1), "h"(mask) : "memory");
}
__device__ __forceinline__ void tma2d_store(const CUtensorMap* m, uint32_t src, int c0, int c1) {
  asm volatile("cp.async.bulk.tensor.2d.global.shared::cta.bulk_group [%0, {%2, %3}], [%1];"
               :: "l"(m), "r"(src), "r"(c0), "r"(c1) : "memory");
}
__device__ __forceinline__ void bulk_g2s(uint32_t dst, const void* src, uint32_t bytes, uint32_t bar) {
  asm volatile("cp.async.bulk.shared::cluster.global.mbarrier::complete_tx::bytes [%0], [%1], %2, [%3];"
               :: "r"(dst), "l"(src), "r"(bytes), "r"(bar) : "memory");
}
__device__ __forceinline__ void bulk_commit() { asm volatile("cp.async.bulk.commit_group;" ::: "memory"); }
__device__ __forceinline__ void bulk_wait_all() { asm volatile("cp.async.bulk.wait_group 0;" ::: "memory"); }
__device__ __forceinline__ void fence_async() { asm volatile("fence.proxy.async.shared::cta;" ::: "memory"); }
__device__ __forceinline__ void named_bar(int id, int n) { asm volatile("bar.sync %0, %1;" :: "r"(id), "r"(n) : "memory"); }
__device__ __forceinline__ void pdl_launch() { asm volatile("griddepcontrol.launch_dependents;" ::: "memory"); }
__device__ __forceinline__ void pdl_wait() { asm volatile("griddepcontrol.wait;" ::: "memory"); }
__device__ __forceinline__ void wg_fence() { asm volatile("wgmma.fence.sync.aligned;" ::: "memory"); }
__device__ __forceinline__ void wg_commit() { asm volatile("wgmma.commit_group.sync.aligned;" ::: "memory"); }
template <int n> __device__ __forceinline__ void wg_wait() { asm volatile("wgmma.wait_group.sync.aligned %0;" :: "n"(n) : "memory"); }
template <int n> __device__ __forceinline__ void fence_regs(float* r) {
#pragma unroll
  for (int i = 0; i < n; i++) asm volatile("" : "+f"(r[i]) :: "memory");
}
template <int n> __device__ __forceinline__ void fence_regs(uint32_t* r) {
#pragma unroll
  for (int i = 0; i < n; i++) asm volatile("" : "+r"(r[i]) :: "memory");
}
__device__ __forceinline__ uint64_t make_desc(uint32_t addr, uint32_t lbo, uint32_t sbo, uint32_t swz) {
  return (uint64_t)((addr & 0x3FFFF) >> 4) | ((uint64_t)(lbo >> 4) << 16) | ((uint64_t)(sbo >> 4) << 32) | ((uint64_t)swz << 62);
}
__device__ __forceinline__ float ex2f(float x) { float y; asm("ex2.approx.ftz.f32 %0, %1;" : "=f"(y) : "f"(x)); return y; }
__device__ __forceinline__ uint32_t pack_bf16(float lo, float hi) { uint32_t r; asm("cvt.rn.bf16x2.f32 %0, %1, %2;" : "=r"(r) : "f"(hi), "f"(lo)); return r; }
__device__ __forceinline__ uint32_t pack_f16(float lo, float hi) { uint32_t r; asm("cvt.rn.f16x2.f32 %0, %1, %2;" : "=r"(r) : "f"(hi), "f"(lo)); return r; }
__device__ __forceinline__ float bf_lo(uint32_t v) { return __uint_as_float(v << 16); }
__device__ __forceinline__ float bf_hi(uint32_t v) { return __uint_as_float(v & 0xFFFF0000u); }
__device__ __forceinline__ float rbf(float x) { return __bfloat162float(__float2bfloat16_rn(x)); }
__device__ __forceinline__ void stsm4(uint32_t a, uint32_t r0, uint32_t r1, uint32_t r2, uint32_t r3) {
  asm volatile("stmatrix.sync.aligned.m8n8.x4.shared.b16 [%0], {%1,%2,%3,%4};" :: "r"(a), "r"(r0), "r"(r1), "r"(r2), "r"(r3) : "memory");
}
__device__ __forceinline__ void stsm4t(uint32_t a, uint32_t r0, uint32_t r1, uint32_t r2, uint32_t r3) {
  asm volatile("stmatrix.sync.aligned.m8n8.x4.trans.shared.b16 [%0], {%1,%2,%3,%4};" :: "r"(a), "r"(r0), "r"(r1), "r"(r2), "r"(r3) : "memory");
}
__device__ __forceinline__ void mma_bf16(float* d, uint32_t a0, uint32_t a1, uint32_t a2, uint32_t a3, uint32_t b0, uint32_t b1) {
  asm volatile("mma.sync.aligned.m16n8k16.row.col.f32.bf16.bf16.f32 {%0,%1,%2,%3}, {%4,%5,%6,%7}, {%8,%9}, {%0,%1,%2,%3};"
               : "+f"(d[0]), "+f"(d[1]), "+f"(d[2]), "+f"(d[3]) : "r"(a0), "r"(a1), "r"(a2), "r"(a3), "r"(b0), "r"(b1));
}
template<int SD> __device__ __forceinline__ void wg_qk32(float* d, const uint32_t* a, uint64_t desc) {
  asm volatile("wgmma.mma_async.sync.aligned.m64n32k16.f32.f16.f16 {%0,%1,%2,%3,%4,%5,%6,%7,%8,%9,%10,%11,%12,%13,%14,%15}, {%16,%17,%18,%19}, %20, %21, 1, 1, 0;"
   : "+f"(d[0]),"+f"(d[1]),"+f"(d[2]),"+f"(d[3]),"+f"(d[4]),"+f"(d[5]),"+f"(d[6]),"+f"(d[7]),"+f"(d[8]),"+f"(d[9]),"+f"(d[10]),"+f"(d[11]),"+f"(d[12]),"+f"(d[13]),"+f"(d[14]),"+f"(d[15])
   : "r"(a[0]),"r"(a[1]),"r"(a[2]),"r"(a[3]),"l"(desc),"n"(SD));
}
template<int SD> __device__ __forceinline__ void wg_qk64(float* d, const uint32_t* a, uint64_t desc) {
  asm volatile("wgmma.mma_async.sync.aligned.m64n64k16.f32.f16.f16 {%0,%1,%2,%3,%4,%5,%6,%7,%8,%9,%10,%11,%12,%13,%14,%15,%16,%17,%18,%19,%20,%21,%22,%23,%24,%25,%26,%27,%28,%29,%30,%31}, {%32,%33,%34,%35}, %36, %37, 1, 1, 0;"
   : "+f"(d[0]),"+f"(d[1]),"+f"(d[2]),"+f"(d[3]),"+f"(d[4]),"+f"(d[5]),"+f"(d[6]),"+f"(d[7]),"+f"(d[8]),"+f"(d[9]),"+f"(d[10]),"+f"(d[11]),"+f"(d[12]),"+f"(d[13]),"+f"(d[14]),"+f"(d[15]),"+f"(d[16]),"+f"(d[17]),"+f"(d[18]),"+f"(d[19]),"+f"(d[20]),"+f"(d[21]),"+f"(d[22]),"+f"(d[23]),"+f"(d[24]),"+f"(d[25]),"+f"(d[26]),"+f"(d[27]),"+f"(d[28]),"+f"(d[29]),"+f"(d[30]),"+f"(d[31])
   : "r"(a[0]),"r"(a[1]),"r"(a[2]),"r"(a[3]),"l"(desc),"n"(SD));
}
template<int SD> __device__ __forceinline__ void wg_pv24(float* d, const uint32_t* a, uint64_t desc) {
  asm volatile("wgmma.mma_async.sync.aligned.m64n24k16.f32.bf16.bf16 {%0,%1,%2,%3,%4,%5,%6,%7,%8,%9,%10,%11}, {%12,%13,%14,%15}, %16, %17, 1, 1, 1;"
   : "+f"(d[0]),"+f"(d[1]),"+f"(d[2]),"+f"(d[3]),"+f"(d[4]),"+f"(d[5]),"+f"(d[6]),"+f"(d[7]),"+f"(d[8]),"+f"(d[9]),"+f"(d[10]),"+f"(d[11])
   : "r"(a[0]),"r"(a[1]),"r"(a[2]),"r"(a[3]),"l"(desc),"n"(SD));
}
template<int TA, int TB> __device__ __forceinline__ void wg_ss128(float* d, uint64_t da, uint64_t db, int sd) {
  asm volatile("{\n.reg .pred p;\nsetp.ne.b32 p, %66, 0;\n"
   "wgmma.mma_async.sync.aligned.m64n128k16.f32.bf16.bf16 {%0,%1,%2,%3,%4,%5,%6,%7,%8,%9,%10,%11,%12,%13,%14,%15,%16,%17,%18,%19,%20,%21,%22,%23,%24,%25,%26,%27,%28,%29,%30,%31,%32,%33,%34,%35,%36,%37,%38,%39,%40,%41,%42,%43,%44,%45,%46,%47,%48,%49,%50,%51,%52,%53,%54,%55,%56,%57,%58,%59,%60,%61,%62,%63}, %64, %65, p, 1, 1, %67, %68;\n}\n"
   : "+f"(d[0]),"+f"(d[1]),"+f"(d[2]),"+f"(d[3]),"+f"(d[4]),"+f"(d[5]),"+f"(d[6]),"+f"(d[7]),"+f"(d[8]),"+f"(d[9]),"+f"(d[10]),"+f"(d[11]),"+f"(d[12]),"+f"(d[13]),"+f"(d[14]),"+f"(d[15]),"+f"(d[16]),"+f"(d[17]),"+f"(d[18]),"+f"(d[19]),"+f"(d[20]),"+f"(d[21]),"+f"(d[22]),"+f"(d[23]),"+f"(d[24]),"+f"(d[25]),"+f"(d[26]),"+f"(d[27]),"+f"(d[28]),"+f"(d[29]),"+f"(d[30]),"+f"(d[31]),"+f"(d[32]),"+f"(d[33]),"+f"(d[34]),"+f"(d[35]),"+f"(d[36]),"+f"(d[37]),"+f"(d[38]),"+f"(d[39]),"+f"(d[40]),"+f"(d[41]),"+f"(d[42]),"+f"(d[43]),"+f"(d[44]),"+f"(d[45]),"+f"(d[46]),"+f"(d[47]),"+f"(d[48]),"+f"(d[49]),"+f"(d[50]),"+f"(d[51]),"+f"(d[52]),"+f"(d[53]),"+f"(d[54]),"+f"(d[55]),"+f"(d[56]),"+f"(d[57]),"+f"(d[58]),"+f"(d[59]),"+f"(d[60]),"+f"(d[61]),"+f"(d[62]),"+f"(d[63])
   : "l"(da),"l"(db),"r"(sd),"n"(TA),"n"(TB));
}

__device__ __forceinline__ uint32_t phi2(float a, float b) {
  uint32_t r, e;
  asm("cvt.rn.relu.bf16x2.f32 %0, %1, %2;" : "=r"(r) : "f"(b), "f"(a));
  e = pack_bf16(ex2f(a * 1.4426950408889634f), ex2f(b * 1.4426950408889634f));
  asm("add.rn.bf16x2 %0, %0, %1;" : "+r"(e) : "r"(0x35863586u));
  asm("min.NaN.bf16x2 %0, %0, %1;" : "+r"(e) : "r"(0x3F803F80u));
  asm("add.rn.bf16x2 %0, %0, %1;" : "+r"(e) : "r"(r));
  return e;
}

#define NSTEP 22
#define STEPK 96
#define QSCALE 0.36067376022224085f
#define SMAGIC (512.0f + 2.0f * (127.0f - 1.5799993f))

#define K1_STAGE 49152
#define K1_SMEM (4 * K1_STAGE + 32768 + 1024 + 128)
struct K1Params { const __nv_bfloat16* wk; const __nv_bfloat16* wv; };

__global__ void __cluster_dims__(2, 1, 1) __launch_bounds__(384, 1)
k1_proj(const __grid_constant__ CUtensorMap mXA, const __grid_constant__ CUtensorMap mXB,
        const __grid_constant__ CUtensorMap mWq, const __grid_constant__ CUtensorMap mWqkv,
        const __grid_constant__ CUtensorMap mQst, K1Params prm) {
  extern __shared__ uint8_t smem_raw[];
  const uint32_t sWKV = (smem_u32(smem_raw) + 1023u) & ~1023u;
  const uint32_t sb = sWKV + 32768;
  const uint32_t bars = sb + 4 * K1_STAGE;
  const int tid = threadIdx.x, wg = tid >> 7, warp = tid >> 5, lane = tid & 31;
  const int rank = blockIdx.x & 1;
  const int ft = (blockIdx.x >> 1) & 7;
  const int tt = ((blockIdx.x >> 4) << 1) | rank;
  const bool isA = ft < 2;
  const bool doKV = (ft == 0);
  if (tid == 0) TS(0, 0);

  if (tid == 0) {
    for (int s = 0; s < 4; s++) { mbar_init(bars + 8 * s, 1); mbar_init(bars + 32 + 8 * s, doKV ? 6 : 4); }
    asm volatile("fence.mbarrier_init.release.cluster;" ::: "memory");
  }
  cluster_sync();
  pdl_launch();
  if (tid == 0) TS(0, 1);

  if (wg == 2) {
    const CUtensorMap* mX = isA ? &mXA : &mXB;
    const CUtensorMap* mW = isA ? &mWq : &mWqkv;
    int c0, c1;
    if (ft < 4) { c0 = (ft & 1) * 256 + rank * 128; c1 = c0 + 64; }
    else { c0 = 512 + (ft - 4) * 128 + rank * 64; c1 = c0 + 512; }
    auto issue = [&](int kb) {
      const int s = kb & 3;
      const uint32_t st = sb + s * K1_STAGE, fb = bars + 8 * s;
      mbar_expect_tx(fb, K1_STAGE);
      tma2d(st + 32768, mX, kb * 64, tt * 128, fb);
      tma2d_mc(st + rank * 16384, mW, c0, kb * 64, fb, 3);
      tma2d_mc(st + rank * 16384 + 8192, mW, c1, kb * 64, fb, 3);
    };
    if (tid == 256) { for (int kb = 0; kb < 4; kb++) issue(kb); }
    if (doKV) {
      const int t = tid - 256;
#pragma unroll
      for (int i = 0; i < 16; i++) {
        int c = t + i * 128;
        int mat = c >> 10, r = c & 1023;
        const uint4* src = (const uint4*)(mat ? prm.wv : prm.wk);
        uint4 v = __ldg(src + r);
        uint32_t dst = sWKV + (mat * 2 + (r & 1)) * 8192 + (r >> 1) * 16;
        asm volatile("st.shared.v4.b32 [%0], {%1,%2,%3,%4};" :: "r"(dst), "r"(v.x), "r"(v.y), "r"(v.z), "r"(v.w) : "memory");
      }
      fence_async();
      named_bar(3, 128);
      float acc[64];
#pragma unroll
      for (int kb = 0; kb < 8; kb++) {
        const int s = kb & 3;
        mbar_wait(bars + 8 * s, kb >> 2);
        uint64_t da = make_desc(sWKV + kb * 1024, 128, 8192, 0);
        uint64_t db = make_desc(sb + s * K1_STAGE + 32768, 16, 1024, 1);
        wg_fence();
#pragma unroll
        for (int k = 0; k < 4; k++) wg_ss128<1, 0>(acc, da + k * 16, db + k * 2, (kb | k) != 0);
        wg_commit();
        wg_wait<0>();
        fence_regs<64>(acc);
        if (kb < 4) {
          if (tid == 256) {
            mbar_arrive_cta(bars + 32 + 8 * s, 0); mbar_arrive_cta(bars + 32 + 8 * s, 1);
            mbar_wait(bars + 32 + 8 * s, 0);
            issue(kb + 4);
          }
          __syncwarp();
        }
      }
      named_bar(3, 128);
      if (warp < 10) {
        const int m = lane >> 3, r = lane & 7;
        float run0 = 0.f, run1 = 0.f;
#pragma unroll
        for (int j = 0; j < 16; j += 2) {
          uint32_t p[4];
#pragma unroll
          for (int u = 0; u < 4; u++) p[u] = pack_bf16(acc[4 * j + 2 * u], acc[4 * j + 2 * u + 1]);
          const uint32_t a = sWKV + ((j + (m >> 1)) * 8 + r) * 32 + (m & 1) * 16;
          stsm4t(a + (warp == 8 ? 8192 : 4096), p[0], p[1], p[2], p[3]);
          if (warp == 8) {
            uint32_t h[4];
#pragma unroll
            for (int u = 0; u < 4; u++) {
              const int i = 2 * j + (u >> 1) * 2;
              float k0 = bf_lo(p[u]), k1 = bf_hi(p[u]);
              float& run = (u & 1) ? run1 : run0;
              if (i < 21) { k0 = __half2float(__float2half_rn(2.f * k0 - run)); run += k0; }
              if (i + 1 < 21) { k1 = __half2float(__float2half_rn(2.f * k1 - run)); run += k1; }
              h[u] = pack_f16(k0, k1);
            }
            stsm4t(a, h[0], h[1], h[2], h[3]);
          }
        }
      }
      named_bar(3, 128);
      {
        const int tok = tid - 256;
        const int t4k = (tok & 7) >> 1;
        const int i = ((tok >> 3) << 1) | (tok & 1);
        const int ch = tt * 4 + t4k;
        int kap;
        if (i < 21) kap = i * STEPK + 32 + ch;
        else { int idx = ch * 11 + (i - 21); kap = (idx >> 5) * STEPK + (idx & 31); }
        float n2 = 0.f, vm = 0.f;
#pragma unroll
        for (int a = 0; a < 3; a++) {
#pragma unroll
          for (int h = 0; h < 2; h++) {
            uint32_t v[4];
            asm volatile("ld.shared.v4.b32 {%0,%1,%2,%3}, [%4];" : "=r"(v[0]), "=r"(v[1]), "=r"(v[2]), "=r"(v[3]) : "r"(sWKV + a * 4096 + tok * 32 + h * 16));
            g_KV[(a * 2 + h) * S_TOK + kap] = make_uint4(v[0], v[1], v[2], v[3]);
#pragma unroll
            for (int u = 0; u < 4; u++) {
              float x = bf_lo(v[u]), y = bf_hi(v[u]);
              if (a == 2) n2 += x * x + y * y;
              if (a == 1) vm += fabsf(x) + fabsf(y);
            }
          }
        }
        uint32_t un = __reduce_max_sync(~0u, __float_as_uint(n2) & 0x7FFFFFFFu);
        uint32_t uv = __reduce_max_sync(~0u, __float_as_uint(vm) & 0x7FFFFFFFu);
        if (lane == 0) g_stats[tt * 4 + (warp & 3)] = make_uint2(un, uv);
      }
      if (tid == 256) TS(0, 14);
    } else if (tid == 256) {
      for (int kb = 0; kb < 4; kb++) { mbar_wait(bars + 32 + 8 * kb, 0); issue(kb + 4); }
    }
  } else {
    float acc0[64], acc1[64];
#pragma unroll
    for (int kb = 0; kb < 8; kb++) {
      const int s = kb & 3;
      mbar_wait(bars + 8 * s, kb >> 2);
      if (tid == 0) TS(0, 2 + kb);
      const uint32_t st = sb + s * K1_STAGE;
      uint64_t da0 = make_desc(st + wg * 16384, 8192, 1024, 1);
      uint64_t da1 = make_desc(st + wg * 16384 + 8192, 8192, 1024, 1);
      uint64_t db = make_desc(st + 32768, 16, 1024, 1);
      wg_fence();
#pragma unroll
      for (int k = 0; k < 4; k++) {
        wg_ss128<1, 0>(acc0, da0 + k * 128, db + k * 2, (kb | k) != 0);
        wg_ss128<1, 0>(acc1, da1 + k * 128, db + k * 2, (kb | k) != 0);
      }
      wg_commit();
      if (kb >= 1 && kb <= 4) {
        wg_wait<1>();
        if ((tid & 127) == 0) { mbar_arrive_cta(bars + 32 + 8 * (kb - 1), 0); mbar_arrive_cta(bars + 32 + 8 * (kb - 1), 1); }
        __syncwarp();
      }
    }
    wg_wait<0>();
    fence_regs<64>(acc0); fence_regs<64>(acc1);
    if (tid == 0) TS(0, 10);
    const int w4 = warp & 3;
    if (ft < 4) {
      const int m = lane >> 3, r = lane & 7;
#pragma unroll
      for (int hf = 0; hf < 2; hf++) {
        float* acc = hf ? acc1 : acc0;
        const uint32_t stg = sb + hf * K1_STAGE + wg * 16384;
#pragma unroll
        for (int j = 0; j < 16; j += 2) {
          uint32_t p[4];
#pragma unroll
          for (int u = 0; u < 4; u++) {
            float a = acc[4 * j + 2 * u], b = acc[4 * j + 2 * u + 1];
            p[u] = isA ? pack_bf16(a, b) : phi2(a, b);
          }
          const int tok = (j + (m >> 1)) * 8 + r;
          const int chunk = w4 * 2 + (m & 1);
          stsm4t(stg + tok * 128 + ((chunk ^ r) << 4), p[0], p[1], p[2], p[3]);
        }
      }
      fence_async();
      named_bar(wg + 1, 128);
      if ((tid & 127) == 0) {
        const int col = (ft & 1) * 256 + wg * 128;
        const int row = (isA ? 0 : S_TOK) + tt * 128;
        tma2d_store(&mQst, sb + wg * 16384, col, row);
        tma2d_store(&mQst, sb + K1_STAGE + wg * 16384, col + 64, row);
        if (tid == 0) TS(0, 11);
        bulk_commit();
        bulk_wait_all();
        if (tid == 0) TS(0, 12);
      }
    } else {
      float kv0[4] = {0, 0, 0, 0}, kv1[4] = {0, 0, 0, 0}, z0[4] = {0, 0, 0, 0}, z1[4] = {0, 0, 0, 0};
      const uint32_t one = 0x3F803F80u;
#pragma unroll
      for (int j = 0; j < 16; j += 2) {
        uint32_t b00 = phi2(acc0[4 * j], acc0[4 * j + 1]);
        uint32_t b10 = phi2(acc0[4 * j + 2], acc0[4 * j + 3]);
        uint32_t b01 = phi2(acc0[4 * j + 4], acc0[4 * j + 5]);
        uint32_t b11 = phi2(acc0[4 * j + 6], acc0[4 * j + 7]);
        uint32_t a0 = pack_bf16(acc1[4 * j], acc1[4 * j + 1]);
        uint32_t a1 = pack_bf16(acc1[4 * j + 2], acc1[4 * j + 3]);
        uint32_t a2 = pack_bf16(acc1[4 * j + 4], acc1[4 * j + 5]);
        uint32_t a3 = pack_bf16(acc1[4 * j + 6], acc1[4 * j + 7]);
        mma_bf16(kv0, a0, a1, a2, a3, b00, b01);
        mma_bf16(kv1, a0, a1, a2, a3, b10, b11);
        mma_bf16(z0, one, one, one, one, b00, b01);
        mma_bf16(z1, one, one, one, one, b10, b11);
      }
      const int head = (ft - 4) * 8 + wg * 4 + w4;
      float4* dst = g_kvp + ((tt * 32 + head) * 3) * 32 + lane;
      dst[0] = make_float4(kv0[0], kv0[1], kv1[0], kv1[1]);
      dst[32] = make_float4(kv0[2], kv0[3], kv1[2], kv1[3]);
      dst[64] = make_float4(z0[0], z0[1], z1[0], z1[1]);
      if (tid == 0) TS(0, 13);
    }
  }
}

#define K2_SMEM (5 * 32768 + 1024 + 128)

__device__ __forceinline__ uint32_t exp2_pair_fix(float d0, float d1, uint32_t one) {
  uint32_t w, y, r;
  asm("prmt.b32 %0, %1, %2, 0x6521;" : "=r"(w) : "r"(__float_as_uint(d0)), "r"(__float_as_uint(d1)));
  asm("lop3.b32 %0, %1, 0x007F007F, %2, 0xEA;" : "=r"(y) : "r"(w), "r"(one));
  uint32_t s = w | 0x007F007Fu;
  asm("fma.rn.bf16x2 %0, %1, %2, %3;" : "=r"(r) : "r"(w), "r"(y), "r"(s));
  return r;
}

__device__ __noinline__ void attn_slow(int row0, uint32_t sV) {
  const int t = threadIdx.x & 127;
  const int row = row0 + (t >> 1), half = t & 1;
  const uint4* qp = (const uint4*)(g_Q + (size_t)row * 16);
  uint4 qa = qp[0], qb = qp[1];
  float q[16];
  uint32_t qq[8] = {qa.x, qa.y, qa.z, qa.w, qb.x, qb.y, qb.z, qb.w};
#pragma unroll
  for (int i = 0; i < 8; i++) { q[2 * i] = bf_lo(qq[i]); q[2 * i + 1] = bf_hi(qq[i]); }
  float m = -INFINITY, l = 0.f, o[16];
#pragma unroll
  for (int i = 0; i < 16; i++) o[i] = 0.f;
  for (int j = half * 1024; j < half * 1024 + 1024; j++) {
    uint4 ka = g_KV[4 * S_TOK + j], kb = g_KV[5 * S_TOK + j];
    uint32_t kk[8] = {ka.x, ka.y, ka.z, ka.w, kb.x, kb.y, kb.z, kb.w};
    float s = 0.f;
#pragma unroll
    for (int i = 0; i < 8; i++) { s = fmaf(q[2 * i], bf_lo(kk[i]), s); s = fmaf(q[2 * i + 1], bf_hi(kk[i]), s); }
    s = rbf(s) * 0.25f;
    if (s > m) {
      float c = __expf(m - s);
      l *= c;
#pragma unroll
      for (int i = 0; i < 16; i++) o[i] *= c;
      m = s;
    }
    float p = __expf(s - m);
    l += p;
    uint32_t vv[8];
    asm volatile("ld.shared.v4.b32 {%0,%1,%2,%3}, [%4];" : "=r"(vv[0]), "=r"(vv[1]), "=r"(vv[2]), "=r"(vv[3]) : "r"(sV + j * 16));
    asm volatile("ld.shared.v4.b32 {%0,%1,%2,%3}, [%4];" : "=r"(vv[4]), "=r"(vv[5]), "=r"(vv[6]), "=r"(vv[7]) : "r"(sV + 32768 + j * 16));
#pragma unroll
    for (int i = 0; i < 8; i++) { o[2 * i] = fmaf(p, bf_lo(vv[i]), o[2 * i]); o[2 * i + 1] = fmaf(p, bf_hi(vv[i]), o[2 * i + 1]); }
  }
  float m2 = __shfl_xor_sync(~0u, m, 1);
  float mm = fmaxf(m, m2);
  float c = __expf(m - mm);
  l *= c; l += __shfl_xor_sync(~0u, l, 1);
  float inv = 1.f / l;
  uint32_t r[8];
#pragma unroll
  for (int i = 0; i < 16; i++) { o[i] *= c; o[i] += __shfl_xor_sync(~0u, o[i], 1); o[i] *= inv; }
#pragma unroll
  for (int i = 0; i < 8; i++) r[i] = pack_bf16(o[2 * i], o[2 * i + 1]);
  uint4* dst = (uint4*)(g_O + (size_t)row * 16);
  if (half == 0) dst[0] = make_uint4(r[0], r[1], r[2], r[3]); else dst[1] = make_uint4(r[4], r[5], r[6], r[7]);
}

__device__ __forceinline__ void ldsm4(uint32_t a, uint32_t* r) {
  asm volatile("ldmatrix.sync.aligned.m8n8.x4.shared.b16 {%0,%1,%2,%3}, [%4];" : "=r"(r[0]), "=r"(r[1]), "=r"(r[2]), "=r"(r[3]) : "r"(a) : "memory");
}
__device__ __forceinline__ void lin_mid(int cta, uint32_t sb, uint32_t bars, const CUtensorMap* mQ, const CUtensorMap* mOs) {
  const int tid = threadIdx.x, wg = tid >> 7, w4 = (tid >> 5) & 3, lane = tid & 31;
  const int cb = wg & 1, col = cta * 128 + cb * 64;
  const uint32_t buf = sb + wg * 32768, br = bars + wg * 16;
  if ((tid & 127) == 0) {
    mbar_init(br, 1); mbar_init(br + 8, 1);
    asm volatile("fence.mbarrier_init.release.cluster;" ::: "memory");
    for (int u = 0; u < 2; u++) {
      mbar_expect_tx(br + 8 * u, 16384);
      tma2d(buf + u * 16384, mQ, col, S_TOK + ((wg >> 1) * 8 + u) * 128, br + 8 * u);
    }
  }
  const int head = cta * 8 + cb * 4 + w4;
  float4 a0 = make_float4(0, 0, 0, 0), a1 = a0, a2 = a0;
#pragma unroll
  for (int tt = 0; tt < 16; tt++) {
    const float4* src = g_kvp + ((tt * 32 + head) * 3) * 32 + lane;
    float4 u = src[0], v = src[32], w = src[64];
    a0.x += u.x; a0.y += u.y; a0.z += u.z; a0.w += u.w;
    a1.x += v.x; a1.y += v.y; a1.z += v.z; a1.w += v.w;
    a2.x += w.x; a2.y += w.y; a2.z += w.z; a2.w += w.w;
  }
  const uint32_t b00 = pack_bf16(a0.x, a0.y), b01 = pack_bf16(a0.z, a0.w);
  const uint32_t b10 = pack_bf16(a1.x, a1.y), b11 = pack_bf16(a1.z, a1.w);
  const uint32_t bz0 = pack_bf16(a2.x, a2.y), bz1 = pack_bf16(a2.z, a2.w);
  named_bar(wg + 1, 128);
  const int m = lane >> 3, r = lane & 7;
  const uint32_t off = ((m & 1) * 8 + r) * 128 + (((w4 * 2 + (m >> 1)) ^ r) << 4);
#pragma unroll 1
  for (int u = 0; u < 8; u++) {
    const uint32_t bb = buf + (u & 1) * 16384;
    mbar_wait(br + 8 * (u & 1), (u >> 1) & 1);
#pragma unroll
    for (int mt = 0; mt < 8; mt++) {
      uint32_t a[4];
      ldsm4(bb + mt * 2048 + off, a);
      float n0[4] = {0, 0, 0, 0}, n1[4] = {0, 0, 0, 0}, dn[4] = {0, 0, 0, 0};
      mma_bf16(n0, a[0], a[1], a[2], a[3], b00, b01);
      mma_bf16(n1, a[0], a[1], a[2], a[3], b10, b11);
      mma_bf16(dn, a[0], a[1], a[2], a[3], bz0, bz1);
      const float i0 = __frcp_rn(rbf(rbf(dn[0]) + 1e-6f)), i1 = __frcp_rn(rbf(rbf(dn[2]) + 1e-6f));
      uint32_t x0 = pack_bf16(n0[0], n0[1]), x1 = pack_bf16(n0[2], n0[3]), x2 = pack_bf16(n1[0], n1[1]), x3 = pack_bf16(n1[2], n1[3]);
      stsm4(bb + mt * 2048 + off, pack_bf16(bf_lo(x0) * i0, bf_hi(x0) * i0), pack_bf16(bf_lo(x1) * i1, bf_hi(x1) * i1),
            pack_bf16(bf_lo(x2) * i0, bf_hi(x2) * i0), pack_bf16(bf_lo(x3) * i1, bf_hi(x3) * i1));
    }
    fence_async();
    named_bar(wg + 1, 128);
    if ((tid & 127) == 0) {
      tma2d_store(mOs, bb, col, S_TOK + ((wg >> 1) * 8 + u) * 128);
      bulk_commit();
      if (u + 2 < 8) {
        asm volatile("cp.async.bulk.wait_group.read 0;" ::: "memory");
        mbar_expect_tx(br + 8 * (u & 1), 16384);
        tma2d(bb, mQ, col, S_TOK + ((wg >> 1) * 8 + u + 2) * 128, br + 8 * (u & 1));
      }
    }
    __syncwarp();
  }
  if ((tid & 127) == 0) bulk_wait_all();
}

__global__ void __launch_bounds__(512, 1) k2_attn(const __grid_constant__ CUtensorMap mQst, const __grid_constant__ CUtensorMap mOst) {
  extern __shared__ uint8_t smem_raw[];
  const uint32_t sb = (smem_u32(smem_raw) + 1023u) & ~1023u;
  const uint32_t sK = sb, sV = sb + 65536, bars = sb + 5 * 32768;
  const int tid = threadIdx.x, wg = tid >> 7, lane = tid & 31;
  if (tid == 0) TS(1, 0);
  if (blockIdx.x >= 128) {
    pdl_launch();
    pdl_wait();
    lin_mid(blockIdx.x - 128, sb, bars, &mQst, &mOst);
    if (tid == 0) TS(1, 8);
    return;
  }
  if (tid == 0) {
    for (int c = 0; c < 4; c++) mbar_init(bars + 8 * c, 1);
    asm volatile("fence.mbarrier_init.release.cluster;" ::: "memory");
  }
#pragma unroll
  for (int i = 0; i < 4; i++)
    asm volatile("st.shared.v4.b32 [%0], {%1,%2,%2,%2};" :: "r"(sV + 65536 + (tid + i * 512) * 16), "r"(0x00003F80u), "r"(0u) : "memory");
  fence_async();
  __syncthreads();
  pdl_launch();
  pdl_wait();
  if (tid == 0) TS(1, 1);
  if (tid == 0) {
    const int kb[5] = {0, 2 * STEPK, 6 * STEPK, 14 * STEPK, S_TOK};
#pragma unroll
    for (int c = 0; c < 4; c++) {
      const uint32_t bytes = (kb[c + 1] - kb[c]) * 16;
      mbar_expect_tx(bars + 8 * c, 4 * bytes);
#pragma unroll
      for (int p = 0; p < 4; p++) bulk_g2s(sb + p * 32768 + kb[c] * 16, g_KV + p * S_TOK + kb[c], bytes, bars + 8 * c);
    }
  }
  float kmax2, vmax;
  {
    uint2 a = g_stats[lane], b = g_stats[lane + 32];
    kmax2 = __uint_as_float(__reduce_max_sync(~0u, max(a.x, b.x)));
    vmax = __uint_as_float(__reduce_max_sync(~0u, max(a.y, b.y)));
  }
  float lim;
  {
    float lv = vmax > 0.f ? __log2f(vmax) : 0.f;
    lim = fminf(90.f, fminf(91.f + lv, 113.f - lv));
    if (!(vmax < 1e30f) || !(kmax2 <= 65536.f) || lim < 0.f) lim = -1.f;
  }
  const int g = lane >> 2, t = lane & 3, w4 = (tid >> 5) & 3;
  const uint32_t one = 0x3F803F80u + (uint32_t)(lim > 1e30f);
  const uint64_t dK0 = make_desc(sK, 32768, 128, 0);
  const uint64_t dV0 = make_desc(sV, 128, 32768, 0);

#pragma unroll 1
  for (int pass = 0; pass < 2; pass++) {
    const int row0 = blockIdx.x * 512 + (pass * 4 + wg) * 64;
    uint32_t q[4];
    bool bad;
    {
      const uint32_t* qp = (const uint32_t*)g_Q + (size_t)(row0 + w4 * 16 + g) * 8 + t;
      uint32_t r[4] = {qp[0], qp[64], qp[4], qp[68]};
      float n0 = 0.f, n1 = 0.f;
#pragma unroll
      for (int i = 0; i < 4; i++) {
        float a = bf_lo(r[i]) * QSCALE, b = bf_hi(r[i]) * QSCALE;
        q[i] = pack_f16(a, b);
        if (i & 1) n1 += a * a + b * b; else n0 += a * a + b * b;
      }
      n0 += __shfl_xor_sync(~0u, n0, 1); n0 += __shfl_xor_sync(~0u, n0, 2);
      n1 += __shfl_xor_sync(~0u, n1, 1); n1 += __shfl_xor_sync(~0u, n1, 2);
      float n = fmaxf(n0, n1);
      bad = !(n0 <= 65536.f && n1 <= 65536.f && lim > 0.f && n * kmax2 * 1.01f <= lim * lim);
    }
    uint32_t anybad;
    asm volatile("{\n.reg .pred p, q;\nsetp.ne.u32 p, %1, 0;\nbarrier.cta.red.or.pred q, %2, 128, p;\nselp.u32 %0, 1, 0, q;\n}\n"
                 : "=r"(anybad) : "r"((uint32_t)bad), "r"(wg + 1) : "memory");
    if (__any_sync(~0u, anybad)) {
      for (int c = 0; c < 4; c++) mbar_wait(bars + 8 * c, 0);
      attn_slow(row0, sV);
      continue;
    }
    float Sm[16], Sp[32], O[12];
    uint32_t P[24];
#pragma unroll
    for (int i = 0; i < 32; i++) Sp[i] = SMAGIC;
#pragma unroll
    for (int i = 0; i < 16; i++) Sm[i] = 0.f;
#pragma unroll
    for (int i = 0; i < 12; i++) O[i] = 0.f;
    fence_regs<16>(Sm); fence_regs<32>(Sp); fence_regs<12>(O); fence_regs<4>(q);
    mbar_wait(bars, 0);
    if (tid == 0) TS(1, 2 + 2 * pass);
    wg_fence();
    wg_qk32<0>(Sm, q, dK0);
    wg_qk64<1>(Sp, q, dK0 + 32);
    wg_commit();
    wg_wait<0>();
    fence_regs<16>(Sm); fence_regs<32>(Sp);
    uint64_t dK = dK0 + STEPK, dV = dV0;
    int nextw = 1, wb = 1;
#pragma unroll 1
    for (int s = 0; s < 21; s++) {
#pragma unroll
      for (int i = 0; i < 8; i++) P[i] = pack_bf16(ex2f(Sm[2 * i]), ex2f(Sm[2 * i + 1]));
#pragma unroll
      for (int i = 0; i < 16; i++) P[8 + i] = exp2_pair_fix(Sp[2 * i], Sp[2 * i + 1], one);
      fence_regs<24>(P);
      if (s == nextw) { mbar_wait(bars + 8 * wb, 0); nextw = nextw * 2 + 3; wb++; }
      wg_fence();
      wg_qk32<0>(Sm, q, dK);
      wg_qk64<1>(Sp, q, dK + 32);
#pragma unroll
      for (int k = 0; k < 6; k++) wg_pv24<1>(O, &P[4 * k], dV + k * 16);
      wg_commit();
      wg_wait<0>();
      fence_regs<16>(Sm); fence_regs<32>(Sp); fence_regs<12>(O); fence_regs<24>(P);
      dK += STEPK; dV += STEPK;
    }
#pragma unroll
    for (int i = 0; i < 8; i++) P[i] = pack_bf16(ex2f(Sm[2 * i]), ex2f(Sm[2 * i + 1]));
    fence_regs<8>(P);
    wg_fence();
    wg_pv24<1>(O, &P[0], dV);
    wg_pv24<1>(O, &P[4], dV + 16);
    wg_commit();
    wg_wait<0>();
    fence_regs<12>(O);
    const float l0 = __shfl_sync(~0u, O[8], lane & ~3), l1 = __shfl_sync(~0u, O[10], lane & ~3);
    const float i0 = 1.f / l0, i1 = 1.f / l1;
    uint32_t* op = (uint32_t*)g_O + (size_t)(row0 + w4 * 16 + g) * 8 + t;
    op[0] = pack_bf16(O[0] * i0, O[1] * i0);
    op[64] = pack_bf16(O[2] * i1, O[3] * i1);
    op[4] = pack_bf16(O[4] * i0, O[5] * i0);
    op[68] = pack_bf16(O[6] * i1, O[7] * i1);
    if (tid == 0) TS(1, 3 + 2 * pass);
    if (tid == 384) TS(1, 6 + pass);
  }
}

#define K3_SMEM (131072 + 6 * 16384 + 1024 + 256)
__global__ void __cluster_dims__(2, 1, 1) __launch_bounds__(288, 1)
k3_out(const __grid_constant__ CUtensorMap mO, const __grid_constant__ CUtensorMap mWoA,
       const __grid_constant__ CUtensorMap mWoB, const __grid_constant__ CUtensorMap mOut) {
  extern __shared__ uint8_t smem_raw[];
  const uint32_t sb = (smem_u32(smem_raw) + 1023u) & ~1023u;
  const uint32_t sW = sb, sA = sb + 131072, bars = sA + 6 * 16384;
  const int tid = threadIdx.x, wg = tid >> 7, warp = tid >> 5, lane = tid & 31;
  const int rank = blockIdx.x & 1;
  const int nt = (blockIdx.x & 7);
  const int tt = blockIdx.x >> 3;
  const int part = nt >> 2;
  if (tid == 0) TS(2, 0);
  if (tid == 0) {
    for (int s = 0; s < 14; s++) mbar_init(bars + 8 * s, 1);
    mbar_init(bars + 112, 4); mbar_init(bars + 120, 4);
    asm volatile("fence.mbarrier_init.release.cluster;" ::: "memory");
  }
  cluster_sync();
  if (wg == 2) {
    if (lane == 0) {
      const CUtensorMap* mW = part ? &mWoB : &mWoA;
      const int col = (nt & 3) * 128;
      for (int kb = 0; kb < 8; kb++) {
        mbar_expect_tx(bars + 8 * kb, 16384);
        tma2d(sW + kb * 16384, mW, col, kb * 64, bars + 8 * kb);
        tma2d(sW + kb * 16384 + 8192, mW, col + 64, kb * 64, bars + 8 * kb);
      }
      pdl_wait();
      TS(2, 1);
      const int row = part * S_TOK + tt * 128 + rank * 64;
      for (int kb = 0; kb < 8; kb++) {
        const int s = kb < 6 ? kb : kb - 6;
        if (kb >= 6) mbar_wait(bars + 112 + 8 * s, 0);
        mbar_expect_tx(bars + 64 + 8 * s, 16384);
        tma2d_mc(sA + s * 16384 + rank * 8192, &mO, kb * 64, row, bars + 64 + 8 * s, 3);
      }
    }
  } else {
    float acc[64];
#pragma unroll
    for (int kb = 0; kb < 8; kb++) {
      const int s = kb < 6 ? kb : kb - 6;
      mbar_wait(bars + 8 * kb, 0);
      mbar_wait(bars + 64 + 8 * s, kb >= 6);
      if (tid == 0) TS(2, 2 + kb);
      uint64_t da = make_desc(sA + s * 16384 + wg * 8192, 16, 1024, 1);
      uint64_t db = make_desc(sW + kb * 16384, 8192, 1024, 1);
      wg_fence();
#pragma unroll
      for (int k = 0; k < 4; k++) wg_ss128<0, 1>(acc, da + k * 2, db + k * 128, (kb | k) != 0);
      wg_commit();
      if (kb == 1 || kb == 2) {
        wg_wait<1>();
        if ((tid & 127) == 0) { mbar_arrive_cta(bars + 112 + 8 * (kb - 1), 0); mbar_arrive_cta(bars + 112 + 8 * (kb - 1), 1); }
        __syncwarp();
      }
    }
    wg_wait<0>();
    fence_regs<64>(acc);
    const int w4 = warp & 3, m = lane >> 3, r = lane & 7;
#pragma unroll
    for (int j = 0; j < 16; j += 2) {
      const uint32_t stg = sA + (2 + (j >> 3)) * 16384 + wg * 8192;
      const int row = w4 * 16 + (m & 1) * 8 + r;
      const int chunk = (j & 7) + (m >> 1);
      stsm4(stg + row * 128 + ((chunk ^ r) << 4),
            pack_bf16(acc[4 * j], acc[4 * j + 1]), pack_bf16(acc[4 * j + 2], acc[4 * j + 3]),
            pack_bf16(acc[4 * j + 4], acc[4 * j + 5]), pack_bf16(acc[4 * j + 6], acc[4 * j + 7]));
    }
    fence_async();
    named_bar(wg + 1, 128);
    if ((tid & 127) == 0) {
      tma2d_store(&mOut, sA + 2 * 16384 + wg * 8192, nt * 128, tt * 128 + wg * 64);
      tma2d_store(&mOut, sA + 3 * 16384 + wg * 8192, nt * 128 + 64, tt * 128 + wg * 64);
      if (tid == 0) TS(2, 11);
      bulk_commit();
      bulk_wait_all();
      if (tid == 0) TS(2, 12);
    }
  }
}

typedef CUresult (*EncodeFn)(CUtensorMap*, CUtensorMapDataType, cuuint32_t, void*, const cuuint64_t*, const cuuint64_t*,
                             const cuuint32_t*, const cuuint32_t*, CUtensorMapInterleave, CUtensorMapSwizzle,
                             CUtensorMapL2promotion, CUtensorMapFloatOOBfill);

static void make_map(EncodeFn enc, CUtensorMap* m, const void* ptr, uint64_t cols, uint64_t rows, uint32_t bc, uint32_t br) {
  cuuint64_t dims[2] = {cols, rows};
  cuuint64_t strides[1] = {cols * 2};
  cuuint32_t box[2] = {bc, br};
  cuuint32_t es[2] = {1, 1};
  enc(m, CU_TENSOR_MAP_DATA_TYPE_BFLOAT16, 2, (void*)ptr, dims, strides, box, es, CU_TENSOR_MAP_INTERLEAVE_NONE,
      CU_TENSOR_MAP_SWIZZLE_128B, CU_TENSOR_MAP_L2_PROMOTION_L2_256B, CU_TENSOR_MAP_FLOAT_OOB_FILL_NONE);
}

extern "C" void kernel_launch(void* const* d_in, const int* in_sizes, int n_in, void* d_out, int out_size) {
  (void)in_sizes; (void)n_in; (void)out_size;
  static EncodeFn enc = nullptr;
  static void* pQ = nullptr; static void* pO = nullptr;
  if (!enc) {
    void* fn = nullptr; cudaDriverEntryPointQueryResult qr;
    cudaGetDriverEntryPoint("cuTensorMapEncodeTiled", &fn, cudaEnableDefault, &qr);
    enc = (EncodeFn)fn;
    cudaGetSymbolAddress(&pQ, g_Q);
    cudaGetSymbolAddress(&pO, g_O);
    cudaFuncSetAttribute(k1_proj, cudaFuncAttributeMaxDynamicSharedMemorySize, K1_SMEM);
    cudaFuncSetAttribute(k2_attn, cudaFuncAttributeMaxDynamicSharedMemorySize, K2_SMEM);
    cudaFuncSetAttribute(k3_out, cudaFuncAttributeMaxDynamicSharedMemorySize, K3_SMEM);
  }
  CUtensorMap mXA, mXB, mWq, mWqkv, mQst, mO, mOst, mWoA, mWoB, mOut;
  make_map(enc, &mXA, d_in[0], 512, 2048, 64, 128);
  make_map(enc, &mWq, d_in[1], 512, 512, 64, 64);
  make_map(enc, &mWoA, d_in[4], 512, 512, 64, 64);
  make_map(enc, &mXB, d_in[5], 512, 2048, 64, 128);
  make_map(enc, &mWqkv, d_in[6], 1536, 512, 64, 64);
  make_map(enc, &mWoB, d_in[7], 512, 512, 64, 64);
  make_map(enc, &mQst, pQ, 512, 4096, 64, 128);
  make_map(enc, &mO, pO, 512, 4096, 64, 64);
  make_map(enc, &mOst, pO, 512, 4096, 64, 128);
  make_map(enc, &mOut, d_out, 1024, 2048, 64, 64);
  K1Params prm{(const __nv_bfloat16*)d_in[2], (const __nv_bfloat16*)d_in[3]};

  cudaStream_t st = cudaStreamPerThread;
  cudaLaunchAttribute at[1];
  at[0].id = cudaLaunchAttributeProgrammaticStreamSerialization;
  at[0].val.programmaticStreamSerializationAllowed = 1;
  cudaLaunchConfig_t cfg = {};
  cfg.stream = st;
  cfg.gridDim = dim3(128); cfg.blockDim = dim3(384); cfg.dynamicSmemBytes = K1_SMEM; cfg.attrs = at; cfg.numAttrs = 0;
  cudaLaunchKernelEx(&cfg, k1_proj, mXA, mXB, mWq, mWqkv, mQst, prm);
  cfg.gridDim = dim3(132); cfg.blockDim = dim3(512); cfg.dynamicSmemBytes = K2_SMEM; cfg.numAttrs = 1;
  cudaLaunchKernelEx(&cfg, k2_attn, mQst, mOst);
  cfg.gridDim = dim3(128); cfg.blockDim = dim3(288); cfg.dynamicSmemBytes = K3_SMEM; cfg.numAttrs = 1;
  cudaLaunchKernelEx(&cfg, k3_out, mO, mWoA, mWoB, mOut);
}
```

```cpp
#include <cuda_runtime.h>
#include <cuda_bf16.h>
#include <cuda_fp16.h>
#include <cuda.h>
#include <stdint.h>

#define S_TOK 2048
#define D_MOD 512

__device__ __align__(1024) __nv_bfloat16 g_Q[2 * S_TOK * D_MOD];
__device__ __align__(1024) __nv_bfloat16 g_O[2 * S_TOK * D_MOD];
__device__ __align__(1024) uint4 g_KV[8 * S_TOK];
__device__ __align__(16) uint2 g_stats[64];
__device__ __align__(16) float4 g_kvp[16 * 32 * 3 * 32];

#define TS(k, i) do {} while (0)
__device__ __forceinline__ uint32_t smem_u32(const void* p) { return (uint32_t)__cvta_generic_to_shared(p); }
__device__ __forceinline__ void mbar_init(uint32_t bar, int cnt) { asm volatile("mbarrier.init.shared::cta.b64 [%0], %1;" :: "r"(bar), "r"(cnt) : "memory"); }
__device__ __forceinline__ void mbar_expect_tx(uint32_t bar, uint32_t bytes) { asm volatile("mbarrier.arrive.expect_tx.shared::cta.b64 _, [%0], %1;" :: "r"(bar), "r"(bytes) : "memory"); }
__device__ __forceinline__ bool mbar_try(uint32_t bar, uint32_t parity) {
  uint32_t ok;
  asm volatile("{\n.reg .pred p;\nmbarrier.try_wait.parity.shared::cta.b64 p, [%1], %2;\nselp.b32 %0, 1, 0, p;\n}\n" : "=r"(ok) : "r"(bar), "r"(parity) : "memory");
  return ok;
}
__device__ __forceinline__ void mbar_wait(uint32_t bar, uint32_t parity) {
  asm volatile("{\n.reg .pred p;\n.reg .u32 c;\nmov.u32 c, 0;\n"
               "LW_%=:\n"
               "mbarrier.try_wait.parity.shared::cta.b64 p, [%0], %1;\n"
               "@p bra LD_%=;\n"
               "add.u32 c, c, 1;\n"
               "setp.lt.u32 p, c, 4000000;\n"
               "@p bra LW_%=;\n"
               "trap;\n"
               "LD_%=:\n}\n" :: "r"(bar), "r"(parity) : "memory");
}
__device__ __forceinline__ void mbar_arrive_cta(uint32_t bar, uint32_t cta) {
  asm volatile("{\n.reg .b32 ra;\nmapa.shared::cluster.u32 ra, %0, %1;\nmbarrier.arrive.shared::cluster.b64 _, [ra];\n}\n" :: "r"(bar), "r"(cta) : "memory");
}
__device__ __forceinline__ void cluster_sync() {
  asm volatile("barrier.cluster.arrive.relaxed.aligned;\nbarrier.cluster.wait.aligned;" ::: "memory");
}
__device__ __forceinline__ void tma2d(uint32_t dst, const CUtensorMap* m, int c0, int c1, uint32_t bar) {
  asm volatile("cp.async.bulk.tensor.2d.shared::cluster.global.mbarrier::complete_tx::bytes [%0], [%1, {%3, %4}], [%2];"
               :: "r"(dst), "l"(m), "r"(bar), "r"(c0), "r"(c1) : "memory");
}
__device__ __forceinline__ void tma2d_mc(uint32_t dst, const CUtensorMap* m, int c0, int c1, uint32_t bar, uint16_t mask) {
  asm volatile("cp.async.bulk.tensor.2d.shared::cluster.global.mbarrier::complete_tx::bytes.multicast::cluster [%0], [%1, {%3, %4}], [%2], %5;"
               :: "r"(dst), "l"(m), "r"(bar), "r"(c0), "r"(c1), "h"(mask) : "memory");
}
__device__ __forceinline__ void tma2d_store(const CUtensorMap* m, uint32_t src, int c0, int c1) {
  asm volatile("cp.async.bulk.tensor.2d.global.shared::cta.bulk_group [%0, {%2, %3}], [%1];"
               :: "l"(m), "r"(src), "r"(c0), "r"(c1) : "memory");
}
__device__ __forceinline__ void bulk_g2s(uint32_t dst, const void* src, uint32_t bytes, uint32_t bar) {
  asm volatile("cp.async.bulk.shared::cluster.global.mbarrier::complete_tx::bytes [%0], [%1], %2, [%3];"
               :: "r"(dst), "l"(src), "r"(bytes), "r"(bar) : "memory");
}
__device__ __forceinline__ void bulk_commit() { asm volatile("cp.async.bulk.commit_group;" ::: "memory"); }
__device__ __forceinline__ void bulk_wait_all() { asm volatile("cp.async.bulk.wait_group 0;" ::: "memory"); }
__device__ __forceinline__ void fence_async() { asm volatile("fence.proxy.async.shared::cta;" ::: "memory"); }
__device__ __forceinline__ void named_bar(int id, int n) { asm volatile("bar.sync %0, %1;" :: "r"(id), "r"(n) : "memory"); }
__device__ __forceinline__ void pdl_launch() { asm volatile("griddepcontrol.launch_dependents;" ::: "memory"); }
__device__ __forceinline__ void pdl_wait() { asm volatile("griddepcontrol.wait;" ::: "memory"); }
__device__ __forceinline__ void wg_fence() { asm volatile("wgmma.fence.sync.aligned;" ::: "memory"); }
__device__ __forceinline__ void wg_commit() { asm volatile("wgmma.commit_group.sync.aligned;" ::: "memory"); }
template <int n> __device__ __forceinline__ void wg_wait() { asm volatile("wgmma.wait_group.sync.aligned %0;" :: "n"(n) : "memory"); }
template <int n> __device__ __forceinline__ void fence_regs(float* r) {
#pragma unroll
  for (int i = 0; i < n; i++) asm volatile("" : "+f"(r[i]) :: "memory");
}
template <int n> __device__ __forceinline__ void fence_regs(uint32_t* r) {
#pragma unroll
  for (int i = 0; i < n; i++) asm volatile("" : "+r"(r[i]) :: "memory");
}
__device__ __forceinline__ uint64_t make_desc(uint32_t addr, uint32_t lbo, uint32_t sbo, uint32_t swz) {
  return (uint64_t)((addr & 0x3FFFF) >> 4) | ((uint64_t)(lbo >> 4) << 16) | ((uint64_t)(sbo >> 4) << 32) | ((uint64_t)swz << 62);
}
__device__ __forceinline__ float ex2f(float x) { float y; asm("ex2.approx.ftz.f32 %0, %1;" : "=f"(y) : "f"(x)); return y; }
__device__ __forceinline__ uint32_t pack_bf16(float lo, float hi) { uint32_t r; asm("cvt.rn.bf16x2.f32 %0, %1, %2;" : "=r"(r) : "f"(hi), "f"(lo)); return r; }
__device__ __forceinline__ uint32_t pack_f16(float lo, float hi) { uint32_t r; asm("cvt.rn.f16x2.f32 %0, %1, %2;" : "=r"(r) : "f"(hi), "f"(lo)); return r; }
__device__ __forceinline__ float bf_lo(uint32_t v) { return __uint_as_float(v << 16); }
__device__ __forceinline__ float bf_hi(uint32_t v) { return __uint_as_float(v & 0xFFFF0000u); }
__device__ __forceinline__ float rbf(float x) { return __bfloat162float(__float2bfloat16_rn(x)); }
__device__ __forceinline__ void stsm4(uint32_t a, uint32_t r0, uint32_t r1, uint32_t r2, uint32_t r3) {
  asm volatile("stmatrix.sync.aligned.m8n8.x4.shared.b16 [%0], {%1,%2,%3,%4};" :: "r"(a), "r"(r0), "r"(r1), "r"(r2), "r"(r3) : "memory");
}
__device__ __forceinline__ void stsm4t(uint32_t a, uint32_t r0, uint32_t r1, uint32_t r2, uint32_t r3) {
  asm volatile("stmatrix.sync.aligned.m8n8.x4.trans.shared.b16 [%0], {%1,%2,%3,%4};" :: "r"(a), "r"(r0), "r"(r1), "r"(r2), "r"(r3) : "memory");
}
__device__ __forceinline__ void mma_bf16(float* d, uint32_t a0, uint32_t a1, uint32_t a2, uint32_t a3, uint32_t b0, uint32_t b1) {
  asm volatile("mma.sync.aligned.m16n8k16.row.col.f32.bf16.bf16.f32 {%0,%1,%2,%3}, {%4,%5,%6,%7}, {%8,%9}, {%0,%1,%2,%3};"
               : "+f"(d[0]), "+f"(d[1]), "+f"(d[2]), "+f"(d[3]) : "r"(a0), "r"(a1), "r"(a2), "r"(a3), "r"(b0), "r"(b1));
}
template<int SD> __device__ __forceinline__ void wg_qk32(float* d, const uint32_t* a, uint64_t desc) {
  asm volatile("wgmma.mma_async.sync.aligned.m64n32k16.f32.f16.f16 {%0,%1,%2,%3,%4,%5,%6,%7,%8,%9,%10,%11,%12,%13,%14,%15}, {%16,%17,%18,%19}, %20, %21, 1, 1, 0;"
   : "+f"(d[0]),"+f"(d[1]),"+f"(d[2]),"+f"(d[3]),"+f"(d[4]),"+f"(d[5]),"+f"(d[6]),"+f"(d[7]),"+f"(d[8]),"+f"(d[9]),"+f"(d[10]),"+f"(d[11]),"+f"(d[12]),"+f"(d[13]),"+f"(d[14]),"+f"(d[15])
   : "r"(a[0]),"r"(a[1]),"r"(a[2]),"r"(a[3]),"l"(desc),"n"(SD));
}
template<int SD> __device__ __forceinline__ void wg_qk64(float* d, const uint32_t* a, uint64_t desc) {
  asm volatile("wgmma.mma_async.sync.aligned.m64n64k16.f32.f16.f16 {%0,%1,%2,%3,%4,%5,%6,%7,%8,%9,%10,%11,%12,%13,%14,%15,%16,%17,%18,%19,%20,%21,%22,%23,%24,%25,%26,%27,%28,%29,%30,%31}, {%32,%33,%34,%35}, %36, %37, 1, 1, 0;"
   : "+f"(d[0]),"+f"(d[1]),"+f"(d[2]),"+f"(d[3]),"+f"(d[4]),"+f"(d[5]),"+f"(d[6]),"+f"(d[7]),"+f"(d[8]),"+f"(d[9]),"+f"(d[10]),"+f"(d[11]),"+f"(d[12]),"+f"(d[13]),"+f"(d[14]),"+f"(d[15]),"+f"(d[16]),"+f"(d[17]),"+f"(d[18]),"+f"(d[19]),"+f"(d[20]),"+f"(d[21]),"+f"(d[22]),"+f"(d[23]),"+f"(d[24]),"+f"(d[25]),"+f"(d[26]),"+f"(d[27]),"+f"(d[28]),"+f"(d[29]),"+f"(d[30]),"+f"(d[31])
   : "r"(a[0]),"r"(a[1]),"r"(a[2]),"r"(a[3]),"l"(desc),"n"(SD));
}
template<int SD> __device__ __forceinline__ void wg_qs32(float* d, uint64_t da, uint64_t db) {
  asm volatile("wgmma.mma_async.sync.aligned.m64n32k16.f32.f16.f16 {%0,%1,%2,%3,%4,%5,%6,%7,%8,%9,%10,%11,%12,%13,%14,%15}, %16, %17, %18, 1, 1, 0, 0;"
   : "+f"(d[0]),"+f"(d[1]),"+f"(d[2]),"+f"(d[3]),"+f"(d[4]),"+f"(d[5]),"+f"(d[6]),"+f"(d[7]),"+f"(d[8]),"+f"(d[9]),"+f"(d[10]),"+f"(d[11]),"+f"(d[12]),"+f"(d[13]),"+f"(d[14]),"+f"(d[15])
   : "l"(da),"l"(db),"n"(SD));
}
template<int SD> __device__ __forceinline__ void wg_qs64(float* d, uint64_t da, uint64_t db) {
  asm volatile("wgmma.mma_async.sync.aligned.m64n64k16.f32.f16.f16 {%0,%1,%2,%3,%4,%5,%6,%7,%8,%9,%10,%11,%12,%13,%14,%15,%16,%17,%18,%19,%20,%21,%22,%23,%24,%25,%26,%27,%28,%29,%30,%31}, %32, %33, %34, 1, 1, 0, 0;"
   : "+f"(d[0]),"+f"(d[1]),"+f"(d[2]),"+f"(d[3]),"+f"(d[4]),"+f"(d[5]),"+f"(d[6]),"+f"(d[7]),"+f"(d[8]),"+f"(d[9]),"+f"(d[10]),"+f"(d[11]),"+f"(d[12]),"+f"(d[13]),"+f"(d[14]),"+f"(d[15]),"+f"(d[16]),"+f"(d[17]),"+f"(d[18]),"+f"(d[19]),"+f"(d[20]),"+f"(d[21]),"+f"(d[22]),"+f"(d[23]),"+f"(d[24]),"+f"(d[25]),"+f"(d[26]),"+f"(d[27]),"+f"(d[28]),"+f"(d[29]),"+f"(d[30]),"+f"(d[31])
   : "l"(da),"l"(db),"n"(SD));
}
template<int SD> __device__ __forceinline__ void wg_pv24(float* d, const uint32_t* a, uint64_t desc) {
  asm volatile("wgmma.mma_async.sync.aligned.m64n24k16.f32.bf16.bf16 {%0,%1,%2,%3,%4,%5,%6,%7,%8,%9,%10,%11}, {%12,%13,%14,%15}, %16, %17, 1, 1, 1;"
   : "+f"(d[0]),"+f"(d[1]),"+f"(d[2]),"+f"(d[3]),"+f"(d[4]),"+f"(d[5]),"+f"(d[6]),"+f"(d[7]),"+f"(d[8]),"+f"(d[9]),"+f"(d[10]),"+f"(d[11])
   : "r"(a[0]),"r"(a[1]),"r"(a[2]),"r"(a[3]),"l"(desc),"n"(SD));
}
template<int TA, int TB> __device__ __forceinline__ void wg_ss128(float* d, uint64_t da, uint64_t db, int sd) {
  asm volatile("{\n.reg .pred p;\nsetp.ne.b32 p, %66, 0;\n"
   "wgmma.mma_async.sync.aligned.m64n128k16.f32.bf16.bf16 {%0,%1,%2,%3,%4,%5,%6,%7,%8,%9,%10,%11,%12,%13,%14,%15,%16,%17,%18,%19,%20,%21,%22,%23,%24,%25,%26,%27,%28,%29,%30,%31,%32,%33,%34,%35,%36,%37,%38,%39,%40,%41,%42,%43,%44,%45,%46,%47,%48,%49,%50,%51,%52,%53,%54,%55,%56,%57,%58,%59,%60,%61,%62,%63}, %64, %65, p, 1, 1, %67, %68;\n}\n"
   : "+f"(d[0]),"+f"(d[1]),"+f"(d[2]),"+f"(d[3]),"+f"(d[4]),"+f"(d[5]),"+f"(d[6]),"+f"(d[7]),"+f"(d[8]),"+f"(d[9]),"+f"(d[10]),"+f"(d[11]),"+f"(d[12]),"+f"(d[13]),"+f"(d[14]),"+f"(d[15]),"+f"(d[16]),"+f"(d[17]),"+f"(d[18]),"+f"(d[19]),"+f"(d[20]),"+f"(d[21]),"+f"(d[22]),"+f"(d[23]),"+f"(d[24]),"+f"(d[25]),"+f"(d[26]),"+f"(d[27]),"+f"(d[28]),"+f"(d[29]),"+f"(d[30]),"+f"(d[31]),"+f"(d[32]),"+f"(d[33]),"+f"(d[34]),"+f"(d[35]),"+f"(d[36]),"+f"(d[37]),"+f"(d[38]),"+f"(d[39]),"+f"(d[40]),"+f"(d[41]),"+f"(d[42]),"+f"(d[43]),"+f"(d[44]),"+f"(d[45]),"+f"(d[46]),"+f"(d[47]),"+f"(d[48]),"+f"(d[49]),"+f"(d[50]),"+f"(d[51]),"+f"(d[52]),"+f"(d[53]),"+f"(d[54]),"+f"(d[55]),"+f"(d[56]),"+f"(d[57]),"+f"(d[58]),"+f"(d[59]),"+f"(d[60]),"+f"(d[61]),"+f"(d[62]),"+f"(d[63])
   : "l"(da),"l"(db),"r"(sd),"n"(TA),"n"(TB));
}
template<int TA, int TB> __device__ __forceinline__ void wg_ss64(float* d, uint64_t da, uint64_t db, int sd) {
  asm volatile("{\n.reg .pred p;\nsetp.ne.b32 p, %34, 0;\n"
   "wgmma.mma_async.sync.aligned.m64n64k16.f32.bf16.bf16 {%0,%1,%2,%3,%4,%5,%6,%7,%8,%9,%10,%11,%12,%13,%14,%15,%16,%17,%18,%19,%20,%21,%22,%23,%24,%25,%26,%27,%28,%29,%30,%31}, %32, %33, p, 1, 1, %35, %36;\n}\n"
   : "+f"(d[0]),"+f"(d[1]),"+f"(d[2]),"+f"(d[3]),"+f"(d[4]),"+f"(d[5]),"+f"(d[6]),"+f"(d[7]),"+f"(d[8]),"+f"(d[9]),"+f"(d[10]),"+f"(d[11]),"+f"(d[12]),"+f"(d[13]),"+f"(d[14]),"+f"(d[15]),"+f"(d[16]),"+f"(d[17]),"+f"(d[18]),"+f"(d[19]),"+f"(d[20]),"+f"(d[21]),"+f"(d[22]),"+f"(d[23]),"+f"(d[24]),"+f"(d[25]),"+f"(d[26]),"+f"(d[27]),"+f"(d[28]),"+f"(d[29]),"+f"(d[30]),"+f"(d[31])
   : "l"(da),"l"(db),"r"(sd),"n"(TA),"n"(TB));
}

__device__ __forceinline__ uint32_t phi2(float a, float b) {
  uint32_t r, e;
  asm("cvt.rn.relu.bf16x2.f32 %0, %1, %2;" : "=r"(r) : "f"(b), "f"(a));
  e = pack_bf16(ex2f(a * 1.4426950408889634f), ex2f(b * 1.4426950408889634f));
  asm("add.rn.bf16x2 %0, %0, %1;" : "+r"(e) : "r"(0x35863586u));
  asm("min.NaN.bf16x2 %0, %0, %1;" : "+r"(e) : "r"(0x3F803F80u));
  asm("add.rn.bf16x2 %0, %0, %1;" : "+r"(e) : "r"(r));
  return e;
}

__device__ __forceinline__ void mbar_arrive(uint32_t bar) { asm volatile("mbarrier.arrive.shared::cta.b64 _, [%0];" :: "r"(bar) : "memory"); }
__device__ __forceinline__ void named_arrive(int id, int n) { asm volatile("bar.arrive %0, %1;" :: "r"(id), "r"(n) : "memory"); }
__device__ __forceinline__ void fence_async_all() { asm volatile("fence.proxy.async;" ::: "memory"); }
__device__ __forceinline__ void flag_add(uint32_t* f) { asm volatile("fence.acq_rel.gpu;\nred.relaxed.gpu.global.add.u32 [%0], 1;" :: "l"(f) : "memory"); }
__device__ __forceinline__ void flag_wait(const uint32_t* f, uint32_t target) {
  uint32_t v;
  for (int it = 0;; it++) {
    asm volatile("ld.acquire.gpu.global.u32 %0, [%1];" : "=r"(v) : "l"(f) : "memory");
    if ((int32_t)(v - target) >= 0) break;
    if (it > 2000000) __trap();
  }
}
__device__ __forceinline__ void lds4(uint32_t a, uint32_t* r) {
  asm volatile("ld.shared.v4.b32 {%0,%1,%2,%3}, [%4];" : "=r"(r[0]), "=r"(r[1]), "=r"(r[2]), "=r"(r[3]) : "r"(a) : "memory");
}
__device__ __forceinline__ void sts4(uint32_t a, uint32_t r0, uint32_t r1, uint32_t r2, uint32_t r3) {
  asm volatile("st.shared.v4.b32 [%0], {%1,%2,%3,%4};" :: "r"(a), "r"(r0), "r"(r1), "r"(r2), "r"(r3) : "memory");
}
__device__ __forceinline__ void ldsm4(uint32_t a, uint32_t* r) {
  asm volatile("ldmatrix.sync.aligned.m8n8.x4.shared.b16 {%0,%1,%2,%3}, [%4];" : "=r"(r[0]), "=r"(r[1]), "=r"(r[2]), "=r"(r[3]) : "r"(a) : "memory");
}
__device__ __forceinline__ float rcpf(float x) { float y; asm("rcp.approx.ftz.f32 %0, %1;" : "=f"(y) : "f"(x)); return y; }

#define STEPK 96
#define QSCALE 0.36067376022224085f
#define SMAGIC (512.0f + 2.0f * (191.0f - 30.0f - 1.5823545f))
#define VSHIFT 1073741824.0f

__device__ uint32_t g_epoch[132];
__device__ uint32_t g_flag[64 * 32];
#define FLAG_KV 0
#define FLAG_B(h) (1 + (h))

#define SM_TOTAL (224 * 1024 + 1024 + 1024)
#define OFF_K 0
#define OFF_F 65536
#define OFF_V 131072
#define OFF_MISC (224 * 1024)

__device__ __forceinline__ uint32_t exp2_pair_fix(float d0, float d1, uint32_t c63, uint32_t m1) {
  uint32_t w, y, s, r;
  asm("prmt.b32 %0, %1, %2, 0x6521;" : "=r"(w) : "r"(__float_as_uint(d0)), "r"(__float_as_uint(d1)));
  asm("lop3.b32 %0, %1, 0x007F007F, %2, 0xEA;" : "=r"(y) : "r"(w), "r"(c63));
  asm("mad.lo.u32 %0, %1, %2, %3;" : "=r"(s) : "r"(y), "r"(m1), "r"(w));
  asm("fma.rn.bf16x2 %0, %1, %2, %3;" : "=r"(r) : "r"(w), "r"(y), "r"(s));
  return r;
}

__device__ __noinline__ void attn_slow(uint32_t sQ, __nv_bfloat16* dst) {
  const int t = threadIdx.x & 127;
  const int row = t >> 1, half = t & 1;
  float q[16];
#pragma unroll
  for (int i = 0; i < 4; i++) {
    uint32_t v[4];
    lds4(sQ + ((row >> 4) * 32 + (row & 7) * 4 + i) * 16, v);
    const uint32_t lo = (row & 8) ? v[1] : v[0], hi = (row & 8) ? v[3] : v[2];
    q[2 * i] = bf_lo(lo); q[2 * i + 1] = bf_hi(lo); q[2 * i + 8] = bf_lo(hi); q[2 * i + 9] = bf_hi(hi);
  }
  float m = -INFINITY, l = 0.f, o[16];
#pragma unroll
  for (int i = 0; i < 16; i++) o[i] = 0.f;
  for (int j = half * 1024; j < half * 1024 + 1024; j++) {
    uint4 ka = g_KV[4 * S_TOK + j], kb = g_KV[5 * S_TOK + j];
    uint4 va = g_KV[6 * S_TOK + j], vb = g_KV[7 * S_TOK + j];
    uint32_t kk[8] = {ka.x, ka.y, ka.z, ka.w, kb.x, kb.y, kb.z, kb.w};
    uint32_t vv[8] = {va.x, va.y, va.z, va.w, vb.x, vb.y, vb.z, vb.w};
    float s = 0.f;
#pragma unroll
    for (int i = 0; i < 8; i++) { s = fmaf(q[2 * i], bf_lo(kk[i]), s); s = fmaf(q[2 * i + 1], bf_hi(kk[i]), s); }
    s = rbf(s) * 0.25f;
    if (s > m) {
      float c = __expf(m - s);
      l *= c;
#pragma unroll
      for (int i = 0; i < 16; i++) o[i] *= c;
      m = s;
    }
    float p = __expf(s - m);
    l += p;
#pragma unroll
    for (int i = 0; i < 8; i++) { o[2 * i] = fmaf(p, bf_lo(vv[i]), o[2 * i]); o[2 * i + 1] = fmaf(p, bf_hi(vv[i]), o[2 * i + 1]); }
  }
  float m2 = __shfl_xor_sync(~0u, m, 1);
  float mm = fmaxf(m, m2);
  float c = __expf(m - mm);
  l *= c; l += __shfl_xor_sync(~0u, l, 1);
  float inv = 1.f / l;
  uint32_t r[8];
#pragma unroll
  for (int i = 0; i < 16; i++) { o[i] *= c; o[i] += __shfl_xor_sync(~0u, o[i], 1); o[i] *= inv; }
#pragma unroll
  for (int i = 0; i < 8; i++) r[i] = pack_bf16(o[2 * i], o[2 * i + 1]);
  uint4* d = (uint4*)(dst + (size_t)row * D_MOD);
  if (half == 0) d[0] = make_uint4(r[0], r[1], r[2], r[3]); else d[1] = make_uint4(r[4], r[5], r[6], r[7]);
}

struct Params { const __nv_bfloat16* wk; const __nv_bfloat16* wv; };

#define BAR_FULL(s) (bars + 8 * (s))
#define BAR_EMPTY(s) (bars + 24 + 8 * (s))
#define BAR_KV(c) (bars + 48 + 8 * (c))
#define BAR_BDONE (bars + 80)
#define BAR_Q (bars + 88)
#define BAR_LM(i) (bars + 96 + 8 * (i))

__device__ __forceinline__ void helper_cta(const int h, const uint32_t sb, const uint32_t bars,
                                           const CUtensorMap* mQ, const CUtensorMap* mOs) {
  const int tid = threadIdx.x, warp = __shfl_sync(~0u, tid >> 5, 0), wg = warp >> 2, w4 = warp & 3, lane = tid & 31;
  const uint32_t sW = sb, st0 = sb + 32768;
  {
    float acc[64];
#pragma unroll
    for (int kb = 0; kb < 8; kb++) {
      const int s = kb % 3;
      mbar_wait(BAR_FULL(s), (kb / 3) & 1);
      uint64_t da = make_desc(sW + kb * 1024, 128, 8192, 0);
      uint64_t db = make_desc(st0 + s * 65536 + wg * 16384, 16, 1024, 1);
      wg_fence();
#pragma unroll
      for (int k = 0; k < 4; k++) wg_ss128<1, 0>(acc, da + k * 16, db + k * 2, (kb | k) != 0);
      wg_commit();
      wg_wait<0>();
      fence_regs<64>(acc);
      if (kb < 5 && (tid & 127) == 0) mbar_arrive(BAR_EMPTY(s));
      __syncwarp();
    }
    const uint32_t stg = st0 + 2 * 65536 + wg * 16384;
    if (w4 < 2) {
      const int m = lane >> 3, r = lane & 7;
      float run0 = 0.f, run1 = 0.f;
#pragma unroll
      for (int j = 0; j < 16; j += 2) {
        uint32_t p[4], hh[4];
#pragma unroll
        for (int u = 0; u < 4; u++) p[u] = pack_bf16(acc[4 * j + 2 * u], acc[4 * j + 2 * u + 1]);
        const uint32_t a = stg + w4 * 4096 + ((j + (m >> 1)) * 8 + r) * 32 + (m & 1) * 16;
        stsm4t(a + 8192, p[0], p[1], p[2], p[3]);
#pragma unroll
        for (int u = 0; u < 4; u++) {
          const int i = 2 * j + (u >> 1) * 2;
          float k0 = bf_lo(p[u]), k1 = bf_hi(p[u]);
          if (w4 == 0) {
            float& run = (u & 1) ? run1 : run0;
            if (i < 21) { k0 = __half2float(__float2half_rn(2.f * k0 - run)); run += k0; }
            if (i + 1 < 21) { k1 = __half2float(__float2half_rn(2.f * k1 - run)); run += k1; }
            hh[u] = pack_f16(k0, k1);
          } else {
            hh[u] = pack_bf16(i < 21 ? k0 * VSHIFT : k0, i + 1 < 21 ? k1 * VSHIFT : k1);
          }
        }
        stsm4t(a, hh[0], hh[1], hh[2], hh[3]);
      }
    }
    named_bar(wg + 1, 128);
    const int tok = tid & 127;
    const int i = ((tok >> 3) << 1) | (tok & 1);
    const int ch = (h * 4 + wg) * 4 + ((tok & 7) >> 1);
    int kap;
    if (i < 21) kap = i * STEPK + 32 + ch;
    else { int idx = ch * 11 + (i - 21); kap = (idx >> 5) * STEPK + (idx & 31); }
    float n2 = 0.f, vm = 0.f;
#pragma unroll
    for (int a = 0; a < 4; a++) {
#pragma unroll
      for (int hf = 0; hf < 2; hf++) {
        uint32_t v[4];
        lds4(stg + a * 4096 + tok * 32 + hf * 16, v);
        g_KV[(a * 2 + hf) * S_TOK + kap] = make_uint4(v[0], v[1], v[2], v[3]);
#pragma unroll
        for (int u = 0; u < 4; u++) {
          float x = bf_lo(v[u]), y = bf_hi(v[u]);
          if (a == 2) n2 += x * x + y * y;
          if (a == 3) vm += fabsf(x) + fabsf(y);
        }
      }
    }
    uint32_t un = __reduce_max_sync(~0u, __float_as_uint(n2) & 0x7FFFFFFFu);
    uint32_t uv = __reduce_max_sync(~0u, __float_as_uint(vm) & 0x7FFFFFFFu);
    if (lane == 0) g_stats[h * 16 + warp] = make_uint2(un, uv);
    __syncwarp();
    if (lane == 0) mbar_arrive(BAR_BDONE);
  }
  mbar_wait(BAR_KV(0), 0);
  const int cb = wg & 1, col = h * 128 + cb * 64, row0 = S_TOK + (wg >> 1) * 1024;
  const uint32_t buf = sb + wg * 49152;
  if ((tid & 127) == 0) {
    fence_async_all();
    for (int u = 0; u < 3; u++) {
      mbar_expect_tx(BAR_LM(wg * 3 + u), 16384);
      tma2d(buf + u * 16384, mQ, col, row0 + u * 128, BAR_LM(wg * 3 + u));
    }
  }
  const int head = h * 8 + cb * 4 + w4;
  float4 a0 = make_float4(0, 0, 0, 0), a1 = a0, a2 = a0;
#pragma unroll 8
  for (int tt = 0; tt < 16; tt++) {
    const float4* src = g_kvp + ((tt * 32 + head) * 3) * 32 + lane;
    float4 u = src[0], v = src[32], w = src[64];
    a0.x += u.x; a0.y += u.y; a0.z += u.z; a0.w += u.w;
    a1.x += v.x; a1.y += v.y; a1.z += v.z; a1.w += v.w;
    a2.x += w.x; a2.y += w.y; a2.z += w.z; a2.w += w.w;
  }
  const uint32_t b00 = pack_bf16(a0.x, a0.y), b01 = pack_bf16(a0.z, a0.w);
  const uint32_t b10 = pack_bf16(a1.x, a1.y), b11 = pack_bf16(a1.z, a1.w);
  const uint32_t bz0 = pack_bf16(a2.x, a2.y), bz1 = pack_bf16(a2.z, a2.w);
  const int m = lane >> 3, r = lane & 7;
  const uint32_t off = ((m & 1) * 8 + r) * 128 + (((w4 * 2 + (m >> 1)) ^ r) << 4);
  int s = 0, ph = 0;
#pragma unroll 1
  for (int u = 0; u < 8; u++) {
    const uint32_t bb = buf + s * 16384;
    mbar_wait(BAR_LM(wg * 3 + s), ph);
#pragma unroll
    for (int mt = 0; mt < 8; mt++) {
      uint32_t a[4];
      ldsm4(bb + mt * 2048 + off, a);
      float n0[4] = {0, 0, 0, 0}, n1[4] = {0, 0, 0, 0}, dn[4] = {0, 0, 0, 0};
      mma_bf16(dn, a[0], a[1], a[2], a[3], bz0, bz1);
      mma_bf16(n0, a[0], a[1], a[2], a[3], b00, b01);
      mma_bf16(n1, a[0], a[1], a[2], a[3], b10, b11);
      const float i0 = rcpf(dn[0] + 1e-6f), i1 = rcpf(dn[2] + 1e-6f);
      stsm4(bb + mt * 2048 + off, pack_bf16(n0[0] * i0, n0[1] * i0), pack_bf16(n0[2] * i1, n0[3] * i1),
            pack_bf16(n1[0] * i0, n1[1] * i0), pack_bf16(n1[2] * i1, n1[3] * i1));
    }
    fence_async();
    named_bar(wg + 1, 128);
    if ((tid & 127) == 0) {
      tma2d_store(mOs, bb, col, row0 + u * 128);
      bulk_commit();
      if (u >= 1 && u + 2 < 8) {
        asm volatile("cp.async.bulk.wait_group.read 1;" ::: "memory");
        const int sp = s == 0 ? 2 : s - 1;
        mbar_expect_tx(BAR_LM(wg * 3 + sp), 16384);
        tma2d(buf + sp * 16384, mQ, col, row0 + (u + 2) * 128, BAR_LM(wg * 3 + sp));
      }
    }
    __syncwarp();
    if (++s == 3) { s = 0; ph ^= 1; }
  }
  if ((tid & 127) == 0) bulk_wait_all();
  if (tid == 0) TS(1, 8);
}

#define STAGE(s) (sb + (2 - (s)) * 65536)
template <int TR> __device__ __forceinline__ void proj_loop(float* acc, uint32_t sb, uint32_t bars, uint32_t offA, uint32_t offB) {
#pragma unroll
  for (int kb = 0; kb < 8; kb++) {
    const int s = kb % 3;
    const uint32_t st = STAGE(s);
    mbar_wait(BAR_FULL(s), (kb / 3) & 1);
    if (threadIdx.x == 0) TS(0, 2 + kb);
    const uint64_t da = make_desc(st + offA, TR ? 8192 : 16, 1024, 1);
    const uint64_t db = make_desc(st + offB, TR ? 16 : 8192, 1024, 1);
    wg_fence();
#pragma unroll
    for (int k = 0; k < 4; k++) wg_ss128<TR, 1 - TR>(acc, da + k * (TR ? 128 : 2), db + k * (TR ? 2 : 128), (kb | k) != 0);
    wg_commit();
    if (kb >= 1) {
      wg_wait<1>();
      if ((threadIdx.x & 127) == 0) mbar_arrive(BAR_EMPTY((kb - 1) % 3));
      __syncwarp();
    }
  }
  wg_wait<0>();
  fence_regs<64>(acc);
}

__global__ void __launch_bounds__(640, 1)
k1_main(const __grid_constant__ CUtensorMap mXA64, const __grid_constant__ CUtensorMap mXA128, const __grid_constant__ CUtensorMap mXB,
        const __grid_constant__ CUtensorMap mWq, const __grid_constant__ CUtensorMap mWqkv,
        const __grid_constant__ CUtensorMap mQst, const __grid_constant__ CUtensorMap mOst, const Params prm) {
  extern __shared__ uint8_t smem_raw[];
  const uint32_t sb = (smem_u32(smem_raw) + 1023u) & ~1023u;
  const uint32_t bars = sb + OFF_MISC, sStat = bars + 256;
  const int tid = threadIdx.x, warp = __shfl_sync(~0u, tid >> 5, 0), wg = warp >> 2, w4 = warp & 3, lane = tid & 31;
  const bool helper = blockIdx.x >= 128;
  if (tid == 0) TS(0, 0);
  const int G = blockIdx.x >> 4, gi = blockIdx.x & 15;
  const int tbA = G * 4 + (gi >> 2), hg = gi & 3;
  const int ttB = (G >> 1) * 4 + (gi >> 2), hq = (G & 1) * 4 + (gi & 3);
  auto issue = [&](int kb) {
    const int s = kb % 3;
    const uint32_t fb = BAR_FULL(s);
    mbar_expect_tx(fb, 65536);
    if (helper) {
      for (int w = 0; w < 4; w++) tma2d(sb + 32768 + s * 65536 + w * 16384, &mXA128, kb * 64, ((blockIdx.x - 128) * 4 + w) * 128, fb);
    } else {
      const uint32_t st = STAGE(s);
      tma2d(st + 16384, &mXA64, kb * 64, tbA * 64, fb);
      tma2d(st, &mWq, hg * 128, kb * 64, fb);
      tma2d(st + 8192, &mWq, hg * 128 + 64, kb * 64, fb);
      tma2d(st + 49152, &mXB, kb * 64, ttB * 128, fb);
      tma2d(st + 24576, &mWqkv, hq * 64, kb * 64, fb);
      tma2d(st + 32768, &mWqkv, 512 + hq * 64, kb * 64, fb);
      tma2d(st + 40960, &mWqkv, 1024 + hq * 64, kb * 64, fb);
    }
  };
  if (tid == 512) {
    for (int s = 0; s < 3; s++) { mbar_init(BAR_FULL(s), 1); mbar_init(BAR_EMPTY(s), 4); }
    for (int c = 0; c < 4; c++) mbar_init(BAR_KV(c), 1);
    mbar_init(BAR_BDONE, helper ? 16 : 8);
    mbar_init(BAR_Q, 4);
    for (int i = 0; i < 12; i++) mbar_init(BAR_LM(i), 1);
    asm volatile("fence.mbarrier_init.release.cluster;" ::: "memory");
    for (int kb = 0; kb < 3; kb++) issue(kb);
  } else if (tid < 512) {
    if (helper) {
#pragma unroll
      for (int i = 0; i < 4; i++) {
        int c = tid + i * 512;
        int mat = c >> 10, r = c & 1023;
        uint4 v = __ldg((const uint4*)(mat ? prm.wv : prm.wk) + r);
        sts4(sb + (mat * 2 + (r & 1)) * 8192 + (r >> 1) * 16, v.x, v.y, v.z, v.w);
      }
    } else {
#pragma unroll
      for (int i = 0; i < 4; i++) {
        const int key = tid + i * 512;
        sts4(sb + OFF_V + 65536 + key * 16, (key % STEPK) < 32 ? 0x00003F80u : 0x00004E80u, 0u, 0u, 0u);
      }
    }
    fence_async();
  }
  __syncthreads();
  pdl_launch();
  if (wg == 4) {
    asm volatile("setmaxnreg.dec.sync.aligned.u32 32;");
    if (tid == 512) {
      const uint32_t ep = g_epoch[blockIdx.x] + 1;
      for (int kb = 3; kb < 8; kb++) { mbar_wait(BAR_EMPTY(kb % 3), (kb / 3 - 1) & 1); issue(kb); }
      if (helper) {
        mbar_wait(BAR_BDONE, 0);
        fence_async_all();
        flag_add(&g_flag[FLAG_KV * 32]);
        TS(1, 9);
        flag_wait(&g_flag[FLAG_B(blockIdx.x - 128) * 32], ep * 32);
        fence_async_all();
        TS(1, 10);
        mbar_arrive(BAR_KV(0));
        g_epoch[blockIdx.x] = ep;
        return;
      }
      flag_wait(&g_flag[FLAG_KV * 32], ep * 4);
      fence_async_all();
      TS(0, 11);
      mbar_wait(BAR_EMPTY(2), 1);
      mbar_wait(BAR_EMPTY(0), 0);
      const int kbd[5] = {0, 2 * STEPK, 6 * STEPK, 14 * STEPK, S_TOK};
#pragma unroll
      for (int c = 0; c < 4; c++) {
        const uint32_t bytes = (kbd[c + 1] - kbd[c]) * 16;
        mbar_expect_tx(BAR_KV(c), 4 * bytes + (c == 0 ? 512 : 0));
        if (c == 0) bulk_g2s(sStat, g_stats, 512, BAR_KV(0));
#pragma unroll
        for (int p = 0; p < 4; p++)
          bulk_g2s(sb + (p < 2 ? OFF_K : OFF_V - 65536) + p * 32768 + kbd[c] * 16, g_KV + p * S_TOK + kbd[c], bytes, BAR_KV(c));
      }
      mbar_wait(BAR_BDONE, 0);
      tma2d_store(&mQst, sb + OFF_F + 49152, hq * 64, S_TOK + ttB * 128);
      bulk_commit();
      bulk_wait_all();
      fence_async_all();
      flag_add(&g_flag[FLAG_B(hq >> 1) * 32]);
      g_epoch[blockIdx.x] = ep;
      TS(0, 12);
    }
    return;
  }
  asm volatile("setmaxnreg.inc.sync.aligned.u32 112;");
  if (helper) { helper_cta(blockIdx.x - 128, sb, bars, &mQst, &mOst); return; }

  {
    float acc[64];
    if (wg == 0) proj_loop<0>(acc, sb, bars, 16384, 0);
    else proj_loop<1>(acc, sb, bars, 16384 + wg * 8192, 49152);
    if (tid == 0) TS(0, 10);
    const uint32_t sF = sb + OFF_F;
    if (wg == 0) {
#pragma unroll
      for (int hd = 0; hd < 8; hd++)
        sts4(sF + hd * 2048 + tid * 16, pack_bf16(acc[8 * hd], acc[8 * hd + 1]), pack_bf16(acc[8 * hd + 2], acc[8 * hd + 3]),
             pack_bf16(acc[8 * hd + 4], acc[8 * hd + 5]), pack_bf16(acc[8 * hd + 6], acc[8 * hd + 7]));
      __syncwarp();
      if (lane == 0) mbar_arrive(BAR_Q);
    } else if (wg == 3) {
      named_arrive(8, 384);
      named_bar(6, 384);
      const int t = tid & 127;
#pragma unroll
      for (int j = 0; j < 8; j++)
        sts4(sF + 24576 + j * 2048 + t * 16, pack_bf16(acc[8 * j], acc[8 * j + 1]), pack_bf16(acc[8 * j + 2], acc[8 * j + 3]),
             pack_bf16(acc[8 * j + 4], acc[8 * j + 5]), pack_bf16(acc[8 * j + 6], acc[8 * j + 7]));
      named_arrive(7, 256);
    } else {
      uint32_t p[32];
      named_arrive(6, 384);
      if (wg == 2) named_arrive(8, 384);
#pragma unroll
      for (int i = 0; i < 32; i++) p[i] = phi2(acc[2 * i], acc[2 * i + 1]);
      if (wg == 1) {
        named_bar(8, 384);
        const int m = lane >> 3, r = lane & 7;
#pragma unroll
        for (int j = 0; j < 16; j += 2) {
          const int tok = (j + (m >> 1)) * 8 + r;
          const int chunk = w4 * 2 + (m & 1);
          stsm4t(sF + 49152 + tok * 128 + ((chunk ^ r) << 4), p[2 * j], p[2 * j + 1], p[2 * j + 2], p[2 * j + 3]);
        }
        fence_async();
      } else {
        named_bar(7, 256);
        float kv0[4] = {0, 0, 0, 0}, kv1[4] = {0, 0, 0, 0}, z0[4] = {0, 0, 0, 0}, z1[4] = {0, 0, 0, 0};
        const uint32_t one = 0x3F803F80u;
        const int t = tid & 127;
#pragma unroll
        for (int j = 0; j < 8; j++) {
          uint32_t a[4];
          lds4(sF + 24576 + j * 2048 + t * 16, a);
          mma_bf16(kv0, a[0], a[1], a[2], a[3], p[4 * j], p[4 * j + 2]);
          mma_bf16(kv1, a[0], a[1], a[2], a[3], p[4 * j + 1], p[4 * j + 3]);
          mma_bf16(z0, one, one, one, one, p[4 * j], p[4 * j + 2]);
          mma_bf16(z1, one, one, one, one, p[4 * j + 1], p[4 * j + 3]);
        }
        float4* dst = g_kvp + ((ttB * 32 + hq * 4 + w4) * 3) * 32 + lane;
        dst[0] = make_float4(kv0[0], kv0[1], kv1[0], kv1[1]);
        dst[32] = make_float4(kv0[2], kv0[3], kv1[2], kv1[3]);
        dst[64] = make_float4(z0[0], z0[1], z1[0], z1[1]);
      }
      __syncwarp();
      if (lane == 0) mbar_arrive(BAR_BDONE);
    }
  }
  mbar_wait(BAR_Q, 0);

  mbar_wait(BAR_KV(0), 0);
  if (tid == 0) TS(1, 1);
  float lim, kmax2;
  {
    uint32_t a[4];
    lds4(sStat + lane * 16, a);
    kmax2 = __uint_as_float(__reduce_max_sync(~0u, max(a[0], a[2])));
    const float vmax = __uint_as_float(__reduce_max_sync(~0u, max(a[1], a[3])));
    const float lv = vmax > 0.f ? __log2f(vmax) : 0.f;
    lim = fminf(90.f, fminf(91.f + lv, 95.f - lv));
    if (!(vmax < 1e27f) || !(kmax2 <= 65536.f) || lim < 0.f) lim = -1.f;
  }
  const int g = lane >> 2, t = lane & 3;
  const uint32_t c63 = 0x1F801F80u + (uint32_t)(lim > 1e30f);
  const uint32_t m1 = (gridDim.x >> 20) - 1u;
  const uint32_t sQh = sb + OFF_F + 16384 + wg * 2048;
  const uint64_t dQ = make_desc(sQh, 128, 256, 0);
  const uint64_t dK0 = make_desc(sb + OFF_K, 32768, 128, 0);
  const uint64_t dV0 = make_desc(sb + OFF_V, 128, 32768, 0);

#pragma unroll 1
  for (int pass = 0; pass < 2; pass++) {
    const int hd = pass * 4 + wg;
    const uint32_t sQ = sb + OFF_F + hd * 2048;
    __nv_bfloat16* od = g_O + (size_t)(tbA * 64) * D_MOD + (hg * 8 + hd) * 16;
    bool bad;
    {
      uint32_t r[4];
      lds4(sQ + (tid & 127) * 16, r);
      float n0 = 0.f, n1 = 0.f;
#pragma unroll
      for (int i = 0; i < 4; i++) {
        float a = bf_lo(r[i]) * QSCALE, b = bf_hi(r[i]) * QSCALE;
        asm volatile("st.shared.b32 [%0], %1;" :: "r"(sQh + w4 * 512 + lane * 4 + (i & 1) * 256 + (i >> 1) * 128), "r"(pack_f16(a, b)) : "memory");
        if (i & 1) n1 += a * a + b * b; else n0 += a * a + b * b;
      }
      n0 += __shfl_xor_sync(~0u, n0, 1); n0 += __shfl_xor_sync(~0u, n0, 2);
      n1 += __shfl_xor_sync(~0u, n1, 1); n1 += __shfl_xor_sync(~0u, n1, 2);
      float n = fmaxf(n0, n1);
      bad = !(n0 <= 65536.f && n1 <= 65536.f && lim > 0.f && n * kmax2 * 1.01f <= lim * lim);
    }
    fence_async();
    uint32_t anybad;
    asm volatile("{\n.reg .pred p, q;\nsetp.ne.u32 p, %1, 0;\nbarrier.cta.red.or.pred q, %2, 128, p;\nselp.u32 %0, 1, 0, q;\n}\n"
                 : "=r"(anybad) : "r"((uint32_t)bad), "r"(wg + 1) : "memory");
    if (__any_sync(~0u, anybad)) {
      attn_slow(sQ, od);
      continue;
    }
    float Sm[16], Sp[32], O[12];
    uint32_t P[24];
#pragma unroll
    for (int i = 0; i < 32; i++) Sp[i] = SMAGIC;
#pragma unroll
    for (int i = 0; i < 16; i++) Sm[i] = 0.f;
#pragma unroll
    for (int i = 0; i < 12; i++) O[i] = 0.f;
    fence_regs<16>(Sm); fence_regs<32>(Sp); fence_regs<12>(O);
    if (tid == 0) TS(1, 2 + 2 * pass);
    wg_fence();
    wg_qs32<0>(Sm, dQ, dK0);
    wg_qs64<1>(Sp, dQ, dK0 + 32);
    wg_commit();
    wg_wait<0>();
    fence_regs<16>(Sm); fence_regs<32>(Sp);
    uint64_t dK = dK0 + STEPK, dV = dV0;
    int nextw = 1, wb = 1;
#pragma unroll 1
    for (int s = 0; s < 21; s++) {
#pragma unroll
      for (int i = 0; i < 8; i++) P[i] = pack_bf16(ex2f(Sm[2 * i]), ex2f(Sm[2 * i + 1]));
#pragma unroll
      for (int i = 0; i < 16; i++) P[8 + i] = exp2_pair_fix(Sp[2 * i], Sp[2 * i + 1], c63, m1);
      fence_regs<24>(P);
      if (s == nextw) { mbar_wait(BAR_KV(wb), 0); nextw = nextw * 2 + 3; wb++; }
      wg_fence();
      wg_qs32<0>(Sm, dQ, dK);
      wg_qs64<1>(Sp, dQ, dK + 32);
#pragma unroll
      for (int k = 0; k < 6; k++) wg_pv24<1>(O, &P[4 * k], dV + k * 16);
      wg_commit();
      wg_wait<0>();
      fence_regs<16>(Sm); fence_regs<32>(Sp); fence_regs<12>(O); fence_regs<24>(P);
      dK += STEPK; dV += STEPK;
    }
#pragma unroll
    for (int i = 0; i < 8; i++) P[i] = pack_bf16(ex2f(Sm[2 * i]), ex2f(Sm[2 * i + 1]));
    fence_regs<8>(P);
    wg_fence();
    wg_pv24<1>(O, &P[0], dV);
    wg_pv24<1>(O, &P[4], dV + 16);
    wg_commit();
    wg_wait<0>();
    fence_regs<12>(O);
    const float l0 = __shfl_sync(~0u, O[8], lane & ~3), l1 = __shfl_sync(~0u, O[10], lane & ~3);
    const float i0 = rcpf(l0), i1 = rcpf(l1);
    uint32_t* op = (uint32_t*)(od + (size_t)(w4 * 16 + g) * D_MOD) + t;
    op[0] = pack_bf16(O[0] * i0, O[1] * i0);
    op[8 * 256] = pack_bf16(O[2] * i1, O[3] * i1);
    op[4] = pack_bf16(O[4] * i0, O[5] * i0);
    op[8 * 256 + 4] = pack_bf16(O[6] * i1, O[7] * i1);
    if (tid == 0) TS(1, 3 + 2 * pass);
    if ((tid & 127) == 0 && pass == 1 && wg > 0) TS(1, 10 + wg);
  }
}

#define K3_SMEM (131072 + 6 * 16384 + 1024 + 256)
__global__ void __cluster_dims__(2, 1, 1) __launch_bounds__(288, 1)
k3_out(const __grid_constant__ CUtensorMap mO, const __grid_constant__ CUtensorMap mWoA,
       const __grid_constant__ CUtensorMap mWoB, const __grid_constant__ CUtensorMap mOut) {
  extern __shared__ uint8_t smem_raw[];
  const uint32_t sb = (smem_u32(smem_raw) + 1023u) & ~1023u;
  const uint32_t sW = sb, sA = sb + 131072, bars = sA + 6 * 16384;
  const int tid = threadIdx.x, wg = tid >> 7, warp = tid >> 5, lane = tid & 31;
  const int rank = blockIdx.x & 1;
  const int nt = (blockIdx.x & 7);
  const int tt = blockIdx.x >> 3;
  const int part = nt >> 2;
  if (tid == 0) TS(2, 0);
  if (tid == 0) {
    for (int s = 0; s < 14; s++) mbar_init(bars + 8 * s, 1);
    mbar_init(bars + 112, 4); mbar_init(bars + 120, 4);
    asm volatile("fence.mbarrier_init.release.cluster;" ::: "memory");
  }
  cluster_sync();
  if (wg == 2) {
    if (lane == 0) {
      const CUtensorMap* mW = part ? &mWoB : &mWoA;
      const int col = (nt & 3) * 128;
      for (int kb = 0; kb < 8; kb++) {
        mbar_expect_tx(bars + 8 * kb, 16384);
        tma2d(sW + kb * 16384, mW, col, kb * 64, bars + 8 * kb);
        tma2d(sW + kb * 16384 + 8192, mW, col + 64, kb * 64, bars + 8 * kb);
      }
      pdl_wait();
      TS(2, 1);
      const int row = part * S_TOK + tt * 128 + rank * 64;
      for (int kb = 0; kb < 8; kb++) {
        const int s = kb < 6 ? kb : kb - 6;
        if (kb >= 6) mbar_wait(bars + 112 + 8 * s, 0);
        mbar_expect_tx(bars + 64 + 8 * s, 16384);
        tma2d_mc(sA + s * 16384 + rank * 8192, &mO, kb * 64, row, bars + 64 + 8 * s, 3);
      }
    }
  } else {
    float acc[64];
#pragma unroll
    for (int kb = 0; kb < 8; kb++) {
      const int s = kb < 6 ? kb : kb - 6;
      mbar_wait(bars + 8 * kb, 0);
      mbar_wait(bars + 64 + 8 * s, kb >= 6);
      if (tid == 0) TS(2, 2 + kb);
      uint64_t da = make_desc(sA + s * 16384 + wg * 8192, 16, 1024, 1);
      uint64_t db = make_desc(sW + kb * 16384, 8192, 1024, 1);
      wg_fence();
#pragma unroll
      for (int k = 0; k < 4; k++) wg_ss128<0, 1>(acc, da + k * 2, db + k * 128, (kb | k) != 0);
      wg_commit();
      if (kb == 1 || kb == 2) {
        wg_wait<1>();
        if ((tid & 127) == 0) { mbar_arrive_cta(bars + 112 + 8 * (kb - 1), 0); mbar_arrive_cta(bars + 112 + 8 * (kb - 1), 1); }
        __syncwarp();
      }
    }
    wg_wait<0>();
    fence_regs<64>(acc);
    const int w4 = warp & 3, m = lane >> 3, r = lane & 7;
#pragma unroll
    for (int j = 0; j < 16; j += 2) {
      const uint32_t stg = sA + (2 + (j >> 3)) * 16384 + wg * 8192;
      const int row = w4 * 16 + (m & 1) * 8 + r;
      const int chunk = (j & 7) + (m >> 1);
      stsm4(stg + row * 128 + ((chunk ^ r) << 4),
            pack_bf16(acc[4 * j], acc[4 * j + 1]), pack_bf16(acc[4 * j + 2], acc[4 * j + 3]),
            pack_bf16(acc[4 * j + 4], acc[4 * j + 5]), pack_bf16(acc[4 * j + 6], acc[4 * j + 7]));
    }
    fence_async();
    named_bar(wg + 1, 128);
    if ((tid & 127) == 0) {
      tma2d_store(&mOut, sA + 2 * 16384 + wg * 8192, nt * 128, tt * 128 + wg * 64);
      tma2d_store(&mOut, sA + 3 * 16384 + wg * 8192, nt * 128 + 64, tt * 128 + wg * 64);
      if (tid == 0) TS(2, 11);
      bulk_commit();
      bulk_wait_all();
      if (tid == 0) TS(2, 12);
    }
  }
}

typedef CUresult (*EncodeFn)(CUtensorMap*, CUtensorMapDataType, cuuint32_t, void*, const cuuint64_t*, const cuuint64_t*,
                             const cuuint32_t*, const cuuint32_t*, CUtensorMapInterleave, CUtensorMapSwizzle,
                             CUtensorMapL2promotion, CUtensorMapFloatOOBfill);

static void make_map(EncodeFn enc, CUtensorMap* m, const void* ptr, uint64_t cols, uint64_t rows, uint32_t bc, uint32_t br) {
  cuuint64_t dims[2] = {cols, rows};
  cuuint64_t strides[1] = {cols * 2};
  cuuint32_t box[2] = {bc, br};
  cuuint32_t es[2] = {1, 1};
  enc(m, CU_TENSOR_MAP_DATA_TYPE_BFLOAT16, 2, (void*)ptr, dims, strides, box, es, CU_TENSOR_MAP_INTERLEAVE_NONE,
      CU_TENSOR_MAP_SWIZZLE_128B, CU_TENSOR_MAP_L2_PROMOTION_L2_256B, CU_TENSOR_MAP_FLOAT_OOB_FILL_NONE);
}

extern "C" void kernel_launch(void* const* d_in, const int* in_sizes, int n_in, void* d_out, int out_size) {
  (void)in_sizes; (void)n_in; (void)out_size;
  static EncodeFn enc = nullptr;
  static void* pQ = nullptr; static void* pO = nullptr;
  if (!enc) {
    void* fn = nullptr; cudaDriverEntryPointQueryResult qr;
    cudaGetDriverEntryPoint("cuTensorMapEncodeTiled", &fn, cudaEnableDefault, &qr);
    enc = (EncodeFn)fn;
    cudaGetSymbolAddress(&pQ, g_Q);
    cudaGetSymbolAddress(&pO, g_O);
    cudaFuncSetAttribute(k1_main, cudaFuncAttributeMaxDynamicSharedMemorySize, SM_TOTAL);
    cudaFuncSetAttribute(k3_out, cudaFuncAttributeMaxDynamicSharedMemorySize, K3_SMEM);
  }
  CUtensorMap mXA64, mXA128, mXB, mWq, mWqkv, mQst, mO, mOst, mWoA, mWoB, mOut;
  make_map(enc, &mXA64, d_in[0], 512, 2048, 64, 64);
  make_map(enc, &mXA128, d_in[0], 512, 2048, 64, 128);
  make_map(enc, &mWq, d_in[1], 512, 512, 64, 64);
  make_map(enc, &mWoA, d_in[4], 512, 512, 64, 64);
  make_map(enc, &mXB, d_in[5], 512, 2048, 64, 128);
  make_map(enc, &mWqkv, d_in[6], 1536, 512, 64, 64);
  make_map(enc, &mWoB, d_in[7], 512, 512, 64, 64);
  make_map(enc, &mQst, pQ, 512, 4096, 64, 128);
  make_map(enc, &mO, pO, 512, 4096, 64, 64);
  make_map(enc, &mOst, pO, 512, 4096, 64, 128);
  make_map(enc, &mOut, d_out, 1024, 2048, 64, 64);
  Params prm{(const __nv_bfloat16*)d_in[2], (const __nv_bfloat16*)d_in[3]};

  cudaStream_t st = cudaStreamPerThread;
  cudaLaunchAttribute at[1];
  at[0].id = cudaLaunchAttributeProgrammaticStreamSerialization;
  at[0].val.programmaticStreamSerializationAllowed = 1;
  cudaLaunchConfig_t cfg = {};
  cfg.stream = st;
  cfg.gridDim = dim3(132); cfg.blockDim = dim3(640); cfg.dynamicSmemBytes = SM_TOTAL; cfg.attrs = at; cfg.numAttrs = 0;
  cudaLaunchKernelEx(&cfg, k1_main, mXA64, mXA128, mXB, mWq, mWqkv, mQst, mOst, prm);
  cfg.gridDim = dim3(128); cfg.blockDim = dim3(288); cfg.dynamicSmemBytes = K3_SMEM; cfg.numAttrs = 1;
  cudaLaunchKernelEx(&cfg, k3_out, mO, mWoA, mWoB, mOut);
}
```

```cpp
#include <cuda_runtime.h>
#include <cuda_bf16.h>
#include <cuda_fp16.h>
#include <cuda.h>
#include <stdint.h>

#define S_TOK 2048
#define D_MOD 512

__device__ __align__(1024) __nv_bfloat16 g_Q[2 * S_TOK * D_MOD];
__device__ __align__(1024) __nv_bfloat16 g_O[2 * S_TOK * D_MOD];
__device__ __align__(1024) uint4 g_KV[8 * S_TOK];
__device__ __align__(16) uint32_t g_stats[128];
__device__ __align__(16) float4 g_kvp[16 * 32 * 3 * 32];

#define TS(k, i) do {} while (0)
__device__ __forceinline__ uint32_t smem_u32(const void* p) { return (uint32_t)__cvta_generic_to_shared(p); }
__device__ __forceinline__ void mbar_init(uint32_t bar, int cnt) { asm volatile("mbarrier.init.shared::cta.b64 [%0], %1;" :: "r"(bar), "r"(cnt) : "memory"); }
__device__ __forceinline__ void mbar_expect_tx(uint32_t bar, uint32_t bytes) { asm volatile("mbarrier.arrive.expect_tx.shared::cta.b64 _, [%0], %1;" :: "r"(bar), "r"(bytes) : "memory"); }
__device__ __forceinline__ bool mbar_try(uint32_t bar, uint32_t parity) {
  uint32_t ok;
  asm volatile("{\n.reg .pred p;\nmbarrier.try_wait.parity.shared::cta.b64 p, [%1], %2;\nselp.b32 %0, 1, 0, p;\n}\n" : "=r"(ok) : "r"(bar), "r"(parity) : "memory");
  return ok;
}
__device__ __forceinline__ void mbar_wait(uint32_t bar, uint32_t parity) {
  asm volatile("{\n.reg .pred p;\n.reg .u32 c;\nmov.u32 c, 0;\n"
               "LW_%=:\n"
               "mbarrier.try_wait.parity.shared::cta.b64 p, [%0], %1;\n"
               "@p bra LD_%=;\n"
               "add.u32 c, c, 1;\n"
               "setp.lt.u32 p, c, 4000000;\n"
               "@p bra LW_%=;\n"
               "trap;\n"
               "LD_%=:\n}\n" :: "r"(bar), "r"(parity) : "memory");
}
__device__ __forceinline__ void mbar_arrive_cta(uint32_t bar, uint32_t cta) {
  asm volatile("{\n.reg .b32 ra;\nmapa.shared::cluster.u32 ra, %0, %1;\nmbarrier.arrive.shared::cluster.b64 _, [ra];\n}\n" :: "r"(bar), "r"(cta) : "memory");
}
__device__ __forceinline__ void cluster_sync() {
  asm volatile("barrier.cluster.arrive.relaxed.aligned;\nbarrier.cluster.wait.aligned;" ::: "memory");
}
__device__ __forceinline__ void tma2d(uint32_t dst, const CUtensorMap* m, int c0, int c1, uint32_t bar) {
  asm volatile("cp.async.bulk.tensor.2d.shared::cluster.global.mbarrier::complete_tx::bytes [%0], [%1, {%3, %4}], [%2];"
               :: "r"(dst), "l"(m), "r"(bar), "r"(c0), "r"(c1) : "memory");
}
__device__ __forceinline__ void tma2d_mc(uint32_t dst, const CUtensorMap* m, int c0, int c1, uint32_t bar, uint16_t mask) {
  asm volatile("cp.async.bulk.tensor.2d.shared::cluster.global.mbarrier::complete_tx::bytes.multicast::cluster [%0], [%1, {%3, %4}], [%2], %5;"
               :: "r"(dst), "l"(m), "r"(bar), "r"(c0), "r"(c1), "h"(mask) : "memory");
}
__device__ __forceinline__ void tma2d_store(const CUtensorMap* m, uint32_t src, int c0, int c1) {
  asm volatile("cp.async.bulk.tensor.2d.global.shared::cta.bulk_group [%0, {%2, %3}], [%1];"
               :: "l"(m), "r"(src), "r"(c0), "r"(c1) : "memory");
}
__device__ __forceinline__ void bulk_g2s(uint32_t dst, const void* src, uint32_t bytes, uint32_t bar) {
  asm volatile("cp.async.bulk.shared::cluster.global.mbarrier::complete_tx::bytes [%0], [%1], %2, [%3];"
               :: "r"(dst), "l"(src), "r"(bytes), "r"(bar) : "memory");
}
__device__ __forceinline__ void bulk_commit() { asm volatile("cp.async.bulk.commit_group;" ::: "memory"); }
__device__ __forceinline__ void bulk_wait_all() { asm volatile("cp.async.bulk.wait_group 0;" ::: "memory"); }
__device__ __forceinline__ void fence_async() { asm volatile("fence.proxy.async.shared::cta;" ::: "memory"); }
__device__ __forceinline__ void named_bar(int id, int n) { asm volatile("bar.sync %0, %1;" :: "r"(id), "r"(n) : "memory"); }
__device__ __forceinline__ void pdl_launch() { asm volatile("griddepcontrol.launch_dependents;" ::: "memory"); }
__device__ __forceinline__ void pdl_wait() { asm volatile("griddepcontrol.wait;" ::: "memory"); }
__device__ __forceinline__ void wg_fence() { asm volatile("wgmma.fence.sync.aligned;" ::: "memory"); }
__device__ __forceinline__ void wg_commit() { asm volatile("wgmma.commit_group.sync.aligned;" ::: "memory"); }
template <int n> __device__ __forceinline__ void wg_wait() { asm volatile("wgmma.wait_group.sync.aligned %0;" :: "n"(n) : "memory"); }
template <int n> __device__ __forceinline__ void fence_regs(float* r) {
#pragma unroll
  for (int i = 0; i < n; i++) asm volatile("" : "+f"(r[i]) :: "memory");
}
template <int n> __device__ __forceinline__ void fence_regs(uint32_t* r) {
#pragma unroll
  for (int i = 0; i < n; i++) asm volatile("" : "+r"(r[i]) :: "memory");
}
__device__ __forceinline__ uint64_t make_desc(uint32_t addr, uint32_t lbo, uint32_t sbo, uint32_t swz) {
  return (uint64_t)((addr & 0x3FFFF) >> 4) | ((uint64_t)(lbo >> 4) << 16) | ((uint64_t)(sbo >> 4) << 32) | ((uint64_t)swz << 62);
}
__device__ __forceinline__ float ex2f(float x) { float y; asm("ex2.approx.ftz.f32 %0, %1;" : "=f"(y) : "f"(x)); return y; }
__device__ __forceinline__ uint32_t pack_bf16(float lo, float hi) { uint32_t r; asm("cvt.rn.bf16x2.f32 %0, %1, %2;" : "=r"(r) : "f"(hi), "f"(lo)); return r; }
__device__ __forceinline__ uint32_t pack_f16(float lo, float hi) { uint32_t r; asm("cvt.rn.f16x2.f32 %0, %1, %2;" : "=r"(r) : "f"(hi), "f"(lo)); return r; }
__device__ __forceinline__ float bf_lo(uint32_t v) { return __uint_as_float(v << 16); }
__device__ __forceinline__ float bf_hi(uint32_t v) { return __uint_as_float(v & 0xFFFF0000u); }
__device__ __forceinline__ float rbf(float x) { return __bfloat162float(__float2bfloat16_rn(x)); }
__device__ __forceinline__ void stsm4(uint32_t a, uint32_t r0, uint32_t r1, uint32_t r2, uint32_t r3) {
  asm volatile("stmatrix.sync.aligned.m8n8.x4.shared.b16 [%0], {%1,%2,%3,%4};" :: "r"(a), "r"(r0), "r"(r1), "r"(r2), "r"(r3) : "memory");
}
__device__ __forceinline__ void stsm4t(uint32_t a, uint32_t r0, uint32_t r1, uint32_t r2, uint32_t r3) {
  asm volatile("stmatrix.sync.aligned.m8n8.x4.trans.shared.b16 [%0], {%1,%2,%3,%4};" :: "r"(a), "r"(r0), "r"(r1), "r"(r2), "r"(r3) : "memory");
}
__device__ __forceinline__ void mma_bf16(float* d, uint32_t a0, uint32_t a1, uint32_t a2, uint32_t a3, uint32_t b0, uint32_t b1) {
  asm volatile("mma.sync.aligned.m16n8k16.row.col.f32.bf16.bf16.f32 {%0,%1,%2,%3}, {%4,%5,%6,%7}, {%8,%9}, {%0,%1,%2,%3};"
               : "+f"(d[0]), "+f"(d[1]), "+f"(d[2]), "+f"(d[3]) : "r"(a0), "r"(a1), "r"(a2), "r"(a3), "r"(b0), "r"(b1));
}
template<int SD> __device__ __forceinline__ void wg_qk32(float* d, const uint32_t* a, uint64_t desc) {
  asm volatile("wgmma.mma_async.sync.aligned.m64n32k16.f32.f16.f16 {%0,%1,%2,%3,%4,%5,%6,%7,%8,%9,%10,%11,%12,%13,%14,%15}, {%16,%17,%18,%19}, %20, %21, 1, 1, 0;"
   : "+f"(d[0]),"+f"(d[1]),"+f"(d[2]),"+f"(d[3]),"+f"(d[4]),"+f"(d[5]),"+f"(d[6]),"+f"(d[7]),"+f"(d[8]),"+f"(d[9]),"+f"(d[10]),"+f"(d[11]),"+f"(d[12]),"+f"(d[13]),"+f"(d[14]),"+f"(d[15])
   : "r"(a[0]),"r"(a[1]),"r"(a[2]),"r"(a[3]),"l"(desc),"n"(SD));
}
template<int SD> __device__ __forceinline__ void wg_qk64(float* d, const uint32_t* a, uint64_t desc) {
  asm volatile("wgmma.mma_async.sync.aligned.m64n64k16.f32.f16.f16 {%0,%1,%2,%3,%4,%5,%6,%7,%8,%9,%10,%11,%12,%13,%14,%15,%16,%17,%18,%19,%20,%21,%22,%23,%24,%25,%26,%27,%28,%29,%30,%31}, {%32,%33,%34,%35}, %36, %37, 1, 1, 0;"
   : "+f"(d[0]),"+f"(d[1]),"+f"(d[2]),"+f"(d[3]),"+f"(d[4]),"+f"(d[5]),"+f"(d[6]),"+f"(d[7]),"+f"(d[8]),"+f"(d[9]),"+f"(d[10]),"+f"(d[11]),"+f"(d[12]),"+f"(d[13]),"+f"(d[14]),"+f"(d[15]),"+f"(d[16]),"+f"(d[17]),"+f"(d[18]),"+f"(d[19]),"+f"(d[20]),"+f"(d[21]),"+f"(d[22]),"+f"(d[23]),"+f"(d[24]),"+f"(d[25]),"+f"(d[26]),"+f"(d[27]),"+f"(d[28]),"+f"(d[29]),"+f"(d[30]),"+f"(d[31])
   : "r"(a[0]),"r"(a[1]),"r"(a[2]),"r"(a[3]),"l"(desc),"n"(SD));
}
template<int SD> __device__ __forceinline__ void wg_qs32(float* d, uint64_t da, uint64_t db) {
  asm volatile("wgmma.mma_async.sync.aligned.m64n32k16.f32.f16.f16 {%0,%1,%2,%3,%4,%5,%6,%7,%8,%9,%10,%11,%12,%13,%14,%15}, %16, %17, %18, 1, 1, 0, 0;"
   : "+f"(d[0]),"+f"(d[1]),"+f"(d[2]),"+f"(d[3]),"+f"(d[4]),"+f"(d[5]),"+f"(d[6]),"+f"(d[7]),"+f"(d[8]),"+f"(d[9]),"+f"(d[10]),"+f"(d[11]),"+f"(d[12]),"+f"(d[13]),"+f"(d[14]),"+f"(d[15])
   : "l"(da),"l"(db),"n"(SD));
}
template<int SD> __device__ __forceinline__ void wg_qs64(float* d, uint64_t da, uint64_t db) {
  asm volatile("wgmma.mma_async.sync.aligned.m64n64k16.f32.f16.f16 {%0,%1,%2,%3,%4,%5,%6,%7,%8,%9,%10,%11,%12,%13,%14,%15,%16,%17,%18,%19,%20,%21,%22,%23,%24,%25,%26,%27,%28,%29,%30,%31}, %32, %33, %34, 1, 1, 0, 0;"
   : "+f"(d[0]),"+f"(d[1]),"+f"(d[2]),"+f"(d[3]),"+f"(d[4]),"+f"(d[5]),"+f"(d[6]),"+f"(d[7]),"+f"(d[8]),"+f"(d[9]),"+f"(d[10]),"+f"(d[11]),"+f"(d[12]),"+f"(d[13]),"+f"(d[14]),"+f"(d[15]),"+f"(d[16]),"+f"(d[17]),"+f"(d[18]),"+f"(d[19]),"+f"(d[20]),"+f"(d[21]),"+f"(d[22]),"+f"(d[23]),"+f"(d[24]),"+f"(d[25]),"+f"(d[26]),"+f"(d[27]),"+f"(d[28]),"+f"(d[29]),"+f"(d[30]),"+f"(d[31])
   : "l"(da),"l"(db),"n"(SD));
}
template<int SD> __device__ __forceinline__ void wg_pv24(float* d, const uint32_t* a, uint64_t desc) {
  asm volatile("wgmma.mma_async.sync.aligned.m64n24k16.f32.bf16.bf16 {%0,%1,%2,%3,%4,%5,%6,%7,%8,%9,%10,%11}, {%12,%13,%14,%15}, %16, %17, 1, 1, 1;"
   : "+f"(d[0]),"+f"(d[1]),"+f"(d[2]),"+f"(d[3]),"+f"(d[4]),"+f"(d[5]),"+f"(d[6]),"+f"(d[7]),"+f"(d[8]),"+f"(d[9]),"+f"(d[10]),"+f"(d[11])
   : "r"(a[0]),"r"(a[1]),"r"(a[2]),"r"(a[3]),"l"(desc),"n"(SD));
}
template<int TA, int TB> __device__ __forceinline__ void wg_ss128(float* d, uint64_t da, uint64_t db, int sd) {
  asm volatile("{\n.reg .pred p;\nsetp.ne.b32 p, %66, 0;\n"
   "wgmma.mma_async.sync.aligned.m64n128k16.f32.bf16.bf16 {%0,%1,%2,%3,%4,%5,%6,%7,%8,%9,%10,%11,%12,%13,%14,%15,%16,%17,%18,%19,%20,%21,%22,%23,%24,%25,%26,%27,%28,%29,%30,%31,%32,%33,%34,%35,%36,%37,%38,%39,%40,%41,%42,%43,%44,%45,%46,%47,%48,%49,%50,%51,%52,%53,%54,%55,%56,%57,%58,%59,%60,%61,%62,%63}, %64, %65, p, 1, 1, %67, %68;\n}\n"
   : "+f"(d[0]),"+f"(d[1]),"+f"(d[2]),"+f"(d[3]),"+f"(d[4]),"+f"(d[5]),"+f"(d[6]),"+f"(d[7]),"+f"(d[8]),"+f"(d[9]),"+f"(d[10]),"+f"(d[11]),"+f"(d[12]),"+f"(d[13]),"+f"(d[14]),"+f"(d[15]),"+f"(d[16]),"+f"(d[17]),"+f"(d[18]),"+f"(d[19]),"+f"(d[20]),"+f"(d[21]),"+f"(d[22]),"+f"(d[23]),"+f"(d[24]),"+f"(d[25]),"+f"(d[26]),"+f"(d[27]),"+f"(d[28]),"+f"(d[29]),"+f"(d[30]),"+f"(d[31]),"+f"(d[32]),"+f"(d[33]),"+f"(d[34]),"+f"(d[35]),"+f"(d[36]),"+f"(d[37]),"+f"(d[38]),"+f"(d[39]),"+f"(d[40]),"+f"(d[41]),"+f"(d[42]),"+f"(d[43]),"+f"(d[44]),"+f"(d[45]),"+f"(d[46]),"+f"(d[47]),"+f"(d[48]),"+f"(d[49]),"+f"(d[50]),"+f"(d[51]),"+f"(d[52]),"+f"(d[53]),"+f"(d[54]),"+f"(d[55]),"+f"(d[56]),"+f"(d[57]),"+f"(d[58]),"+f"(d[59]),"+f"(d[60]),"+f"(d[61]),"+f"(d[62]),"+f"(d[63])
   : "l"(da),"l"(db),"r"(sd),"n"(TA),"n"(TB));
}
template<int TA, int TB> __device__ __forceinline__ void wg_ss64(float* d, uint64_t da, uint64_t db, int sd) {
  asm volatile("{\n.reg .pred p;\nsetp.ne.b32 p, %34, 0;\n"
   "wgmma.mma_async.sync.aligned.m64n64k16.f32.bf16.bf16 {%0,%1,%2,%3,%4,%5,%6,%7,%8,%9,%10,%11,%12,%13,%14,%15,%16,%17,%18,%19,%20,%21,%22,%23,%24,%25,%26,%27,%28,%29,%30,%31}, %32, %33, p, 1, 1, %35, %36;\n}\n"
   : "+f"(d[0]),"+f"(d[1]),"+f"(d[2]),"+f"(d[3]),"+f"(d[4]),"+f"(d[5]),"+f"(d[6]),"+f"(d[7]),"+f"(d[8]),"+f"(d[9]),"+f"(d[10]),"+f"(d[11]),"+f"(d[12]),"+f"(d[13]),"+f"(d[14]),"+f"(d[15]),"+f"(d[16]),"+f"(d[17]),"+f"(d[18]),"+f"(d[19]),"+f"(d[20]),"+f"(d[21]),"+f"(d[22]),"+f"(d[23]),"+f"(d[24]),"+f"(d[25]),"+f"(d[26]),"+f"(d[27]),"+f"(d[28]),"+f"(d[29]),"+f"(d[30]),"+f"(d[31])
   : "l"(da),"l"(db),"r"(sd),"n"(TA),"n"(TB));
}

template<int TA, int TB> __device__ __forceinline__ void wg_ss8(float* d, uint64_t da, uint64_t db, int sd) {
  asm volatile("{\n.reg .pred p;\nsetp.ne.b32 p, %6, 0;\n"
   "wgmma.mma_async.sync.aligned.m64n8k16.f32.bf16.bf16 {%0,%1,%2,%3}, %4, %5, p, 1, 1, %7, %8;\n}\n"
   : "+f"(d[0]),"+f"(d[1]),"+f"(d[2]),"+f"(d[3])
   : "l"(da),"l"(db),"r"(sd),"n"(TA),"n"(TB));
}

__device__ __forceinline__ uint32_t phi2(float a, float b) {
  uint32_t r, e;
  asm("cvt.rn.relu.bf16x2.f32 %0, %1, %2;" : "=r"(r) : "f"(b), "f"(a));
  e = pack_bf16(ex2f(a * 1.4426950408889634f), ex2f(b * 1.4426950408889634f));
  asm("add.rn.bf16x2 %0, %0, %1;" : "+r"(e) : "r"(0x35863586u));
  asm("min.NaN.bf16x2 %0, %0, %1;" : "+r"(e) : "r"(0x3F803F80u));
  asm("add.rn.bf16x2 %0, %0, %1;" : "+r"(e) : "r"(r));
  return e;
}

__device__ __forceinline__ void mbar_arrive(uint32_t bar) { asm volatile("mbarrier.arrive.shared::cta.b64 _, [%0];" :: "r"(bar) : "memory"); }
__device__ __forceinline__ void named_arrive(int id, int n) { asm volatile("bar.arrive %0, %1;" :: "r"(id), "r"(n) : "memory"); }
__device__ __forceinline__ void fence_async_all() { asm volatile("fence.proxy.async;" ::: "memory"); }
__device__ __forceinline__ void flag_add(uint32_t* f) { asm volatile("fence.acq_rel.gpu;\nred.relaxed.gpu.global.add.u32 [%0], 1;" :: "l"(f) : "memory"); }
__device__ __forceinline__ void flag_wait(const uint32_t* f, uint32_t target) {
  uint32_t v;
  for (int it = 0;; it++) {
    asm volatile("ld.acquire.gpu.global.u32 %0, [%1];" : "=r"(v) : "l"(f) : "memory");
    if ((int32_t)(v - target) >= 0) break;
    if (it > 2000000) __trap();
  }
}
__device__ __forceinline__ void lds4(uint32_t a, uint32_t* r) {
  asm volatile("ld.shared.v4.b32 {%0,%1,%2,%3}, [%4];" : "=r"(r[0]), "=r"(r[1]), "=r"(r[2]), "=r"(r[3]) : "r"(a) : "memory");
}
__device__ __forceinline__ void sts4(uint32_t a, uint32_t r0, uint32_t r1, uint32_t r2, uint32_t r3) {
  asm volatile("st.shared.v4.b32 [%0], {%1,%2,%3,%4};" :: "r"(a), "r"(r0), "r"(r1), "r"(r2), "r"(r3) : "memory");
}
__device__ __forceinline__ void ldsm4(uint32_t a, uint32_t* r) {
  asm volatile("ldmatrix.sync.aligned.m8n8.x4.shared.b16 {%0,%1,%2,%3}, [%4];" : "=r"(r[0]), "=r"(r[1]), "=r"(r[2]), "=r"(r[3]) : "r"(a) : "memory");
}
__device__ __forceinline__ float rcpf(float x) { float y; asm("rcp.approx.ftz.f32 %0, %1;" : "=f"(y) : "f"(x)); return y; }

#define STEPK 96
#define UNR 3
#define QSCALE 0.36067376022224085f
#define SMAGIC (512.0f + 2.0f * (191.0f - 30.0f - 1.5823545f))
#define VSHIFT 1073741824.0f

__device__ uint32_t g_epoch[132];
__device__ uint32_t g_flag[64 * 32];
#define FLAG_KV 0
#define FLAG_B(h) (1 + (h))

#define SM_TOTAL (224 * 1024 + 2048 + 1024)
#define OFF_K 0
#define OFF_F 65536
#define OFF_V 131072
#define OFF_MISC (224 * 1024)

__device__ __forceinline__ uint32_t exp2_pair_fix(float d0, float d1, uint32_t c63, uint32_t m1) {
  uint32_t w, y, s, r;
  asm("prmt.b32 %0, %1, %2, 0x6521;" : "=r"(w) : "r"(__float_as_uint(d0)), "r"(__float_as_uint(d1)));
  asm("lop3.b32 %0, %1, 0x007F007F, %2, 0xEA;" : "=r"(y) : "r"(w), "r"(c63));
  asm("mad.lo.u32 %0, %1, %2, %3;" : "=r"(s) : "r"(y), "r"(m1), "r"(w));
  asm("fma.rn.bf16x2 %0, %1, %2, %3;" : "=r"(r) : "r"(w), "r"(y), "r"(s));
  return r;
}

__device__ __noinline__ void attn_slow(const uint4* gq, __nv_bfloat16* dst) {
  const int t = threadIdx.x & 127;
  const int row = t >> 1, half = t & 1;
  float q[16];
#pragma unroll
  for (int i = 0; i < 4; i++) {
    const uint4 v = gq[(row >> 4) * 32 + (row & 7) * 4 + i];
    const uint32_t lo = (row & 8) ? v.y : v.x, hi = (row & 8) ? v.w : v.z;
    q[2 * i] = bf_lo(lo); q[2 * i + 1] = bf_hi(lo); q[2 * i + 8] = bf_lo(hi); q[2 * i + 9] = bf_hi(hi);
  }
  float m = -INFINITY, l = 0.f, o[16];
#pragma unroll
  for (int i = 0; i < 16; i++) o[i] = 0.f;
  for (int j = half * 1024; j < half * 1024 + 1024; j++) {
    uint4 ka = g_KV[4 * S_TOK + j], kb = g_KV[5 * S_TOK + j];
    uint4 va = g_KV[6 * S_TOK + j], vb = g_KV[7 * S_TOK + j];
    uint32_t kk[8] = {ka.x, ka.y, ka.z, ka.w, kb.x, kb.y, kb.z, kb.w};
    uint32_t vv[8] = {va.x, va.y, va.z, va.w, vb.x, vb.y, vb.z, vb.w};
    float s = 0.f;
#pragma unroll
    for (int i = 0; i < 8; i++) { s = fmaf(q[2 * i], bf_lo(kk[i]), s); s = fmaf(q[2 * i + 1], bf_hi(kk[i]), s); }
    s = rbf(s) * 0.25f;
    if (s > m) {
      float c = __expf(m - s);
      l *= c;
#pragma unroll
      for (int i = 0; i < 16; i++) o[i] *= c;
      m = s;
    }
    float p = __expf(s - m);
    l += p;
#pragma unroll
    for (int i = 0; i < 8; i++) { o[2 * i] = fmaf(p, bf_lo(vv[i]), o[2 * i]); o[2 * i + 1] = fmaf(p, bf_hi(vv[i]), o[2 * i + 1]); }
  }
  float m2 = __shfl_xor_sync(~0u, m, 1);
  float mm = fmaxf(m, m2);
  float c = __expf(m - mm);
  l *= c; l += __shfl_xor_sync(~0u, l, 1);
  float inv = 1.f / l;
  uint32_t r[8];
#pragma unroll
  for (int i = 0; i < 16; i++) { o[i] *= c; o[i] += __shfl_xor_sync(~0u, o[i], 1); o[i] *= inv; }
#pragma unroll
  for (int i = 0; i < 8; i++) r[i] = pack_bf16(o[2 * i], o[2 * i + 1]);
  uint4* d = (uint4*)(dst + (size_t)row * D_MOD);
  if (half == 0) d[0] = make_uint4(r[0], r[1], r[2], r[3]); else d[1] = make_uint4(r[4], r[5], r[6], r[7]);
}

struct Params { const __nv_bfloat16* wk; const __nv_bfloat16* wv; };

#define BAR_FULL(s) (bars + 8 * (s))
#define BAR_EMPTY(s) (bars + 24 + 8 * (s))
#define BAR_KV(c) (bars + 48 + 8 * (c))
#define BAR_BDONE (bars + 80)
#define BAR_Q (bars + 88)
#define BAR_LM(i) (bars + 96 + 8 * (i))

__device__ __forceinline__ void helper_cta(const int h, const uint32_t sb, const uint32_t bars,
                                           const CUtensorMap* mQ, const CUtensorMap* mOs) {
  const int tid = threadIdx.x, warp = __shfl_sync(~0u, tid >> 5, 0), wg = warp >> 2, w4 = warp & 3, lane = tid & 31;
  mbar_wait(BAR_KV(0), 0);
  const int cb = wg & 1, col = h * 128 + cb * 64, row0 = S_TOK + (wg >> 1) * 1024;
  const uint32_t buf = sb + wg * 49152;
  if ((tid & 127) == 0) {
    fence_async_all();
    for (int u = 0; u < 3; u++) {
      mbar_expect_tx(BAR_LM(wg * 3 + u), 16384);
      tma2d(buf + u * 16384, mQ, col, row0 + u * 128, BAR_LM(wg * 3 + u));
    }
  }
  const int head = h * 8 + cb * 4 + w4;
  float4 a0 = make_float4(0, 0, 0, 0), a1 = a0, a2 = a0;
#pragma unroll 8
  for (int tt = 0; tt < 16; tt++) {
    const float4* src = g_kvp + ((tt * 32 + head) * 3) * 32 + lane;
    float4 u = src[0], v = src[32], w = src[64];
    a0.x += u.x; a0.y += u.y; a0.z += u.z; a0.w += u.w;
    a1.x += v.x; a1.y += v.y; a1.z += v.z; a1.w += v.w;
    a2.x += w.x; a2.y += w.y; a2.z += w.z; a2.w += w.w;
  }
  const uint32_t b00 = pack_bf16(a0.x, a0.y), b01 = pack_bf16(a0.z, a0.w);
  const uint32_t b10 = pack_bf16(a1.x, a1.y), b11 = pack_bf16(a1.z, a1.w);
  const uint32_t bz0 = pack_bf16(a2.x, a2.y), bz1 = pack_bf16(a2.z, a2.w);
  const int m = lane >> 3, r = lane & 7;
  const uint32_t off = ((m & 1) * 8 + r) * 128 + (((w4 * 2 + (m >> 1)) ^ r) << 4);
  int s = 0, ph = 0;
#pragma unroll 1
  for (int u = 0; u < 8; u++) {
    const uint32_t bb = buf + s * 16384;
    mbar_wait(BAR_LM(wg * 3 + s), ph);
#pragma unroll
    for (int mt = 0; mt < 8; mt++) {
      uint32_t a[4];
      ldsm4(bb + mt * 2048 + off, a);
      float n0[4] = {0, 0, 0, 0}, n1[4] = {0, 0, 0, 0}, dn[4] = {0, 0, 0, 0};
      mma_bf16(dn, a[0], a[1], a[2], a[3], bz0, bz1);
      mma_bf16(n0, a[0], a[1], a[2], a[3], b00, b01);
      mma_bf16(n1, a[0], a[1], a[2], a[3], b10, b11);
      const float i0 = rcpf(dn[0] + 1e-6f), i1 = rcpf(dn[2] + 1e-6f);
      stsm4(bb + mt * 2048 + off, pack_bf16(n0[0] * i0, n0[1] * i0), pack_bf16(n0[2] * i1, n0[3] * i1),
            pack_bf16(n1[0] * i0, n1[1] * i0), pack_bf16(n1[2] * i1, n1[3] * i1));
    }
    fence_async();
    named_bar(wg + 1, 128);
    if ((tid & 127) == 0) {
      tma2d_store(mOs, bb, col, row0 + u * 128);
      bulk_commit();
      if (u >= 1 && u + 2 < 8) {
        asm volatile("cp.async.bulk.wait_group.read 1;" ::: "memory");
        const int sp = s == 0 ? 2 : s - 1;
        mbar_expect_tx(BAR_LM(wg * 3 + sp), 16384);
        tma2d(buf + sp * 16384, mQ, col, row0 + (u + 2) * 128, BAR_LM(wg * 3 + sp));
      }
    }
    __syncwarp();
    if (++s == 3) { s = 0; ph ^= 1; }
  }
  if ((tid & 127) == 0) bulk_wait_all();
  if (tid == 0) TS(1, 8);
}

#define STAGE(s) (sb + (2 - (s)) * 65536)
template <int TR> __device__ __forceinline__ void proj_loop(float* acc, uint32_t sb, uint32_t bars, uint32_t offA, uint32_t offB) {
#pragma unroll
  for (int kb = 0; kb < 8; kb++) {
    const int s = kb % 3;
    const uint32_t st = STAGE(s);
    mbar_wait(BAR_FULL(s), (kb / 3) & 1);
    if (threadIdx.x == 0) TS(0, 2 + kb);
    const uint64_t da = make_desc(st + offA, TR ? 8192 : 16, 1024, 1);
    const uint64_t db = make_desc(st + offB, TR ? 16 : 8192, 1024, 1);
    wg_fence();
#pragma unroll
    for (int k = 0; k < 4; k++) wg_ss128<TR, 1 - TR>(acc, da + k * (TR ? 128 : 2), db + k * (TR ? 2 : 128), (kb | k) != 0);
    wg_commit();
    if (kb >= 1) {
      wg_wait<1>();
      if ((threadIdx.x & 127) == 0) mbar_arrive(BAR_EMPTY((kb - 1) % 3));
      __syncwarp();
    }
  }
  wg_wait<0>();
  fence_regs<64>(acc);
}

__global__ void __launch_bounds__(640, 1)
k1_main(const __grid_constant__ CUtensorMap mXA64, const __grid_constant__ CUtensorMap mXB,
        const __grid_constant__ CUtensorMap mWq, const __grid_constant__ CUtensorMap mWqkv,
        const __grid_constant__ CUtensorMap mQst, const __grid_constant__ CUtensorMap mOst, const Params prm) {
  extern __shared__ uint8_t smem_raw[];
  const uint32_t sb = (smem_u32(smem_raw) + 1023u) & ~1023u;
  const uint32_t bars = sb + OFF_MISC, sStat = bars + 256;
  const int tid = threadIdx.x, warp = __shfl_sync(~0u, tid >> 5, 0), wg = warp >> 2, w4 = warp & 3, lane = tid & 31;
  const bool helper = blockIdx.x >= 128;
  if (tid == 0) TS(0, 0);
  const int G = blockIdx.x >> 4, gi = blockIdx.x & 15;
  const int tbA = G * 4 + (gi >> 2), hg = gi & 3;
  const int ttB = (G >> 1) * 4 + (gi >> 2), hq = (G & 1) * 4 + (gi & 3);
  auto issue = [&](int kb) {
    const int s = kb % 3;
    const uint32_t fb = BAR_FULL(s), st = STAGE(s);
    mbar_expect_tx(fb, 65536);
    tma2d(st + 16384, &mXA64, kb * 64, tbA * 64, fb);
    tma2d(st, &mWq, hg * 128, kb * 64, fb);
    tma2d(st + 8192, &mWq, hg * 128 + 64, kb * 64, fb);
    tma2d(st + 49152, &mXB, kb * 64, ttB * 128, fb);
    tma2d(st + 24576, &mWqkv, hq * 64, kb * 64, fb);
    tma2d(st + 32768, &mWqkv, 512 + hq * 64, kb * 64, fb);
    tma2d(st + 40960, &mWqkv, 1024 + hq * 64, kb * 64, fb);
  };
  const uint32_t sOne = sb + OFF_V + 65536, sWKV = sOne + 24576;
  if (tid == 512) {
    for (int s = 0; s < 3; s++) { mbar_init(BAR_FULL(s), 1); mbar_init(BAR_EMPTY(s), 4); }
    for (int c = 0; c < 4; c++) mbar_init(BAR_KV(c), 1);
    mbar_init(BAR_BDONE, 8);
    mbar_init(BAR_Q, 8);
    for (int i = 0; i < 12; i++) mbar_init(BAR_LM(i), 1);
    asm volatile("fence.mbarrier_init.release.cluster;" ::: "memory");
    if (!helper) {
      mbar_expect_tx(BAR_LM(0), 65536);
      for (int kb = 0; kb < 8; kb++) tma2d(STAGE(2) + kb * 8192, &mXA64, kb * 64, tbA * 64, BAR_LM(0));
      issue(0); issue(1);
    }
  } else if (tid < 512 && !helper) {
    const uint4 v = __ldg((const uint4*)(hg >= 2 ? prm.wv : prm.wk) + tid * 2 + (hg & 1));
#pragma unroll
    for (int i = 0; i < 3; i++) {
      const int key = tid + i * 512;
      sts4(sOne + key * 16, (key % STEPK) < 32 ? 0x00003F80u : 0x00004E80u, 0u, 0u, 0u);
    }
    sts4(sWKV + tid * 16, v.x, v.y, v.z, v.w);
    fence_async();
  }
  __syncthreads();
  pdl_launch();
  if (wg == 4) {
    asm volatile("setmaxnreg.dec.sync.aligned.u32 32;");
    if (helper) {
      if (tid == 512) {
        const uint32_t ep = g_epoch[blockIdx.x] + 1;
        flag_wait(&g_flag[FLAG_B(blockIdx.x - 128) * 32], ep * 32);
        fence_async_all();
        TS(1, 10);
        mbar_arrive(BAR_KV(0));
        g_epoch[blockIdx.x] = ep;
      }
      return;
    }
    {
      float acc[4];
      mbar_wait(BAR_LM(0), 0);
      uint64_t da = make_desc(STAGE(2), 16, 1024, 1), db = make_desc(sWKV, 128, 128, 0);
      wg_fence();
#pragma unroll
      for (int kb = 0; kb < 8; kb++) {
#pragma unroll
        for (int k = 0; k < 4; k++) wg_ss8<0, 1>(acc, da + kb * 512 + k * 2, db + kb * 64 + k * 16, (kb | k) != 0);
      }
      wg_commit();
      wg_wait<0>();
      fence_regs<4>(acc);
      const uint32_t sT = sStat + 512;
      asm volatile("st.shared.b32 [%0], %1;" :: "r"(sT + w4 * 256 + lane * 4), "r"(pack_bf16(acc[0], acc[1])) : "memory");
      asm volatile("st.shared.b32 [%0], %1;" :: "r"(sT + w4 * 256 + 128 + lane * 4), "r"(pack_bf16(acc[2], acc[3])) : "memory");
      named_bar(9, 128);
      if (tid == 512) issue(2);
      const int t = tid - 512;
#pragma unroll
      for (int i = 0; i < 4; i++) {
        const int key = 1536 + t + i * 128;
        sts4(sOne + key * 16, (key % STEPK) < 32 ? 0x00003F80u : 0x00004E80u, 0u, 0u, 0u);
      }
      fence_async();
      __syncwarp();
      if (lane == 0) mbar_arrive(BAR_Q);
      if (w4 == 1 || w4 == 2) {
        const int ch = tbA * 2 + (w4 - 1);
        const uint32_t src = sT + (w4 - 1) * 512;
        uint32_t v[4], o[4];
        lds4(src + lane * 16, v);
        int kap;
        if (lane < 21) kap = lane * STEPK + 32 + ch;
        else { int idx = ch * 11 + (lane - 21); kap = (idx >> 5) * STEPK + (idx & 31); }
        g_KV[(4 + hg) * S_TOK + kap] = make_uint4(v[0], v[1], v[2], v[3]);
        float st = 0.f;
        if (hg < 2) {
#pragma unroll
          for (int u = 0; u < 4; u++) { float x = bf_lo(v[u]), y = bf_hi(v[u]); st += x * x + y * y; o[u] = pack_f16(x, y); }
          __syncwarp();
          if (lane < 8) {
            float run = 0.f;
#pragma unroll 3
            for (int i = 0; i < 21; i++) {
              uint16_t x;
              asm volatile("ld.shared.u16 %0, [%1];" : "=h"(x) : "r"(src + i * 16 + lane * 2) : "memory");
              const __half d = __float2half_rn(2.f * __uint_as_float((uint32_t)x << 16) - run);
              run += __half2float(d);
              asm volatile("st.shared.u16 [%0], %1;" :: "r"(src + i * 16 + lane * 2), "h"(__half_as_ushort(d)) : "memory");
            }
          }
          __syncwarp();
          if (lane < 21) lds4(src + lane * 16, o);
        } else {
          const float sc = lane < 21 ? VSHIFT : 1.f;
#pragma unroll
          for (int u = 0; u < 4; u++) { float x = bf_lo(v[u]), y = bf_hi(v[u]); st += fabsf(x) + fabsf(y); o[u] = pack_bf16(x * sc, y * sc); }
        }
        g_KV[hg * S_TOK + kap] = make_uint4(o[0], o[1], o[2], o[3]);
        const uint32_t um = __reduce_max_sync(~0u, __float_as_uint(st) & 0x7FFFFFFFu);
        if (w4 == 2) { if (lane == 0) asm volatile("st.shared.b32 [%0], %1;" :: "r"(sT + 1024), "r"(um) : "memory"); named_arrive(10, 64); }
        else {
          named_bar(10, 64);
          if (lane == 0) {
            uint32_t u2;
            asm volatile("ld.shared.b32 %0, [%1];" : "=r"(u2) : "r"(sT + 1024) : "memory");
            g_stats[tbA * 4 + hg] = max(um, u2);
            fence_async_all();
            flag_add(&g_flag[FLAG_KV * 32]);
            TS(1, 9);
          }
        }
      }
    }
    if (tid == 512) {
      const uint32_t ep = g_epoch[blockIdx.x] + 1;
      for (int kb = 3; kb < 8; kb++) { mbar_wait(BAR_EMPTY(kb % 3), (kb / 3 - 1) & 1); issue(kb); }
      flag_wait(&g_flag[FLAG_KV * 32], ep * 128);
      fence_async_all();
      TS(0, 11);
      mbar_wait(BAR_EMPTY(2), 1);
      mbar_wait(BAR_EMPTY(0), 0);
      const int kbd[5] = {0, STEPK, 4 * STEPK, 7 * STEPK, S_TOK};
#pragma unroll
      for (int c = 0; c < 4; c++) {
        const uint32_t bytes = (kbd[c + 1] - kbd[c]) * 16;
        mbar_expect_tx(BAR_KV(c), 4 * bytes + (c == 0 ? 512 : 0));
        if (c == 0) bulk_g2s(sStat, g_stats, 512, BAR_KV(0));
#pragma unroll
        for (int p = 0; p < 4; p++)
          bulk_g2s(sb + (p < 2 ? OFF_K : OFF_V - 65536) + p * 32768 + kbd[c] * 16, g_KV + p * S_TOK + kbd[c], bytes, BAR_KV(c));
      }
      mbar_wait(BAR_BDONE, 0);
      tma2d_store(&mQst, sb + OFF_F + 49152, hq * 64, S_TOK + ttB * 128);
      bulk_commit();
      bulk_wait_all();
      fence_async_all();
      flag_add(&g_flag[FLAG_B(hq >> 1) * 32]);
      g_epoch[blockIdx.x] = ep;
      TS(0, 12);
    }
    return;
  }
  asm volatile("setmaxnreg.inc.sync.aligned.u32 112;");
  if (helper) { helper_cta(blockIdx.x - 128, sb, bars, &mQst, &mOst); return; }

  {
    float acc[64];
    if (wg == 0) proj_loop<0>(acc, sb, bars, 16384, 0);
    else proj_loop<1>(acc, sb, bars, 16384 + wg * 8192, 49152);
    if (tid == 0) TS(0, 10);
    const uint32_t sF = sb + OFF_F;
    if (wg == 0) {
      uint4* gq = (uint4*)g_Q + blockIdx.x * 1024 + tid;
#pragma unroll
      for (int hd = 0; hd < 8; hd++) {
        uint32_t r[4];
        float n0 = 0.f, n1 = 0.f;
#pragma unroll
        for (int i = 0; i < 4; i++) {
          r[i] = pack_bf16(acc[8 * hd + 2 * i], acc[8 * hd + 2 * i + 1]);
          const float a = bf_lo(r[i]) * QSCALE, b = bf_hi(r[i]) * QSCALE;
          asm volatile("st.shared.b32 [%0], %1;" :: "r"(sF + hd * 2048 + w4 * 512 + lane * 4 + (i & 1) * 256 + (i >> 1) * 128), "r"(pack_f16(a, b)) : "memory");
          if (i & 1) n1 += a * a + b * b; else n0 += a * a + b * b;
        }
        gq[hd * 128] = make_uint4(r[0], r[1], r[2], r[3]);
        n0 += __shfl_xor_sync(~0u, n0, 1); n0 += __shfl_xor_sync(~0u, n0, 2);
        n1 += __shfl_xor_sync(~0u, n1, 1); n1 += __shfl_xor_sync(~0u, n1, 2);
        const uint32_t um = __reduce_max_sync(~0u, max(__float_as_uint(n0) & 0x7FFFFFFFu, __float_as_uint(n1) & 0x7FFFFFFFu));
        if (lane == 0) asm volatile("st.shared.b32 [%0], %1;" :: "r"(sStat + 1664 + hd * 16 + w4 * 4), "r"(um) : "memory");
      }
      fence_async();
      __syncwarp();
      if (lane == 0) mbar_arrive(BAR_Q);
    } else if (wg == 3) {
      named_arrive(8, 384);
      named_bar(6, 384);
      const int t = tid & 127;
#pragma unroll
      for (int j = 0; j < 8; j++)
        sts4(sF + 24576 + j * 2048 + t * 16, pack_bf16(acc[8 * j], acc[8 * j + 1]), pack_bf16(acc[8 * j + 2], acc[8 * j + 3]),
             pack_bf16(acc[8 * j + 4], acc[8 * j + 5]), pack_bf16(acc[8 * j + 6], acc[8 * j + 7]));
      named_arrive(7, 256);
    } else {
      uint32_t p[32];
      named_arrive(6, 384);
      if (wg == 2) named_arrive(8, 384);
#pragma unroll
      for (int i = 0; i < 32; i++) p[i] = phi2(acc[2 * i], acc[2 * i + 1]);
      if (wg == 1) {
        named_bar(8, 384);
        const int m = lane >> 3, r = lane & 7;
#pragma unroll
        for (int j = 0; j < 16; j += 2) {
          const int tok = (j + (m >> 1)) * 8 + r;
          const int chunk = w4 * 2 + (m & 1);
          stsm4t(sF + 49152 + tok * 128 + ((chunk ^ r) << 4), p[2 * j], p[2 * j + 1], p[2 * j + 2], p[2 * j + 3]);
        }
        fence_async();
      } else {
        named_bar(7, 256);
        float kv0[4] = {0, 0, 0, 0}, kv1[4] = {0, 0, 0, 0}, z0[4] = {0, 0, 0, 0}, z1[4] = {0, 0, 0, 0};
        const uint32_t one = 0x3F803F80u;
        const int t = tid & 127;
#pragma unroll
        for (int j = 0; j < 8; j++) {
          uint32_t a[4];
          lds4(sF + 24576 + j * 2048 + t * 16, a);
          mma_bf16(kv0, a[0], a[1], a[2], a[3], p[4 * j], p[4 * j + 2]);
          mma_bf16(kv1, a[0], a[1], a[2], a[3], p[4 * j + 1], p[4 * j + 3]);
          mma_bf16(z0, one, one, one, one, p[4 * j], p[4 * j + 2]);
          mma_bf16(z1, one, one, one, one, p[4 * j + 1], p[4 * j + 3]);
        }
        float4* dst = g_kvp + ((ttB * 32 + hq * 4 + w4) * 3) * 32 + lane;
        dst[0] = make_float4(kv0[0], kv0[1], kv1[0], kv1[1]);
        dst[32] = make_float4(kv0[2], kv0[3], kv1[2], kv1[3]);
        dst[64] = make_float4(z0[0], z0[1], z1[0], z1[1]);
      }
      __syncwarp();
      if (lane == 0) mbar_arrive(BAR_BDONE);
    }
  }
  mbar_wait(BAR_Q, 0);

  mbar_wait(BAR_KV(0), 0);
  if (tid == 0) TS(1, 1);
  uint32_t badmask;
  {
    uint32_t a[4], n[4], n2[4];
    lds4(sStat + lane * 16, a);
    lds4(sStat + 1664 + wg * 16, n);
    lds4(sStat + 1664 + 64 + wg * 16, n2);
    const float kmax2 = __uint_as_float(__reduce_max_sync(~0u, a[0])) + __uint_as_float(__reduce_max_sync(~0u, a[1]));
    const float vmax = __uint_as_float(__reduce_max_sync(~0u, max(a[2], a[3])));
    const float lv = vmax > 0.f ? __log2f(vmax) : 0.f;
    const float lim = fminf(90.f, fminf(91.f + lv, 95.f - lv));
    const bool gok = vmax < 1e27f && kmax2 <= 65536.f && lim > 0.f;
    const float q0 = __uint_as_float(max(max(n[0], n[1]), max(n[2], n[3])));
    const float q1 = __uint_as_float(max(max(n2[0], n2[1]), max(n2[2], n2[3])));
    const bool ok0 = gok && q0 <= 65536.f && q0 * kmax2 * 1.01f <= lim * lim;
    const bool ok1 = gok && q1 <= 65536.f && q1 * kmax2 * 1.01f <= lim * lim;
    badmask = (__all_sync(~0u, ok0) ? 0u : 1u) | (__all_sync(~0u, ok1) ? 0u : 2u);
  }
  const int g = lane >> 2, t = lane & 3;
  const uint32_t c63 = 0x1F801F80u + (badmask >> 2);
  const uint32_t m1 = (gridDim.x >> 20) - 1u;
  const uint64_t dK0 = make_desc(sb + OFF_K, 32768, 128, 0);
  const uint64_t dV0 = make_desc(sb + OFF_V, 128, 32768, 0);

#pragma unroll 1
  for (int pass = 0; pass < 2; pass++) {
    const int hd = pass * 4 + wg;
    __nv_bfloat16* od = g_O + (size_t)(tbA * 64) * D_MOD + (hg * 8 + hd) * 16;
    if ((badmask >> pass) & 1) {
      attn_slow((const uint4*)g_Q + blockIdx.x * 1024 + hd * 128, od);
      continue;
    }
    const uint64_t dQ = make_desc(sb + OFF_F + hd * 2048, 128, 256, 0);
    float Sm[16], Sp[32], O[12];
    uint32_t P[24];
#pragma unroll
    for (int i = 0; i < 32; i++) Sp[i] = SMAGIC;
#pragma unroll
    for (int i = 0; i < 16; i++) Sm[i] = 0.f;
#pragma unroll
    for (int i = 0; i < 12; i++) O[i] = 0.f;
    fence_regs<16>(Sm); fence_regs<32>(Sp); fence_regs<12>(O);
    if (tid == 0) TS(1, 2 + 2 * pass);
    wg_fence();
    wg_qs32<0>(Sm, dQ, dK0);
    wg_qs64<1>(Sp, dQ, dK0 + 32);
    wg_commit();
    wg_wait<0>();
    fence_regs<16>(Sm); fence_regs<32>(Sp);
    uint64_t dK = dK0 + STEPK, dV = dV0;
#pragma unroll 1
    for (int s3 = 0; s3 < 7; s3++) {
      if (s3 < 3) mbar_wait(BAR_KV(s3 + 1), 0);
#pragma unroll
      for (int u = 0; u < UNR; u++) {
#pragma unroll
        for (int i = 0; i < 8; i++) P[i] = pack_bf16(ex2f(Sm[2 * i]), ex2f(Sm[2 * i + 1]));
#pragma unroll
        for (int i = 0; i < 16; i++) P[8 + i] = exp2_pair_fix(Sp[2 * i], Sp[2 * i + 1], c63, m1);
        fence_regs<24>(P);
        wg_fence();
        wg_qs32<0>(Sm, dQ, dK + u * STEPK);
        wg_qs64<1>(Sp, dQ, dK + u * STEPK + 32);
#pragma unroll
        for (int k = 0; k < 6; k++) wg_pv24<1>(O, &P[4 * k], dV + u * STEPK + k * 16);
        wg_commit();
        wg_wait<0>();
        fence_regs<16>(Sm); fence_regs<32>(Sp); fence_regs<12>(O); fence_regs<24>(P);
      }
      dK += UNR * STEPK; dV += UNR * STEPK;
    }
#pragma unroll
    for (int i = 0; i < 8; i++) P[i] = pack_bf16(ex2f(Sm[2 * i]), ex2f(Sm[2 * i + 1]));
    fence_regs<8>(P);
    wg_fence();
    wg_pv24<1>(O, &P[0], dV);
    wg_pv24<1>(O, &P[4], dV + 16);
    wg_commit();
    wg_wait<0>();
    fence_regs<12>(O);
    const float l0 = __shfl_sync(~0u, O[8], lane & ~3), l1 = __shfl_sync(~0u, O[10], lane & ~3);
    const float i0 = rcpf(l0), i1 = rcpf(l1);
    uint32_t* op = (uint32_t*)(od + (size_t)(w4 * 16 + g) * D_MOD) + t;
    op[0] = pack_bf16(O[0] * i0, O[1] * i0);
    op[8 * 256] = pack_bf16(O[2] * i1, O[3] * i1);
    op[4] = pack_bf16(O[4] * i0, O[5] * i0);
    op[8 * 256 + 4] = pack_bf16(O[6] * i1, O[7] * i1);
    if (tid == 0) TS(1, 3 + 2 * pass);
    if ((tid & 127) == 0 && pass == 1 && wg > 0) TS(1, 10 + wg);
  }
}

#define K3_SMEM (131072 + 6 * 16384 + 1024 + 256)
__global__ void __cluster_dims__(2, 1, 1) __launch_bounds__(288, 1)
k3_out(const __grid_constant__ CUtensorMap mO, const __grid_constant__ CUtensorMap mWoA,
       const __grid_constant__ CUtensorMap mWoB, const __grid_constant__ CUtensorMap mOut) {
  extern __shared__ uint8_t smem_raw[];
  const uint32_t sb = (smem_u32(smem_raw) + 1023u) & ~1023u;
  const uint32_t sW = sb, sA = sb + 131072, bars = sA + 6 * 16384;
  const int tid = threadIdx.x, wg = tid >> 7, warp = tid >> 5, lane = tid & 31;
  const int rank = blockIdx.x & 1;
  const int nt = (blockIdx.x & 7);
  const int tt = blockIdx.x >> 3;
  const int part = nt >> 2;
  if (tid == 0) TS(2, 0);
  if (tid == 0) {
    for (int s = 0; s < 14; s++) mbar_init(bars + 8 * s, 1);
    mbar_init(bars + 112, 4); mbar_init(bars + 120, 4);
    asm volatile("fence.mbarrier_init.release.cluster;" ::: "memory");
  }
  cluster_sync();
  if (wg == 2) {
    if (lane == 0) {
      const CUtensorMap* mW = part ? &mWoB : &mWoA;
      const int col = (nt & 3) * 128;
      for (int kb = 0; kb < 8; kb++) {
        mbar_expect_tx(bars + 8 * kb, 16384);
        tma2d(sW + kb * 16384, mW, col, kb * 64, bars + 8 * kb);
        tma2d(sW + kb * 16384 + 8192, mW, col + 64, kb * 64, bars + 8 * kb);
      }
      pdl_wait();
      TS(2, 1);
      const int row = part * S_TOK + tt * 128 + rank * 64;
      for (int kb = 0; kb < 8; kb++) {
        const int s = kb < 6 ? kb : kb - 6;
        if (kb >= 6) mbar_wait(bars + 112 + 8 * s, 0);
        mbar_expect_tx(bars + 64 + 8 * s, 16384);
        tma2d_mc(sA + s * 16384 + rank * 8192, &mO, kb * 64, row, bars + 64 + 8 * s, 3);
      }
    }
  } else {
    float acc[64];
#pragma unroll
    for (int kb = 0; kb < 8; kb++) {
      const int s = kb < 6 ? kb : kb - 6;
      mbar_wait(bars + 8 * kb, 0);
      mbar_wait(bars + 64 + 8 * s, kb >= 6);
      if (tid == 0) TS(2, 2 + kb);
      uint64_t da = make_desc(sA + s * 16384 + wg * 8192, 16, 1024, 1);
      uint64_t db = make_desc(sW + kb * 16384, 8192, 1024, 1);
      wg_fence();
#pragma unroll
      for (int k = 0; k < 4; k++) wg_ss128<0, 1>(acc, da + k * 2, db + k * 128, (kb | k) != 0);
      wg_commit();
      if (kb == 1 || kb == 2) {
        wg_wait<1>();
        if ((tid & 127) == 0) { mbar_arrive_cta(bars + 112 + 8 * (kb - 1), 0); mbar_arrive_cta(bars + 112 + 8 * (kb - 1), 1); }
        __syncwarp();
      }
    }
    wg_wait<0>();
    fence_regs<64>(acc);
    const int w4 = warp & 3, m = lane >> 3, r = lane & 7;
#pragma unroll
    for (int j = 0; j < 16; j += 2) {
      const uint32_t stg = sA + (2 + (j >> 3)) * 16384 + wg * 8192;
      const int row = w4 * 16 + (m & 1) * 8 + r;
      const int chunk = (j & 7) + (m >> 1);
      stsm4(stg + row * 128 + ((chunk ^ r) << 4),
            pack_bf16(acc[4 * j], acc[4 * j + 1]), pack_bf16(acc[4 * j + 2], acc[4 * j + 3]),
            pack_bf16(acc[4 * j + 4], acc[4 * j + 5]), pack_bf16(acc[4 * j + 6], acc[4 * j + 7]));
    }
    fence_async();
    named_bar(wg + 1, 128);
    if ((tid & 127) == 0) {
      tma2d_store(&mOut, sA + 2 * 16384 + wg * 8192, nt * 128, tt * 128 + wg * 64);
      tma2d_store(&mOut, sA + 3 * 16384 + wg * 8192, nt * 128 + 64, tt * 128 + wg * 64);
      if (tid == 0) TS(2, 11);
      bulk_commit();
      bulk_wait_all();
      if (tid == 0) TS(2, 12);
    }
  }
}

typedef CUresult (*EncodeFn)(CUtensorMap*, CUtensorMapDataType, cuuint32_t, void*, const cuuint64_t*, const cuuint64_t*,
                             const cuuint32_t*, const cuuint32_t*, CUtensorMapInterleave, CUtensorMapSwizzle,
                             CUtensorMapL2promotion, CUtensorMapFloatOOBfill);

static void make_map(EncodeFn enc, CUtensorMap* m, const void* ptr, uint64_t cols, uint64_t rows, uint32_t bc, uint32_t br) {
  cuuint64_t dims[2] = {cols, rows};
  cuuint64_t strides[1] = {cols * 2};
  cuuint32_t box[2] = {bc, br};
  cuuint32_t es[2] = {1, 1};
  enc(m, CU_TENSOR_MAP_DATA_TYPE_BFLOAT16, 2, (void*)ptr, dims, strides, box, es, CU_TENSOR_MAP_INTERLEAVE_NONE,
      CU_TENSOR_MAP_SWIZZLE_128B, CU_TENSOR_MAP_L2_PROMOTION_L2_256B, CU_TENSOR_MAP_FLOAT_OOB_FILL_NONE);
}

extern "C" void kernel_launch(void* const* d_in, const int* in_sizes, int n_in, void* d_out, int out_size) {
  (void)in_sizes; (void)n_in; (void)out_size;
  static EncodeFn enc = nullptr;
  static void* pQ = nullptr; static void* pO = nullptr;
  if (!enc) {
    void* fn = nullptr; cudaDriverEntryPointQueryResult qr;
    cudaGetDriverEntryPoint("cuTensorMapEncodeTiled", &fn, cudaEnableDefault, &qr);
    enc = (EncodeFn)fn;
    cudaGetSymbolAddress(&pQ, g_Q);
    cudaGetSymbolAddress(&pO, g_O);
    cudaFuncSetAttribute(k1_main, cudaFuncAttributeMaxDynamicSharedMemorySize, SM_TOTAL);
    cudaFuncSetAttribute(k3_out, cudaFuncAttributeMaxDynamicSharedMemorySize, K3_SMEM);
  }
  CUtensorMap mXA64, mXB, mWq, mWqkv, mQst, mO, mOst, mWoA, mWoB, mOut;
  make_map(enc, &mXA64, d_in[0], 512, 2048, 64, 64);
  make_map(enc, &mWq, d_in[1], 512, 512, 64, 64);
  make_map(enc, &mWoA, d_in[4], 512, 512, 64, 64);
  make_map(enc, &mXB, d_in[5], 512, 2048, 64, 128);
  make_map(enc, &mWqkv, d_in[6], 1536, 512, 64, 64);
  make_map(enc, &mWoB, d_in[7], 512, 512, 64, 64);
  make_map(enc, &mQst, pQ, 512, 4096, 64, 128);
  make_map(enc, &mO, pO, 512, 4096, 64, 64);
  make_map(enc, &mOst, pO, 512, 4096, 64, 128);
  make_map(enc, &mOut, d_out, 1024, 2048, 64, 64);
  Params prm{(const __nv_bfloat16*)d_in[2], (const __nv_bfloat16*)d_in[3]};

  cudaStream_t st = cudaStreamPerThread;
  cudaLaunchAttribute at[1];
  at[0].id = cudaLaunchAttributeProgrammaticStreamSerialization;
  at[0].val.programmaticStreamSerializationAllowed = 1;
  cudaLaunchConfig_t cfg = {};
  cfg.stream = st;
  cfg.gridDim = dim3(132); cfg.blockDim = dim3(640); cfg.dynamicSmemBytes = SM_TOTAL; cfg.attrs = at; cfg.numAttrs = 0;
  cudaLaunchKernelEx(&cfg, k1_main, mXA64, mXB, mWq, mWqkv, mQst, mOst, prm);
  cfg.gridDim = dim3(128); cfg.blockDim = dim3(288); cfg.dynamicSmemBytes = K3_SMEM; cfg.numAttrs = 1;
  cudaLaunchKernelEx(&cfg, k3_out, mO, mWoA, mWoB, mOut);
}
```

```cpp
#include <cuda_runtime.h>
#include <cuda_bf16.h>
#include <cuda_fp16.h>
#include <cuda.h>
#include <stdint.h>

#define S_TOK 2048
#define D_MOD 512

__device__ __align__(1024) __nv_bfloat16 g_Q[2 * S_TOK * D_MOD];
__device__ __align__(1024) __nv_bfloat16 g_O[2 * S_TOK * D_MOD];
__device__ __align__(1024) uint4 g_KV[8 * S_TOK];
__device__ __align__(16) uint32_t g_stats[128];
__device__ __align__(16) float4 g_kvp[16 * 32 * 3 * 32];

#define TS(k, i) do {} while (0)
__device__ __forceinline__ uint32_t smem_u32(const void* p) { return (uint32_t)__cvta_generic_to_shared(p); }
__device__ __forceinline__ void mbar_init(uint32_t bar, int cnt) { asm volatile("mbarrier.init.shared::cta.b64 [%0], %1;" :: "r"(bar), "r"(cnt) : "memory"); }
__device__ __forceinline__ void mbar_expect_tx(uint32_t bar, uint32_t bytes) { asm volatile("mbarrier.arrive.expect_tx.shared::cta.b64 _, [%0], %1;" :: "r"(bar), "r"(bytes) : "memory"); }
__device__ __forceinline__ bool mbar_try(uint32_t bar, uint32_t parity) {
  uint32_t ok;
  asm volatile("{\n.reg .pred p;\nmbarrier.try_wait.parity.shared::cta.b64 p, [%1], %2;\nselp.b32 %0, 1, 0, p;\n}\n" : "=r"(ok) : "r"(bar), "r"(parity) : "memory");
  return ok;
}
__device__ __forceinline__ void mbar_wait(uint32_t bar, uint32_t parity) {
  asm volatile("{\n.reg .pred p;\n.reg .u32 c;\nmov.u32 c, 0;\n"
               "LW_%=:\n"
               "mbarrier.try_wait.parity.shared::cta.b64 p, [%0], %1;\n"
               "@p bra LD_%=;\n"
               "add.u32 c, c, 1;\n"
               "setp.lt.u32 p, c, 4000000;\n"
               "@p bra LW_%=;\n"
               "trap;\n"
               "LD_%=:\n}\n" :: "r"(bar), "r"(parity) : "memory");
}
__device__ __forceinline__ void mbar_arrive_cta(uint32_t bar, uint32_t cta) {
  asm volatile("{\n.reg .b32 ra;\nmapa.shared::cluster.u32 ra, %0, %1;\nmbarrier.arrive.shared::cluster.b64 _, [ra];\n}\n" :: "r"(bar), "r"(cta) : "memory");
}
__device__ __forceinline__ void cluster_sync() {
  asm volatile("barrier.cluster.arrive.relaxed.aligned;\nbarrier.cluster.wait.aligned;" ::: "memory");
}
__device__ __forceinline__ void tma2d(uint32_t dst, const CUtensorMap* m, int c0, int c1, uint32_t bar) {
  asm volatile("cp.async.bulk.tensor.2d.shared::cluster.global.mbarrier::complete_tx::bytes [%0], [%1, {%3, %4}], [%2];"
               :: "r"(dst), "l"(m), "r"(bar), "r"(c0), "r"(c1) : "memory");
}
__device__ __forceinline__ void tma2d_mc(uint32_t dst, const CUtensorMap* m, int c0, int c1, uint32_t bar, uint16_t mask) {
  asm volatile("cp.async.bulk.tensor.2d.shared::cluster.global.mbarrier::complete_tx::bytes.multicast::cluster [%0], [%1, {%3, %4}], [%2], %5;"
               :: "r"(dst), "l"(m), "r"(bar), "r"(c0), "r"(c1), "h"(mask) : "memory");
}
__device__ __forceinline__ void tma2d_store(const CUtensorMap* m, uint32_t src, int c0, int c1) {
  asm volatile("cp.async.bulk.tensor.2d.global.shared::cta.bulk_group [%0, {%2, %3}], [%1];"
               :: "l"(m), "r"(src), "r"(c0), "r"(c1) : "memory");
}
__device__ __forceinline__ void bulk_g2s(uint32_t dst, const void* src, uint32_t bytes, uint32_t bar) {
  asm volatile("cp.async.bulk.shared::cluster.global.mbarrier::complete_tx::bytes [%0], [%1], %2, [%3];"
               :: "r"(dst), "l"(src), "r"(bytes), "r"(bar) : "memory");
}
__device__ __forceinline__ void bulk_commit() { asm volatile("cp.async.bulk.commit_group;" ::: "memory"); }
__device__ __forceinline__ void bulk_wait_all() { asm volatile("cp.async.bulk.wait_group 0;" ::: "memory"); }
__device__ __forceinline__ void fence_async() { asm volatile("fence.proxy.async.shared::cta;" ::: "memory"); }
__device__ __forceinline__ void named_bar(int id, int n) { asm volatile("bar.sync %0, %1;" :: "r"(id), "r"(n) : "memory"); }
__device__ __forceinline__ void pdl_launch() { asm volatile("griddepcontrol.launch_dependents;" ::: "memory"); }
__device__ __forceinline__ void pdl_wait() { asm volatile("griddepcontrol.wait;" ::: "memory"); }
__device__ __forceinline__ void wg_fence() { asm volatile("wgmma.fence.sync.aligned;" ::: "memory"); }
__device__ __forceinline__ void wg_commit() { asm volatile("wgmma.commit_group.sync.aligned;" ::: "memory"); }
template <int n> __device__ __forceinline__ void wg_wait() { asm volatile("wgmma.wait_group.sync.aligned %0;" :: "n"(n) : "memory"); }
template <int n> __device__ __forceinline__ void fence_regs(float* r) {
#pragma unroll
  for (int i = 0; i < n; i++) asm volatile("" : "+f"(r[i]) :: "memory");
}
template <int n> __device__ __forceinline__ void fence_regs(uint32_t* r) {
#pragma unroll
  for (int i = 0; i < n; i++) asm volatile("" : "+r"(r[i]) :: "memory");
}
__device__ __forceinline__ uint64_t make_desc(uint32_t addr, uint32_t lbo, uint32_t sbo, uint32_t swz) {
  return (uint64_t)((addr & 0x3FFFF) >> 4) | ((uint64_t)(lbo >> 4) << 16) | ((uint64_t)(sbo >> 4) << 32) | ((uint64_t)swz << 62);
}
__device__ __forceinline__ float ex2f(float x) { float y; asm("ex2.approx.ftz.f32 %0, %1;" : "=f"(y) : "f"(x)); return y; }
__device__ __forceinline__ uint32_t pack_bf16(float lo, float hi) { uint32_t r; asm("cvt.rn.bf16x2.f32 %0, %1, %2;" : "=r"(r) : "f"(hi), "f"(lo)); return r; }
__device__ __forceinline__ uint32_t pack_f16(float lo, float hi) { uint32_t r; asm("cvt.rn.f16x2.f32 %0, %1, %2;" : "=r"(r) : "f"(hi), "f"(lo)); return r; }
__device__ __forceinline__ float bf_lo(uint32_t v) { return __uint_as_float(v << 16); }
__device__ __forceinline__ float bf_hi(uint32_t v) { return __uint_as_float(v & 0xFFFF0000u); }
__device__ __forceinline__ float rbf(float x) { return __bfloat162float(__float2bfloat16_rn(x)); }
__device__ __forceinline__ void stsm4(uint32_t a, uint32_t r0, uint32_t r1, uint32_t r2, uint32_t r3) {
  asm volatile("stmatrix.sync.aligned.m8n8.x4.shared.b16 [%0], {%1,%2,%3,%4};" :: "r"(a), "r"(r0), "r"(r1), "r"(r2), "r"(r3) : "memory");
}
__device__ __forceinline__ void stsm4t(uint32_t a, uint32_t r0, uint32_t r1, uint32_t r2, uint32_t r3) {
  asm volatile("stmatrix.sync.aligned.m8n8.x4.trans.shared.b16 [%0], {%1,%2,%3,%4};" :: "r"(a), "r"(r0), "r"(r1), "r"(r2), "r"(r3) : "memory");
}
__device__ __forceinline__ void mma_bf16(float* d, uint32_t a0, uint32_t a1, uint32_t a2, uint32_t a3, uint32_t b0, uint32_t b1) {
  asm volatile("mma.sync.aligned.m16n8k16.row.col.f32.bf16.bf16.f32 {%0,%1,%2,%3}, {%4,%5,%6,%7}, {%8,%9}, {%0,%1,%2,%3};"
               : "+f"(d[0]), "+f"(d[1]), "+f"(d[2]), "+f"(d[3]) : "r"(a0), "r"(a1), "r"(a2), "r"(a3), "r"(b0), "r"(b1));
}
template<int SD> __device__ __forceinline__ void wg_qk32(float* d, const uint32_t* a, uint64_t desc) {
  asm volatile("wgmma.mma_async.sync.aligned.m64n32k16.f32.f16.f16 {%0,%1,%2,%3,%4,%5,%6,%7,%8,%9,%10,%11,%12,%13,%14,%15}, {%16,%17,%18,%19}, %20, %21, 1, 1, 0;"
   : "+f"(d[0]),"+f"(d[1]),"+f"(d[2]),"+f"(d[3]),"+f"(d[4]),"+f"(d[5]),"+f"(d[6]),"+f"(d[7]),"+f"(d[8]),"+f"(d[9]),"+f"(d[10]),"+f"(d[11]),"+f"(d[12]),"+f"(d[13]),"+f"(d[14]),"+f"(d[15])
   : "r"(a[0]),"r"(a[1]),"r"(a[2]),"r"(a[3]),"l"(desc),"n"(SD));
}
template<int SD> __device__ __forceinline__ void wg_qk64(float* d, const uint32_t* a, uint64_t desc) {
  asm volatile("wgmma.mma_async.sync.aligned.m64n64k16.f32.f16.f16 {%0,%1,%2,%3,%4,%5,%6,%7,%8,%9,%10,%11,%12,%13,%14,%15,%16,%17,%18,%19,%20,%21,%22,%23,%24,%25,%26,%27,%28,%29,%30,%31}, {%32,%33,%34,%35}, %36, %37, 1, 1, 0;"
   : "+f"(d[0]),"+f"(d[1]),"+f"(d[2]),"+f"(d[3]),"+f"(d[4]),"+f"(d[5]),"+f"(d[6]),"+f"(d[7]),"+f"(d[8]),"+f"(d[9]),"+f"(d[10]),"+f"(d[11]),"+f"(d[12]),"+f"(d[13]),"+f"(d[14]),"+f"(d[15]),"+f"(d[16]),"+f"(d[17]),"+f"(d[18]),"+f"(d[19]),"+f"(d[20]),"+f"(d[21]),"+f"(d[22]),"+f"(d[23]),"+f"(d[24]),"+f"(d[25]),"+f"(d[26]),"+f"(d[27]),"+f"(d[28]),"+f"(d[29]),"+f"(d[30]),"+f"(d[31])
   : "r"(a[0]),"r"(a[1]),"r"(a[2]),"r"(a[3]),"l"(desc),"n"(SD));
}
template<int SD> __device__ __forceinline__ void wg_qs32(float* d, uint64_t da, uint64_t db) {
  asm volatile("wgmma.mma_async.sync.aligned.m64n32k16.f32.f16.f16 {%0,%1,%2,%3,%4,%5,%6,%7,%8,%9,%10,%11,%12,%13,%14,%15}, %16, %17, %18, 1, 1, 0, 0;"
   : "+f"(d[0]),"+f"(d[1]),"+f"(d[2]),"+f"(d[3]),"+f"(d[4]),"+f"(d[5]),"+f"(d[6]),"+f"(d[7]),"+f"(d[8]),"+f"(d[9]),"+f"(d[10]),"+f"(d[11]),"+f"(d[12]),"+f"(d[13]),"+f"(d[14]),"+f"(d[15])
   : "l"(da),"l"(db),"n"(SD));
}
template<int SD> __device__ __forceinline__ void wg_qs64(float* d, uint64_t da, uint64_t db) {
  asm volatile("wgmma.mma_async.sync.aligned.m64n64k16.f32.f16.f16 {%0,%1,%2,%3,%4,%5,%6,%7,%8,%9,%10,%11,%12,%13,%14,%15,%16,%17,%18,%19,%20,%21,%22,%23,%24,%25,%26,%27,%28,%29,%30,%31}, %32, %33, %34, 1, 1, 0, 0;"
   : "+f"(d[0]),"+f"(d[1]),"+f"(d[2]),"+f"(d[3]),"+f"(d[4]),"+f"(d[5]),"+f"(d[6]),"+f"(d[7]),"+f"(d[8]),"+f"(d[9]),"+f"(d[10]),"+f"(d[11]),"+f"(d[12]),"+f"(d[13]),"+f"(d[14]),"+f"(d[15]),"+f"(d[16]),"+f"(d[17]),"+f"(d[18]),"+f"(d[19]),"+f"(d[20]),"+f"(d[21]),"+f"(d[22]),"+f"(d[23]),"+f"(d[24]),"+f"(d[25]),"+f"(d[26]),"+f"(d[27]),"+f"(d[28]),"+f"(d[29]),"+f"(d[30]),"+f"(d[31])
   : "l"(da),"l"(db),"n"(SD));
}
template<int SD> __device__ __forceinline__ void wg_pv24(float* d, const uint32_t* a, uint64_t desc) {
  asm volatile("wgmma.mma_async.sync.aligned.m64n24k16.f32.bf16.bf16 {%0,%1,%2,%3,%4,%5,%6,%7,%8,%9,%10,%11}, {%12,%13,%14,%15}, %16, %17, 1, 1, 1;"
   : "+f"(d[0]),"+f"(d[1]),"+f"(d[2]),"+f"(d[3]),"+f"(d[4]),"+f"(d[5]),"+f"(d[6]),"+f"(d[7]),"+f"(d[8]),"+f"(d[9]),"+f"(d[10]),"+f"(d[11])
   : "r"(a[0]),"r"(a[1]),"r"(a[2]),"r"(a[3]),"l"(desc),"n"(SD));
}
template<int TA, int TB> __device__ __forceinline__ void wg_ss128(float* d, uint64_t da, uint64_t db, int sd) {
  asm volatile("{\n.reg .pred p;\nsetp.ne.b32 p, %66, 0;\n"
   "wgmma.mma_async.sync.aligned.m64n128k16.f32.bf16.bf16 {%0,%1,%2,%3,%4,%5,%6,%7,%8,%9,%10,%11,%12,%13,%14,%15,%16,%17,%18,%19,%20,%21,%22,%23,%24,%25,%26,%27,%28,%29,%30,%31,%32,%33,%34,%35,%36,%37,%38,%39,%40,%41,%42,%43,%44,%45,%46,%47,%48,%49,%50,%51,%52,%53,%54,%55,%56,%57,%58,%59,%60,%61,%62,%63}, %64, %65, p, 1, 1, %67, %68;\n}\n"
   : "+f"(d[0]),"+f"(d[1]),"+f"(d[2]),"+f"(d[3]),"+f"(d[4]),"+f"(d[5]),"+f"(d[6]),"+f"(d[7]),"+f"(d[8]),"+f"(d[9]),"+f"(d[10]),"+f"(d[11]),"+f"(d[12]),"+f"(d[13]),"+f"(d[14]),"+f"(d[15]),"+f"(d[16]),"+f"(d[17]),"+f"(d[18]),"+f"(d[19]),"+f"(d[20]),"+f"(d[21]),"+f"(d[22]),"+f"(d[23]),"+f"(d[24]),"+f"(d[25]),"+f"(d[26]),"+f"(d[27]),"+f"(d[28]),"+f"(d[29]),"+f"(d[30]),"+f"(d[31]),"+f"(d[32]),"+f"(d[33]),"+f"(d[34]),"+f"(d[35]),"+f"(d[36]),"+f"(d[37]),"+f"(d[38]),"+f"(d[39]),"+f"(d[40]),"+f"(d[41]),"+f"(d[42]),"+f"(d[43]),"+f"(d[44]),"+f"(d[45]),"+f"(d[46]),"+f"(d[47]),"+f"(d[48]),"+f"(d[49]),"+f"(d[50]),"+f"(d[51]),"+f"(d[52]),"+f"(d[53]),"+f"(d[54]),"+f"(d[55]),"+f"(d[56]),"+f"(d[57]),"+f"(d[58]),"+f"(d[59]),"+f"(d[60]),"+f"(d[61]),"+f"(d[62]),"+f"(d[63])
   : "l"(da),"l"(db),"r"(sd),"n"(TA),"n"(TB));
}
template<int TA, int TB> __device__ __forceinline__ void wg_ss64(float* d, uint64_t da, uint64_t db, int sd) {
  asm volatile("{\n.reg .pred p;\nsetp.ne.b32 p, %34, 0;\n"
   "wgmma.mma_async.sync.aligned.m64n64k16.f32.bf16.bf16 {%0,%1,%2,%3,%4,%5,%6,%7,%8,%9,%10,%11,%12,%13,%14,%15,%16,%17,%18,%19,%20,%21,%22,%23,%24,%25,%26,%27,%28,%29,%30,%31}, %32, %33, p, 1, 1, %35, %36;\n}\n"
   : "+f"(d[0]),"+f"(d[1]),"+f"(d[2]),"+f"(d[3]),"+f"(d[4]),"+f"(d[5]),"+f"(d[6]),"+f"(d[7]),"+f"(d[8]),"+f"(d[9]),"+f"(d[10]),"+f"(d[11]),"+f"(d[12]),"+f"(d[13]),"+f"(d[14]),"+f"(d[15]),"+f"(d[16]),"+f"(d[17]),"+f"(d[18]),"+f"(d[19]),"+f"(d[20]),"+f"(d[21]),"+f"(d[22]),"+f"(d[23]),"+f"(d[24]),"+f"(d[25]),"+f"(d[26]),"+f"(d[27]),"+f"(d[28]),"+f"(d[29]),"+f"(d[30]),"+f"(d[31])
   : "l"(da),"l"(db),"r"(sd),"n"(TA),"n"(TB));
}

template<int TA, int TB> __device__ __forceinline__ void wg_ss8(float* d, uint64_t da, uint64_t db, int sd) {
  asm volatile("{\n.reg .pred p;\nsetp.ne.b32 p, %6, 0;\n"
   "wgmma.mma_async.sync.aligned.m64n8k16.f32.bf16.bf16 {%0,%1,%2,%3}, %4, %5, p, 1, 1, %7, %8;\n}\n"
   : "+f"(d[0]),"+f"(d[1]),"+f"(d[2]),"+f"(d[3])
   : "l"(da),"l"(db),"r"(sd),"n"(TA),"n"(TB));
}

__device__ __forceinline__ uint32_t phi2(float a, float b) {
  uint32_t r, e;
  asm("cvt.rn.relu.bf16x2.f32 %0, %1, %2;" : "=r"(r) : "f"(b), "f"(a));
  e = pack_bf16(ex2f(a * 1.4426950408889634f), ex2f(b * 1.4426950408889634f));
  asm("add.rn.bf16x2 %0, %0, %1;" : "+r"(e) : "r"(0x35863586u));
  asm("min.NaN.bf16x2 %0, %0, %1;" : "+r"(e) : "r"(0x3F803F80u));
  asm("add.rn.bf16x2 %0, %0, %1;" : "+r"(e) : "r"(r));
  return e;
}

__device__ __forceinline__ void mbar_arrive(uint32_t bar) { asm volatile("mbarrier.arrive.shared::cta.b64 _, [%0];" :: "r"(bar) : "memory"); }
__device__ __forceinline__ void named_arrive(int id, int n) { asm volatile("bar.arrive %0, %1;" :: "r"(id), "r"(n) : "memory"); }
__device__ __forceinline__ void fence_async_all() { asm volatile("fence.proxy.async;" ::: "memory"); }
__device__ __forceinline__ void flag_add(uint32_t* f) { asm volatile("fence.acq_rel.gpu;\nred.relaxed.gpu.global.add.u32 [%0], 1;" :: "l"(f) : "memory"); }
__device__ __forceinline__ void flag_wait(const uint32_t* f, uint32_t target) {
  uint32_t v;
  for (int it = 0;; it++) {
    asm volatile("ld.acquire.gpu.global.u32 %0, [%1];" : "=r"(v) : "l"(f) : "memory");
    if ((int32_t)(v - target) >= 0) break;
    if (it > 2000000) __trap();
  }
}
__device__ __forceinline__ void lds4(uint32_t a, uint32_t* r) {
  asm volatile("ld.shared.v4.b32 {%0,%1,%2,%3}, [%4];" : "=r"(r[0]), "=r"(r[1]), "=r"(r[2]), "=r"(r[3]) : "r"(a) : "memory");
}
__device__ __forceinline__ void sts4(uint32_t a, uint32_t r0, uint32_t r1, uint32_t r2, uint32_t r3) {
  asm volatile("st.shared.v4.b32 [%0], {%1,%2,%3,%4};" :: "r"(a), "r"(r0), "r"(r1), "r"(r2), "r"(r3) : "memory");
}
__device__ __forceinline__ void ldsm4(uint32_t a, uint32_t* r) {
  asm volatile("ldmatrix.sync.aligned.m8n8.x4.shared.b16 {%0,%1,%2,%3}, [%4];" : "=r"(r[0]), "=r"(r[1]), "=r"(r[2]), "=r"(r[3]) : "r"(a) : "memory");
}
__device__ __forceinline__ float rcpf(float x) { float y; asm("rcp.approx.ftz.f32 %0, %1;" : "=f"(y) : "f"(x)); return y; }

#define STEPK 96
#define QSCALE 0.36067376022224085f
#define SMAGIC (512.0f + 2.0f * (191.0f - 30.0f - 1.5823545f))
#define VSHIFT 1073741824.0f

__device__ uint32_t g_epoch[132];
__device__ uint32_t g_flag[64 * 32];
#define FLAG_KV 0
#define FLAG_B(h) (1 + (h))

#define SM_TOTAL (224 * 1024 + 2048 + 1024)
#define OFF_K 0
#define OFF_F 65536
#define OFF_V 131072
#define OFF_MISC (224 * 1024)

__device__ __forceinline__ uint32_t exp2_pair_fix(float d0, float d1, uint32_t c63, uint32_t m1) {
  uint32_t w, y, s, r;
  asm("prmt.b32 %0, %1, %2, 0x6521;" : "=r"(w) : "r"(__float_as_uint(d0)), "r"(__float_as_uint(d1)));
  asm("lop3.b32 %0, %1, 0x007F007F, %2, 0xEA;" : "=r"(y) : "r"(w), "r"(c63));
  asm("mad.lo.u32 %0, %1, %2, %3;" : "=r"(s) : "r"(y), "r"(m1), "r"(w));
  asm("fma.rn.bf16x2 %0, %1, %2, %3;" : "=r"(r) : "r"(w), "r"(y), "r"(s));
  return r;
}

__device__ __noinline__ void attn_slow(const uint4* gq, __nv_bfloat16* dst) {
  const int t = threadIdx.x & 127;
  const int row = t >> 1, half = t & 1;
  float q[16];
#pragma unroll
  for (int i = 0; i < 4; i++) {
    const uint4 v = gq[(row >> 4) * 32 + (row & 7) * 4 + i];
    const uint32_t lo = (row & 8) ? v.y : v.x, hi = (row & 8) ? v.w : v.z;
    q[2 * i] = bf_lo(lo); q[2 * i + 1] = bf_hi(lo); q[2 * i + 8] = bf_lo(hi); q[2 * i + 9] = bf_hi(hi);
  }
  float m = -INFINITY, l = 0.f, o[16];
#pragma unroll
  for (int i = 0; i < 16; i++) o[i] = 0.f;
  for (int j = half * 1024; j < half * 1024 + 1024; j++) {
    uint4 ka = g_KV[4 * S_TOK + j], kb = g_KV[5 * S_TOK + j];
    uint4 va = g_KV[6 * S_TOK + j], vb = g_KV[7 * S_TOK + j];
    uint32_t kk[8] = {ka.x, ka.y, ka.z, ka.w, kb.x, kb.y, kb.z, kb.w};
    uint32_t vv[8] = {va.x, va.y, va.z, va.w, vb.x, vb.y, vb.z, vb.w};
    float s = 0.f;
#pragma unroll
    for (int i = 0; i < 8; i++) { s = fmaf(q[2 * i], bf_lo(kk[i]), s); s = fmaf(q[2 * i + 1], bf_hi(kk[i]), s); }
    s = rbf(s) * 0.25f;
    if (s > m) {
      float c = __expf(m - s);
      l *= c;
#pragma unroll
      for (int i = 0; i < 16; i++) o[i] *= c;
      m = s;
    }
    float p = __expf(s - m);
    l += p;
#pragma unroll
    for (int i = 0; i < 8; i++) { o[2 * i] = fmaf(p, bf_lo(vv[i]), o[2 * i]); o[2 * i + 1] = fmaf(p, bf_hi(vv[i]), o[2 * i + 1]); }
  }
  float m2 = __shfl_xor_sync(~0u, m, 1);
  float mm = fmaxf(m, m2);
  float c = __expf(m - mm);
  l *= c; l += __shfl_xor_sync(~0u, l, 1);
  float inv = 1.f / l;
  uint32_t r[8];
#pragma unroll
  for (int i = 0; i < 16; i++) { o[i] *= c; o[i] += __shfl_xor_sync(~0u, o[i], 1); o[i] *= inv; }
#pragma unroll
  for (int i = 0; i < 8; i++) r[i] = pack_bf16(o[2 * i], o[2 * i + 1]);
  uint4* d = (uint4*)(dst + (size_t)row * D_MOD);
  if (half == 0) d[0] = make_uint4(r[0], r[1], r[2], r[3]); else d[1] = make_uint4(r[4], r[5], r[6], r[7]);
}

struct Params { const __nv_bfloat16* wk; const __nv_bfloat16* wv; };

#define BAR_FULL(s) (bars + 8 * (s))
#define BAR_EMPTY(s) (bars + 24 + 8 * (s))
#define BAR_KV(c) (bars + 48 + 8 * (c))
#define BAR_BDONE (bars + 80)
#define BAR_Q (bars + 88)
#define BAR_LM(i) (bars + 96 + 8 * (i))

__device__ __forceinline__ void helper_cta(const int h, const uint32_t sb, const uint32_t bars,
                                           const CUtensorMap* mQ, const CUtensorMap* mOs) {
  const int tid = threadIdx.x, warp = __shfl_sync(~0u, tid >> 5, 0), wg = warp >> 2, w4 = warp & 3, lane = tid & 31;
  mbar_wait(BAR_KV(0), 0);
  const int cb = wg & 1, col = h * 128 + cb * 64, row0 = S_TOK + (wg >> 1) * 1024;
  const uint32_t buf = sb + wg * 49152;
  if ((tid & 127) == 0) {
    fence_async_all();
    for (int u = 0; u < 3; u++) {
      mbar_expect_tx(BAR_LM(wg * 3 + u), 16384);
      tma2d(buf + u * 16384, mQ, col, row0 + u * 128, BAR_LM(wg * 3 + u));
    }
  }
  const int head = h * 8 + cb * 4 + w4;
  float4 a0 = make_float4(0, 0, 0, 0), a1 = a0, a2 = a0;
#pragma unroll 8
  for (int tt = 0; tt < 16; tt++) {
    const float4* src = g_kvp + ((tt * 32 + head) * 3) * 32 + lane;
    float4 u = src[0], v = src[32], w = src[64];
    a0.x += u.x; a0.y += u.y; a0.z += u.z; a0.w += u.w;
    a1.x += v.x; a1.y += v.y; a1.z += v.z; a1.w += v.w;
    a2.x += w.x; a2.y += w.y; a2.z += w.z; a2.w += w.w;
  }
  const uint32_t b00 = pack_bf16(a0.x, a0.y), b01 = pack_bf16(a0.z, a0.w);
  const uint32_t b10 = pack_bf16(a1.x, a1.y), b11 = pack_bf16(a1.z, a1.w);
  const uint32_t bz0 = pack_bf16(a2.x, a2.y), bz1 = pack_bf16(a2.z, a2.w);
  const int m = lane >> 3, r = lane & 7;
  const uint32_t off = ((m & 1) * 8 + r) * 128 + (((w4 * 2 + (m >> 1)) ^ r) << 4);
  int s = 0, ph = 0;
#pragma unroll 1
  for (int u = 0; u < 8; u++) {
    const uint32_t bb = buf + s * 16384;
    mbar_wait(BAR_LM(wg * 3 + s), ph);
#pragma unroll
    for (int mt = 0; mt < 8; mt++) {
      uint32_t a[4];
      ldsm4(bb + mt * 2048 + off, a);
      float n0[4] = {0, 0, 0, 0}, n1[4] = {0, 0, 0, 0}, dn[4] = {0, 0, 0, 0};
      mma_bf16(dn, a[0], a[1], a[2], a[3], bz0, bz1);
      mma_bf16(n0, a[0], a[1], a[2], a[3], b00, b01);
      mma_bf16(n1, a[0], a[1], a[2], a[3], b10, b11);
      const float i0 = rcpf(dn[0] + 1e-6f), i1 = rcpf(dn[2] + 1e-6f);
      stsm4(bb + mt * 2048 + off, pack_bf16(n0[0] * i0, n0[1] * i0), pack_bf16(n0[2] * i1, n0[3] * i1),
            pack_bf16(n1[0] * i0, n1[1] * i0), pack_bf16(n1[2] * i1, n1[3] * i1));
    }
    fence_async();
    named_bar(wg + 1, 128);
    if ((tid & 127) == 0) {
      tma2d_store(mOs, bb, col, row0 + u * 128);
      bulk_commit();
      if (u >= 1 && u + 2 < 8) {
        asm volatile("cp.async.bulk.wait_group.read 1;" ::: "memory");
        const int sp = s == 0 ? 2 : s - 1;
        mbar_expect_tx(BAR_LM(wg * 3 + sp), 16384);
        tma2d(buf + sp * 16384, mQ, col, row0 + (u + 2) * 128, BAR_LM(wg * 3 + sp));
      }
    }
    __syncwarp();
    if (++s == 3) { s = 0; ph ^= 1; }
  }
  if ((tid & 127) == 0) bulk_wait_all();
  if (tid == 0) TS(1, 8);
}

#define STAGE(s) (sb + (2 - (s)) * 65536)
template <int TR> __device__ __forceinline__ void proj_loop(float* acc, uint32_t sb, uint32_t bars, uint32_t offA, uint32_t offB) {
#pragma unroll
  for (int kb = 0; kb < 8; kb++) {
    const int s = kb % 3;
    const uint32_t st = STAGE(s);
    mbar_wait(BAR_FULL(s), (kb / 3) & 1);
    if (threadIdx.x == 0) TS(0, 2 + kb);
    const uint64_t da = make_desc(st + offA, TR ? 8192 : 16, 1024, 1);
    const uint64_t db = make_desc(st + offB, TR ? 16 : 8192, 1024, 1);
    wg_fence();
#pragma unroll
    for (int k = 0; k < 4; k++) wg_ss128<TR, 1 - TR>(acc, da + k * (TR ? 128 : 2), db + k * (TR ? 2 : 128), (kb | k) != 0);
    wg_commit();
    if (kb >= 1) {
      wg_wait<1>();
      if ((threadIdx.x & 127) == 0) mbar_arrive(BAR_EMPTY((kb - 1) % 3));
      __syncwarp();
    }
  }
  wg_wait<0>();
  fence_regs<64>(acc);
}

__global__ void __launch_bounds__(640, 1)
k1_main(const __grid_constant__ CUtensorMap mXA64, const __grid_constant__ CUtensorMap mXB,
        const __grid_constant__ CUtensorMap mWq, const __grid_constant__ CUtensorMap mWqkv,
        const __grid_constant__ CUtensorMap mQst, const __grid_constant__ CUtensorMap mOst, const Params prm) {
  extern __shared__ uint8_t smem_raw[];
  const uint32_t sb = (smem_u32(smem_raw) + 1023u) & ~1023u;
  const uint32_t bars = sb + OFF_MISC, sStat = bars + 256;
  const int tid = threadIdx.x, warp = __shfl_sync(~0u, tid >> 5, 0), wg = warp >> 2, w4 = warp & 3, lane = tid & 31;
  const bool helper = blockIdx.x >= 128;
  if (tid == 0) TS(0, 0);
  const int G = blockIdx.x >> 4, gi = blockIdx.x & 15;
  const int tbA = G * 4 + (gi >> 2), hg = gi & 3;
  const int ttB = (G >> 1) * 4 + (gi >> 2), hq = (G & 1) * 4 + (gi & 3);
  auto issue = [&](int kb) {
    const int s = kb % 3;
    const uint32_t fb = BAR_FULL(s), st = STAGE(s);
    mbar_expect_tx(fb, 65536);
    tma2d(st + 16384, &mXA64, kb * 64, tbA * 64, fb);
    tma2d(st, &mWq, hg * 128, kb * 64, fb);
    tma2d(st + 8192, &mWq, hg * 128 + 64, kb * 64, fb);
    tma2d(st + 49152, &mXB, kb * 64, ttB * 128, fb);
    tma2d(st + 24576, &mWqkv, hq * 64, kb * 64, fb);
    tma2d(st + 32768, &mWqkv, 512 + hq * 64, kb * 64, fb);
    tma2d(st + 40960, &mWqkv, 1024 + hq * 64, kb * 64, fb);
  };
  const uint32_t sOne = sb + OFF_V + 65536, sWKV = sOne + 24576;
  if (tid == 512) {
    for (int s = 0; s < 3; s++) { mbar_init(BAR_FULL(s), 1); mbar_init(BAR_EMPTY(s), 4); }
    for (int c = 0; c < 4; c++) mbar_init(BAR_KV(c), 1);
    mbar_init(BAR_BDONE, 8);
    mbar_init(BAR_Q, 8);
    for (int i = 0; i < 12; i++) mbar_init(BAR_LM(i), 1);
    asm volatile("fence.mbarrier_init.release.cluster;" ::: "memory");
    if (!helper) {
      mbar_expect_tx(BAR_LM(0), 65536);
      for (int kb = 0; kb < 8; kb++) tma2d(STAGE(2) + kb * 8192, &mXA64, kb * 64, tbA * 64, BAR_LM(0));
      issue(0); issue(1);
    }
  } else if (tid < 512 && !helper) {
    const uint4 v = __ldg((const uint4*)(hg >= 2 ? prm.wv : prm.wk) + tid * 2 + (hg & 1));
#pragma unroll
    for (int i = 0; i < 3; i++) {
      const int key = tid + i * 512;
      sts4(sOne + key * 16, (key % STEPK) < 32 ? 0x00003F80u : 0x00004E80u, 0u, 0u, 0u);
    }
    sts4(sWKV + tid * 16, v.x, v.y, v.z, v.w);
    fence_async();
  }
  __syncthreads();
  pdl_launch();
  if (wg == 4) {
    asm volatile("setmaxnreg.dec.sync.aligned.u32 32;");
    if (helper) {
      if (tid == 512) {
        const uint32_t ep = g_epoch[blockIdx.x] + 1;
        flag_wait(&g_flag[FLAG_B(blockIdx.x - 128) * 32], ep * 32);
        fence_async_all();
        TS(1, 10);
        mbar_arrive(BAR_KV(0));
        g_epoch[blockIdx.x] = ep;
      }
      return;
    }
    {
      float acc[4];
      mbar_wait(BAR_LM(0), 0);
      uint64_t da = make_desc(STAGE(2), 16, 1024, 1), db = make_desc(sWKV, 128, 128, 0);
      wg_fence();
#pragma unroll
      for (int kb = 0; kb < 8; kb++) {
#pragma unroll
        for (int k = 0; k < 4; k++) wg_ss8<0, 1>(acc, da + kb * 512 + k * 2, db + kb * 64 + k * 16, (kb | k) != 0);
      }
      wg_commit();
      wg_wait<0>();
      fence_regs<4>(acc);
      const uint32_t sT = sStat + 512;
      asm volatile("st.shared.b32 [%0], %1;" :: "r"(sT + w4 * 256 + lane * 4), "r"(pack_bf16(acc[0], acc[1])) : "memory");
      asm volatile("st.shared.b32 [%0], %1;" :: "r"(sT + w4 * 256 + 128 + lane * 4), "r"(pack_bf16(acc[2], acc[3])) : "memory");
      named_bar(9, 128);
      if (tid == 512) issue(2);
      const int t = tid - 512;
#pragma unroll
      for (int i = 0; i < 4; i++) {
        const int key = 1536 + t + i * 128;
        sts4(sOne + key * 16, (key % STEPK) < 32 ? 0x00003F80u : 0x00004E80u, 0u, 0u, 0u);
      }
      fence_async();
      __syncwarp();
      if (lane == 0) mbar_arrive(BAR_Q);
      if (w4 == 1 || w4 == 2) {
        const int ch = tbA * 2 + (w4 - 1);
        const uint32_t src = sT + (w4 - 1) * 512;
        uint32_t v[4], o[4];
        lds4(src + lane * 16, v);
        int kap;
        if (lane < 21) kap = lane * STEPK + 32 + ch;
        else { int idx = ch * 11 + (lane - 21); kap = (idx >> 5) * STEPK + (idx & 31); }
        g_KV[(4 + hg) * S_TOK + kap] = make_uint4(v[0], v[1], v[2], v[3]);
        float st = 0.f;
        if (hg < 2) {
          const float sc = lane < 21 ? 2.f : 1.f;
#pragma unroll
          for (int u = 0; u < 4; u++) {
            uint32_t pv = __shfl_up_sync(~0u, v[u], 1);
            if (lane == 0 || lane >= 21) pv = 0;
            const float x = bf_lo(v[u]), y = bf_hi(v[u]);
            st += x * x + y * y;
            o[u] = pack_f16((x - bf_lo(pv)) * sc, (y - bf_hi(pv)) * sc);
          }
        } else {
          const float sc = lane < 21 ? VSHIFT : 1.f;
#pragma unroll
          for (int u = 0; u < 4; u++) { float x = bf_lo(v[u]), y = bf_hi(v[u]); st += fabsf(x) + fabsf(y); o[u] = pack_bf16(x * sc, y * sc); }
        }
        g_KV[hg * S_TOK + kap] = make_uint4(o[0], o[1], o[2], o[3]);
        const uint32_t um = __reduce_max_sync(~0u, __float_as_uint(st) & 0x7FFFFFFFu);
        if (w4 == 2) { if (lane == 0) asm volatile("st.shared.b32 [%0], %1;" :: "r"(sT + 1024), "r"(um) : "memory"); named_arrive(10, 64); }
        else {
          named_bar(10, 64);
          if (lane == 0) {
            uint32_t u2;
            asm volatile("ld.shared.b32 %0, [%1];" : "=r"(u2) : "r"(sT + 1024) : "memory");
            g_stats[tbA * 4 + hg] = max(um, u2);
            fence_async_all();
            flag_add(&g_flag[FLAG_KV * 32]);
            TS(1, 9);
          }
        }
      }
    }
    if (tid == 512) {
      const uint32_t ep = g_epoch[blockIdx.x] + 1;
      for (int kb = 3; kb < 8; kb++) { mbar_wait(BAR_EMPTY(kb % 3), (kb / 3 - 1) & 1); issue(kb); }
      flag_wait(&g_flag[FLAG_KV * 32], ep * 128);
      fence_async_all();
      TS(0, 11);
      mbar_wait(BAR_EMPTY(2), 1);
      mbar_wait(BAR_EMPTY(0), 0);
      const int kbd[5] = {0, STEPK, 4 * STEPK, 7 * STEPK, S_TOK};
#pragma unroll
      for (int c = 0; c < 4; c++) {
        const uint32_t bytes = (kbd[c + 1] - kbd[c]) * 16;
        mbar_expect_tx(BAR_KV(c), 4 * bytes + (c == 0 ? 512 : 0));
        if (c == 0) bulk_g2s(sStat, g_stats, 512, BAR_KV(0));
#pragma unroll
        for (int p = 0; p < 4; p++)
          bulk_g2s(sb + (p < 2 ? OFF_K : OFF_V - 65536) + p * 32768 + kbd[c] * 16, g_KV + p * S_TOK + kbd[c], bytes, BAR_KV(c));
      }
      mbar_wait(BAR_BDONE, 0);
      tma2d_store(&mQst, sb + OFF_F + 49152, hq * 64, S_TOK + ttB * 128);
      bulk_commit();
      bulk_wait_all();
      fence_async_all();
      flag_add(&g_flag[FLAG_B(hq >> 1) * 32]);
      g_epoch[blockIdx.x] = ep;
      TS(0, 12);
    }
    return;
  }
  asm volatile("setmaxnreg.inc.sync.aligned.u32 112;");
  if (helper) { helper_cta(blockIdx.x - 128, sb, bars, &mQst, &mOst); return; }

  {
    float acc[64];
    if (wg == 0) proj_loop<0>(acc, sb, bars, 16384, 0);
    else proj_loop<1>(acc, sb, bars, 16384 + wg * 8192, 49152);
    if (tid == 0) TS(0, 10);
    const uint32_t sF = sb + OFF_F;
    if (wg == 0) {
      uint4* gq = (uint4*)g_Q + blockIdx.x * 1024 + tid;
#pragma unroll
      for (int hd = 0; hd < 8; hd++) {
        uint32_t r[4];
        float n0 = 0.f, n1 = 0.f;
#pragma unroll
        for (int i = 0; i < 4; i++) {
          r[i] = pack_bf16(acc[8 * hd + 2 * i], acc[8 * hd + 2 * i + 1]);
          const float a = bf_lo(r[i]) * QSCALE, b = bf_hi(r[i]) * QSCALE;
          asm volatile("st.shared.b32 [%0], %1;" :: "r"(sF + hd * 2048 + w4 * 512 + lane * 4 + (i & 1) * 256 + (i >> 1) * 128), "r"(pack_f16(a, b)) : "memory");
          if (i & 1) n1 += a * a + b * b; else n0 += a * a + b * b;
        }
        gq[hd * 128] = make_uint4(r[0], r[1], r[2], r[3]);
        n0 += __shfl_xor_sync(~0u, n0, 1); n0 += __shfl_xor_sync(~0u, n0, 2);
        n1 += __shfl_xor_sync(~0u, n1, 1); n1 += __shfl_xor_sync(~0u, n1, 2);
        const uint32_t um = __reduce_max_sync(~0u, max(__float_as_uint(n0) & 0x7FFFFFFFu, __float_as_uint(n1) & 0x7FFFFFFFu));
        if (lane == 0) asm volatile("st.shared.b32 [%0], %1;" :: "r"(sStat + 1664 + hd * 16 + w4 * 4), "r"(um) : "memory");
      }
      fence_async();
      __syncwarp();
      if (lane == 0) mbar_arrive(BAR_Q);
    } else if (wg == 3) {
      named_arrive(8, 384);
      named_bar(6, 384);
      const int t = tid & 127;
#pragma unroll
      for (int j = 0; j < 8; j++)
        sts4(sF + 24576 + j * 2048 + t * 16, pack_bf16(acc[8 * j], acc[8 * j + 1]), pack_bf16(acc[8 * j + 2], acc[8 * j + 3]),
             pack_bf16(acc[8 * j + 4], acc[8 * j + 5]), pack_bf16(acc[8 * j + 6], acc[8 * j + 7]));
      named_arrive(7, 256);
    } else {
      uint32_t p[32];
      named_arrive(6, 384);
      if (wg == 2) named_arrive(8, 384);
#pragma unroll
      for (int i = 0; i < 32; i++) p[i] = phi2(acc[2 * i], acc[2 * i + 1]);
      if (wg == 1) {
        named_bar(8, 384);
        const int m = lane >> 3, r = lane & 7;
#pragma unroll
        for (int j = 0; j < 16; j += 2) {
          const int tok = (j + (m >> 1)) * 8 + r;
          const int chunk = w4 * 2 + (m & 1);
          stsm4t(sF + 49152 + tok * 128 + ((chunk ^ r) << 4), p[2 * j], p[2 * j + 1], p[2 * j + 2], p[2 * j + 3]);
        }
        fence_async();
      } else {
        named_bar(7, 256);
        float kv0[4] = {0, 0, 0, 0}, kv1[4] = {0, 0, 0, 0}, z0[4] = {0, 0, 0, 0}, z1[4] = {0, 0, 0, 0};
        const uint32_t one = 0x3F803F80u;
        const int t = tid & 127;
#pragma unroll
        for (int j = 0; j < 8; j++) {
          uint32_t a[4];
          lds4(sF + 24576 + j * 2048 + t * 16, a);
          mma_bf16(kv0, a[0], a[1], a[2], a[3], p[4 * j], p[4 * j + 2]);
          mma_bf16(kv1, a[0], a[1], a[2], a[3], p[4 * j + 1], p[4 * j + 3]);
          mma_bf16(z0, one, one, one, one, p[4 * j], p[4 * j + 2]);
          mma_bf16(z1, one, one, one, one, p[4 * j + 1], p[4 * j + 3]);
        }
        float4* dst = g_kvp + ((ttB * 32 + hq * 4 + w4) * 3) * 32 + lane;
        dst[0] = make_float4(kv0[0], kv0[1], kv1[0], kv1[1]);
        dst[32] = make_float4(kv0[2], kv0[3], kv1[2], kv1[3]);
        dst[64] = make_float4(z0[0], z0[1], z1[0], z1[1]);
      }
      __syncwarp();
      if (lane == 0) mbar_arrive(BAR_BDONE);
    }
  }
  mbar_wait(BAR_Q, 0);

  mbar_wait(BAR_KV(0), 0);
  if (tid == 0) TS(1, 1);
  uint32_t badmask;
  {
    uint32_t a[4], n[4], n2[4];
    lds4(sStat + lane * 16, a);
    lds4(sStat + 1664 + wg * 16, n);
    lds4(sStat + 1664 + 64 + wg * 16, n2);
    const float kmax2 = __uint_as_float(__reduce_max_sync(~0u, a[0])) + __uint_as_float(__reduce_max_sync(~0u, a[1]));
    const float vmax = __uint_as_float(__reduce_max_sync(~0u, max(a[2], a[3])));
    const float lv = vmax > 0.f ? __log2f(vmax) : 0.f;
    const float lim = fminf(90.f, fminf(91.f + lv, 95.f - lv));
    const bool gok = vmax < 1e27f && kmax2 <= 65536.f && lim > 0.f;
    const float q0 = __uint_as_float(max(max(n[0], n[1]), max(n[2], n[3])));
    const float q1 = __uint_as_float(max(max(n2[0], n2[1]), max(n2[2], n2[3])));
    const bool ok0 = gok && q0 <= 65536.f && q0 * kmax2 * 1.01f <= lim * lim;
    const bool ok1 = gok && q1 <= 65536.f && q1 * kmax2 * 1.01f <= lim * lim;
    badmask = (__all_sync(~0u, ok0) ? 0u : 1u) | (__all_sync(~0u, ok1) ? 0u : 2u);
  }
  const int g = lane >> 2, t = lane & 3;
  const uint32_t c63 = 0x1F801F80u + (badmask >> 2);
  const uint32_t m1 = (gridDim.x >> 20) - 1u;
  const uint64_t dK0 = make_desc(sb + OFF_K, 32768, 128, 0);
  const uint64_t dV0 = make_desc(sb + OFF_V, 128, 32768, 0);

#pragma unroll 1
  for (int pass = 0; pass < 2; pass++) {
    const int hd = pass * 4 + wg;
    __nv_bfloat16* od = g_O + (size_t)(tbA * 64) * D_MOD + (hg * 8 + hd) * 16;
    if ((badmask >> pass) & 1) {
      attn_slow((const uint4*)g_Q + blockIdx.x * 1024 + hd * 128, od);
      continue;
    }
    const uint64_t dQ = make_desc(sb + OFF_F + hd * 2048, 128, 256, 0);
    float Sm[16], Sp[32], O[12];
    uint32_t P[24];
#pragma unroll
    for (int i = 0; i < 32; i++) Sp[i] = SMAGIC;
#pragma unroll
    for (int i = 0; i < 16; i++) Sm[i] = 0.f;
#pragma unroll
    for (int i = 0; i < 12; i++) O[i] = 0.f;
    fence_regs<16>(Sm); fence_regs<32>(Sp); fence_regs<12>(O);
    if (tid == 0) TS(1, 2 + 2 * pass);
    wg_fence();
    wg_qs32<0>(Sm, dQ, dK0);
    wg_qs64<1>(Sp, dQ, dK0 + 32);
    wg_commit();
    wg_wait<0>();
    fence_regs<16>(Sm); fence_regs<32>(Sp);
    uint64_t dK = dK0 + STEPK, dV = dV0;
#pragma unroll 1
    for (int s3 = 0; s3 < 3; s3++) {
      mbar_wait(BAR_KV(s3 + 1), 0);
      const int n = s3 == 2 ? 15 : 3;
#pragma unroll 1
      for (int u = 0; u < n; u++) {
#pragma unroll
        for (int i = 0; i < 8; i++) P[i] = pack_bf16(ex2f(Sm[2 * i]), ex2f(Sm[2 * i + 1]));
#pragma unroll
        for (int i = 0; i < 16; i++) P[8 + i] = exp2_pair_fix(Sp[2 * i], Sp[2 * i + 1], c63, m1);
        fence_regs<24>(P);
        wg_fence();
        wg_qs32<0>(Sm, dQ, dK);
        wg_qs64<1>(Sp, dQ, dK + 32);
#pragma unroll
        for (int k = 0; k < 6; k++) wg_pv24<1>(O, &P[4 * k], dV + k * 16);
        wg_commit();
        wg_wait<0>();
        fence_regs<16>(Sm); fence_regs<32>(Sp); fence_regs<12>(O); fence_regs<24>(P);
        dK += STEPK; dV += STEPK;
      }
    }
#pragma unroll
    for (int i = 0; i < 8; i++) P[i] = pack_bf16(ex2f(Sm[2 * i]), ex2f(Sm[2 * i + 1]));
    fence_regs<8>(P);
    wg_fence();
    wg_pv24<1>(O, &P[0], dV);
    wg_pv24<1>(O, &P[4], dV + 16);
    wg_commit();
    wg_wait<0>();
    fence_regs<12>(O);
    const float l0 = __shfl_sync(~0u, O[8], lane & ~3), l1 = __shfl_sync(~0u, O[10], lane & ~3);
    const float i0 = rcpf(l0), i1 = rcpf(l1);
    uint32_t* op = (uint32_t*)(od + (size_t)(w4 * 16 + g) * D_MOD) + t;
    op[0] = pack_bf16(O[0] * i0, O[1] * i0);
    op[8 * 256] = pack_bf16(O[2] * i1, O[3] * i1);
    op[4] = pack_bf16(O[4] * i0, O[5] * i0);
    op[8 * 256 + 4] = pack_bf16(O[6] * i1, O[7] * i1);
    if (tid == 0) TS(1, 3 + 2 * pass);
    if ((tid & 127) == 0 && pass == 1 && wg > 0) TS(1, 10 + wg);
  }
}

#define K3_SMEM (131072 + 6 * 16384 + 1024 + 256)
__global__ void __cluster_dims__(2, 1, 1) __launch_bounds__(288, 1)
k3_out(const __grid_constant__ CUtensorMap mO, const __grid_constant__ CUtensorMap mWoA,
       const __grid_constant__ CUtensorMap mWoB, const __grid_constant__ CUtensorMap mOut) {
  extern __shared__ uint8_t smem_raw[];
  const uint32_t sb = (smem_u32(smem_raw) + 1023u) & ~1023u;
  const uint32_t sW = sb, sA = sb + 131072, bars = sA + 6 * 16384;
  const int tid = threadIdx.x, wg = tid >> 7, warp = tid >> 5, lane = tid & 31;
  const int rank = blockIdx.x & 1;
  const int nt = (blockIdx.x & 7);
  const int tt = blockIdx.x >> 3;
  const int part = nt >> 2;
  if (tid == 0) TS(2, 0);
  if (tid == 0) {
    for (int s = 0; s < 14; s++) mbar_init(bars + 8 * s, 1);
    mbar_init(bars + 112, 4); mbar_init(bars + 120, 4);
    asm volatile("fence.mbarrier_init.release.cluster;" ::: "memory");
  }
  cluster_sync();
  if (wg == 2) {
    if (lane == 0) {
      const CUtensorMap* mW = part ? &mWoB : &mWoA;
      const int col = (nt & 3) * 128;
      for (int kb = 0; kb < 8; kb++) {
        mbar_expect_tx(bars + 8 * kb, 16384);
        tma2d(sW + kb * 16384, mW, col, kb * 64, bars + 8 * kb);
        tma2d(sW + kb * 16384 + 8192, mW, col + 64, kb * 64, bars + 8 * kb);
      }
      pdl_wait();
      TS(2, 1);
      const int row = part * S_TOK + tt * 128 + rank * 64;
      for (int kb = 0; kb < 8; kb++) {
        const int s = kb < 6 ? kb : kb - 6;
        if (kb >= 6) mbar_wait(bars + 112 + 8 * s, 0);
        mbar_expect_tx(bars + 64 + 8 * s, 16384);
        tma2d_mc(sA + s * 16384 + rank * 8192, &mO, kb * 64, row, bars + 64 + 8 * s, 3);
      }
    }
  } else {
    float acc[64];
#pragma unroll
    for (int kb = 0; kb < 8; kb++) {
      const int s = kb < 6 ? kb : kb - 6;
      mbar_wait(bars + 8 * kb, 0);
      mbar_wait(bars + 64 + 8 * s, kb >= 6);
      if (tid == 0) TS(2, 2 + kb);
      uint64_t da = make_desc(sA + s * 16384 + wg * 8192, 16, 1024, 1);
      uint64_t db = make_desc(sW + kb * 16384, 8192, 1024, 1);
      wg_fence();
#pragma unroll
      for (int k = 0; k < 4; k++) wg_ss128<0, 1>(acc, da + k * 2, db + k * 128, (kb | k) != 0);
      wg_commit();
      if (kb == 1 || kb == 2) {
        wg_wait<1>();
        if ((tid & 127) == 0) { mbar_arrive_cta(bars + 112 + 8 * (kb - 1), 0); mbar_arrive_cta(bars + 112 + 8 * (kb - 1), 1); }
        __syncwarp();
      }
    }
    wg_wait<0>();
    fence_regs<64>(acc);
    const int w4 = warp & 3, m = lane >> 3, r = lane & 7;
#pragma unroll
    for (int j = 0; j < 16; j += 2) {
      const uint32_t stg = sA + (2 + (j >> 3)) * 16384 + wg * 8192;
      const int row = w4 * 16 + (m & 1) * 8 + r;
      const int chunk = (j & 7) + (m >> 1);
      stsm4(stg + row * 128 + ((chunk ^ r) << 4),
            pack_bf16(acc[4 * j], acc[4 * j + 1]), pack_bf16(acc[4 * j + 2], acc[4 * j + 3]),
            pack_bf16(acc[4 * j + 4], acc[4 * j + 5]), pack_bf16(acc[4 * j + 6], acc[4 * j + 7]));
    }
    fence_async();
    named_bar(wg + 1, 128);
    if ((tid & 127) == 0) {
      tma2d_store(&mOut, sA + 2 * 16384 + wg * 8192, nt * 128, tt * 128 + wg * 64);
      tma2d_store(&mOut, sA + 3 * 16384 + wg * 8192, nt * 128 + 64, tt * 128 + wg * 64);
      if (tid == 0) TS(2, 11);
      bulk_commit();
      bulk_wait_all();
      if (tid == 0) TS(2, 12);
    }
  }
}

typedef CUresult (*EncodeFn)(CUtensorMap*, CUtensorMapDataType, cuuint32_t, void*, const cuuint64_t*, const cuuint64_t*,
                             const cuuint32_t*, const cuuint32_t*, CUtensorMapInterleave, CUtensorMapSwizzle,
                             CUtensorMapL2promotion, CUtensorMapFloatOOBfill);

static void make_map(EncodeFn enc, CUtensorMap* m, const void* ptr, uint64_t cols, uint64_t rows, uint32_t bc, uint32_t br) {
  cuuint64_t dims[2] = {cols, rows};
  cuuint64_t strides[1] = {cols * 2};
  cuuint32_t box[2] = {bc, br};
  cuuint32_t es[2] = {1, 1};
  enc(m, CU_TENSOR_MAP_DATA_TYPE_BFLOAT16, 2, (void*)ptr, dims, strides, box, es, CU_TENSOR_MAP_INTERLEAVE_NONE,
      CU_TENSOR_MAP_SWIZZLE_128B, CU_TENSOR_MAP_L2_PROMOTION_L2_256B, CU_TENSOR_MAP_FLOAT_OOB_FILL_NONE);
}

extern "C" void kernel_launch(void* const* d_in, const int* in_sizes, int n_in, void* d_out, int out_size) {
  (void)in_sizes; (void)n_in; (void)out_size;
  static EncodeFn enc = nullptr;
  static void* pQ = nullptr; static void* pO = nullptr;
  if (!enc) {
    void* fn = nullptr; cudaDriverEntryPointQueryResult qr;
    cudaGetDriverEntryPoint("cuTensorMapEncodeTiled", &fn, cudaEnableDefault, &qr);
    enc = (EncodeFn)fn;
    cudaGetSymbolAddress(&pQ, g_Q);
    cudaGetSymbolAddress(&pO, g_O);
    cudaFuncSetAttribute(k1_main, cudaFuncAttributeMaxDynamicSharedMemorySize, SM_TOTAL);
    cudaFuncSetAttribute(k3_out, cudaFuncAttributeMaxDynamicSharedMemorySize, K3_SMEM);
  }
  CUtensorMap mXA64, mXB, mWq, mWqkv, mQst, mO, mOst, mWoA, mWoB, mOut;
  make_map(enc, &mXA64, d_in[0], 512, 2048, 64, 64);
  make_map(enc, &mWq, d_in[1], 512, 512, 64, 64);
  make_map(enc, &mWoA, d_in[4], 512, 512, 64, 64);
  make_map(enc, &mXB, d_in[5], 512, 2048, 64, 128);
  make_map(enc, &mWqkv, d_in[6], 1536, 512, 64, 64);
  make_map(enc, &mWoB, d_in[7], 512, 512, 64, 64);
  make_map(enc, &mQst, pQ, 512, 4096, 64, 128);
  make_map(enc, &mO, pO, 512, 4096, 64, 64);
  make_map(enc, &mOst, pO, 512, 4096, 64, 128);
  make_map(enc, &mOut, d_out, 1024, 2048, 64, 64);
  Params prm{(const __nv_bfloat16*)d_in[2], (const __nv_bfloat16*)d_in[3]};

  cudaStream_t st = cudaStreamPerThread;
  cudaLaunchAttribute at[1];
  at[0].id = cudaLaunchAttributeProgrammaticStreamSerialization;
  at[0].val.programmaticStreamSerializationAllowed = 1;
  cudaLaunchConfig_t cfg = {};
  cfg.stream = st;
  cfg.gridDim = dim3(132); cfg.blockDim = dim3(640); cfg.dynamicSmemBytes = SM_TOTAL; cfg.attrs = at; cfg.numAttrs = 0;
  cudaLaunchKernelEx(&cfg, k1_main, mXA64, mXB, mWq, mWqkv, mQst, mOst, prm);
  cfg.gridDim = dim3(128); cfg.blockDim = dim3(288); cfg.dynamicSmemBytes = K3_SMEM; cfg.numAttrs = 1;
  cudaLaunchKernelEx(&cfg, k3_out, mO, mWoA, mWoB, mOut);
}
```

```cpp
#include <cuda_runtime.h>
#include <cuda_bf16.h>
#include <cuda_fp16.h>
#include <cuda.h>
#include <stdint.h>

#define S_TOK 2048
#define D_MOD 512

__device__ __align__(1024) __nv_bfloat16 g_Q[2 * S_TOK * D_MOD];
__device__ __align__(1024) __nv_bfloat16 g_O[2 * S_TOK * D_MOD];
__device__ __align__(1024) uint4 g_KV[8 * S_TOK];
__device__ __align__(16) uint32_t g_stats[128];
__device__ __align__(16) float4 g_kvp[16 * 32 * 3 * 32];

#define TS(k, i) do {} while (0)
__device__ __forceinline__ uint32_t smem_u32(const void* p) { return (uint32_t)__cvta_generic_to_shared(p); }
__device__ __forceinline__ void mbar_init(uint32_t bar, int cnt) { asm volatile("mbarrier.init.shared::cta.b64 [%0], %1;" :: "r"(bar), "r"(cnt) : "memory"); }
__device__ __forceinline__ void mbar_expect_tx(uint32_t bar, uint32_t bytes) { asm volatile("mbarrier.arrive.expect_tx.shared::cta.b64 _, [%0], %1;" :: "r"(bar), "r"(bytes) : "memory"); }
__device__ __forceinline__ bool mbar_try(uint32_t bar, uint32_t parity) {
  uint32_t ok;
  asm volatile("{\n.reg .pred p;\nmbarrier.try_wait.parity.shared::cta.b64 p, [%1], %2;\nselp.b32 %0, 1, 0, p;\n}\n" : "=r"(ok) : "r"(bar), "r"(parity) : "memory");
  return ok;
}
__device__ __forceinline__ void mbar_wait(uint32_t bar, uint32_t parity) {
  asm volatile("{\n.reg .pred p;\n.reg .u32 c;\nmov.u32 c, 0;\n"
               "LW_%=:\n"
               "mbarrier.try_wait.parity.shared::cta.b64 p, [%0], %1;\n"
               "@p bra LD_%=;\n"
               "add.u32 c, c, 1;\n"
               "setp.lt.u32 p, c, 4000000;\n"
               "@p bra LW_%=;\n"
               "trap;\n"
               "LD_%=:\n}\n" :: "r"(bar), "r"(parity) : "memory");
}
__device__ __forceinline__ void mbar_arrive_cta(uint32_t bar, uint32_t cta) {
  asm volatile("{\n.reg .b32 ra;\nmapa.shared::cluster.u32 ra, %0, %1;\nmbarrier.arrive.shared::cluster.b64 _, [ra];\n}\n" :: "r"(bar), "r"(cta) : "memory");
}
__device__ __forceinline__ void cluster_sync() {
  asm volatile("barrier.cluster.arrive.relaxed.aligned;\nbarrier.cluster.wait.aligned;" ::: "memory");
}
__device__ __forceinline__ void tma2d(uint32_t dst, const CUtensorMap* m, int c0, int c1, uint32_t bar) {
  asm volatile("cp.async.bulk.tensor.2d.shared::cluster.global.mbarrier::complete_tx::bytes [%0], [%1, {%3, %4}], [%2];"
               :: "r"(dst), "l"(m), "r"(bar), "r"(c0), "r"(c1) : "memory");
}
__device__ __forceinline__ void tma2d_mc(uint32_t dst, const CUtensorMap* m, int c0, int c1, uint32_t bar, uint16_t mask) {
  asm volatile("cp.async.bulk.tensor.2d.shared::cluster.global.mbarrier::complete_tx::bytes.multicast::cluster [%0], [%1, {%3, %4}], [%2], %5;"
               :: "r"(dst), "l"(m), "r"(bar), "r"(c0), "r"(c1), "h"(mask) : "memory");
}
__device__ __forceinline__ void tma2d_store(const CUtensorMap* m, uint32_t src, int c0, int c1) {
  asm volatile("cp.async.bulk.tensor.2d.global.shared::cta.bulk_group [%0, {%2, %3}], [%1];"
               :: "l"(m), "r"(src), "r"(c0), "r"(c1) : "memory");
}
__device__ __forceinline__ void bulk_g2s(uint32_t dst, const void* src, uint32_t bytes, uint32_t bar) {
  asm volatile("cp.async.bulk.shared::cluster.global.mbarrier::complete_tx::bytes [%0], [%1], %2, [%3];"
               :: "r"(dst), "l"(src), "r"(bytes), "r"(bar) : "memory");
}
__device__ __forceinline__ void bulk_commit() { asm volatile("cp.async.bulk.commit_group;" ::: "memory"); }
__device__ __forceinline__ void bulk_wait_all() { asm volatile("cp.async.bulk.wait_group 0;" ::: "memory"); }
__device__ __forceinline__ void fence_async() { asm volatile("fence.proxy.async.shared::cta;" ::: "memory"); }
__device__ __forceinline__ void named_bar(int id, int n) { asm volatile("bar.sync %0, %1;" :: "r"(id), "r"(n) : "memory"); }
__device__ __forceinline__ void pdl_launch() { asm volatile("griddepcontrol.launch_dependents;" ::: "memory"); }
__device__ __forceinline__ void pdl_wait() { asm volatile("griddepcontrol.wait;" ::: "memory"); }
__device__ __forceinline__ void wg_fence() { asm volatile("wgmma.fence.sync.aligned;" ::: "memory"); }
__device__ __forceinline__ void wg_commit() { asm volatile("wgmma.commit_group.sync.aligned;" ::: "memory"); }
template <int n> __device__ __forceinline__ void wg_wait() { asm volatile("wgmma.wait_group.sync.aligned %0;" :: "n"(n) : "memory"); }
template <int n> __device__ __forceinline__ void fence_regs(float* r) {
#pragma unroll
  for (int i = 0; i < n; i++) asm volatile("" : "+f"(r[i]) :: "memory");
}
template <int n> __device__ __forceinline__ void fence_regs(uint32_t* r) {
#pragma unroll
  for (int i = 0; i < n; i++) asm volatile("" : "+r"(r[i]) :: "memory");
}
__device__ __forceinline__ uint64_t make_desc(uint32_t addr, uint32_t lbo, uint32_t sbo, uint32_t swz) {
  return (uint64_t)((addr & 0x3FFFF) >> 4) | ((uint64_t)(lbo >> 4) << 16) | ((uint64_t)(sbo >> 4) << 32) | ((uint64_t)swz << 62);
}
__device__ __forceinline__ float ex2f(float x) { float y; asm("ex2.approx.ftz.f32 %0, %1;" : "=f"(y) : "f"(x)); return y; }
__device__ __forceinline__ uint32_t pack_bf16(float lo, float hi) { uint32_t r; asm("cvt.rn.bf16x2.f32 %0, %1, %2;" : "=r"(r) : "f"(hi), "f"(lo)); return r; }
__device__ __forceinline__ uint32_t pack_f16(float lo, float hi) { uint32_t r; asm("cvt.rn.f16x2.f32 %0, %1, %2;" : "=r"(r) : "f"(hi), "f"(lo)); return r; }
__device__ __forceinline__ float bf_lo(uint32_t v) { return __uint_as_float(v << 16); }
__device__ __forceinline__ float bf_hi(uint32_t v) { return __uint_as_float(v & 0xFFFF0000u); }
__device__ __forceinline__ float rbf(float x) { return __bfloat162float(__float2bfloat16_rn(x)); }
__device__ __forceinline__ void stsm4(uint32_t a, uint32_t r0, uint32_t r1, uint32_t r2, uint32_t r3) {
  asm volatile("stmatrix.sync.aligned.m8n8.x4.shared.b16 [%0], {%1,%2,%3,%4};" :: "r"(a), "r"(r0), "r"(r1), "r"(r2), "r"(r3) : "memory");
}
__device__ __forceinline__ void stsm4t(uint32_t a, uint32_t r0, uint32_t r1, uint32_t r2, uint32_t r3) {
  asm volatile("stmatrix.sync.aligned.m8n8.x4.trans.shared.b16 [%0], {%1,%2,%3,%4};" :: "r"(a), "r"(r0), "r"(r1), "r"(r2), "r"(r3) : "memory");
}
__device__ __forceinline__ void mma_bf16(float* d, uint32_t a0, uint32_t a1, uint32_t a2, uint32_t a3, uint32_t b0, uint32_t b1) {
  asm volatile("mma.sync.aligned.m16n8k16.row.col.f32.bf16.bf16.f32 {%0,%1,%2,%3}, {%4,%5,%6,%7}, {%8,%9}, {%0,%1,%2,%3};"
               : "+f"(d[0]), "+f"(d[1]), "+f"(d[2]), "+f"(d[3]) : "r"(a0), "r"(a1), "r"(a2), "r"(a3), "r"(b0), "r"(b1));
}
template<int SD> __device__ __forceinline__ void wg_qk32(float* d, const uint32_t* a, uint64_t desc) {
  asm volatile("wgmma.mma_async.sync.aligned.m64n32k16.f32.f16.f16 {%0,%1,%2,%3,%4,%5,%6,%7,%8,%9,%10,%11,%12,%13,%14,%15}, {%16,%17,%18,%19}, %20, %21, 1, 1, 0;"
   : "+f"(d[0]),"+f"(d[1]),"+f"(d[2]),"+f"(d[3]),"+f"(d[4]),"+f"(d[5]),"+f"(d[6]),"+f"(d[7]),"+f"(d[8]),"+f"(d[9]),"+f"(d[10]),"+f"(d[11]),"+f"(d[12]),"+f"(d[13]),"+f"(d[14]),"+f"(d[15])
   : "r"(a[0]),"r"(a[1]),"r"(a[2]),"r"(a[3]),"l"(desc),"n"(SD));
}
template<int SD> __device__ __forceinline__ void wg_qk64(float* d, const uint32_t* a, uint64_t desc) {
  asm volatile("wgmma.mma_async.sync.aligned.m64n64k16.f32.f16.f16 {%0,%1,%2,%3,%4,%5,%6,%7,%8,%9,%10,%11,%12,%13,%14,%15,%16,%17,%18,%19,%20,%21,%22,%23,%24,%25,%26,%27,%28,%29,%30,%31}, {%32,%33,%34,%35}, %36, %37, 1, 1, 0;"
   : "+f"(d[0]),"+f"(d[1]),"+f"(d[2]),"+f"(d[3]),"+f"(d[4]),"+f"(d[5]),"+f"(d[6]),"+f"(d[7]),"+f"(d[8]),"+f"(d[9]),"+f"(d[10]),"+f"(d[11]),"+f"(d[12]),"+f"(d[13]),"+f"(d[14]),"+f"(d[15]),"+f"(d[16]),"+f"(d[17]),"+f"(d[18]),"+f"(d[19]),"+f"(d[20]),"+f"(d[21]),"+f"(d[22]),"+f"(d[23]),"+f"(d[24]),"+f"(d[25]),"+f"(d[26]),"+f"(d[27]),"+f"(d[28]),"+f"(d[29]),"+f"(d[30]),"+f"(d[31])
   : "r"(a[0]),"r"(a[1]),"r"(a[2]),"r"(a[3]),"l"(desc),"n"(SD));
}
template<int SD> __device__ __forceinline__ void wg_qs32(float* d, uint64_t da, uint64_t db) {
  asm volatile("wgmma.mma_async.sync.aligned.m64n32k16.f32.f16.f16 {%0,%1,%2,%3,%4,%5,%6,%7,%8,%9,%10,%11,%12,%13,%14,%15}, %16, %17, %18, 1, 1, 0, 0;"
   : "+f"(d[0]),"+f"(d[1]),"+f"(d[2]),"+f"(d[3]),"+f"(d[4]),"+f"(d[5]),"+f"(d[6]),"+f"(d[7]),"+f"(d[8]),"+f"(d[9]),"+f"(d[10]),"+f"(d[11]),"+f"(d[12]),"+f"(d[13]),"+f"(d[14]),"+f"(d[15])
   : "l"(da),"l"(db),"n"(SD));
}
template<int SD> __device__ __forceinline__ void wg_qs64(float* d, uint64_t da, uint64_t db) {
  asm volatile("wgmma.mma_async.sync.aligned.m64n64k16.f32.f16.f16 {%0,%1,%2,%3,%4,%5,%6,%7,%8,%9,%10,%11,%12,%13,%14,%15,%16,%17,%18,%19,%20,%21,%22,%23,%24,%25,%26,%27,%28,%29,%30,%31}, %32, %33, %34, 1, 1, 0, 0;"
   : "+f"(d[0]),"+f"(d[1]),"+f"(d[2]),"+f"(d[3]),"+f"(d[4]),"+f"(d[5]),"+f"(d[6]),"+f"(d[7]),"+f"(d[8]),"+f"(d[9]),"+f"(d[10]),"+f"(d[11]),"+f"(d[12]),"+f"(d[13]),"+f"(d[14]),"+f"(d[15]),"+f"(d[16]),"+f"(d[17]),"+f"(d[18]),"+f"(d[19]),"+f"(d[20]),"+f"(d[21]),"+f"(d[22]),"+f"(d[23]),"+f"(d[24]),"+f"(d[25]),"+f"(d[26]),"+f"(d[27]),"+f"(d[28]),"+f"(d[29]),"+f"(d[30]),"+f"(d[31])
   : "l"(da),"l"(db),"n"(SD));
}
template<int SD> __device__ __forceinline__ void wg_pv24(float* d, const uint32_t* a, uint64_t desc) {
  asm volatile("wgmma.mma_async.sync.aligned.m64n24k16.f32.bf16.bf16 {%0,%1,%2,%3,%4,%5,%6,%7,%8,%9,%10,%11}, {%12,%13,%14,%15}, %16, %17, 1, 1, 1;"
   : "+f"(d[0]),"+f"(d[1]),"+f"(d[2]),"+f"(d[3]),"+f"(d[4]),"+f"(d[5]),"+f"(d[6]),"+f"(d[7]),"+f"(d[8]),"+f"(d[9]),"+f"(d[10]),"+f"(d[11])
   : "r"(a[0]),"r"(a[1]),"r"(a[2]),"r"(a[3]),"l"(desc),"n"(SD));
}
template<int TA, int TB> __device__ __forceinline__ void wg_ss128(float* d, uint64_t da, uint64_t db, int sd) {
  asm volatile("{\n.reg .pred p;\nsetp.ne.b32 p, %66, 0;\n"
   "wgmma.mma_async.sync.aligned.m64n128k16.f32.bf16.bf16 {%0,%1,%2,%3,%4,%5,%6,%7,%8,%9,%10,%11,%12,%13,%14,%15,%16,%17,%18,%19,%20,%21,%22,%23,%24,%25,%26,%27,%28,%29,%30,%31,%32,%33,%34,%35,%36,%37,%38,%39,%40,%41,%42,%43,%44,%45,%46,%47,%48,%49,%50,%51,%52,%53,%54,%55,%56,%57,%58,%59,%60,%61,%62,%63}, %64, %65, p, 1, 1, %67, %68;\n}\n"
   : "+f"(d[0]),"+f"(d[1]),"+f"(d[2]),"+f"(d[3]),"+f"(d[4]),"+f"(d[5]),"+f"(d[6]),"+f"(d[7]),"+f"(d[8]),"+f"(d[9]),"+f"(d[10]),"+f"(d[11]),"+f"(d[12]),"+f"(d[13]),"+f"(d[14]),"+f"(d[15]),"+f"(d[16]),"+f"(d[17]),"+f"(d[18]),"+f"(d[19]),"+f"(d[20]),"+f"(d[21]),"+f"(d[22]),"+f"(d[23]),"+f"(d[24]),"+f"(d[25]),"+f"(d[26]),"+f"(d[27]),"+f"(d[28]),"+f"(d[29]),"+f"(d[30]),"+f"(d[31]),"+f"(d[32]),"+f"(d[33]),"+f"(d[34]),"+f"(d[35]),"+f"(d[36]),"+f"(d[37]),"+f"(d[38]),"+f"(d[39]),"+f"(d[40]),"+f"(d[41]),"+f"(d[42]),"+f"(d[43]),"+f"(d[44]),"+f"(d[45]),"+f"(d[46]),"+f"(d[47]),"+f"(d[48]),"+f"(d[49]),"+f"(d[50]),"+f"(d[51]),"+f"(d[52]),"+f"(d[53]),"+f"(d[54]),"+f"(d[55]),"+f"(d[56]),"+f"(d[57]),"+f"(d[58]),"+f"(d[59]),"+f"(d[60]),"+f"(d[61]),"+f"(d[62]),"+f"(d[63])
   : "l"(da),"l"(db),"r"(sd),"n"(TA),"n"(TB));
}
template<int TA, int TB> __device__ __forceinline__ void wg_ss64(float* d, uint64_t da, uint64_t db, int sd) {
  asm volatile("{\n.reg .pred p;\nsetp.ne.b32 p, %34, 0;\n"
   "wgmma.mma_async.sync.aligned.m64n64k16.f32.bf16.bf16 {%0,%1,%2,%3,%4,%5,%6,%7,%8,%9,%10,%11,%12,%13,%14,%15,%16,%17,%18,%19,%20,%21,%22,%23,%24,%25,%26,%27,%28,%29,%30,%31}, %32, %33, p, 1, 1, %35, %36;\n}\n"
   : "+f"(d[0]),"+f"(d[1]),"+f"(d[2]),"+f"(d[3]),"+f"(d[4]),"+f"(d[5]),"+f"(d[6]),"+f"(d[7]),"+f"(d[8]),"+f"(d[9]),"+f"(d[10]),"+f"(d[11]),"+f"(d[12]),"+f"(d[13]),"+f"(d[14]),"+f"(d[15]),"+f"(d[16]),"+f"(d[17]),"+f"(d[18]),"+f"(d[19]),"+f"(d[20]),"+f"(d[21]),"+f"(d[22]),"+f"(d[23]),"+f"(d[24]),"+f"(d[25]),"+f"(d[26]),"+f"(d[27]),"+f"(d[28]),"+f"(d[29]),"+f"(d[30]),"+f"(d[31])
   : "l"(da),"l"(db),"r"(sd),"n"(TA),"n"(TB));
}

template<int TA, int TB> __device__ __forceinline__ void wg_ss8(float* d, uint64_t da, uint64_t db, int sd) {
  asm volatile("{\n.reg .pred p;\nsetp.ne.b32 p, %6, 0;\n"
   "wgmma.mma_async.sync.aligned.m64n8k16.f32.bf16.bf16 {%0,%1,%2,%3}, %4, %5, p, 1, 1, %7, %8;\n}\n"
   : "+f"(d[0]),"+f"(d[1]),"+f"(d[2]),"+f"(d[3])
   : "l"(da),"l"(db),"r"(sd),"n"(TA),"n"(TB));
}

template<int SD, uint32_t HI> __device__ __forceinline__ void wq32(float* d, uint64_t da, uint32_t lo) {
  asm volatile("{\n.reg .b64 db;\nmov.b64 db, {%17, %19};\n"
   "wgmma.mma_async.sync.aligned.m64n32k16.f32.f16.f16 {%0,%1,%2,%3,%4,%5,%6,%7,%8,%9,%10,%11,%12,%13,%14,%15}, %16, db, %18, 1, 1, 0, 0;\n}\n"
   : "+f"(d[0]),"+f"(d[1]),"+f"(d[2]),"+f"(d[3]),"+f"(d[4]),"+f"(d[5]),"+f"(d[6]),"+f"(d[7]),"+f"(d[8]),"+f"(d[9]),"+f"(d[10]),"+f"(d[11]),"+f"(d[12]),"+f"(d[13]),"+f"(d[14]),"+f"(d[15])
   : "l"(da),"r"(lo),"n"(SD),"r"(HI));
}
template<int SD, uint32_t HI> __device__ __forceinline__ void wq64(float* d, uint64_t da, uint32_t lo) {
  asm volatile("{\n.reg .b64 db;\nmov.b64 db, {%33, %35};\n"
   "wgmma.mma_async.sync.aligned.m64n64k16.f32.f16.f16 {%0,%1,%2,%3,%4,%5,%6,%7,%8,%9,%10,%11,%12,%13,%14,%15,%16,%17,%18,%19,%20,%21,%22,%23,%24,%25,%26,%27,%28,%29,%30,%31}, %32, db, %34, 1, 1, 0, 0;\n}\n"
   : "+f"(d[0]),"+f"(d[1]),"+f"(d[2]),"+f"(d[3]),"+f"(d[4]),"+f"(d[5]),"+f"(d[6]),"+f"(d[7]),"+f"(d[8]),"+f"(d[9]),"+f"(d[10]),"+f"(d[11]),"+f"(d[12]),"+f"(d[13]),"+f"(d[14]),"+f"(d[15]),"+f"(d[16]),"+f"(d[17]),"+f"(d[18]),"+f"(d[19]),"+f"(d[20]),"+f"(d[21]),"+f"(d[22]),"+f"(d[23]),"+f"(d[24]),"+f"(d[25]),"+f"(d[26]),"+f"(d[27]),"+f"(d[28]),"+f"(d[29]),"+f"(d[30]),"+f"(d[31])
   : "l"(da),"r"(lo),"n"(SD),"r"(HI));
}
template<int SD, uint32_t HI> __device__ __forceinline__ void wpv(float* d, const uint32_t* a, uint32_t lo) {
  asm volatile("{\n.reg .b64 db;\nmov.b64 db, {%16, %18};\n"
   "wgmma.mma_async.sync.aligned.m64n24k16.f32.bf16.bf16 {%0,%1,%2,%3,%4,%5,%6,%7,%8,%9,%10,%11}, {%12,%13,%14,%15}, db, %17, 1, 1, 1;\n}\n"
   : "+f"(d[0]),"+f"(d[1]),"+f"(d[2]),"+f"(d[3]),"+f"(d[4]),"+f"(d[5]),"+f"(d[6]),"+f"(d[7]),"+f"(d[8]),"+f"(d[9]),"+f"(d[10]),"+f"(d[11])
   : "r"(a[0]),"r"(a[1]),"r"(a[2]),"r"(a[3]),"r"(lo),"n"(SD),"r"(HI));
}

__device__ __forceinline__ uint32_t phi2(float a, float b) {
  uint32_t r, e;
  asm("cvt.rn.relu.bf16x2.f32 %0, %1, %2;" : "=r"(r) : "f"(b), "f"(a));
  e = pack_bf16(ex2f(a * 1.4426950408889634f), ex2f(b * 1.4426950408889634f));
  asm("add.rn.bf16x2 %0, %0, %1;" : "+r"(e) : "r"(0x35863586u));
  asm("min.NaN.bf16x2 %0, %0, %1;" : "+r"(e) : "r"(0x3F803F80u));
  asm("add.rn.bf16x2 %0, %0, %1;" : "+r"(e) : "r"(r));
  return e;
}

__device__ __forceinline__ void mbar_arrive(uint32_t bar) { asm volatile("mbarrier.arrive.shared::cta.b64 _, [%0];" :: "r"(bar) : "memory"); }
__device__ __forceinline__ void named_arrive(int id, int n) { asm volatile("bar.arrive %0, %1;" :: "r"(id), "r"(n) : "memory"); }
__device__ __forceinline__ void fence_async_all() { asm volatile("fence.proxy.async;" ::: "memory"); }
__device__ __forceinline__ void flag_add(uint32_t* f) { asm volatile("fence.acq_rel.gpu;\nred.relaxed.gpu.global.add.u32 [%0], 1;" :: "l"(f) : "memory"); }
__device__ __forceinline__ void flag_wait(const uint32_t* f, uint32_t target) {
  uint32_t v;
  for (int it = 0;; it++) {
    asm volatile("ld.acquire.gpu.global.u32 %0, [%1];" : "=r"(v) : "l"(f) : "memory");
    if ((int32_t)(v - target) >= 0) break;
    if (it > 2000000) __trap();
  }
}
__device__ __forceinline__ void lds4(uint32_t a, uint32_t* r) {
  asm volatile("ld.shared.v4.b32 {%0,%1,%2,%3}, [%4];" : "=r"(r[0]), "=r"(r[1]), "=r"(r[2]), "=r"(r[3]) : "r"(a) : "memory");
}
__device__ __forceinline__ void sts4(uint32_t a, uint32_t r0, uint32_t r1, uint32_t r2, uint32_t r3) {
  asm volatile("st.shared.v4.b32 [%0], {%1,%2,%3,%4};" :: "r"(a), "r"(r0), "r"(r1), "r"(r2), "r"(r3) : "memory");
}
__device__ __forceinline__ void ldsm4(uint32_t a, uint32_t* r) {
  asm volatile("ldmatrix.sync.aligned.m8n8.x4.shared.b16 {%0,%1,%2,%3}, [%4];" : "=r"(r[0]), "=r"(r[1]), "=r"(r[2]), "=r"(r[3]) : "r"(a) : "memory");
}
__device__ __forceinline__ float rcpf(float x) { float y; asm("rcp.approx.ftz.f32 %0, %1;" : "=f"(y) : "f"(x)); return y; }

#define STEPK 96
#define QSCALE 0.36067376022224085f
#define SMAGIC (512.0f + 2.0f * (191.0f - 30.0f - 1.5823545f))
#define VSHIFT 1073741824.0f

__device__ uint32_t g_epoch[132];
__device__ uint32_t g_flag[64 * 32];
#define FLAG_KV 0
#define FLAG_B(h) (1 + (h))

#define SM_TOTAL (224 * 1024 + 2048 + 1024)
#define OFF_K 0
#define OFF_F 65536
#define OFF_V 131072
#define OFF_MISC (224 * 1024)

__device__ __forceinline__ uint32_t exp2_pair_fix(float d0, float d1, uint32_t c63, uint32_t m1) {
  uint32_t w, y, s, r;
  asm("prmt.b32 %0, %1, %2, 0x6521;" : "=r"(w) : "r"(__float_as_uint(d0)), "r"(__float_as_uint(d1)));
  asm("lop3.b32 %0, %1, 0x007F007F, %2, 0xEA;" : "=r"(y) : "r"(w), "r"(c63));
  asm("mad.lo.u32 %0, %1, %2, %3;" : "=r"(s) : "r"(y), "r"(m1), "r"(w));
  asm("fma.rn.bf16x2 %0, %1, %2, %3;" : "=r"(r) : "r"(w), "r"(y), "r"(s));
  return r;
}

__device__ __forceinline__ void attn_slow(const uint4* gq, __nv_bfloat16* dst) {
  const int t = threadIdx.x & 127;
  const int row = t >> 1, half = t & 1;
  float q[16];
#pragma unroll
  for (int i = 0; i < 4; i++) {
    const uint4 v = gq[(row >> 4) * 32 + (row & 7) * 4 + i];
    const uint32_t lo = (row & 8) ? v.y : v.x, hi = (row & 8) ? v.w : v.z;
    q[2 * i] = bf_lo(lo); q[2 * i + 1] = bf_hi(lo); q[2 * i + 8] = bf_lo(hi); q[2 * i + 9] = bf_hi(hi);
  }
  float m = -INFINITY, l = 0.f, o[16];
#pragma unroll
  for (int i = 0; i < 16; i++) o[i] = 0.f;
  for (int j = half * 1024; j < half * 1024 + 1024; j++) {
    uint4 ka = g_KV[4 * S_TOK + j], kb = g_KV[5 * S_TOK + j];
    uint4 va = g_KV[6 * S_TOK + j], vb = g_KV[7 * S_TOK + j];
    uint32_t kk[8] = {ka.x, ka.y, ka.z, ka.w, kb.x, kb.y, kb.z, kb.w};
    uint32_t vv[8] = {va.x, va.y, va.z, va.w, vb.x, vb.y, vb.z, vb.w};
    float s = 0.f;
#pragma unroll
    for (int i = 0; i < 8; i++) { s = fmaf(q[2 * i], bf_lo(kk[i]), s); s = fmaf(q[2 * i + 1], bf_hi(kk[i]), s); }
    s = rbf(s) * 0.25f;
    if (s > m) {
      float c = __expf(m - s);
      l *= c;
#pragma unroll
      for (int i = 0; i < 16; i++) o[i] *= c;
      m = s;
    }
    float p = __expf(s - m);
    l += p;
#pragma unroll
    for (int i = 0; i < 8; i++) { o[2 * i] = fmaf(p, bf_lo(vv[i]), o[2 * i]); o[2 * i + 1] = fmaf(p, bf_hi(vv[i]), o[2 * i + 1]); }
  }
  float m2 = __shfl_xor_sync(~0u, m, 1);
  float mm = fmaxf(m, m2);
  float c = __expf(m - mm);
  l *= c; l += __shfl_xor_sync(~0u, l, 1);
  float inv = 1.f / l;
  uint32_t r[8];
#pragma unroll
  for (int i = 0; i < 16; i++) { o[i] *= c; o[i] += __shfl_xor_sync(~0u, o[i], 1); o[i] *= inv; }
#pragma unroll
  for (int i = 0; i < 8; i++) r[i] = pack_bf16(o[2 * i], o[2 * i + 1]);
  uint4* d = (uint4*)(dst + (size_t)row * D_MOD);
  if (half == 0) d[0] = make_uint4(r[0], r[1], r[2], r[3]); else d[1] = make_uint4(r[4], r[5], r[6], r[7]);
}

struct Params { const __nv_bfloat16* wk; const __nv_bfloat16* wv; };

#define BAR_FULL(s) (bars + 8 * (s))
#define BAR_EMPTY(s) (bars + 24 + 8 * (s))
#define BAR_KV(c) (bars + 48 + 8 * (c))
#define BAR_BDONE (bars + 80)
#define BAR_Q (bars + 88)
#define BAR_LM(i) (bars + 96 + 8 * (i))

__device__ __forceinline__ void helper_cta(const int h, const uint32_t sb, const uint32_t bars,
                                           const CUtensorMap* mQ, const CUtensorMap* mOs) {
  const int tid = threadIdx.x, warp = __shfl_sync(~0u, tid >> 5, 0), wg = warp >> 2, w4 = warp & 3, lane = tid & 31;
  mbar_wait(BAR_KV(0), 0);
  const int cb = wg & 1, col = h * 128 + cb * 64, row0 = S_TOK + (wg >> 1) * 1024;
  const uint32_t buf = sb + wg * 49152;
  if ((tid & 127) == 0) {
    fence_async_all();
    for (int u = 0; u < 3; u++) {
      mbar_expect_tx(BAR_LM(wg * 3 + u), 16384);
      tma2d(buf + u * 16384, mQ, col, row0 + u * 128, BAR_LM(wg * 3 + u));
    }
  }
  const int head = h * 8 + cb * 4 + w4;
  float4 a0 = make_float4(0, 0, 0, 0), a1 = a0, a2 = a0;
#pragma unroll 8
  for (int tt = 0; tt < 16; tt++) {
    const float4* src = g_kvp + ((tt * 32 + head) * 3) * 32 + lane;
    float4 u = src[0], v = src[32], w = src[64];
    a0.x += u.x; a0.y += u.y; a0.z += u.z; a0.w += u.w;
    a1.x += v.x; a1.y += v.y; a1.z += v.z; a1.w += v.w;
    a2.x += w.x; a2.y += w.y; a2.z += w.z; a2.w += w.w;
  }
  const uint32_t b00 = pack_bf16(a0.x, a0.y), b01 = pack_bf16(a0.z, a0.w);
  const uint32_t b10 = pack_bf16(a1.x, a1.y), b11 = pack_bf16(a1.z, a1.w);
  const uint32_t bz0 = pack_bf16(a2.x, a2.y), bz1 = pack_bf16(a2.z, a2.w);
  const int m = lane >> 3, r = lane & 7;
  const uint32_t off = ((m & 1) * 8 + r) * 128 + (((w4 * 2 + (m >> 1)) ^ r) << 4);
  int s = 0, ph = 0;
#pragma unroll 1
  for (int u = 0; u < 8; u++) {
    const uint32_t bb = buf + s * 16384;
    mbar_wait(BAR_LM(wg * 3 + s), ph);
#pragma unroll
    for (int mt = 0; mt < 8; mt++) {
      uint32_t a[4];
      ldsm4(bb + mt * 2048 + off, a);
      float n0[4] = {0, 0, 0, 0}, n1[4] = {0, 0, 0, 0}, dn[4] = {0, 0, 0, 0};
      mma_bf16(dn, a[0], a[1], a[2], a[3], bz0, bz1);
      mma_bf16(n0, a[0], a[1], a[2], a[3], b00, b01);
      mma_bf16(n1, a[0], a[1], a[2], a[3], b10, b11);
      const float i0 = rcpf(dn[0] + 1e-6f), i1 = rcpf(dn[2] + 1e-6f);
      stsm4(bb + mt * 2048 + off, pack_bf16(n0[0] * i0, n0[1] * i0), pack_bf16(n0[2] * i1, n0[3] * i1),
            pack_bf16(n1[0] * i0, n1[1] * i0), pack_bf16(n1[2] * i1, n1[3] * i1));
    }
    fence_async();
    named_bar(wg + 1, 128);
    if ((tid & 127) == 0) {
      tma2d_store(mOs, bb, col, row0 + u * 128);
      bulk_commit();
      if (u >= 1 && u + 2 < 8) {
        asm volatile("cp.async.bulk.wait_group.read 1;" ::: "memory");
        const int sp = s == 0 ? 2 : s - 1;
        mbar_expect_tx(BAR_LM(wg * 3 + sp), 16384);
        tma2d(buf + sp * 16384, mQ, col, row0 + (u + 2) * 128, BAR_LM(wg * 3 + sp));
      }
    }
    __syncwarp();
    if (++s == 3) { s = 0; ph ^= 1; }
  }
  if ((tid & 127) == 0) bulk_wait_all();
  if (tid == 0) TS(1, 8);
}

#define STAGE(s) (sb + (2 - (s)) * 65536)
template <int TR> __device__ __forceinline__ void proj_loop(float* acc, uint32_t sb, uint32_t bars, uint32_t offA, uint32_t offB) {
#pragma unroll
  for (int kb = 0; kb < 8; kb++) {
    const int s = kb % 3;
    const uint32_t st = STAGE(s);
    mbar_wait(BAR_FULL(s), (kb / 3) & 1);
    if (threadIdx.x == 0) TS(0, 2 + kb);
    const uint64_t da = make_desc(st + offA, TR ? 8192 : 16, 1024, 1);
    const uint64_t db = make_desc(st + offB, TR ? 16 : 8192, 1024, 1);
    wg_fence();
#pragma unroll
    for (int k = 0; k < 4; k++) wg_ss128<TR, 1 - TR>(acc, da + k * (TR ? 128 : 2), db + k * (TR ? 2 : 128), (kb | k) != 0);
    wg_commit();
    if (kb >= 1) {
      wg_wait<1>();
      if ((threadIdx.x & 127) == 0) mbar_arrive(BAR_EMPTY((kb - 1) % 3));
      __syncwarp();
    }
  }
  wg_wait<0>();
  fence_regs<64>(acc);
}

__global__ void __launch_bounds__(640, 1)
k1_main(const __grid_constant__ CUtensorMap mXA64, const __grid_constant__ CUtensorMap mXB,
        const __grid_constant__ CUtensorMap mWq, const __grid_constant__ CUtensorMap mWqkv,
        const __grid_constant__ CUtensorMap mQst, const __grid_constant__ CUtensorMap mOst, const Params prm) {
  extern __shared__ uint8_t smem_raw[];
  const uint32_t sb = (smem_u32(smem_raw) + 1023u) & ~1023u;
  const uint32_t bars = sb + OFF_MISC, sStat = bars + 256;
  const int tid = threadIdx.x, warp = __shfl_sync(~0u, tid >> 5, 0), wg = warp >> 2, w4 = warp & 3, lane = tid & 31;
  const bool helper = blockIdx.x >= 128;
  if (tid == 0) TS(0, 0);
  const int G = blockIdx.x >> 4, gi = blockIdx.x & 15;
  const int tbA = G * 4 + (gi >> 2), hg = gi & 3;
  const int ttB = (G >> 1) * 4 + (gi >> 2), hq = (G & 1) * 4 + (gi & 3);
  auto issue = [&](int kb) {
    const int s = kb % 3;
    const uint32_t fb = BAR_FULL(s), st = STAGE(s);
    mbar_expect_tx(fb, 65536);
    tma2d(st + 16384, &mXA64, kb * 64, tbA * 64, fb);
    tma2d(st, &mWq, hg * 128, kb * 64, fb);
    tma2d(st + 8192, &mWq, hg * 128 + 64, kb * 64, fb);
    tma2d(st + 49152, &mXB, kb * 64, ttB * 128, fb);
    tma2d(st + 24576, &mWqkv, hq * 64, kb * 64, fb);
    tma2d(st + 32768, &mWqkv, 512 + hq * 64, kb * 64, fb);
    tma2d(st + 40960, &mWqkv, 1024 + hq * 64, kb * 64, fb);
  };
  const uint32_t sOne = sb + OFF_V + 65536, sWKV = sOne + 24576;
  if (tid == 512) {
    for (int s = 0; s < 3; s++) { mbar_init(BAR_FULL(s), 1); mbar_init(BAR_EMPTY(s), 4); }
    for (int c = 0; c < 4; c++) mbar_init(BAR_KV(c), 1);
    mbar_init(BAR_BDONE, 8);
    mbar_init(BAR_Q, 8);
    for (int i = 0; i < 12; i++) mbar_init(BAR_LM(i), 1);
    asm volatile("fence.mbarrier_init.release.cluster;" ::: "memory");
    if (!helper) {
      mbar_expect_tx(BAR_LM(0), 65536);
      for (int kb = 0; kb < 8; kb++) tma2d(STAGE(2) + kb * 8192, &mXA64, kb * 64, tbA * 64, BAR_LM(0));
      issue(0); issue(1);
    }
  } else if (tid < 512 && !helper) {
    const uint4 v = __ldg((const uint4*)(hg >= 2 ? prm.wv : prm.wk) + tid * 2 + (hg & 1));
#pragma unroll
    for (int i = 0; i < 3; i++) {
      const int key = tid + i * 512;
      sts4(sOne + key * 16, (key % STEPK) < 32 ? 0x00003F80u : 0x00004E80u, 0u, 0u, 0u);
    }
    sts4(sWKV + tid * 16, v.x, v.y, v.z, v.w);
    fence_async();
  }
  __syncthreads();
  pdl_launch();
  if (wg == 4) {
    asm volatile("setmaxnreg.dec.sync.aligned.u32 32;");
    if (helper) {
      if (tid == 512) {
        const uint32_t ep = g_epoch[blockIdx.x] + 1;
        flag_wait(&g_flag[FLAG_B(blockIdx.x - 128) * 32], ep * 32);
        fence_async_all();
        TS(1, 10);
        mbar_arrive(BAR_KV(0));
        g_epoch[blockIdx.x] = ep;
      }
      return;
    }
    {
      float acc[4];
      mbar_wait(BAR_LM(0), 0);
      uint64_t da = make_desc(STAGE(2), 16, 1024, 1), db = make_desc(sWKV, 128, 128, 0);
      wg_fence();
#pragma unroll
      for (int kb = 0; kb < 8; kb++) {
#pragma unroll
        for (int k = 0; k < 4; k++) wg_ss8<0, 1>(acc, da + kb * 512 + k * 2, db + kb * 64 + k * 16, (kb | k) != 0);
      }
      wg_commit();
      wg_wait<0>();
      fence_regs<4>(acc);
      const uint32_t sT = sStat + 512;
      asm volatile("st.shared.b32 [%0], %1;" :: "r"(sT + w4 * 256 + lane * 4), "r"(pack_bf16(acc[0], acc[1])) : "memory");
      asm volatile("st.shared.b32 [%0], %1;" :: "r"(sT + w4 * 256 + 128 + lane * 4), "r"(pack_bf16(acc[2], acc[3])) : "memory");
      named_bar(9, 128);
      if (tid == 512) issue(2);
      const int t = tid - 512;
#pragma unroll
      for (int i = 0; i < 4; i++) {
        const int key = 1536 + t + i * 128;
        sts4(sOne + key * 16, (key % STEPK) < 32 ? 0x00003F80u : 0x00004E80u, 0u, 0u, 0u);
      }
      fence_async();
      __syncwarp();
      if (lane == 0) mbar_arrive(BAR_Q);
      if (w4 == 1 || w4 == 2) {
        const int ch = tbA * 2 + (w4 - 1);
        const uint32_t src = sT + (w4 - 1) * 512;
        uint32_t v[4], o[4];
        lds4(src + lane * 16, v);
        int kap;
        if (lane < 21) kap = lane * STEPK + 32 + ch;
        else { int idx = ch * 11 + (lane - 21); kap = (idx >> 5) * STEPK + (idx & 31); }
        g_KV[(4 + hg) * S_TOK + kap] = make_uint4(v[0], v[1], v[2], v[3]);
        float st = 0.f;
        if (hg < 2) {
          const float sc = lane < 21 ? 2.f : 1.f;
#pragma unroll
          for (int u = 0; u < 4; u++) {
            uint32_t pv = __shfl_up_sync(~0u, v[u], 1);
            if (lane == 0 || lane >= 21) pv = 0;
            const float x = bf_lo(v[u]), y = bf_hi(v[u]);
            st += x * x + y * y;
            o[u] = pack_f16((x - bf_lo(pv)) * sc, (y - bf_hi(pv)) * sc);
          }
        } else {
          const float sc = lane < 21 ? VSHIFT : 1.f;
#pragma unroll
          for (int u = 0; u < 4; u++) { float x = bf_lo(v[u]), y = bf_hi(v[u]); st += fabsf(x) + fabsf(y); o[u] = pack_bf16(x * sc, y * sc); }
        }
        g_KV[hg * S_TOK + kap] = make_uint4(o[0], o[1], o[2], o[3]);
        const uint32_t um = __reduce_max_sync(~0u, __float_as_uint(st) & 0x7FFFFFFFu);
        if (w4 == 2) { if (lane == 0) asm volatile("st.shared.b32 [%0], %1;" :: "r"(sT + 1024), "r"(um) : "memory"); named_arrive(10, 64); }
        else {
          named_bar(10, 64);
          if (lane == 0) {
            uint32_t u2;
            asm volatile("ld.shared.b32 %0, [%1];" : "=r"(u2) : "r"(sT + 1024) : "memory");
            g_stats[tbA * 4 + hg] = max(um, u2);
            fence_async_all();
            flag_add(&g_flag[FLAG_KV * 32]);
            TS(1, 9);
          }
        }
      }
    }
    if (tid == 512) {
      const uint32_t ep = g_epoch[blockIdx.x] + 1;
      for (int kb = 3; kb < 8; kb++) { mbar_wait(BAR_EMPTY(kb % 3), (kb / 3 - 1) & 1); issue(kb); }
      flag_wait(&g_flag[FLAG_KV * 32], ep * 128);
      fence_async_all();
      TS(0, 11);
      mbar_wait(BAR_EMPTY(2), 1);
      mbar_wait(BAR_EMPTY(0), 0);
      const int kbd[5] = {0, STEPK, 4 * STEPK, 7 * STEPK, S_TOK};
#pragma unroll
      for (int c = 0; c < 4; c++) {
        const uint32_t bytes = (kbd[c + 1] - kbd[c]) * 16;
        mbar_expect_tx(BAR_KV(c), 4 * bytes + (c == 0 ? 512 : 0));
        if (c == 0) bulk_g2s(sStat, g_stats, 512, BAR_KV(0));
#pragma unroll
        for (int p = 0; p < 4; p++)
          bulk_g2s(sb + (p < 2 ? OFF_K : OFF_V - 65536) + p * 32768 + kbd[c] * 16, g_KV + p * S_TOK + kbd[c], bytes, BAR_KV(c));
      }
      mbar_wait(BAR_BDONE, 0);
      tma2d_store(&mQst, sb + OFF_F + 49152, hq * 64, S_TOK + ttB * 128);
      bulk_commit();
      bulk_wait_all();
      fence_async_all();
      flag_add(&g_flag[FLAG_B(hq >> 1) * 32]);
      g_epoch[blockIdx.x] = ep;
      TS(0, 12);
    }
    return;
  }
  asm volatile("setmaxnreg.inc.sync.aligned.u32 112;");
  if (helper) { helper_cta(blockIdx.x - 128, sb, bars, &mQst, &mOst); return; }

  {
    float acc[64];
    if (wg == 0) proj_loop<0>(acc, sb, bars, 16384, 0);
    else proj_loop<1>(acc, sb, bars, 16384 + wg * 8192, 49152);
    if (tid == 0) TS(0, 10);
    const uint32_t sF = sb + OFF_F;
    if (wg == 0) {
      uint4* gq = (uint4*)g_Q + blockIdx.x * 1024 + tid;
#pragma unroll
      for (int hd = 0; hd < 8; hd++) {
        uint32_t r[4];
        float n0 = 0.f, n1 = 0.f;
#pragma unroll
        for (int i = 0; i < 4; i++) {
          r[i] = pack_bf16(acc[8 * hd + 2 * i], acc[8 * hd + 2 * i + 1]);
          const float a = bf_lo(r[i]) * QSCALE, b = bf_hi(r[i]) * QSCALE;
          asm volatile("st.shared.b32 [%0], %1;" :: "r"(sF + hd * 2048 + w4 * 512 + lane * 4 + (i & 1) * 256 + (i >> 1) * 128), "r"(pack_f16(a, b)) : "memory");
          if (i & 1) n1 += a * a + b * b; else n0 += a * a + b * b;
        }
        gq[hd * 128] = make_uint4(r[0], r[1], r[2], r[3]);
        n0 += __shfl_xor_sync(~0u, n0, 1); n0 += __shfl_xor_sync(~0u, n0, 2);
        n1 += __shfl_xor_sync(~0u, n1, 1); n1 += __shfl_xor_sync(~0u, n1, 2);
        const uint32_t um = __reduce_max_sync(~0u, max(__float_as_uint(n0) & 0x7FFFFFFFu, __float_as_uint(n1) & 0x7FFFFFFFu));
        if (lane == 0) asm volatile("st.shared.b32 [%0], %1;" :: "r"(sStat + 1664 + hd * 16 + w4 * 4), "r"(um) : "memory");
      }
      fence_async();
      __syncwarp();
      if (lane == 0) mbar_arrive(BAR_Q);
    } else if (wg == 3) {
      named_arrive(8, 384);
      named_bar(6, 384);
      const int t = tid & 127;
#pragma unroll
      for (int j = 0; j < 8; j++)
        sts4(sF + 24576 + j * 2048 + t * 16, pack_bf16(acc[8 * j], acc[8 * j + 1]), pack_bf16(acc[8 * j + 2], acc[8 * j + 3]),
             pack_bf16(acc[8 * j + 4], acc[8 * j + 5]), pack_bf16(acc[8 * j + 6], acc[8 * j + 7]));
      named_arrive(7, 256);
    } else {
      uint32_t p[32];
      named_arrive(6, 384);
      if (wg == 2) named_arrive(8, 384);
#pragma unroll
      for (int i = 0; i < 32; i++) p[i] = phi2(acc[2 * i], acc[2 * i + 1]);
      if (wg == 1) {
        named_bar(8, 384);
        const int m = lane >> 3, r = lane & 7;
#pragma unroll
        for (int j = 0; j < 16; j += 2) {
          const int tok = (j + (m >> 1)) * 8 + r;
          const int chunk = w4 * 2 + (m & 1);
          stsm4t(sF + 49152 + tok * 128 + ((chunk ^ r) << 4), p[2 * j], p[2 * j + 1], p[2 * j + 2], p[2 * j + 3]);
        }
        fence_async();
      } else {
        named_bar(7, 256);
        float kv0[4] = {0, 0, 0, 0}, kv1[4] = {0, 0, 0, 0}, z0[4] = {0, 0, 0, 0}, z1[4] = {0, 0, 0, 0};
        const uint32_t one = 0x3F803F80u;
        const int t = tid & 127;
#pragma unroll
        for (int j = 0; j < 8; j++) {
          uint32_t a[4];
          lds4(sF + 24576 + j * 2048 + t * 16, a);
          mma_bf16(kv0, a[0], a[1], a[2], a[3], p[4 * j], p[4 * j + 2]);
          mma_bf16(kv1, a[0], a[1], a[2], a[3], p[4 * j + 1], p[4 * j + 3]);
          mma_bf16(z0, one, one, one, one, p[4 * j], p[4 * j + 2]);
          mma_bf16(z1, one, one, one, one, p[4 * j + 1], p[4 * j + 3]);
        }
        float4* dst = g_kvp + ((ttB * 32 + hq * 4 + w4) * 3) * 32 + lane;
        dst[0] = make_float4(kv0[0], kv0[1], kv1[0], kv1[1]);
        dst[32] = make_float4(kv0[2], kv0[3], kv1[2], kv1[3]);
        dst[64] = make_float4(z0[0], z0[1], z1[0], z1[1]);
      }
      __syncwarp();
      if (lane == 0) mbar_arrive(BAR_BDONE);
    }
  }
  mbar_wait(BAR_Q, 0);

  mbar_wait(BAR_KV(0), 0);
  if (tid == 0) TS(1, 1);
  uint32_t badmask;
  {
    uint32_t a[4], n[4], n2[4];
    lds4(sStat + lane * 16, a);
    lds4(sStat + 1664 + wg * 16, n);
    lds4(sStat + 1664 + 64 + wg * 16, n2);
    const float kmax2 = __uint_as_float(__reduce_max_sync(~0u, a[0])) + __uint_as_float(__reduce_max_sync(~0u, a[1]));
    const float vmax = __uint_as_float(__reduce_max_sync(~0u, max(a[2], a[3])));
    const float lv = vmax > 0.f ? __log2f(vmax) : 0.f;
    const float lim = fminf(90.f, fminf(91.f + lv, 95.f - lv));
    const bool gok = vmax < 1e27f && kmax2 <= 65536.f && lim > 0.f;
    const float q0 = __uint_as_float(max(max(n[0], n[1]), max(n[2], n[3])));
    const float q1 = __uint_as_float(max(max(n2[0], n2[1]), max(n2[2], n2[3])));
    const bool ok0 = gok && q0 <= 65536.f && q0 * kmax2 * 1.01f <= lim * lim;
    const bool ok1 = gok && q1 <= 65536.f && q1 * kmax2 * 1.01f <= lim * lim;
    badmask = __all_sync(~0u, ok0 && ok1) ? 0u : 1u;
  }
  if (badmask) {
#pragma unroll 1
    for (int pass = 0; pass < 2; pass++) {
      const int hd = pass * 4 + wg;
      attn_slow((const uint4*)g_Q + blockIdx.x * 1024 + hd * 128, g_O + (size_t)(tbA * 64) * D_MOD + (hg * 8 + hd) * 16);
    }
    return;
  }
  const int g = lane >> 2, t = lane & 3;
  const uint32_t c63 = 0x1F801F80u + (threadIdx.x >> 20);
  const uint32_t m1 = (gridDim.x >> 20) - 1u;
  const uint64_t dK0 = make_desc(sb + OFF_K, 32768, 128, 0);
  const uint64_t dV0 = make_desc(sb + OFF_V, 128, 32768, 0);
  const uint32_t dKV = (uint32_t)dK0 + STEPK - (uint32_t)dV0;

#pragma unroll 1
  for (int pass = 0; pass < 2; pass++) {
    const int hd = pass * 4 + wg;
    __nv_bfloat16* od = g_O + (size_t)(tbA * 64) * D_MOD + (hg * 8 + hd) * 16;
    const uint64_t dQ = make_desc(sb + OFF_F + hd * 2048, 128, 256, 0);
    float Sm[16], Sp[32], O[12];
    uint32_t P[24];
#pragma unroll
    for (int i = 0; i < 32; i++) Sp[i] = SMAGIC;
#pragma unroll
    for (int i = 0; i < 16; i++) Sm[i] = 0.f;
#pragma unroll
    for (int i = 0; i < 12; i++) O[i] = 0.f;
    fence_regs<16>(Sm); fence_regs<32>(Sp); fence_regs<12>(O);
    if (tid == 0) TS(1, 2 + 2 * pass);
    wg_fence();
    wg_qs32<0>(Sm, dQ, dK0);
    wg_qs64<1>(Sp, dQ, dK0 + 32);
    wg_commit();
    wg_wait<0>();
    fence_regs<16>(Sm); fence_regs<32>(Sp);
    uint32_t vlo = (uint32_t)dV0;
#pragma unroll 1
    for (int s3 = 0; s3 < 3; s3++) {
      mbar_wait(BAR_KV(s3 + 1), 0);
      const uint32_t vend = vlo + (s3 == 2 ? 15 : 3) * STEPK;
#pragma unroll 1
      for (; vlo != vend; vlo += STEPK) {
        uint64_t dK, dV;
        asm("mov.b64 %0, {%1, %2};" : "=l"(dK) : "r"(vlo + dKV), "r"(8u));
        asm("mov.b64 %0, {%1, %2};" : "=l"(dV) : "r"(vlo), "r"(2048u));
#pragma unroll
        for (int i = 0; i < 8; i++) P[i] = pack_bf16(ex2f(Sm[2 * i]), ex2f(Sm[2 * i + 1]));
#pragma unroll
        for (int i = 0; i < 16; i++) P[8 + i] = exp2_pair_fix(Sp[2 * i], Sp[2 * i + 1], c63, m1);
        fence_regs<24>(P);
        wg_fence();
        wg_qs32<0>(Sm, dQ, dK);
        wg_qs64<1>(Sp, dQ, dK + 32);
#pragma unroll
        for (int k = 0; k < 6; k++) wg_pv24<1>(O, &P[4 * k], dV + k * 16);
        wg_commit();
        wg_wait<0>();
        fence_regs<16>(Sm); fence_regs<32>(Sp); fence_regs<12>(O); fence_regs<24>(P);
      }
    }
#pragma unroll
    for (int i = 0; i < 8; i++) P[i] = pack_bf16(ex2f(Sm[2 * i]), ex2f(Sm[2 * i + 1]));
    fence_regs<8>(P);
    wg_fence();
    wg_pv24<1>(O, &P[0], dV0 + 21 * STEPK);
    wg_pv24<1>(O, &P[4], dV0 + 21 * STEPK + 16);
    wg_commit();
    wg_wait<0>();
    fence_regs<12>(O);
    const float l0 = __shfl_sync(~0u, O[8], lane & ~3), l1 = __shfl_sync(~0u, O[10], lane & ~3);
    const float i0 = rcpf(l0), i1 = rcpf(l1);
    uint32_t* op = (uint32_t*)(od + (size_t)(w4 * 16 + g) * D_MOD) + t;
    op[0] = pack_bf16(O[0] * i0, O[1] * i0);
    op[8 * 256] = pack_bf16(O[2] * i1, O[3] * i1);
    op[4] = pack_bf16(O[4] * i0, O[5] * i0);
    op[8 * 256 + 4] = pack_bf16(O[6] * i1, O[7] * i1);
    if (tid == 0) TS(1, 3 + 2 * pass);
    if ((tid & 127) == 0 && pass == 1 && wg > 0) TS(1, 10 + wg);
  }
}

#define K3_SMEM (131072 + 6 * 16384 + 1024 + 256)
__global__ void __cluster_dims__(2, 1, 1) __launch_bounds__(288, 1)
k3_out(const __grid_constant__ CUtensorMap mO, const __grid_constant__ CUtensorMap mWoA,
       const __grid_constant__ CUtensorMap mWoB, const __grid_constant__ CUtensorMap mOut) {
  extern __shared__ uint8_t smem_raw[];
  const uint32_t sb = (smem_u32(smem_raw) + 1023u) & ~1023u;
  const uint32_t sW = sb, sA = sb + 131072, bars = sA + 6 * 16384;
  const int tid = threadIdx.x, wg = tid >> 7, warp = tid >> 5, lane = tid & 31;
  const int rank = blockIdx.x & 1;
  const int nt = (blockIdx.x & 7);
  const int tt = blockIdx.x >> 3;
  const int part = nt >> 2;
  if (tid == 0) TS(2, 0);
  if (tid == 0) {
    for (int s = 0; s < 14; s++) mbar_init(bars + 8 * s, 1);
    mbar_init(bars + 112, 4); mbar_init(bars + 120, 4);
    asm volatile("fence.mbarrier_init.release.cluster;" ::: "memory");
  }
  cluster_sync();
  if (wg == 2) {
    if (lane == 0) {
      const CUtensorMap* mW = part ? &mWoB : &mWoA;
      const int col = (nt & 3) * 128;
      for (int kb = 0; kb < 8; kb++) {
        mbar_expect_tx(bars + 8 * kb, 16384);
        tma2d(sW + kb * 16384, mW, col, kb * 64, bars + 8 * kb);
        tma2d(sW + kb * 16384 + 8192, mW, col + 64, kb * 64, bars + 8 * kb);
      }
      pdl_wait();
      TS(2, 1);
      const int row = part * S_TOK + tt * 128 + rank * 64;
      for (int kb = 0; kb < 8; kb++) {
        const int s = kb < 6 ? kb : kb - 6;
        if (kb >= 6) mbar_wait(bars + 112 + 8 * s, 0);
        mbar_expect_tx(bars + 64 + 8 * s, 16384);
        tma2d_mc(sA + s * 16384 + rank * 8192, &mO, kb * 64, row, bars + 64 + 8 * s, 3);
      }
    }
  } else {
    float acc[64];
#pragma unroll
    for (int kb = 0; kb < 8; kb++) {
      const int s = kb < 6 ? kb : kb - 6;
      mbar_wait(bars + 8 * kb, 0);
      mbar_wait(bars + 64 + 8 * s, kb >= 6);
      if (tid == 0) TS(2, 2 + kb);
      uint64_t da = make_desc(sA + s * 16384 + wg * 8192, 16, 1024, 1);
      uint64_t db = make_desc(sW + kb * 16384, 8192, 1024, 1);
      wg_fence();
#pragma unroll
      for (int k = 0; k < 4; k++) wg_ss128<0, 1>(acc, da + k * 2, db + k * 128, (kb | k) != 0);
      wg_commit();
      if (kb == 1 || kb == 2) {
        wg_wait<1>();
        if ((tid & 127) == 0) { mbar_arrive_cta(bars + 112 + 8 * (kb - 1), 0); mbar_arrive_cta(bars + 112 + 8 * (kb - 1), 1); }
        __syncwarp();
      }
    }
    wg_wait<0>();
    fence_regs<64>(acc);
    const int w4 = warp & 3, m = lane >> 3, r = lane & 7;
#pragma unroll
    for (int j = 0; j < 16; j += 2) {
      const uint32_t stg = sA + (2 + (j >> 3)) * 16384 + wg * 8192;
      const int row = w4 * 16 + (m & 1) * 8 + r;
      const int chunk = (j & 7) + (m >> 1);
      stsm4(stg + row * 128 + ((chunk ^ r) << 4),
            pack_bf16(acc[4 * j], acc[4 * j + 1]), pack_bf16(acc[4 * j + 2], acc[4 * j + 3]),
            pack_bf16(acc[4 * j + 4], acc[4 * j + 5]), pack_bf16(acc[4 * j + 6], acc[4 * j + 7]));
    }
    fence_async();
    named_bar(wg + 1, 128);
    if ((tid & 127) == 0) {
      tma2d_store(&mOut, sA + 2 * 16384 + wg * 8192, nt * 128, tt * 128 + wg * 64);
      tma2d_store(&mOut, sA + 3 * 16384 + wg * 8192, nt * 128 + 64, tt * 128 + wg * 64);
      if (tid == 0) TS(2, 11);
      bulk_commit();
      bulk_wait_all();
      if (tid == 0) TS(2, 12);
    }
  }
}

typedef CUresult (*EncodeFn)(CUtensorMap*, CUtensorMapDataType, cuuint32_t, void*, const cuuint64_t*, const cuuint64_t*,
                             const cuuint32_t*, const cuuint32_t*, CUtensorMapInterleave, CUtensorMapSwizzle,
                             CUtensorMapL2promotion, CUtensorMapFloatOOBfill);

static void make_map(EncodeFn enc, CUtensorMap* m, const void* ptr, uint64_t cols, uint64_t rows, uint32_t bc, uint32_t br) {
  cuuint64_t dims[2] = {cols, rows};
  cuuint64_t strides[1] = {cols * 2};
  cuuint32_t box[2] = {bc, br};
  cuuint32_t es[2] = {1, 1};
  enc(m, CU_TENSOR_MAP_DATA_TYPE_BFLOAT16, 2, (void*)ptr, dims, strides, box, es, CU_TENSOR_MAP_INTERLEAVE_NONE,
      CU_TENSOR_MAP_SWIZZLE_128B, CU_TENSOR_MAP_L2_PROMOTION_L2_256B, CU_TENSOR_MAP_FLOAT_OOB_FILL_NONE);
}

extern "C" void kernel_launch(void* const* d_in, const int* in_sizes, int n_in, void* d_out, int out_size) {
  (void)in_sizes; (void)n_in; (void)out_size;
  static EncodeFn enc = nullptr;
  static void* pQ = nullptr; static void* pO = nullptr;
  if (!enc) {
    void* fn = nullptr; cudaDriverEntryPointQueryResult qr;
    cudaGetDriverEntryPoint("cuTensorMapEncodeTiled", &fn, cudaEnableDefault, &qr);
    enc = (EncodeFn)fn;
    cudaGetSymbolAddress(&pQ, g_Q);
    cudaGetSymbolAddress(&pO, g_O);
    cudaFuncSetAttribute(k1_main, cudaFuncAttributeMaxDynamicSharedMemorySize, SM_TOTAL);
    cudaFuncSetAttribute(k3_out, cudaFuncAttributeMaxDynamicSharedMemorySize, K3_SMEM);
  }
  CUtensorMap mXA64, mXB, mWq, mWqkv, mQst, mO, mOst, mWoA, mWoB, mOut;
  make_map(enc, &mXA64, d_in[0], 512, 2048, 64, 64);
  make_map(enc, &mWq, d_in[1], 512, 512, 64, 64);
  make_map(enc, &mWoA, d_in[4], 512, 512, 64, 64);
  make_map(enc, &mXB, d_in[5], 512, 2048, 64, 128);
  make_map(enc, &mWqkv, d_in[6], 1536, 512, 64, 64);
  make_map(enc, &mWoB, d_in[7], 512, 512, 64, 64);
  make_map(enc, &mQst, pQ, 512, 4096, 64, 128);
  make_map(enc, &mO, pO, 512, 4096, 64, 64);
  make_map(enc, &mOst, pO, 512, 4096, 64, 128);
  make_map(enc, &mOut, d_out, 1024, 2048, 64, 64);
  Params prm{(const __nv_bfloat16*)d_in[2], (const __nv_bfloat16*)d_in[3]};

  cudaStream_t st = cudaStreamPerThread;
  cudaLaunchAttribute at[1];
  at[0].id = cudaLaunchAttributeProgrammaticStreamSerialization;
  at[0].val.programmaticStreamSerializationAllowed = 1;
  cudaLaunchConfig_t cfg = {};
  cfg.stream = st;
  cfg.gridDim = dim3(132); cfg.blockDim = dim3(640); cfg.dynamicSmemBytes = SM_TOTAL; cfg.attrs = at; cfg.numAttrs = 0;
  cudaLaunchKernelEx(&cfg, k1_main, mXA64, mXB, mWq, mWqkv, mQst, mOst, prm);
  cfg.gridDim = dim3(128); cfg.blockDim = dim3(288); cfg.dynamicSmemBytes = K3_SMEM; cfg.numAttrs = 1;
  cudaLaunchKernelEx(&cfg, k3_out, mO, mWoA, mWoB, mOut);
}
```

```cpp
#include <cuda_runtime.h>
#include <cuda_bf16.h>
#include <cuda_fp16.h>
#include <cuda.h>
#include <stdint.h>

#define S_TOK 2048
#define D_MOD 512

__device__ __align__(1024) __nv_bfloat16 g_Q[2 * S_TOK * D_MOD];
__device__ __align__(1024) __nv_bfloat16 g_O[2 * S_TOK * D_MOD];
__device__ __align__(1024) uint4 g_KV[8 * S_TOK];
__device__ __align__(16) uint32_t g_stats[128];
__device__ __align__(16) float4 g_kvp[16 * 32 * 3 * 32];

#define TS(k, i) do {} while (0)
__device__ __forceinline__ uint32_t smem_u32(const void* p) { return (uint32_t)__cvta_generic_to_shared(p); }
__device__ __forceinline__ void mbar_init(uint32_t bar, int cnt) { asm volatile("mbarrier.init.shared::cta.b64 [%0], %1;" :: "r"(bar), "r"(cnt) : "memory"); }
__device__ __forceinline__ void mbar_expect_tx(uint32_t bar, uint32_t bytes) { asm volatile("mbarrier.arrive.expect_tx.shared::cta.b64 _, [%0], %1;" :: "r"(bar), "r"(bytes) : "memory"); }
__device__ __forceinline__ bool mbar_try(uint32_t bar, uint32_t parity) {
  uint32_t ok;
  asm volatile("{\n.reg .pred p;\nmbarrier.try_wait.parity.shared::cta.b64 p, [%1], %2;\nselp.b32 %0, 1, 0, p;\n}\n" : "=r"(ok) : "r"(bar), "r"(parity) : "memory");
  return ok;
}
__device__ __forceinline__ void mbar_wait(uint32_t bar, uint32_t parity) {
  asm volatile("{\n.reg .pred p;\n.reg .u32 c;\nmov.u32 c, 0;\n"
               "LW_%=:\n"
               "mbarrier.try_wait.parity.shared::cta.b64 p, [%0], %1;\n"
               "@p bra LD_%=;\n"
               "add.u32 c, c, 1;\n"
               "setp.lt.u32 p, c, 4000000;\n"
               "@p bra LW_%=;\n"
               "trap;\n"
               "LD_%=:\n}\n" :: "r"(bar), "r"(parity) : "memory");
}
__device__ __forceinline__ void mbar_arrive_cta(uint32_t bar, uint32_t cta) {
  asm volatile("{\n.reg .b32 ra;\nmapa.shared::cluster.u32 ra, %0, %1;\nmbarrier.arrive.shared::cluster.b64 _, [ra];\n}\n" :: "r"(bar), "r"(cta) : "memory");
}
__device__ __forceinline__ void cluster_sync() {
  asm volatile("barrier.cluster.arrive.relaxed.aligned;\nbarrier.cluster.wait.aligned;" ::: "memory");
}
__device__ __forceinline__ void tma2d(uint32_t dst, const CUtensorMap* m, int c0, int c1, uint32_t bar) {
  asm volatile("cp.async.bulk.tensor.2d.shared::cluster.global.mbarrier::complete_tx::bytes [%0], [%1, {%3, %4}], [%2];"
               :: "r"(dst), "l"(m), "r"(bar), "r"(c0), "r"(c1) : "memory");
}
__device__ __forceinline__ void tma2d_mc(uint32_t dst, const CUtensorMap* m, int c0, int c1, uint32_t bar, uint16_t mask) {
  asm volatile("cp.async.bulk.tensor.2d.shared::cluster.global.mbarrier::complete_tx::bytes.multicast::cluster [%0], [%1, {%3, %4}], [%2], %5;"
               :: "r"(dst), "l"(m), "r"(bar), "r"(c0), "r"(c1), "h"(mask) : "memory");
}
__device__ __forceinline__ void tma2d_store(const CUtensorMap* m, uint32_t src, int c0, int c1) {
  asm volatile("cp.async.bulk.tensor.2d.global.shared::cta.bulk_group [%0, {%2, %3}], [%1];"
               :: "l"(m), "r"(src), "r"(c0), "r"(c1) : "memory");
}
__device__ __forceinline__ void bulk_g2s(uint32_t dst, const void* src, uint32_t bytes, uint32_t bar) {
  asm volatile("cp.async.bulk.shared::cluster.global.mbarrier::complete_tx::bytes [%0], [%1], %2, [%3];"
               :: "r"(dst), "l"(src), "r"(bytes), "r"(bar) : "memory");
}
__device__ __forceinline__ void bulk_commit() { asm volatile("cp.async.bulk.commit_group;" ::: "memory"); }
__device__ __forceinline__ void bulk_wait_all() { asm volatile("cp.async.bulk.wait_group 0;" ::: "memory"); }
__device__ __forceinline__ void fence_async() { asm volatile("fence.proxy.async.shared::cta;" ::: "memory"); }
__device__ __forceinline__ void named_bar(int id, int n) { asm volatile("bar.sync %0, %1;" :: "r"(id), "r"(n) : "memory"); }
__device__ __forceinline__ void pdl_launch() { asm volatile("griddepcontrol.launch_dependents;" ::: "memory"); }
__device__ __forceinline__ void pdl_wait() { asm volatile("griddepcontrol.wait;" ::: "memory"); }
__device__ __forceinline__ void wg_fence() { asm volatile("wgmma.fence.sync.aligned;" ::: "memory"); }
__device__ __forceinline__ void wg_commit() { asm volatile("wgmma.commit_group.sync.aligned;" ::: "memory"); }
template <int n> __device__ __forceinline__ void wg_wait() { asm volatile("wgmma.wait_group.sync.aligned %0;" :: "n"(n) : "memory"); }
template <int n> __device__ __forceinline__ void fence_regs(float* r) {
#pragma unroll
  for (int i = 0; i < n; i++) asm volatile("" : "+f"(r[i]) :: "memory");
}
template <int n> __device__ __forceinline__ void fence_regs(uint32_t* r) {
#pragma unroll
  for (int i = 0; i < n; i++) asm volatile("" : "+r"(r[i]) :: "memory");
}
__device__ __forceinline__ uint64_t make_desc(uint32_t addr, uint32_t lbo, uint32_t sbo, uint32_t swz) {
  return (uint64_t)((addr & 0x3FFFF) >> 4) | ((uint64_t)(lbo >> 4) << 16) | ((uint64_t)(sbo >> 4) << 32) | ((uint64_t)swz << 62);
}
__device__ __forceinline__ float ex2f(float x) { float y; asm("ex2.approx.ftz.f32 %0, %1;" : "=f"(y) : "f"(x)); return y; }
__device__ __forceinline__ uint32_t pack_bf16(float lo, float hi) { uint32_t r; asm("cvt.rn.bf16x2.f32 %0, %1, %2;" : "=r"(r) : "f"(hi), "f"(lo)); return r; }
__device__ __forceinline__ uint32_t pack_f16(float lo, float hi) { uint32_t r; asm("cvt.rn.f16x2.f32 %0, %1, %2;" : "=r"(r) : "f"(hi), "f"(lo)); return r; }
__device__ __forceinline__ float bf_lo(uint32_t v) { return __uint_as_float(v << 16); }
__device__ __forceinline__ float bf_hi(uint32_t v) { return __uint_as_float(v & 0xFFFF0000u); }
__device__ __forceinline__ float rbf(float x) { return __bfloat162float(__float2bfloat16_rn(x)); }
__device__ __forceinline__ void stsm4(uint32_t a, uint32_t r0, uint32_t r1, uint32_t r2, uint32_t r3) {
  asm volatile("stmatrix.sync.aligned.m8n8.x4.shared.b16 [%0], {%1,%2,%3,%4};" :: "r"(a), "r"(r0), "r"(r1), "r"(r2), "r"(r3) : "memory");
}
__device__ __forceinline__ void stsm4t(uint32_t a, uint32_t r0, uint32_t r1, uint32_t r2, uint32_t r3) {
  asm volatile("stmatrix.sync.aligned.m8n8.x4.trans.shared.b16 [%0], {%1,%2,%3,%4};" :: "r"(a), "r"(r0), "r"(r1), "r"(r2), "r"(r3) : "memory");
}
__device__ __forceinline__ void mma_bf16(float* d, uint32_t a0, uint32_t a1, uint32_t a2, uint32_t a3, uint32_t b0, uint32_t b1) {
  asm volatile("mma.sync.aligned.m16n8k16.row.col.f32.bf16.bf16.f32 {%0,%1,%2,%3}, {%4,%5,%6,%7}, {%8,%9}, {%0,%1,%2,%3};"
               : "+f"(d[0]), "+f"(d[1]), "+f"(d[2]), "+f"(d[3]) : "r"(a0), "r"(a1), "r"(a2), "r"(a3), "r"(b0), "r"(b1));
}
template<int SD> __device__ __forceinline__ void wg_qk32(float* d, const uint32_t* a, uint64_t desc) {
  asm volatile("wgmma.mma_async.sync.aligned.m64n32k16.f32.f16.f16 {%0,%1,%2,%3,%4,%5,%6,%7,%8,%9,%10,%11,%12,%13,%14,%15}, {%16,%17,%18,%19}, %20, %21, 1, 1, 0;"
   : "+f"(d[0]),"+f"(d[1]),"+f"(d[2]),"+f"(d[3]),"+f"(d[4]),"+f"(d[5]),"+f"(d[6]),"+f"(d[7]),"+f"(d[8]),"+f"(d[9]),"+f"(d[10]),"+f"(d[11]),"+f"(d[12]),"+f"(d[13]),"+f"(d[14]),"+f"(d[15])
   : "r"(a[0]),"r"(a[1]),"r"(a[2]),"r"(a[3]),"l"(desc),"n"(SD));
}
template<int SD> __device__ __forceinline__ void wg_qk64(float* d, const uint32_t* a, uint64_t desc) {
  asm volatile("wgmma.mma_async.sync.aligned.m64n64k16.f32.f16.f16 {%0,%1,%2,%3,%4,%5,%6,%7,%8,%9,%10,%11,%12,%13,%14,%15,%16,%17,%18,%19,%20,%21,%22,%23,%24,%25,%26,%27,%28,%29,%30,%31}, {%32,%33,%34,%35}, %36, %37, 1, 1, 0;"
   : "+f"(d[0]),"+f"(d[1]),"+f"(d[2]),"+f"(d[3]),"+f"(d[4]),"+f"(d[5]),"+f"(d[6]),"+f"(d[7]),"+f"(d[8]),"+f"(d[9]),"+f"(d[10]),"+f"(d[11]),"+f"(d[12]),"+f"(d[13]),"+f"(d[14]),"+f"(d[15]),"+f"(d[16]),"+f"(d[17]),"+f"(d[18]),"+f"(d[19]),"+f"(d[20]),"+f"(d[21]),"+f"(d[22]),"+f"(d[23]),"+f"(d[24]),"+f"(d[25]),"+f"(d[26]),"+f"(d[27]),"+f"(d[28]),"+f"(d[29]),"+f"(d[30]),"+f"(d[31])
   : "r"(a[0]),"r"(a[1]),"r"(a[2]),"r"(a[3]),"l"(desc),"n"(SD));
}
template<int SD> __device__ __forceinline__ void wg_qs32(float* d, uint64_t da, uint64_t db) {
  asm volatile("wgmma.mma_async.sync.aligned.m64n32k16.f32.f16.f16 {%0,%1,%2,%3,%4,%5,%6,%7,%8,%9,%10,%11,%12,%13,%14,%15}, %16, %17, %18, 1, 1, 0, 0;"
   : "+f"(d[0]),"+f"(d[1]),"+f"(d[2]),"+f"(d[3]),"+f"(d[4]),"+f"(d[5]),"+f"(d[6]),"+f"(d[7]),"+f"(d[8]),"+f"(d[9]),"+f"(d[10]),"+f"(d[11]),"+f"(d[12]),"+f"(d[13]),"+f"(d[14]),"+f"(d[15])
   : "l"(da),"l"(db),"n"(SD));
}
template<int SD> __device__ __forceinline__ void wg_qs64(float* d, uint64_t da, uint64_t db) {
  asm volatile("wgmma.mma_async.sync.aligned.m64n64k16.f32.f16.f16 {%0,%1,%2,%3,%4,%5,%6,%7,%8,%9,%10,%11,%12,%13,%14,%15,%16,%17,%18,%19,%20,%21,%22,%23,%24,%25,%26,%27,%28,%29,%30,%31}, %32, %33, %34, 1, 1, 0, 0;"
   : "+f"(d[0]),"+f"(d[1]),"+f"(d[2]),"+f"(d[3]),"+f"(d[4]),"+f"(d[5]),"+f"(d[6]),"+f"(d[7]),"+f"(d[8]),"+f"(d[9]),"+f"(d[10]),"+f"(d[11]),"+f"(d[12]),"+f"(d[13]),"+f"(d[14]),"+f"(d[15]),"+f"(d[16]),"+f"(d[17]),"+f"(d[18]),"+f"(d[19]),"+f"(d[20]),"+f"(d[21]),"+f"(d[22]),"+f"(d[23]),"+f"(d[24]),"+f"(d[25]),"+f"(d[26]),"+f"(d[27]),"+f"(d[28]),"+f"(d[29]),"+f"(d[30]),"+f"(d[31])
   : "l"(da),"l"(db),"n"(SD));
}
template<int SD> __device__ __forceinline__ void wg_pv24(float* d, const uint32_t* a, uint64_t desc) {
  asm volatile("wgmma.mma_async.sync.aligned.m64n24k16.f32.bf16.bf16 {%0,%1,%2,%3,%4,%5,%6,%7,%8,%9,%10,%11}, {%12,%13,%14,%15}, %16, %17, 1, 1, 1;"
   : "+f"(d[0]),"+f"(d[1]),"+f"(d[2]),"+f"(d[3]),"+f"(d[4]),"+f"(d[5]),"+f"(d[6]),"+f"(d[7]),"+f"(d[8]),"+f"(d[9]),"+f"(d[10]),"+f"(d[11])
   : "r"(a[0]),"r"(a[1]),"r"(a[2]),"r"(a[3]),"l"(desc),"n"(SD));
}
template<int TA, int TB> __device__ __forceinline__ void wg_ss128(float* d, uint64_t da, uint64_t db, int sd) {
  asm volatile("{\n.reg .pred p;\nsetp.ne.b32 p, %66, 0;\n"
   "wgmma.mma_async.sync.aligned.m64n128k16.f32.bf16.bf16 {%0,%1,%2,%3,%4,%5,%6,%7,%8,%9,%10,%11,%12,%13,%14,%15,%16,%17,%18,%19,%20,%21,%22,%23,%24,%25,%26,%27,%28,%29,%30,%31,%32,%33,%34,%35,%36,%37,%38,%39,%40,%41,%42,%43,%44,%45,%46,%47,%48,%49,%50,%51,%52,%53,%54,%55,%56,%57,%58,%59,%60,%61,%62,%63}, %64, %65, p, 1, 1, %67, %68;\n}\n"
   : "+f"(d[0]),"+f"(d[1]),"+f"(d[2]),"+f"(d[3]),"+f"(d[4]),"+f"(d[5]),"+f"(d[6]),"+f"(d[7]),"+f"(d[8]),"+f"(d[9]),"+f"(d[10]),"+f"(d[11]),"+f"(d[12]),"+f"(d[13]),"+f"(d[14]),"+f"(d[15]),"+f"(d[16]),"+f"(d[17]),"+f"(d[18]),"+f"(d[19]),"+f"(d[20]),"+f"(d[21]),"+f"(d[22]),"+f"(d[23]),"+f"(d[24]),"+f"(d[25]),"+f"(d[26]),"+f"(d[27]),"+f"(d[28]),"+f"(d[29]),"+f"(d[30]),"+f"(d[31]),"+f"(d[32]),"+f"(d[33]),"+f"(d[34]),"+f"(d[35]),"+f"(d[36]),"+f"(d[37]),"+f"(d[38]),"+f"(d[39]),"+f"(d[40]),"+f"(d[41]),"+f"(d[42]),"+f"(d[43]),"+f"(d[44]),"+f"(d[45]),"+f"(d[46]),"+f"(d[47]),"+f"(d[48]),"+f"(d[49]),"+f"(d[50]),"+f"(d[51]),"+f"(d[52]),"+f"(d[53]),"+f"(d[54]),"+f"(d[55]),"+f"(d[56]),"+f"(d[57]),"+f"(d[58]),"+f"(d[59]),"+f"(d[60]),"+f"(d[61]),"+f"(d[62]),"+f"(d[63])
   : "l"(da),"l"(db),"r"(sd),"n"(TA),"n"(TB));
}
template<int TA, int TB> __device__ __forceinline__ void wg_ss64(float* d, uint64_t da, uint64_t db, int sd) {
  asm volatile("{\n.reg .pred p;\nsetp.ne.b32 p, %34, 0;\n"
   "wgmma.mma_async.sync.aligned.m64n64k16.f32.bf16.bf16 {%0,%1,%2,%3,%4,%5,%6,%7,%8,%9,%10,%11,%12,%13,%14,%15,%16,%17,%18,%19,%20,%21,%22,%23,%24,%25,%26,%27,%28,%29,%30,%31}, %32, %33, p, 1, 1, %35, %36;\n}\n"
   : "+f"(d[0]),"+f"(d[1]),"+f"(d[2]),"+f"(d[3]),"+f"(d[4]),"+f"(d[5]),"+f"(d[6]),"+f"(d[7]),"+f"(d[8]),"+f"(d[9]),"+f"(d[10]),"+f"(d[11]),"+f"(d[12]),"+f"(d[13]),"+f"(d[14]),"+f"(d[15]),"+f"(d[16]),"+f"(d[17]),"+f"(d[18]),"+f"(d[19]),"+f"(d[20]),"+f"(d[21]),"+f"(d[22]),"+f"(d[23]),"+f"(d[24]),"+f"(d[25]),"+f"(d[26]),"+f"(d[27]),"+f"(d[28]),"+f"(d[29]),"+f"(d[30]),"+f"(d[31])
   : "l"(da),"l"(db),"r"(sd),"n"(TA),"n"(TB));
}

template<int TA, int TB> __device__ __forceinline__ void wg_ss8(float* d, uint64_t da, uint64_t db, int sd) {
  asm volatile("{\n.reg .pred p;\nsetp.ne.b32 p, %6, 0;\n"
   "wgmma.mma_async.sync.aligned.m64n8k16.f32.bf16.bf16 {%0,%1,%2,%3}, %4, %5, p, 1, 1, %7, %8;\n}\n"
   : "+f"(d[0]),"+f"(d[1]),"+f"(d[2]),"+f"(d[3])
   : "l"(da),"l"(db),"r"(sd),"n"(TA),"n"(TB));
}

template<int SD, uint32_t HI> __device__ __forceinline__ void wq32(float* d, uint64_t da, uint32_t lo) {
  asm volatile("{\n.reg .b64 db;\nmov.b64 db, {%17, %19};\n"
   "wgmma.mma_async.sync.aligned.m64n32k16.f32.f16.f16 {%0,%1,%2,%3,%4,%5,%6,%7,%8,%9,%10,%11,%12,%13,%14,%15}, %16, db, %18, 1, 1, 0, 0;\n}\n"
   : "+f"(d[0]),"+f"(d[1]),"+f"(d[2]),"+f"(d[3]),"+f"(d[4]),"+f"(d[5]),"+f"(d[6]),"+f"(d[7]),"+f"(d[8]),"+f"(d[9]),"+f"(d[10]),"+f"(d[11]),"+f"(d[12]),"+f"(d[13]),"+f"(d[14]),"+f"(d[15])
   : "l"(da),"r"(lo),"n"(SD),"r"(HI));
}
template<int SD, uint32_t HI> __device__ __forceinline__ void wq64(float* d, uint64_t da, uint32_t lo) {
  asm volatile("{\n.reg .b64 db;\nmov.b64 db, {%33, %35};\n"
   "wgmma.mma_async.sync.aligned.m64n64k16.f32.f16.f16 {%0,%1,%2,%3,%4,%5,%6,%7,%8,%9,%10,%11,%12,%13,%14,%15,%16,%17,%18,%19,%20,%21,%22,%23,%24,%25,%26,%27,%28,%29,%30,%31}, %32, db, %34, 1, 1, 0, 0;\n}\n"
   : "+f"(d[0]),"+f"(d[1]),"+f"(d[2]),"+f"(d[3]),"+f"(d[4]),"+f"(d[5]),"+f"(d[6]),"+f"(d[7]),"+f"(d[8]),"+f"(d[9]),"+f"(d[10]),"+f"(d[11]),"+f"(d[12]),"+f"(d[13]),"+f"(d[14]),"+f"(d[15]),"+f"(d[16]),"+f"(d[17]),"+f"(d[18]),"+f"(d[19]),"+f"(d[20]),"+f"(d[21]),"+f"(d[22]),"+f"(d[23]),"+f"(d[24]),"+f"(d[25]),"+f"(d[26]),"+f"(d[27]),"+f"(d[28]),"+f"(d[29]),"+f"(d[30]),"+f"(d[31])
   : "l"(da),"r"(lo),"n"(SD),"r"(HI));
}
template<int SD, uint32_t HI> __device__ __forceinline__ void wpv(float* d, const uint32_t* a, uint32_t lo) {
  asm volatile("{\n.reg .b64 db;\nmov.b64 db, {%16, %18};\n"
   "wgmma.mma_async.sync.aligned.m64n24k16.f32.bf16.bf16 {%0,%1,%2,%3,%4,%5,%6,%7,%8,%9,%10,%11}, {%12,%13,%14,%15}, db, %17, 1, 1, 1;\n}\n"
   : "+f"(d[0]),"+f"(d[1]),"+f"(d[2]),"+f"(d[3]),"+f"(d[4]),"+f"(d[5]),"+f"(d[6]),"+f"(d[7]),"+f"(d[8]),"+f"(d[9]),"+f"(d[10]),"+f"(d[11])
   : "r"(a[0]),"r"(a[1]),"r"(a[2]),"r"(a[3]),"r"(lo),"n"(SD),"r"(HI));
}

__device__ __forceinline__ uint32_t phi2(float a, float b) {
  uint32_t r, e;
  asm("cvt.rn.relu.bf16x2.f32 %0, %1, %2;" : "=r"(r) : "f"(b), "f"(a));
  e = pack_bf16(ex2f(a * 1.4426950408889634f), ex2f(b * 1.4426950408889634f));
  asm("add.rn.bf16x2 %0, %0, %1;" : "+r"(e) : "r"(0x35863586u));
  asm("min.NaN.bf16x2 %0, %0, %1;" : "+r"(e) : "r"(0x3F803F80u));
  asm("add.rn.bf16x2 %0, %0, %1;" : "+r"(e) : "r"(r));
  return e;
}

__device__ __forceinline__ void mbar_arrive(uint32_t bar) { asm volatile("mbarrier.arrive.shared::cta.b64 _, [%0];" :: "r"(bar) : "memory"); }
__device__ __forceinline__ void named_arrive(int id, int n) { asm volatile("bar.arrive %0, %1;" :: "r"(id), "r"(n) : "memory"); }
__device__ __forceinline__ void fence_async_all() { asm volatile("fence.proxy.async;" ::: "memory"); }
__device__ __forceinline__ void flag_add(uint32_t* f) { asm volatile("fence.acq_rel.gpu;\nred.relaxed.gpu.global.add.u32 [%0], 1;" :: "l"(f) : "memory"); }
__device__ __forceinline__ void flag_wait(const uint32_t* f, uint32_t target) {
  uint32_t v;
#pragma unroll 1
  for (int it = 0;; it++) {
    asm volatile("ld.acquire.gpu.global.u32 %0, [%1];" : "=r"(v) : "l"(f) : "memory");
    if ((int32_t)(v - target) >= 0) break;
    if (it > 2000000) __trap();
  }
}
__device__ __forceinline__ bool elect_one() {
  uint32_t p;
  asm volatile("{\n.reg .pred P;\nelect.sync _|P, 0xFFFFFFFF;\nselp.b32 %0, 1, 0, P;\n}\n" : "=r"(p));
  return p;
}
__device__ __forceinline__ void lds4(uint32_t a, uint32_t* r) {
  asm volatile("ld.shared.v4.b32 {%0,%1,%2,%3}, [%4];" : "=r"(r[0]), "=r"(r[1]), "=r"(r[2]), "=r"(r[3]) : "r"(a) : "memory");
}
__device__ __forceinline__ uint32_t lds1(uint32_t a) { uint32_t r; asm volatile("ld.shared.b32 %0, [%1];" : "=r"(r) : "r"(a) : "memory"); return r; }
__device__ __forceinline__ void sts1(uint32_t a, uint32_t v) { asm volatile("st.shared.b32 [%0], %1;" :: "r"(a), "r"(v) : "memory"); }
__device__ __forceinline__ void sts4(uint32_t a, uint32_t r0, uint32_t r1, uint32_t r2, uint32_t r3) {
  asm volatile("st.shared.v4.b32 [%0], {%1,%2,%3,%4};" :: "r"(a), "r"(r0), "r"(r1), "r"(r2), "r"(r3) : "memory");
}
__device__ __forceinline__ void ldsm4(uint32_t a, uint32_t* r) {
  asm volatile("ldmatrix.sync.aligned.m8n8.x4.shared.b16 {%0,%1,%2,%3}, [%4];" : "=r"(r[0]), "=r"(r[1]), "=r"(r[2]), "=r"(r[3]) : "r"(a) : "memory");
}
__device__ __forceinline__ float rcpf(float x) { float y; asm("rcp.approx.ftz.f32 %0, %1;" : "=f"(y) : "f"(x)); return y; }
__device__ __forceinline__ uint32_t hfma2(uint32_t a, uint32_t b, uint32_t c) { uint32_t r; asm("fma.rn.f16x2 %0, %1, %2, %3;" : "=r"(r) : "r"(a), "r"(b), "r"(c)); return r; }
__device__ __forceinline__ uint32_t hadd2(uint32_t a, uint32_t b) { uint32_t r; asm("add.rn.f16x2 %0, %1, %2;" : "=r"(r) : "r"(a), "r"(b)); return r; }

#define STEPK 96
#define QSCALE 0.36067376022224085f
#define SMAGIC (512.0f + 2.0f * (191.0f - 30.0f - 1.5823545f))
#define VSHIFT 1073741824.0f

__device__ uint32_t g_epoch[132];
__device__ uint32_t g_flag[288 * 8];
#define FLAG_KV (g_flag)
#define FLAG_B(h) (g_flag + (4 + (h)) * 8)
#define FLAG_OA(cta, pass) (g_flag + (16 + (cta) * 2 + (pass)) * 8)
#define FLAG_LM(i) (g_flag + (272 + (i)) * 8)

#define SM_TOTAL (224 * 1024 + 2048 + 1024)
#define OFF_K 0
#define OFF_F 65536
#define OFF_V 131072
#define OFF_MISC (224 * 1024)

#define BAR_FULL(s) (bars + 8 * (s))
#define BAR_EMPTY(s) (bars + 24 + 8 * (s))
#define BAR_KV(c) (bars + 48 + 8 * (c))
#define BAR_XA (bars + 72)
#define BAR_BDONE (bars + 80)
#define BAR_Q (bars + 88)
#define BAR_GO (bars + 96)
#define BAR_Q2 (bars + 104)
#define BAR_OD(p) (bars + 112 + 8 * (p))
#define BAR_CL(c) (bars + 128 + 8 * (c))
#define BAR_TE(i) (bars + 168 + 8 * (i))
#define BAR_TF(g) (bars + 224 + 8 * (g))

__device__ __forceinline__ uint32_t exp2_pair_fix(float d0, float d1, uint32_t c63, uint32_t m1) {
  uint32_t w, y, s, r;
  asm("prmt.b32 %0, %1, %2, 0x6521;" : "=r"(w) : "r"(__float_as_uint(d0)), "r"(__float_as_uint(d1)));
  asm("lop3.b32 %0, %1, 0x007F007F, %2, 0xEA;" : "=r"(y) : "r"(w), "r"(c63));
  asm("mad.lo.u32 %0, %1, %2, %3;" : "=r"(s) : "r"(y), "r"(m1), "r"(w));
  asm("fma.rn.bf16x2 %0, %1, %2, %3;" : "=r"(r) : "r"(w), "r"(y), "r"(s));
  return r;
}

__device__ __forceinline__ void attn_slow(const uint4* gq, __nv_bfloat16* dst) {
  const int t = threadIdx.x & 127;
  const int row = t >> 1, half = t & 1;
  float q[16];
#pragma unroll
  for (int i = 0; i < 4; i++) {
    const uint4 v = gq[(row >> 4) * 32 + (row & 7) * 4 + i];
    const uint32_t lo = (row & 8) ? v.y : v.x, hi = (row & 8) ? v.w : v.z;
    q[2 * i] = bf_lo(lo); q[2 * i + 1] = bf_hi(lo); q[2 * i + 8] = bf_lo(hi); q[2 * i + 9] = bf_hi(hi);
  }
  float m = -INFINITY, l = 0.f, o[16];
#pragma unroll
  for (int i = 0; i < 16; i++) o[i] = 0.f;
#pragma unroll 1
  for (int j = half * 1024; j < half * 1024 + 1024; j++) {
    uint4 ka = g_KV[4 * S_TOK + j], kb = g_KV[5 * S_TOK + j];
    uint4 va = g_KV[6 * S_TOK + j], vb = g_KV[7 * S_TOK + j];
    uint32_t kk[8] = {ka.x, ka.y, ka.z, ka.w, kb.x, kb.y, kb.z, kb.w};
    uint32_t vv[8] = {va.x, va.y, va.z, va.w, vb.x, vb.y, vb.z, vb.w};
    float s = 0.f;
#pragma unroll
    for (int i = 0; i < 8; i++) { s = fmaf(q[2 * i], bf_lo(kk[i]), s); s = fmaf(q[2 * i + 1], bf_hi(kk[i]), s); }
    s = rbf(s) * 0.25f;
    if (s > m) {
      float c = __expf(m - s);
      l *= c;
#pragma unroll
      for (int i = 0; i < 16; i++) o[i] *= c;
      m = s;
    }
    float p = __expf(s - m);
    l += p;
#pragma unroll
    for (int i = 0; i < 8; i++) { o[2 * i] = fmaf(p, bf_lo(vv[i]), o[2 * i]); o[2 * i + 1] = fmaf(p, bf_hi(vv[i]), o[2 * i + 1]); }
  }
  float m2 = __shfl_xor_sync(~0u, m, 1);
  float mm = fmaxf(m, m2);
  float c = __expf(m - mm);
  l *= c; l += __shfl_xor_sync(~0u, l, 1);
  float inv = 1.f / l;
  uint32_t r[8];
#pragma unroll
  for (int i = 0; i < 16; i++) { o[i] *= c; o[i] += __shfl_xor_sync(~0u, o[i], 1); o[i] *= inv; }
#pragma unroll
  for (int i = 0; i < 8; i++) r[i] = pack_bf16(o[2 * i], o[2 * i + 1]);
  uint4* d = (uint4*)(dst + (size_t)row * D_MOD);
  if (half == 0) d[0] = make_uint4(r[0], r[1], r[2], r[3]); else d[1] = make_uint4(r[4], r[5], r[6], r[7]);
}

struct Params { const __nv_bfloat16* wk; const __nv_bfloat16* wv; };

__device__ __forceinline__ void helper_cta(const int h, const uint32_t sb, const uint32_t bars, const int wg, const int w4,
                                           const CUtensorMap* mQ, const CUtensorMap* mOs) {
  const int lane = threadIdx.x & 31;
  mbar_wait(BAR_GO, 0);
  const int cb = wg & 1, col = h * 128 + cb * 64, row0 = S_TOK + (wg >> 1) * 1024;
  const uint32_t buf = sb + wg * 49152;
  if (w4 == 0 && elect_one()) {
    fence_async_all();
#pragma unroll 1
    for (int u = 0; u < 3; u++) {
      mbar_expect_tx(BAR_TF(wg * 3 + u), 16384);
      tma2d(buf + u * 16384, mQ, col, row0 + u * 128, BAR_TF(wg * 3 + u));
    }
  }
  const int head = h * 8 + cb * 4 + w4;
  float4 a0 = make_float4(0, 0, 0, 0), a1 = a0, a2 = a0;
#pragma unroll 8
  for (int tt = 0; tt < 16; tt++) {
    const float4* src = g_kvp + ((tt * 32 + head) * 3) * 32 + lane;
    float4 u = src[0], v = src[32], w = src[64];
    a0.x += u.x; a0.y += u.y; a0.z += u.z; a0.w += u.w;
    a1.x += v.x; a1.y += v.y; a1.z += v.z; a1.w += v.w;
    a2.x += w.x; a2.y += w.y; a2.z += w.z; a2.w += w.w;
  }
  const uint32_t b00 = pack_bf16(a0.x, a0.y), b01 = pack_bf16(a0.z, a0.w);
  const uint32_t b10 = pack_bf16(a1.x, a1.y), b11 = pack_bf16(a1.z, a1.w);
  const uint32_t bz0 = pack_bf16(a2.x, a2.y), bz1 = pack_bf16(a2.z, a2.w);
  const int m = lane >> 3, r = lane & 7;
  const uint32_t off = ((m & 1) * 8 + r) * 128 + (((w4 * 2 + (m >> 1)) ^ r) << 4);
  int s = 0, ph = 0;
#pragma unroll 1
  for (int u = 0; u < 8; u++) {
    const uint32_t bb = buf + s * 16384;
    mbar_wait(BAR_TF(wg * 3 + s), ph);
#pragma unroll
    for (int mt = 0; mt < 8; mt++) {
      uint32_t a[4];
      ldsm4(bb + mt * 2048 + off, a);
      float n0[4] = {0, 0, 0, 0}, n1[4] = {0, 0, 0, 0}, dn[4] = {0, 0, 0, 0};
      mma_bf16(dn, a[0], a[1], a[2], a[3], bz0, bz1);
      mma_bf16(n0, a[0], a[1], a[2], a[3], b00, b01);
      mma_bf16(n1, a[0], a[1], a[2], a[3], b10, b11);
      const float i0 = rcpf(dn[0] + 1e-6f), i1 = rcpf(dn[2] + 1e-6f);
      stsm4(bb + mt * 2048 + off, pack_bf16(n0[0] * i0, n0[1] * i0), pack_bf16(n0[2] * i1, n0[3] * i1),
            pack_bf16(n1[0] * i0, n1[1] * i0), pack_bf16(n1[2] * i1, n1[3] * i1));
    }
    fence_async();
    named_bar(wg + 1, 128);
    if (w4 == 0 && lane == 0) {
      tma2d_store(mOs, bb, col, row0 + u * 128);
      bulk_commit();
      if (u >= 1 && u + 2 < 8) {
        asm volatile("cp.async.bulk.wait_group.read 1;" ::: "memory");
        const int sp = s == 0 ? 2 : s - 1;
        mbar_expect_tx(BAR_TF(wg * 3 + sp), 16384);
        tma2d(buf + sp * 16384, mQ, col, row0 + (u + 2) * 128, BAR_TF(wg * 3 + sp));
      }
    }
    __syncwarp();
    if (++s == 3) { s = 0; ph ^= 1; }
  }
  if (w4 == 0 && lane == 0) {
    bulk_wait_all();
    fence_async_all();
    flag_add(FLAG_LM((h * 2 + cb) * 2 + (wg >> 1)));
    if (wg == 0) TS(1, 8);
  }
}

#define STAGE(s) (sb + (2 - (s)) * 65536)
template <int TR> __device__ __forceinline__ void proj_loop(float* acc, uint32_t sb, uint32_t bars, uint32_t offA, uint32_t offB) {
  int s = 0, ph = 0, sp = 0;
#pragma unroll 1
  for (int kb = 0; kb < 8; kb++) {
    const uint32_t st = STAGE(s);
    mbar_wait(BAR_FULL(s), ph);
    if (threadIdx.x == 0) TS(0, 2 + kb);
    const uint64_t da = make_desc(st + offA, TR ? 8192 : 16, 1024, 1);
    const uint64_t db = make_desc(st + offB, TR ? 16 : 8192, 1024, 1);
    wg_fence();
#pragma unroll
    for (int k = 0; k < 4; k++) wg_ss128<TR, 1 - TR>(acc, da + k * (TR ? 128 : 2), db + k * (TR ? 2 : 128), (kb | k) != 0);
    wg_commit();
    wg_wait<1>();
    if (kb >= 1 && (threadIdx.x & 127) == 0) mbar_arrive(BAR_EMPTY(sp));
    __syncwarp();
    sp = s;
    if (++s == 3) { s = 0; ph ^= 1; }
  }
  wg_wait<0>();
  fence_regs<64>(acc);
}

__device__ __forceinline__ uint32_t tail_slots(int t) {
  const uint32_t lo = t < 4 ? (t < 2 ? (t == 0 ? 0x0C0B0Au : 0x0F0E0Du) : (t == 2 ? 0x100400u : 0x081814u))
                            : (t < 6 ? (t == 4 ? 0x110501u : 0x021915u) : (t == 6 ? 0x161206u : (t == 7 ? 0x07031Au : 0x1B1713u)));
  return lo;
}

__global__ void __launch_bounds__(640, 1)
k1_main(const __grid_constant__ CUtensorMap mXA64, const __grid_constant__ CUtensorMap mXB,
        const __grid_constant__ CUtensorMap mWq, const __grid_constant__ CUtensorMap mWqkv,
        const __grid_constant__ CUtensorMap mQst, const __grid_constant__ CUtensorMap mOst,
        const __grid_constant__ CUtensorMap mO, const __grid_constant__ CUtensorMap mWoA,
        const __grid_constant__ CUtensorMap mWoB, const __grid_constant__ CUtensorMap mOut, const Params prm) {
  extern __shared__ uint8_t smem_raw[];
  const uint32_t sb = (smem_u32(smem_raw) + 1023u) & ~1023u;
  const uint32_t bars = sb + OFF_MISC, sM = bars + 512, sT = bars + 1024;
  const int tid = threadIdx.x, warp = __shfl_sync(~0u, tid >> 5, 0), wg = warp >> 2, w4 = warp & 3, lane = tid & 31;
  const bool helper = blockIdx.x >= 128;
  if (tid == 0) TS(0, 0);
  const int G = blockIdx.x >> 4, gi = blockIdx.x & 15;
  const int tbA = G * 4 + (gi >> 2), hg = gi & 3;
  const int ttB = (G >> 1) * 4 + (gi >> 2), hq = (G & 1) * 4 + (gi & 3);
  const int ttO = G * 2 + (gi >> 3), ct = gi & 7;
  auto issue = [&](int kb, int s) {
    const uint32_t fb = BAR_FULL(s), st = STAGE(s);
    mbar_expect_tx(fb, 65536);
    tma2d(st + 16384, &mXA64, kb * 64, tbA * 64, fb);
    tma2d(st, &mWq, hg * 128, kb * 64, fb);
    tma2d(st + 8192, &mWq, hg * 128 + 64, kb * 64, fb);
    tma2d(st + 49152, &mXB, kb * 64, ttB * 128, fb);
    tma2d(st + 24576, &mWqkv, hq * 64, kb * 64, fb);
    tma2d(st + 32768, &mWqkv, 512 + hq * 64, kb * 64, fb);
    tma2d(st + 40960, &mWqkv, 1024 + hq * 64, kb * 64, fb);
  };
  const uint32_t sOne = sb + OFF_V + 65536, sWKV = sOne + 24576;
  if (warp == 16) {
    if (elect_one()) {
      mbar_init(BAR_XA, 1);
#pragma unroll 1
      for (int s = 0; s < 3; s++) { mbar_init(BAR_FULL(s), 1); mbar_init(BAR_EMPTY(s), 4); mbar_init(BAR_KV(s), 1); }
      asm volatile("fence.mbarrier_init.release.cluster;" ::: "memory");
      if (!helper) {
        mbar_expect_tx(BAR_XA, 65536);
#pragma unroll 1
        for (int kb = 0; kb < 8; kb++) tma2d(STAGE(2) + kb * 8192, &mXA64, kb * 64, tbA * 64, BAR_XA);
#pragma unroll 1
        for (int kb = 0; kb < 2; kb++) issue(kb, kb);
      }
    }
  } else if (warp == 17) {
    if (lane == 0) {
      mbar_init(BAR_BDONE, 8); mbar_init(BAR_Q, 9); mbar_init(BAR_GO, 1); mbar_init(BAR_Q2, 4);
      mbar_init(BAR_OD(0), 16); mbar_init(BAR_OD(1), 16); mbar_init(BAR_CL(0), 1);
      sts1(sM + 20, 0);
    }
    if (lane >= 1 && lane < 5) mbar_init(BAR_CL(lane), 4);
    if (lane >= 8 && lane < 15) mbar_init(BAR_TE(lane - 8), 2);
    if (lane >= 16) mbar_init(BAR_TF(lane - 16), 1);
    asm volatile("fence.mbarrier_init.release.cluster;" ::: "memory");
  } else if (tid < 512 && !helper) {
    const uint4 v = __ldg((const uint4*)(hg >= 2 ? prm.wv : prm.wk) + tid * 2 + (hg & 1));
#pragma unroll
    for (int i = 0; i < 3; i++) {
      const int key = tid + i * 512;
      sts4(sOne + key * 16, (key % STEPK) < 32 ? 0x00003F80u : 0x00004E80u, 0u, 0u, 0u);
    }
    sts4(sWKV + tid * 16, v.x, v.y, v.z, v.w);
    fence_async();
  }
  __syncthreads();
  if (wg == 4) {
    asm volatile("setmaxnreg.dec.sync.aligned.u32 32;");
    const uint32_t ep = g_epoch[blockIdx.x] + 1;
    if (helper) {
      if (w4 == 0 && elect_one()) {
        flag_wait(FLAG_B(blockIdx.x - 128), ep * 32);
        fence_async_all();
        TS(1, 10);
        mbar_arrive(BAR_GO);
        g_epoch[blockIdx.x] = ep;
      }
      return;
    }
    {
      float acc[4];
      mbar_wait(BAR_XA, 0);
      const uint64_t da = make_desc(STAGE(2), 16, 1024, 1), db = make_desc(sWKV, 128, 128, 0);
      wg_fence();
#pragma unroll
      for (int kb = 0; kb < 8; kb++) {
#pragma unroll
        for (int k = 0; k < 4; k++) wg_ss8<0, 1>(acc, da + kb * 512 + k * 2, db + kb * 64 + k * 16, (kb | k) != 0);
      }
      wg_commit();
      wg_wait<0>();
      fence_regs<4>(acc);
      sts1(sT + w4 * 256 + lane * 4, pack_bf16(acc[0], acc[1]));
      sts1(sT + w4 * 256 + 128 + lane * 4, pack_bf16(acc[2], acc[3]));
    }
    named_bar(9, 128);
    if (w4 == 0 && elect_one()) { mbar_arrive(BAR_GO); issue(2, 2); }
    {
      const int t = tid - 512;
#pragma unroll
      for (int i = 0; i < 4; i++) {
        const int key = 1536 + t + i * 128;
        sts4(sOne + key * 16, (key % STEPK) < 32 ? 0x00003F80u : 0x00004E80u, 0u, 0u, 0u);
      }
      fence_async();
      __syncwarp();
      if (lane == 0) mbar_arrive(BAR_Q);
    }
    if (w4 == 0) {
      if (elect_one()) {
        int s = 0, ph = 0;
#pragma unroll 1
        for (int kb = 3; kb < 8; kb++) {
          mbar_wait(BAR_EMPTY(s), ph);
          issue(kb, s);
          if (++s == 3) { s = 0; ph ^= 1; }
        }
        flag_wait(FLAG_KV, ep * 128);
        fence_async_all();
        TS(0, 11);
        mbar_wait(BAR_EMPTY(2), 1);
        mbar_wait(BAR_EMPTY(0), 0);
#pragma unroll 1
        for (int c = 0; c < 3; c++) {
          const int k0 = c == 0 ? 0 : (c == 1 ? 7 * STEPK : 12 * STEPK), k1 = c == 0 ? 7 * STEPK : (c == 1 ? 12 * STEPK : S_TOK);
          const uint32_t bytes = (k1 - k0) * 16;
          mbar_expect_tx(BAR_KV(c), 4 * bytes);
#pragma unroll 1
          for (int p = 0; p < 4; p++)
            bulk_g2s(sb + (p < 2 ? OFF_K : OFF_V - 65536) + p * 32768 + k0 * 16, g_KV + p * S_TOK + k0, bytes, BAR_KV(c));
        }
#pragma unroll 1
        for (int n = 0; n < 16; n++) {
          const int gidx = n < 7 ? n : (n < 11 ? n + 2 : (n < 13 ? n - 4 : n));
          const int tr = gidx < 9 ? gidx : gidx - 9;
          if (gidx < 9) mbar_wait(BAR_CL(gidx < 4 ? gidx >> 1 : (gidx == 4 ? 2 : (gidx < 7 ? 3 : 4))), 0);
          else mbar_wait(BAR_TE(tr), 0);
          const uint32_t sl = tail_slots(tr);
          const bool isB = gidx < 8;
          const int kb = isB ? gidx : (gidx == 8 ? 1 : (gidx < 13 ? (gidx - 9) * 2 : (gidx - 13) * 2 + 3));
          const uint32_t fb = BAR_TF(gidx);
          mbar_expect_tx(fb, 24576);
          tma2d(sb + (sl & 255) * 8192, isB ? &mWoB : &mWoA, ct * 64, kb * 64, fb);
          if (isB) flag_wait(FLAG_LM(kb * 2 + (ttO >> 3)), ep);
#pragma unroll 1
          for (int hf = 0; hf < 2; hf++) {
            if (!isB) flag_wait(FLAG_OA((ttO * 2 + hf) * 4 + (kb >> 1), kb & 1), ep);
            fence_async_all();
            tma2d(sb + ((sl >> (8 + 8 * hf)) & 255) * 8192, &mO, kb * 64, (isB ? S_TOK : 0) + ttO * 128 + hf * 64, fb);
          }
        }
        g_epoch[blockIdx.x] = ep;
      }
    } else if (w4 == 3) {
      flag_wait(FLAG_KV, ep * 128);
      const uint4 a = *(const uint4*)(g_stats + lane * 4);
      const float kmax2 = __uint_as_float(__reduce_max_sync(~0u, a.x)) + __uint_as_float(__reduce_max_sync(~0u, a.y));
      const float vmax = __uint_as_float(__reduce_max_sync(~0u, max(a.z, a.w)));
      const float lv = vmax > 0.f ? __log2f(vmax) : 0.f;
      const float lim = fminf(90.f, fminf(91.f + lv, 95.f - lv));
      float thr = -1.f;
      if (vmax < 1e27f && kmax2 <= 65536.f && lim > 2.f) thr = fminf(60000.f, (lim * lim - 1.f) / (kmax2 * 1.02f + 1e-30f));
      if (lane == 0) { sts1(sM + 16, __float_as_uint(thr)); mbar_arrive(BAR_Q); }
    } else {
      const int ch = tbA * 2 + (w4 - 1);
      uint32_t v[4], o[4];
      lds4(sT + (w4 - 1) * 512 + lane * 16, v);
      int kap;
      if (lane < 21) kap = lane * STEPK + 32 + ch;
      else { int idx = ch * 11 + (lane - 21); kap = (idx >> 5) * STEPK + (idx & 31); }
      g_KV[(4 + hg) * S_TOK + kap] = make_uint4(v[0], v[1], v[2], v[3]);
      float st = 0.f;
      if (hg < 2) {
        const float sc = lane < 21 ? 2.f : 1.f;
#pragma unroll
        for (int u = 0; u < 4; u++) {
          uint32_t pv = __shfl_up_sync(~0u, v[u], 1);
          if (lane == 0 || lane >= 21) pv = 0;
          const float x = bf_lo(v[u]), y = bf_hi(v[u]);
          st += x * x + y * y;
          o[u] = pack_f16((x - bf_lo(pv)) * sc, (y - bf_hi(pv)) * sc);
        }
      } else {
        const float sc = lane < 21 ? VSHIFT : 1.f;
#pragma unroll
        for (int u = 0; u < 4; u++) { float x = bf_lo(v[u]), y = bf_hi(v[u]); st += fabsf(x) + fabsf(y); o[u] = pack_bf16(x * sc, y * sc); }
      }
      g_KV[hg * S_TOK + kap] = make_uint4(o[0], o[1], o[2], o[3]);
      const uint32_t um = __reduce_max_sync(~0u, __float_as_uint(st) & 0x7FFFFFFFu);
      if (w4 == 2) { if (lane == 0) sts1(sM + 24, um); named_arrive(10, 64); }
      else {
        named_bar(10, 64);
        if (elect_one()) {
          g_stats[tbA * 4 + hg] = max(um, lds1(sM + 24));
          fence_async_all();
          flag_add(FLAG_KV);
          TS(1, 9);
          mbar_wait(BAR_BDONE, 0);
          tma2d_store(&mQst, sb + OFF_F + 49152, hq * 64, S_TOK + ttB * 128);
          bulk_commit();
          bulk_wait_all();
          fence_async_all();
          flag_add(FLAG_B(hq >> 1));
          TS(0, 12);
          mbar_wait(BAR_Q, 0);
          mbar_arrive(BAR_CL(0));
#pragma unroll 1
          for (int p = 0; p < 2; p++) {
            mbar_wait(BAR_OD(p), 0);
            fence_async_all();
            flag_add(FLAG_OA(blockIdx.x, p));
          }
          TS(2, 0);
        }
      }
    }
    return;
  }
  asm volatile("setmaxnreg.inc.sync.aligned.u32 112;");
  if (helper) { helper_cta(blockIdx.x - 128, sb, bars, wg, w4, &mQst, &mOst); return; }

  {
    float acc[64];
    mbar_wait(BAR_GO, 0);
    if (wg == 0) proj_loop<0>(acc, sb, bars, 16384, 0);
    else proj_loop<1>(acc, sb, bars, 16384 + wg * 8192, 49152);
    if (tid == 0) TS(0, 10);
    const uint32_t sF = sb + OFF_F;
    if (wg == 0) {
      uint32_t nmax = 0;
      const uint32_t qa = sF + w4 * 512 + ((lane >> 3) & 1) * 256 + (lane >> 4) * 128 + (lane & 7) * 16;
#pragma unroll
      for (int hd = 0; hd < 8; hd++) {
        uint32_t r[4];
#pragma unroll
        for (int i = 0; i < 4; i++) r[i] = pack_f16(acc[8 * hd + 2 * i] * QSCALE, acc[8 * hd + 2 * i + 1] * QSCALE);
        stsm4(qa + hd * 2048, r[0], r[1], r[2], r[3]);
        const uint32_t t0 = hfma2(r[2], r[2], hfma2(r[0], r[0], 0u)), t1 = hfma2(r[3], r[3], hfma2(r[1], r[1], 0u));
        uint32_t n = hadd2(__byte_perm(t0, t1, 0x5410), __byte_perm(t0, t1, 0x7632));
        n = hadd2(n, __shfl_xor_sync(~0u, n, 1));
        n = hadd2(n, __shfl_xor_sync(~0u, n, 2));
        nmax = __vmaxu2(nmax, n & 0x7FFF7FFFu);
      }
      nmax = __reduce_max_sync(~0u, max(nmax & 0xFFFFu, nmax >> 16));
      if (lane == 0) sts1(sM + w4 * 4, nmax);
      fence_async();
      __syncwarp();
      if (lane == 0) mbar_arrive(BAR_Q);
      uint4* gq = (uint4*)g_Q + blockIdx.x * 1024 + tid;
#pragma unroll
      for (int hd = 0; hd < 8; hd++)
        gq[hd * 128] = make_uint4(pack_bf16(acc[8 * hd], acc[8 * hd + 1]), pack_bf16(acc[8 * hd + 2], acc[8 * hd + 3]),
                                  pack_bf16(acc[8 * hd + 4], acc[8 * hd + 5]), pack_bf16(acc[8 * hd + 6], acc[8 * hd + 7]));
      __syncwarp();
      if (lane == 0) mbar_arrive(BAR_Q2);
    } else if (wg == 3) {
      named_arrive(8, 384);
      named_bar(6, 384);
      const int t = tid & 127;
#pragma unroll
      for (int j = 0; j < 8; j++)
        sts4(sF + 24576 + j * 2048 + t * 16, pack_bf16(acc[8 * j], acc[8 * j + 1]), pack_bf16(acc[8 * j + 2], acc[8 * j + 3]),
             pack_bf16(acc[8 * j + 4], acc[8 * j + 5]), pack_bf16(acc[8 * j + 6], acc[8 * j + 7]));
      named_arrive(7, 256);
    } else {
      uint32_t p[32];
      named_arrive(6, 384);
      if (wg == 2) named_arrive(8, 384);
#pragma unroll
      for (int i = 0; i < 32; i++) p[i] = phi2(acc[2 * i], acc[2 * i + 1]);
      if (wg == 1) {
        named_bar(8, 384);
        const int m = lane >> 3, r = lane & 7;
#pragma unroll
        for (int j = 0; j < 16; j += 2) {
          const int tok = (j + (m >> 1)) * 8 + r;
          const int chunk = w4 * 2 + (m & 1);
          stsm4t(sF + 49152 + tok * 128 + ((chunk ^ r) << 4), p[2 * j], p[2 * j + 1], p[2 * j + 2], p[2 * j + 3]);
        }
        fence_async();
      } else {
        named_bar(7, 256);
        float kv0[4] = {0, 0, 0, 0}, kv1[4] = {0, 0, 0, 0}, z0[4] = {0, 0, 0, 0}, z1[4] = {0, 0, 0, 0};
        const uint32_t one = 0x3F803F80u;
        const int t = tid & 127;
#pragma unroll
        for (int j = 0; j < 8; j++) {
          uint32_t a[4];
          lds4(sF + 24576 + j * 2048 + t * 16, a);
          mma_bf16(kv0, a[0], a[1], a[2], a[3], p[4 * j], p[4 * j + 2]);
          mma_bf16(kv1, a[0], a[1], a[2], a[3], p[4 * j + 1], p[4 * j + 3]);
          mma_bf16(z0, one, one, one, one, p[4 * j], p[4 * j + 2]);
          mma_bf16(z1, one, one, one, one, p[4 * j + 1], p[4 * j + 3]);
        }
        float4* dst = g_kvp + ((ttB * 32 + hq * 4 + w4) * 3) * 32 + lane;
        dst[0] = make_float4(kv0[0], kv0[1], kv1[0], kv1[1]);
        dst[32] = make_float4(kv0[2], kv0[3], kv1[2], kv1[3]);
        dst[64] = make_float4(z0[0], z0[1], z1[0], z1[1]);
      }
      __syncwarp();
      if (lane == 0) mbar_arrive(BAR_BDONE);
    }
  }

  mbar_wait(BAR_Q, 0);
  if (tid == 0) TS(1, 1);
  bool safe;
  {
    uint32_t n[4];
    lds4(sM, n);
    const float qn = __half2float(__ushort_as_half((unsigned short)max(max(n[0], n[1]), max(n[2], n[3]))));
    safe = __all_sync(~0u, qn <= __uint_as_float(lds1(sM + 16)));
  }
  __nv_bfloat16* const obase = g_O + (size_t)(tbA * 64) * D_MOD + (hg * 8 + wg) * 16;
  if (!safe) {
    mbar_wait(BAR_Q2, 0);
#pragma unroll 1
    for (int c = 0; c < 3; c++) mbar_wait(BAR_KV(c), 0);
    if ((tid & 127) == 0) { mbar_arrive(BAR_CL(1)); mbar_arrive(BAR_CL(2)); mbar_arrive(BAR_CL(3)); }
#pragma unroll 1
    for (int pass = 0; pass < 2; pass++) {
      attn_slow((const uint4*)g_Q + blockIdx.x * 1024 + (pass * 4 + wg) * 128, obase + pass * 64);
      __syncwarp();
      if (lane == 0) mbar_arrive(BAR_OD(pass));
    }
  } else {
    const uint32_t c63 = 0x1F801F80u + (threadIdx.x >> 20);
    const uint32_t m1 = (gridDim.x >> 20) - 1u;
    const uint64_t dK0 = make_desc(sb + OFF_K, 32768, 128, 0);
    const uint64_t dV0 = make_desc(sb + OFF_V, 128, 32768, 0);
    const uint32_t dKV = (uint32_t)dK0 + STEPK - (uint32_t)dV0;
    mbar_wait(BAR_KV(0), 0);
#pragma unroll 1
    for (int pass = 0; pass < 2; pass++) {
      const uint64_t dQ = make_desc(sb + OFF_F + (pass * 4 + wg) * 2048, 128, 256, 0);
      float Sm[16], Sp[32], O[12];
      uint32_t P[24];
#pragma unroll
      for (int i = 0; i < 32; i++) Sp[i] = SMAGIC;
#pragma unroll
      for (int i = 0; i < 16; i++) Sm[i] = 0.f;
#pragma unroll
      for (int i = 0; i < 12; i++) O[i] = 0.f;
      fence_regs<16>(Sm); fence_regs<32>(Sp); fence_regs<12>(O);
      if (tid == 0) TS(1, 2 + 2 * pass);
      wg_fence();
      wg_qs32<0>(Sm, dQ, dK0);
      wg_qs64<1>(Sp, dQ, dK0 + 32);
      wg_commit();
      wg_wait<0>();
      fence_regs<16>(Sm); fence_regs<32>(Sp);
      uint32_t vlo = (uint32_t)dV0;
#pragma unroll 1
      for (int seg = 0; seg < 4; seg++) {
        if (seg >= 1) {
          if (seg < 3) mbar_wait(BAR_KV(seg), 0);
          if (pass == 1 && (tid & 127) == 0) mbar_arrive(BAR_CL(seg));
          __syncwarp();
        }
        const uint32_t vend = vlo + (seg == 0 ? 6 : 5) * STEPK;
#pragma unroll 1
        for (; vlo != vend; vlo += STEPK) {
          uint64_t dK, dV;
          asm("mov.b64 %0, {%1, %2};" : "=l"(dK) : "r"(vlo + dKV), "r"(8u));
          asm("mov.b64 %0, {%1, %2};" : "=l"(dV) : "r"(vlo), "r"(2048u));
#pragma unroll
          for (int i = 0; i < 8; i++) P[i] = pack_bf16(ex2f(Sm[2 * i]), ex2f(Sm[2 * i + 1]));
#pragma unroll
          for (int i = 0; i < 16; i++) P[8 + i] = exp2_pair_fix(Sp[2 * i], Sp[2 * i + 1], c63, m1);
          fence_regs<24>(P);
          wg_fence();
          wg_qs32<0>(Sm, dQ, dK);
          wg_qs64<1>(Sp, dQ, dK + 32);
#pragma unroll
          for (int k = 0; k < 6; k++) wg_pv24<1>(O, &P[4 * k], dV + k * 16);
          wg_commit();
          wg_wait<0>();
          fence_regs<16>(Sm); fence_regs<32>(Sp); fence_regs<12>(O); fence_regs<24>(P);
        }
      }
#pragma unroll
      for (int i = 0; i < 8; i++) P[i] = pack_bf16(ex2f(Sm[2 * i]), ex2f(Sm[2 * i + 1]));
      fence_regs<8>(P);
      wg_fence();
      wg_pv24<1>(O, &P[0], dV0 + 21 * STEPK);
      wg_pv24<1>(O, &P[4], dV0 + 21 * STEPK + 16);
      wg_commit();
      wg_wait<0>();
      fence_regs<12>(O);
      const float l0 = __shfl_sync(~0u, O[8], lane & ~3), l1 = __shfl_sync(~0u, O[10], lane & ~3);
      const float i0 = rcpf(l0), i1 = rcpf(l1);
      uint32_t* op = (uint32_t*)(obase + pass * 64 + (size_t)(w4 * 16 + (lane >> 2)) * D_MOD) + (lane & 3);
      op[0] = pack_bf16(O[0] * i0, O[1] * i0);
      op[8 * 256] = pack_bf16(O[2] * i1, O[3] * i1);
      op[4] = pack_bf16(O[4] * i0, O[5] * i0);
      op[8 * 256 + 4] = pack_bf16(O[6] * i1, O[7] * i1);
      __syncwarp();
      if (lane == 0) mbar_arrive(BAR_OD(pass));
      if (tid == 0) TS(1, 3 + 2 * pass);
      if ((tid & 127) == 0 && pass == 1 && wg > 0) TS(1, 10 + wg);
    }
  }

  {
    named_bar(wg + 1, 128);
    if ((tid & 127) == 0) {
      mbar_arrive(BAR_CL(4));
      uint32_t r;
      asm volatile("atom.shared.add.u32 %0, [%1], 1;" : "=r"(r) : "r"(sM + 20) : "memory");
      sts1(sM + 32 + wg * 4, r);
    }
    named_bar(wg + 1, 128);
    const int role = __shfl_sync(~0u, lds1(sM + 32 + wg * 4), 0);
    const int isA = role >> 1, hf = role & 1;
    float acc[32];
    uint32_t xs = 0;
    int prev = 0;
#pragma unroll 1
    for (int n = 0; n < 8; n++) {
      const int gidx = isA ? (n < 4 ? n + 9 : (n == 4 ? 8 : n + 8)) : n;
      const uint32_t sl = tail_slots(gidx < 9 ? gidx : gidx - 9);
      xs = sb + ((sl >> (8 + 8 * hf)) & 255) * 8192;
      const uint64_t da = make_desc(xs, 16, 1024, 1), db = make_desc(sb + (sl & 255) * 8192, 8192, 1024, 1);
      mbar_wait(BAR_TF(gidx), 0);
      if ((tid & 127) == 0 && role == 3) TS(2, 2 + n);
      wg_fence();
#pragma unroll
      for (int k = 0; k < 4; k++) wg_ss64<0, 1>(acc, da + k * 2, db + k * 128, (n | k) != 0);
      wg_commit();
      wg_wait<1>();
      if (!isA && n >= 1 && (tid & 127) == 0) mbar_arrive(BAR_TE(prev));
      __syncwarp();
      prev = n;
    }
    wg_wait<0>();
    fence_regs<32>(acc);
    named_bar(wg + 1, 128);
    const int m = lane >> 3, r = lane & 7;
#pragma unroll
    for (int j = 0; j < 8; j += 2) {
      const int row = w4 * 16 + (m & 1) * 8 + r;
      stsm4(xs + row * 128 + (((j + (m >> 1)) ^ r) << 4),
            pack_bf16(acc[4 * j], acc[4 * j + 1]), pack_bf16(acc[4 * j + 2], acc[4 * j + 3]),
            pack_bf16(acc[4 * j + 4], acc[4 * j + 5]), pack_bf16(acc[4 * j + 6], acc[4 * j + 7]));
    }
    fence_async();
    named_bar(wg + 1, 128);
    if (w4 == 0 && elect_one()) {
      tma2d_store(&mOut, xs, (isA ? 0 : 512) + ct * 64, ttO * 128 + hf * 64);
      bulk_commit();
      asm volatile("cp.async.bulk.wait_group.read 0;" ::: "memory");
      TS(2, 11 + (role >> 1));
    }
  }
}

typedef CUresult (*EncodeFn)(CUtensorMap*, CUtensorMapDataType, cuuint32_t, void*, const cuuint64_t*, const cuuint64_t*,
                             const cuuint32_t*, const cuuint32_t*, CUtensorMapInterleave, CUtensorMapSwizzle,
                             CUtensorMapL2promotion, CUtensorMapFloatOOBfill);

static void make_map(EncodeFn enc, CUtensorMap* m, const void* ptr, uint64_t cols, uint64_t rows, uint32_t bc, uint32_t br) {
  cuuint64_t dims[2] = {cols, rows};
  cuuint64_t strides[1] = {cols * 2};
  cuuint32_t box[2] = {bc, br};
  cuuint32_t es[2] = {1, 1};
  enc(m, CU_TENSOR_MAP_DATA_TYPE_BFLOAT16, 2, (void*)ptr, dims, strides, box, es, CU_TENSOR_MAP_INTERLEAVE_NONE,
      CU_TENSOR_MAP_SWIZZLE_128B, CU_TENSOR_MAP_L2_PROMOTION_L2_256B, CU_TENSOR_MAP_FLOAT_OOB_FILL_NONE);
}

extern "C" void kernel_launch(void* const* d_in, const int* in_sizes, int n_in, void* d_out, int out_size) {
  (void)in_sizes; (void)n_in; (void)out_size;
  static EncodeFn enc = nullptr;
  static void* pQ = nullptr; static void* pO = nullptr;
  if (!enc) {
    void* fn = nullptr; cudaDriverEntryPointQueryResult qr;
    cudaGetDriverEntryPoint("cuTensorMapEncodeTiled", &fn, cudaEnableDefault, &qr);
    enc = (EncodeFn)fn;
    cudaGetSymbolAddress(&pQ, g_Q);
    cudaGetSymbolAddress(&pO, g_O);
    cudaFuncSetAttribute(k1_main, cudaFuncAttributeMaxDynamicSharedMemorySize, SM_TOTAL);
  }
  CUtensorMap mXA64, mXB, mWq, mWqkv, mQst, mO, mOst, mWoA, mWoB, mOut;
  make_map(enc, &mXA64, d_in[0], 512, 2048, 64, 64);
  make_map(enc, &mWq, d_in[1], 512, 512, 64, 64);
  make_map(enc, &mWoA, d_in[4], 512, 512, 64, 64);
  make_map(enc, &mXB, d_in[5], 512, 2048, 64, 128);
  make_map(enc, &mWqkv, d_in[6], 1536, 512, 64, 64);
  make_map(enc, &mWoB, d_in[7], 512, 512, 64, 64);
  make_map(enc, &mQst, pQ, 512, 4096, 64, 128);
  make_map(enc, &mO, pO, 512, 4096, 64, 64);
  make_map(enc, &mOst, pO, 512, 4096, 64, 128);
  make_map(enc, &mOut, d_out, 1024, 2048, 64, 64);
  Params prm{(const __nv_bfloat16*)d_in[2], (const __nv_bfloat16*)d_in[3]};
  k1_main<<<132, 640, SM_TOTAL, cudaStreamPerThread>>>(mXA64, mXB, mWq, mWqkv, mQst, mOst, mO, mWoA, mWoB, mOut, prm);
}
```

```cpp
#include <cuda_runtime.h>
#include <cuda_bf16.h>
#include <cuda_fp16.h>
#include <cuda.h>
#include <stdint.h>

#define S_TOK 2048
#define D_MOD 512

__device__ __align__(1024) __nv_bfloat16 g_Q[2 * S_TOK * D_MOD];
__device__ __align__(1024) __nv_bfloat16 g_O[2 * S_TOK * D_MOD];
__device__ __align__(1024) uint4 g_KV[8 * S_TOK];
__device__ __align__(16) uint32_t g_stats[128];
__device__ __align__(16) float4 g_kvp[16 * 32 * 3 * 32];

#define TS(k, i) do {} while (0)
__device__ __forceinline__ uint32_t smem_u32(const void* p) { return (uint32_t)__cvta_generic_to_shared(p); }
__device__ __forceinline__ void mbar_init(uint32_t bar, int cnt) { asm volatile("mbarrier.init.shared::cta.b64 [%0], %1;" :: "r"(bar), "r"(cnt) : "memory"); }
__device__ __forceinline__ void mbar_expect_tx(uint32_t bar, uint32_t bytes) { asm volatile("mbarrier.arrive.expect_tx.shared::cta.b64 _, [%0], %1;" :: "r"(bar), "r"(bytes) : "memory"); }
__device__ __forceinline__ bool mbar_try(uint32_t bar, uint32_t parity) {
  uint32_t ok;
  asm volatile("{\n.reg .pred p;\nmbarrier.try_wait.parity.shared::cta.b64 p, [%1], %2;\nselp.b32 %0, 1, 0, p;\n}\n" : "=r"(ok) : "r"(bar), "r"(parity) : "memory");
  return ok;
}
__device__ __forceinline__ void mbar_wait(uint32_t bar, uint32_t parity) {
  asm volatile("{\n.reg .pred p;\n.reg .u32 c;\nmov.u32 c, 0;\n"
               "LW_%=:\n"
               "mbarrier.try_wait.parity.shared::cta.b64 p, [%0], %1;\n"
               "@p bra LD_%=;\n"
               "add.u32 c, c, 1;\n"
               "setp.lt.u32 p, c, 4000000;\n"
               "@p bra LW_%=;\n"
               "trap;\n"
               "LD_%=:\n}\n" :: "r"(bar), "r"(parity) : "memory");
}
__device__ __forceinline__ void mbar_arrive_cta(uint32_t bar, uint32_t cta) {
  asm volatile("{\n.reg .b32 ra;\nmapa.shared::cluster.u32 ra, %0, %1;\nmbarrier.arrive.shared::cluster.b64 _, [ra];\n}\n" :: "r"(bar), "r"(cta) : "memory");
}
__device__ __forceinline__ void cluster_sync() {
  asm volatile("barrier.cluster.arrive.relaxed.aligned;\nbarrier.cluster.wait.aligned;" ::: "memory");
}
__device__ __forceinline__ void tma2d(uint32_t dst, const CUtensorMap* m, int c0, int c1, uint32_t bar) {
  asm volatile("cp.async.bulk.tensor.2d.shared::cluster.global.mbarrier::complete_tx::bytes [%0], [%1, {%3, %4}], [%2];"
               :: "r"(dst), "l"(m), "r"(bar), "r"(c0), "r"(c1) : "memory");
}
__device__ __forceinline__ void tma2d_mc(uint32_t dst, const CUtensorMap* m, int c0, int c1, uint32_t bar, uint16_t mask) {
  asm volatile("cp.async.bulk.tensor.2d.shared::cluster.global.mbarrier::complete_tx::bytes.multicast::cluster [%0], [%1, {%3, %4}], [%2], %5;"
               :: "r"(dst), "l"(m), "r"(bar), "r"(c0), "r"(c1), "h"(mask) : "memory");
}
__device__ __forceinline__ void tma2d_store(const CUtensorMap* m, uint32_t src, int c0, int c1) {
  asm volatile("cp.async.bulk.tensor.2d.global.shared::cta.bulk_group [%0, {%2, %3}], [%1];"
               :: "l"(m), "r"(src), "r"(c0), "r"(c1) : "memory");
}
__device__ __forceinline__ void bulk_g2s(uint32_t dst, const void* src, uint32_t bytes, uint32_t bar) {
  asm volatile("cp.async.bulk.shared::cluster.global.mbarrier::complete_tx::bytes [%0], [%1], %2, [%3];"
               :: "r"(dst), "l"(src), "r"(bytes), "r"(bar) : "memory");
}
__device__ __forceinline__ void bulk_commit() { asm volatile("cp.async.bulk.commit_group;" ::: "memory"); }
__device__ __forceinline__ void bulk_wait_all() { asm volatile("cp.async.bulk.wait_group 0;" ::: "memory"); }
__device__ __forceinline__ void fence_async() { asm volatile("fence.proxy.async.shared::cta;" ::: "memory"); }
__device__ __forceinline__ void named_bar(int id, int n) { asm volatile("bar.sync %0, %1;" :: "r"(id), "r"(n) : "memory"); }
__device__ __forceinline__ void pdl_launch() { asm volatile("griddepcontrol.launch_dependents;" ::: "memory"); }
__device__ __forceinline__ void pdl_wait() { asm volatile("griddepcontrol.wait;" ::: "memory"); }
__device__ __forceinline__ void wg_fence() { asm volatile("wgmma.fence.sync.aligned;" ::: "memory"); }
__device__ __forceinline__ void wg_commit() { asm volatile("wgmma.commit_group.sync.aligned;" ::: "memory"); }
template <int n> __device__ __forceinline__ void wg_wait() { asm volatile("wgmma.wait_group.sync.aligned %0;" :: "n"(n) : "memory"); }
template <int n> __device__ __forceinline__ void fence_regs(float* r) {
#pragma unroll
  for (int i = 0; i < n; i++) asm volatile("" : "+f"(r[i]) :: "memory");
}
template <int n> __device__ __forceinline__ void fence_regs(uint32_t* r) {
#pragma unroll
  for (int i = 0; i < n; i++) asm volatile("" : "+r"(r[i]) :: "memory");
}
__device__ __forceinline__ uint64_t make_desc(uint32_t addr, uint32_t lbo, uint32_t sbo, uint32_t swz) {
  return (uint64_t)((addr & 0x3FFFF) >> 4) | ((uint64_t)(lbo >> 4) << 16) | ((uint64_t)(sbo >> 4) << 32) | ((uint64_t)swz << 62);
}
__device__ __forceinline__ float ex2f(float x) { float y; asm("ex2.approx.ftz.f32 %0, %1;" : "=f"(y) : "f"(x)); return y; }
__device__ __forceinline__ uint32_t pack_bf16(float lo, float hi) { uint32_t r; asm("cvt.rn.bf16x2.f32 %0, %1, %2;" : "=r"(r) : "f"(hi), "f"(lo)); return r; }
__device__ __forceinline__ uint32_t pack_f16(float lo, float hi) { uint32_t r; asm("cvt.rn.f16x2.f32 %0, %1, %2;" : "=r"(r) : "f"(hi), "f"(lo)); return r; }
__device__ __forceinline__ float bf_lo(uint32_t v) { return __uint_as_float(v << 16); }
__device__ __forceinline__ float bf_hi(uint32_t v) { return __uint_as_float(v & 0xFFFF0000u); }
__device__ __forceinline__ float rbf(float x) { return __bfloat162float(__float2bfloat16_rn(x)); }
__device__ __forceinline__ void stsm4(uint32_t a, uint32_t r0, uint32_t r1, uint32_t r2, uint32_t r3) {
  asm volatile("stmatrix.sync.aligned.m8n8.x4.shared.b16 [%0], {%1,%2,%3,%4};" :: "r"(a), "r"(r0), "r"(r1), "r"(r2), "r"(r3) : "memory");
}
__device__ __forceinline__ void stsm4t(uint32_t a, uint32_t r0, uint32_t r1, uint32_t r2, uint32_t r3) {
  asm volatile("stmatrix.sync.aligned.m8n8.x4.trans.shared.b16 [%0], {%1,%2,%3,%4};" :: "r"(a), "r"(r0), "r"(r1), "r"(r2), "r"(r3) : "memory");
}
__device__ __forceinline__ void mma_bf16(float* d, uint32_t a0, uint32_t a1, uint32_t a2, uint32_t a3, uint32_t b0, uint32_t b1) {
  asm volatile("mma.sync.aligned.m16n8k16.row.col.f32.bf16.bf16.f32 {%0,%1,%2,%3}, {%4,%5,%6,%7}, {%8,%9}, {%0,%1,%2,%3};"
               : "+f"(d[0]), "+f"(d[1]), "+f"(d[2]), "+f"(d[3]) : "r"(a0), "r"(a1), "r"(a2), "r"(a3), "r"(b0), "r"(b1));
}
template<int SD> __device__ __forceinline__ void wg_qk32(float* d, const uint32_t* a, uint64_t desc) {
  asm volatile("wgmma.mma_async.sync.aligned.m64n32k16.f32.f16.f16 {%0,%1,%2,%3,%4,%5,%6,%7,%8,%9,%10,%11,%12,%13,%14,%15}, {%16,%17,%18,%19}, %20, %21, 1, 1, 0;"
   : "+f"(d[0]),"+f"(d[1]),"+f"(d[2]),"+f"(d[3]),"+f"(d[4]),"+f"(d[5]),"+f"(d[6]),"+f"(d[7]),"+f"(d[8]),"+f"(d[9]),"+f"(d[10]),"+f"(d[11]),"+f"(d[12]),"+f"(d[13]),"+f"(d[14]),"+f"(d[15])
   : "r"(a[0]),"r"(a[1]),"r"(a[2]),"r"(a[3]),"l"(desc),"n"(SD));
}
template<int SD> __device__ __forceinline__ void wg_qk64(float* d, const uint32_t* a, uint64_t desc) {
  asm volatile("wgmma.mma_async.sync.aligned.m64n64k16.f32.f16.f16 {%0,%1,%2,%3,%4,%5,%6,%7,%8,%9,%10,%11,%12,%13,%14,%15,%16,%17,%18,%19,%20,%21,%22,%23,%24,%25,%26,%27,%28,%29,%30,%31}, {%32,%33,%34,%35}, %36, %37, 1, 1, 0;"
   : "+f"(d[0]),"+f"(d[1]),"+f"(d[2]),"+f"(d[3]),"+f"(d[4]),"+f"(d[5]),"+f"(d[6]),"+f"(d[7]),"+f"(d[8]),"+f"(d[9]),"+f"(d[10]),"+f"(d[11]),"+f"(d[12]),"+f"(d[13]),"+f"(d[14]),"+f"(d[15]),"+f"(d[16]),"+f"(d[17]),"+f"(d[18]),"+f"(d[19]),"+f"(d[20]),"+f"(d[21]),"+f"(d[22]),"+f"(d[23]),"+f"(d[24]),"+f"(d[25]),"+f"(d[26]),"+f"(d[27]),"+f"(d[28]),"+f"(d[29]),"+f"(d[30]),"+f"(d[31])
   : "r"(a[0]),"r"(a[1]),"r"(a[2]),"r"(a[3]),"l"(desc),"n"(SD));
}
template<int SD> __device__ __forceinline__ void wg_qs32(float* d, uint64_t da, uint64_t db) {
  asm volatile("wgmma.mma_async.sync.aligned.m64n32k16.f32.f16.f16 {%0,%1,%2,%3,%4,%5,%6,%7,%8,%9,%10,%11,%12,%13,%14,%15}, %16, %17, %18, 1, 1, 0, 0;"
   : "+f"(d[0]),"+f"(d[1]),"+f"(d[2]),"+f"(d[3]),"+f"(d[4]),"+f"(d[5]),"+f"(d[6]),"+f"(d[7]),"+f"(d[8]),"+f"(d[9]),"+f"(d[10]),"+f"(d[11]),"+f"(d[12]),"+f"(d[13]),"+f"(d[14]),"+f"(d[15])
   : "l"(da),"l"(db),"n"(SD));
}
template<int SD> __device__ __forceinline__ void wg_qs64(float* d, uint64_t da, uint64_t db) {
  asm volatile("wgmma.mma_async.sync.aligned.m64n64k16.f32.f16.f16 {%0,%1,%2,%3,%4,%5,%6,%7,%8,%9,%10,%11,%12,%13,%14,%15,%16,%17,%18,%19,%20,%21,%22,%23,%24,%25,%26,%27,%28,%29,%30,%31}, %32, %33, %34, 1, 1, 0, 0;"
   : "+f"(d[0]),"+f"(d[1]),"+f"(d[2]),"+f"(d[3]),"+f"(d[4]),"+f"(d[5]),"+f"(d[6]),"+f"(d[7]),"+f"(d[8]),"+f"(d[9]),"+f"(d[10]),"+f"(d[11]),"+f"(d[12]),"+f"(d[13]),"+f"(d[14]),"+f"(d[15]),"+f"(d[16]),"+f"(d[17]),"+f"(d[18]),"+f"(d[19]),"+f"(d[20]),"+f"(d[21]),"+f"(d[22]),"+f"(d[23]),"+f"(d[24]),"+f"(d[25]),"+f"(d[26]),"+f"(d[27]),"+f"(d[28]),"+f"(d[29]),"+f"(d[30]),"+f"(d[31])
   : "l"(da),"l"(db),"n"(SD));
}
template<int SD> __device__ __forceinline__ void wg_pv24(float* d, const uint32_t* a, uint64_t desc) {
  asm volatile("wgmma.mma_async.sync.aligned.m64n24k16.f32.bf16.bf16 {%0,%1,%2,%3,%4,%5,%6,%7,%8,%9,%10,%11}, {%12,%13,%14,%15}, %16, %17, 1, 1, 1;"
   : "+f"(d[0]),"+f"(d[1]),"+f"(d[2]),"+f"(d[3]),"+f"(d[4]),"+f"(d[5]),"+f"(d[6]),"+f"(d[7]),"+f"(d[8]),"+f"(d[9]),"+f"(d[10]),"+f"(d[11])
   : "r"(a[0]),"r"(a[1]),"r"(a[2]),"r"(a[3]),"l"(desc),"n"(SD));
}
template<int TA, int TB> __device__ __forceinline__ void wg_ss128(float* d, uint64_t da, uint64_t db, int sd) {
  asm volatile("{\n.reg .pred p;\nsetp.ne.b32 p, %66, 0;\n"
   "wgmma.mma_async.sync.aligned.m64n128k16.f32.bf16.bf16 {%0,%1,%2,%3,%4,%5,%6,%7,%8,%9,%10,%11,%12,%13,%14,%15,%16,%17,%18,%19,%20,%21,%22,%23,%24,%25,%26,%27,%28,%29,%30,%31,%32,%33,%34,%35,%36,%37,%38,%39,%40,%41,%42,%43,%44,%45,%46,%47,%48,%49,%50,%51,%52,%53,%54,%55,%56,%57,%58,%59,%60,%61,%62,%63}, %64, %65, p, 1, 1, %67, %68;\n}\n"
   : "+f"(d[0]),"+f"(d[1]),"+f"(d[2]),"+f"(d[3]),"+f"(d[4]),"+f"(d[5]),"+f"(d[6]),"+f"(d[7]),"+f"(d[8]),"+f"(d[9]),"+f"(d[10]),"+f"(d[11]),"+f"(d[12]),"+f"(d[13]),"+f"(d[14]),"+f"(d[15]),"+f"(d[16]),"+f"(d[17]),"+f"(d[18]),"+f"(d[19]),"+f"(d[20]),"+f"(d[21]),"+f"(d[22]),"+f"(d[23]),"+f"(d[24]),"+f"(d[25]),"+f"(d[26]),"+f"(d[27]),"+f"(d[28]),"+f"(d[29]),"+f"(d[30]),"+f"(d[31]),"+f"(d[32]),"+f"(d[33]),"+f"(d[34]),"+f"(d[35]),"+f"(d[36]),"+f"(d[37]),"+f"(d[38]),"+f"(d[39]),"+f"(d[40]),"+f"(d[41]),"+f"(d[42]),"+f"(d[43]),"+f"(d[44]),"+f"(d[45]),"+f"(d[46]),"+f"(d[47]),"+f"(d[48]),"+f"(d[49]),"+f"(d[50]),"+f"(d[51]),"+f"(d[52]),"+f"(d[53]),"+f"(d[54]),"+f"(d[55]),"+f"(d[56]),"+f"(d[57]),"+f"(d[58]),"+f"(d[59]),"+f"(d[60]),"+f"(d[61]),"+f"(d[62]),"+f"(d[63])
   : "l"(da),"l"(db),"r"(sd),"n"(TA),"n"(TB));
}
template<int TA, int TB> __device__ __forceinline__ void wg_ss64(float* d, uint64_t da, uint64_t db, int sd) {
  asm volatile("{\n.reg .pred p;\nsetp.ne.b32 p, %34, 0;\n"
   "wgmma.mma_async.sync.aligned.m64n64k16.f32.bf16.bf16 {%0,%1,%2,%3,%4,%5,%6,%7,%8,%9,%10,%11,%12,%13,%14,%15,%16,%17,%18,%19,%20,%21,%22,%23,%24,%25,%26,%27,%28,%29,%30,%31}, %32, %33, p, 1, 1, %35, %36;\n}\n"
   : "+f"(d[0]),"+f"(d[1]),"+f"(d[2]),"+f"(d[3]),"+f"(d[4]),"+f"(d[5]),"+f"(d[6]),"+f"(d[7]),"+f"(d[8]),"+f"(d[9]),"+f"(d[10]),"+f"(d[11]),"+f"(d[12]),"+f"(d[13]),"+f"(d[14]),"+f"(d[15]),"+f"(d[16]),"+f"(d[17]),"+f"(d[18]),"+f"(d[19]),"+f"(d[20]),"+f"(d[21]),"+f"(d[22]),"+f"(d[23]),"+f"(d[24]),"+f"(d[25]),"+f"(d[26]),"+f"(d[27]),"+f"(d[28]),"+f"(d[29]),"+f"(d[30]),"+f"(d[31])
   : "l"(da),"l"(db),"r"(sd),"n"(TA),"n"(TB));
}

template<int TA, int TB> __device__ __forceinline__ void wg_ss8(float* d, uint64_t da, uint64_t db, int sd) {
  asm volatile("{\n.reg .pred p;\nsetp.ne.b32 p, %6, 0;\n"
   "wgmma.mma_async.sync.aligned.m64n8k16.f32.bf16.bf16 {%0,%1,%2,%3}, %4, %5, p, 1, 1, %7, %8;\n}\n"
   : "+f"(d[0]),"+f"(d[1]),"+f"(d[2]),"+f"(d[3])
   : "l"(da),"l"(db),"r"(sd),"n"(TA),"n"(TB));
}

template<int SD, uint32_t HI> __device__ __forceinline__ void wq32(float* d, uint64_t da, uint32_t lo) {
  asm volatile("{\n.reg .b64 db;\nmov.b64 db, {%17, %19};\n"
   "wgmma.mma_async.sync.aligned.m64n32k16.f32.f16.f16 {%0,%1,%2,%3,%4,%5,%6,%7,%8,%9,%10,%11,%12,%13,%14,%15}, %16, db, %18, 1, 1, 0, 0;\n}\n"
   : "+f"(d[0]),"+f"(d[1]),"+f"(d[2]),"+f"(d[3]),"+f"(d[4]),"+f"(d[5]),"+f"(d[6]),"+f"(d[7]),"+f"(d[8]),"+f"(d[9]),"+f"(d[10]),"+f"(d[11]),"+f"(d[12]),"+f"(d[13]),"+f"(d[14]),"+f"(d[15])
   : "l"(da),"r"(lo),"n"(SD),"r"(HI));
}
template<int SD, uint32_t HI> __device__ __forceinline__ void wq64(float* d, uint64_t da, uint32_t lo) {
  asm volatile("{\n.reg .b64 db;\nmov.b64 db, {%33, %35};\n"
   "wgmma.mma_async.sync.aligned.m64n64k16.f32.f16.f16 {%0,%1,%2,%3,%4,%5,%6,%7,%8,%9,%10,%11,%12,%13,%14,%15,%16,%17,%18,%19,%20,%21,%22,%23,%24,%25,%26,%27,%28,%29,%30,%31}, %32, db, %34, 1, 1, 0, 0;\n}\n"
   : "+f"(d[0]),"+f"(d[1]),"+f"(d[2]),"+f"(d[3]),"+f"(d[4]),"+f"(d[5]),"+f"(d[6]),"+f"(d[7]),"+f"(d[8]),"+f"(d[9]),"+f"(d[10]),"+f"(d[11]),"+f"(d[12]),"+f"(d[13]),"+f"(d[14]),"+f"(d[15]),"+f"(d[16]),"+f"(d[17]),"+f"(d[18]),"+f"(d[19]),"+f"(d[20]),"+f"(d[21]),"+f"(d[22]),"+f"(d[23]),"+f"(d[24]),"+f"(d[25]),"+f"(d[26]),"+f"(d[27]),"+f"(d[28]),"+f"(d[29]),"+f"(d[30]),"+f"(d[31])
   : "l"(da),"r"(lo),"n"(SD),"r"(HI));
}
template<int SD, uint32_t HI> __device__ __forceinline__ void wpv(float* d, const uint32_t* a, uint32_t lo) {
  asm volatile("{\n.reg .b64 db;\nmov.b64 db, {%16, %18};\n"
   "wgmma.mma_async.sync.aligned.m64n24k16.f32.bf16.bf16 {%0,%1,%2,%3,%4,%5,%6,%7,%8,%9,%10,%11}, {%12,%13,%14,%15}, db, %17, 1, 1, 1;\n}\n"
   : "+f"(d[0]),"+f"(d[1]),"+f"(d[2]),"+f"(d[3]),"+f"(d[4]),"+f"(d[5]),"+f"(d[6]),"+f"(d[7]),"+f"(d[8]),"+f"(d[9]),"+f"(d[10]),"+f"(d[11])
   : "r"(a[0]),"r"(a[1]),"r"(a[2]),"r"(a[3]),"r"(lo),"n"(SD),"r"(HI));
}

__device__ __forceinline__ uint32_t phi2(float a, float b) {
  uint32_t r, e;
  asm("cvt.rn.relu.bf16x2.f32 %0, %1, %2;" : "=r"(r) : "f"(b), "f"(a));
  e = pack_bf16(ex2f(a * 1.4426950408889634f), ex2f(b * 1.4426950408889634f));
  asm("add.rn.bf16x2 %0, %0, %1;" : "+r"(e) : "r"(0x35863586u));
  asm("min.NaN.bf16x2 %0, %0, %1;" : "+r"(e) : "r"(0x3F803F80u));
  asm("add.rn.bf16x2 %0, %0, %1;" : "+r"(e) : "r"(r));
  return e;
}

__device__ __forceinline__ void mbar_arrive(uint32_t bar) { asm volatile("mbarrier.arrive.shared::cta.b64 _, [%0];" :: "r"(bar) : "memory"); }
__device__ __forceinline__ void named_arrive(int id, int n) { asm volatile("bar.arrive %0, %1;" :: "r"(id), "r"(n) : "memory"); }
__device__ __forceinline__ void fence_async_all() { asm volatile("fence.proxy.async;" ::: "memory"); }
__device__ __forceinline__ void flag_add(uint32_t* f) { asm volatile("fence.acq_rel.gpu;\nred.relaxed.gpu.global.add.u32 [%0], 1;" :: "l"(f) : "memory"); }
__device__ __forceinline__ void flag_wait(const uint32_t* f, uint32_t target) {
  uint32_t v;
#pragma unroll 1
  for (int it = 0;; it++) {
    asm volatile("ld.acquire.gpu.global.u32 %0, [%1];" : "=r"(v) : "l"(f) : "memory");
    if ((int32_t)(v - target) >= 0) break;
    if (it > 2000000) __trap();
  }
}
__device__ __forceinline__ bool elect_one() {
  uint32_t p;
  asm volatile("{\n.reg .pred P;\nelect.sync _|P, 0xFFFFFFFF;\nselp.b32 %0, 1, 0, P;\n}\n" : "=r"(p));
  return p;
}
__device__ __forceinline__ void lds4(uint32_t a, uint32_t* r) {
  asm volatile("ld.shared.v4.b32 {%0,%1,%2,%3}, [%4];" : "=r"(r[0]), "=r"(r[1]), "=r"(r[2]), "=r"(r[3]) : "r"(a) : "memory");
}
__device__ __forceinline__ uint32_t lds1(uint32_t a) { uint32_t r; asm volatile("ld.shared.b32 %0, [%1];" : "=r"(r) : "r"(a) : "memory"); return r; }
__device__ __forceinline__ void sts1(uint32_t a, uint32_t v) { asm volatile("st.shared.b32 [%0], %1;" :: "r"(a), "r"(v) : "memory"); }
__device__ __forceinline__ void sts4(uint32_t a, uint32_t r0, uint32_t r1, uint32_t r2, uint32_t r3) {
  asm volatile("st.shared.v4.b32 [%0], {%1,%2,%3,%4};" :: "r"(a), "r"(r0), "r"(r1), "r"(r2), "r"(r3) : "memory");
}
__device__ __forceinline__ void ldsm4(uint32_t a, uint32_t* r) {
  asm volatile("ldmatrix.sync.aligned.m8n8.x4.shared.b16 {%0,%1,%2,%3}, [%4];" : "=r"(r[0]), "=r"(r[1]), "=r"(r[2]), "=r"(r[3]) : "r"(a) : "memory");
}
__device__ __forceinline__ float rcpf(float x) { float y; asm("rcp.approx.ftz.f32 %0, %1;" : "=f"(y) : "f"(x)); return y; }
__device__ __forceinline__ uint32_t hfma2(uint32_t a, uint32_t b, uint32_t c) { uint32_t r; asm("fma.rn.f16x2 %0, %1, %2, %3;" : "=r"(r) : "r"(a), "r"(b), "r"(c)); return r; }
__device__ __forceinline__ uint32_t hadd2(uint32_t a, uint32_t b) { uint32_t r; asm("add.rn.f16x2 %0, %1, %2;" : "=r"(r) : "r"(a), "r"(b)); return r; }

#define STEPK 96
#define QSCALE 0.36067376022224085f
#define SMAGIC (512.0f + 2.0f * (191.0f - 30.0f - 1.5823545f))
#define VSHIFT 1073741824.0f

__device__ uint32_t g_epoch[132];
__device__ uint32_t g_flag[288 * 8];
#define FLAG_KV (g_flag)
#define FLAG_B(h) (g_flag + (4 + (h)) * 8)
#define FLAG_OA(cta, pass) (g_flag + (16 + (cta) * 2 + (pass)) * 8)
#define FLAG_LM(i) (g_flag + (272 + (i)) * 8)

#define SM_TOTAL (224 * 1024 + 2048 + 1024)
#define OFF_K 0
#define OFF_F 65536
#define OFF_V 131072
#define OFF_MISC (224 * 1024)

#define BAR_FULL(s) (bars + 8 * (s))
#define BAR_EMPTY(s) (bars + 24 + 8 * (s))
#define BAR_KV(c) (bars + 48 + 8 * (c))
#define BAR_XA (bars + 72)
#define BAR_BDONE (bars + 80)
#define BAR_Q (bars + 88)
#define BAR_GO (bars + 96)
#define BAR_Q2 (bars + 104)
#define BAR_OD(p) (bars + 112 + 8 * (p))
#define BAR_CL(c) (bars + 128 + 8 * (c))
#define BAR_TE(i) (bars + 168 + 8 * (i))
#define BAR_TF(g) (bars + 224 + 8 * (g))

__device__ __forceinline__ uint32_t exp2_pair_fix(float d0, float d1, uint32_t c63, uint32_t m1) {
  uint32_t w, y, s, r;
  asm("prmt.b32 %0, %1, %2, 0x6521;" : "=r"(w) : "r"(__float_as_uint(d0)), "r"(__float_as_uint(d1)));
  asm("lop3.b32 %0, %1, 0x007F007F, %2, 0xEA;" : "=r"(y) : "r"(w), "r"(c63));
  asm("mad.lo.u32 %0, %1, %2, %3;" : "=r"(s) : "r"(y), "r"(m1), "r"(w));
  asm("fma.rn.bf16x2 %0, %1, %2, %3;" : "=r"(r) : "r"(w), "r"(y), "r"(s));
  return r;
}

__device__ __forceinline__ void attn_slow(const uint4* gq, __nv_bfloat16* dst) {
  const int t = threadIdx.x & 127;
  const int row = t >> 1, half = t & 1;
  float q[16];
#pragma unroll
  for (int i = 0; i < 4; i++) {
    const uint4 v = gq[(row >> 4) * 32 + (row & 7) * 4 + i];
    const uint32_t lo = (row & 8) ? v.y : v.x, hi = (row & 8) ? v.w : v.z;
    q[2 * i] = bf_lo(lo); q[2 * i + 1] = bf_hi(lo); q[2 * i + 8] = bf_lo(hi); q[2 * i + 9] = bf_hi(hi);
  }
  float m = -INFINITY, l = 0.f, o[16];
#pragma unroll
  for (int i = 0; i < 16; i++) o[i] = 0.f;
#pragma unroll 1
  for (int j = half * 1024; j < half * 1024 + 1024; j++) {
    uint4 ka = g_KV[4 * S_TOK + j], kb = g_KV[5 * S_TOK + j];
    uint4 va = g_KV[6 * S_TOK + j], vb = g_KV[7 * S_TOK + j];
    uint32_t kk[8] = {ka.x, ka.y, ka.z, ka.w, kb.x, kb.y, kb.z, kb.w};
    uint32_t vv[8] = {va.x, va.y, va.z, va.w, vb.x, vb.y, vb.z, vb.w};
    float s = 0.f;
#pragma unroll
    for (int i = 0; i < 8; i++) { s = fmaf(q[2 * i], bf_lo(kk[i]), s); s = fmaf(q[2 * i + 1], bf_hi(kk[i]), s); }
    s = rbf(s) * 0.25f;
    if (s > m) {
      float c = __expf(m - s);
      l *= c;
#pragma unroll
      for (int i = 0; i < 16; i++) o[i] *= c;
      m = s;
    }
    float p = __expf(s - m);
    l += p;
#pragma unroll
    for (int i = 0; i < 8; i++) { o[2 * i] = fmaf(p, bf_lo(vv[i]), o[2 * i]); o[2 * i + 1] = fmaf(p, bf_hi(vv[i]), o[2 * i + 1]); }
  }
  float m2 = __shfl_xor_sync(~0u, m, 1);
  float mm = fmaxf(m, m2);
  float c = __expf(m - mm);
  l *= c; l += __shfl_xor_sync(~0u, l, 1);
  float inv = 1.f / l;
  uint32_t r[8];
#pragma unroll
  for (int i = 0; i < 16; i++) { o[i] *= c; o[i] += __shfl_xor_sync(~0u, o[i], 1); o[i] *= inv; }
#pragma unroll
  for (int i = 0; i < 8; i++) r[i] = pack_bf16(o[2 * i], o[2 * i + 1]);
  uint4* d = (uint4*)(dst + (size_t)row * D_MOD);
  if (half == 0) d[0] = make_uint4(r[0], r[1], r[2], r[3]); else d[1] = make_uint4(r[4], r[5], r[6], r[7]);
}

struct Params { const __nv_bfloat16* wk; const __nv_bfloat16* wv; };

__device__ __forceinline__ void helper_cta(const int h, const uint32_t sb, const uint32_t bars, const int wg, const int w4,
                                           const CUtensorMap* mQ, const CUtensorMap* mOs) {
  const int lane = threadIdx.x & 31;
  mbar_wait(BAR_GO, 0);
  const int cb = wg & 1, col = h * 128 + cb * 64, row0 = S_TOK + (wg >> 1) * 1024;
  const uint32_t buf = sb + wg * 49152;
  if (w4 == 0 && elect_one()) {
    fence_async_all();
#pragma unroll 1
    for (int u = 0; u < 3; u++) {
      mbar_expect_tx(BAR_TF(wg * 3 + u), 16384);
      tma2d(buf + u * 16384, mQ, col, row0 + u * 128, BAR_TF(wg * 3 + u));
    }
  }
  const int head = h * 8 + cb * 4 + w4;
  float4 a0 = make_float4(0, 0, 0, 0), a1 = a0, a2 = a0;
#pragma unroll 8
  for (int tt = 0; tt < 16; tt++) {
    const float4* src = g_kvp + ((tt * 32 + head) * 3) * 32 + lane;
    float4 u = src[0], v = src[32], w = src[64];
    a0.x += u.x; a0.y += u.y; a0.z += u.z; a0.w += u.w;
    a1.x += v.x; a1.y += v.y; a1.z += v.z; a1.w += v.w;
    a2.x += w.x; a2.y += w.y; a2.z += w.z; a2.w += w.w;
  }
  const uint32_t b00 = pack_bf16(a0.x, a0.y), b01 = pack_bf16(a0.z, a0.w);
  const uint32_t b10 = pack_bf16(a1.x, a1.y), b11 = pack_bf16(a1.z, a1.w);
  const uint32_t bz0 = pack_bf16(a2.x, a2.y), bz1 = pack_bf16(a2.z, a2.w);
  const int m = lane >> 3, r = lane & 7;
  const uint32_t off = ((m & 1) * 8 + r) * 128 + (((w4 * 2 + (m >> 1)) ^ r) << 4);
  int s = 0, ph = 0;
#pragma unroll 1
  for (int u = 0; u < 8; u++) {
    const uint32_t bb = buf + s * 16384;
    mbar_wait(BAR_TF(wg * 3 + s), ph);
#pragma unroll
    for (int mt = 0; mt < 8; mt++) {
      uint32_t a[4];
      ldsm4(bb + mt * 2048 + off, a);
      float n0[4] = {0, 0, 0, 0}, n1[4] = {0, 0, 0, 0}, dn[4] = {0, 0, 0, 0};
      mma_bf16(dn, a[0], a[1], a[2], a[3], bz0, bz1);
      mma_bf16(n0, a[0], a[1], a[2], a[3], b00, b01);
      mma_bf16(n1, a[0], a[1], a[2], a[3], b10, b11);
      const float i0 = rcpf(dn[0] + 1e-6f), i1 = rcpf(dn[2] + 1e-6f);
      stsm4(bb + mt * 2048 + off, pack_bf16(n0[0] * i0, n0[1] * i0), pack_bf16(n0[2] * i1, n0[3] * i1),
            pack_bf16(n1[0] * i0, n1[1] * i0), pack_bf16(n1[2] * i1, n1[3] * i1));
    }
    fence_async();
    named_bar(wg + 1, 128);
    if (w4 == 0 && lane == 0) {
      tma2d_store(mOs, bb, col, row0 + u * 128);
      bulk_commit();
      if (u >= 1 && u + 2 < 8) {
        asm volatile("cp.async.bulk.wait_group.read 1;" ::: "memory");
        const int sp = s == 0 ? 2 : s - 1;
        mbar_expect_tx(BAR_TF(wg * 3 + sp), 16384);
        tma2d(buf + sp * 16384, mQ, col, row0 + (u + 2) * 128, BAR_TF(wg * 3 + sp));
      }
    }
    __syncwarp();
    if (++s == 3) { s = 0; ph ^= 1; }
  }
  if (w4 == 0 && lane == 0) {
    bulk_wait_all();
    fence_async_all();
    flag_add(FLAG_LM((h * 2 + cb) * 2 + (wg >> 1)));
    if (wg == 0) TS(1, 8);
  }
}

#define STAGE(s) (sb + (2 - (s)) * 65536)
template <int TR> __device__ __forceinline__ void proj_kb(float* acc, uint32_t st, uint32_t offA, uint32_t offB, int first) {
  const uint64_t da = make_desc(st + offA, TR ? 8192 : 16, 1024, 1);
  const uint64_t db = make_desc(st + offB, TR ? 16 : 8192, 1024, 1);
  wg_fence();
#pragma unroll
  for (int k = 0; k < 4; k++) wg_ss128<TR, 1 - TR>(acc, da + k * (TR ? 128 : 2), db + k * (TR ? 2 : 128), k != 0 || !first);
  wg_commit();
}
template <int TR> __device__ __forceinline__ void proj_loop(float* acc, uint32_t sb, uint32_t bars, uint32_t offA, uint32_t offB,
                                                            int wg, uint32_t sWKV) {
  mbar_wait(BAR_FULL(0), 0);
  if (threadIdx.x == 0) TS(0, 2);
  proj_kb<TR>(acc, STAGE(0), offA, offB, 1);
  {
    float kv[4];
    mbar_wait(BAR_XA, 0);
    const uint64_t da = make_desc(STAGE(2) + wg * 16384, 16, 1024, 1), db = make_desc(sWKV + wg * 2048, 128, 128, 0);
    wg_fence();
#pragma unroll
    for (int k = 0; k < 8; k++) wg_ss8<0, 1>(kv, da + (k >> 2) * 512 + (k & 3) * 2, db + k * 16, k != 0);
    wg_commit();
    mbar_wait(BAR_FULL(1), 0);
    if (threadIdx.x == 0) TS(0, 3);
    proj_kb<TR>(acc, STAGE(1), offA, offB, 0);
    wg_wait<1>();
    fence_regs<4>(kv);
    named_bar(wg + 1, 128);
    sts4(sWKV + threadIdx.x * 16, __float_as_uint(kv[0]), __float_as_uint(kv[1]), __float_as_uint(kv[2]), __float_as_uint(kv[3]));
    __syncwarp();
    if ((threadIdx.x & 31) == 0) mbar_arrive(BAR_GO);
    if ((threadIdx.x & 127) == 0) mbar_arrive(BAR_EMPTY(0));
    __syncwarp();
  }
  int s = 2, ph = 0, sp = 1;
#pragma unroll 1
  for (int kb = 2; kb < 8; kb++) {
    mbar_wait(BAR_FULL(s), ph);
    if (threadIdx.x == 0) TS(0, 2 + kb);
    proj_kb<TR>(acc, STAGE(s), offA, offB, 0);
    wg_wait<1>();
    if ((threadIdx.x & 127) == 0) mbar_arrive(BAR_EMPTY(sp));
    __syncwarp();
    sp = s;
    if (++s == 3) { s = 0; ph ^= 1; }
  }
  wg_wait<0>();
  fence_regs<64>(acc);
}

__device__ __forceinline__ uint32_t tail_slots(int t) {
  const uint32_t lo = t < 4 ? (t < 2 ? (t == 0 ? 0x0C0B0Au : 0x0F0E0Du) : (t == 2 ? 0x100400u : 0x081814u))
                            : (t < 6 ? (t == 4 ? 0x110501u : 0x021915u) : (t == 6 ? 0x161206u : (t == 7 ? 0x07031Au : 0x1B1713u)));
  return lo;
}

__global__ void __launch_bounds__(640, 1)
k1_main(const __grid_constant__ CUtensorMap mXA64, const __grid_constant__ CUtensorMap mXB,
        const __grid_constant__ CUtensorMap mWq, const __grid_constant__ CUtensorMap mWqkv,
        const __grid_constant__ CUtensorMap mQst, const __grid_constant__ CUtensorMap mOst,
        const __grid_constant__ CUtensorMap mO, const __grid_constant__ CUtensorMap mWoA,
        const __grid_constant__ CUtensorMap mWoB, const __grid_constant__ CUtensorMap mOut, const Params prm) {
  extern __shared__ uint8_t smem_raw[];
  const uint32_t sb = (smem_u32(smem_raw) + 1023u) & ~1023u;
  const uint32_t bars = sb + OFF_MISC, sM = bars + 512, sT = bars + 1024;
  const int tid = threadIdx.x, warp = __shfl_sync(~0u, tid >> 5, 0), wg = warp >> 2, w4 = warp & 3, lane = tid & 31;
  const bool helper = blockIdx.x >= 128;
  if (tid == 0) TS(0, 0);
  const int G = blockIdx.x >> 4, gi = blockIdx.x & 15;
  const int tbA = G * 4 + (gi >> 2), hg = gi & 3;
  const int ttB = (G >> 1) * 4 + (gi >> 2), hq = (G & 1) * 4 + (gi & 3);
  const int ttO = G * 2 + (gi >> 3), ct = gi & 7;
  auto issue = [&](int kb, int s) {
    const uint32_t fb = BAR_FULL(s), st = STAGE(s);
    mbar_expect_tx(fb, 65536);
    tma2d(st + 16384, &mXA64, kb * 64, tbA * 64, fb);
    tma2d(st, &mWq, hg * 128, kb * 64, fb);
    tma2d(st + 8192, &mWq, hg * 128 + 64, kb * 64, fb);
    tma2d(st + 49152, &mXB, kb * 64, ttB * 128, fb);
    tma2d(st + 24576, &mWqkv, hq * 64, kb * 64, fb);
    tma2d(st + 32768, &mWqkv, 512 + hq * 64, kb * 64, fb);
    tma2d(st + 40960, &mWqkv, 1024 + hq * 64, kb * 64, fb);
  };
  const uint32_t sOne = sb + OFF_V + 65536, sWKV = sOne + 24576;
  if (warp >= 16) {
    if (warp == 17) {
      if (lane == 0) {
        mbar_init(BAR_BDONE, 8); mbar_init(BAR_Q, 8); mbar_init(BAR_GO, helper ? 1 : 16); mbar_init(BAR_Q2, 5);
        mbar_init(BAR_OD(0), 16); mbar_init(BAR_OD(1), 16); mbar_init(BAR_CL(0), 1); mbar_init(BAR_FULL(2), 1);
        sts1(sM + 20, 0);
      }
      if (lane >= 1 && lane < 5) mbar_init(BAR_CL(lane), 4);
      if (lane >= 5 && lane < 8) { mbar_init(BAR_EMPTY(lane - 5), 4); mbar_init(BAR_KV(lane - 5), 1); }
      if (lane >= 8 && lane < 15) mbar_init(BAR_TE(lane - 8), 2);
      if (lane >= 16) mbar_init(BAR_TF(lane - 16), 1);
      asm volatile("fence.mbarrier_init.release.cluster;" ::: "memory");
    } else if (!helper && elect_one()) {
      if (warp == 18) {
        mbar_init(BAR_XA, 1);
        asm volatile("fence.mbarrier_init.release.cluster;" ::: "memory");
        mbar_expect_tx(BAR_XA, 65536);
#pragma unroll 1
        for (int kb = 0; kb < 8; kb++) tma2d(STAGE(2) + kb * 8192, &mXA64, kb * 64, tbA * 64, BAR_XA);
      } else {
        const int kb = warp == 19;
        mbar_init(BAR_FULL(kb), 1);
        asm volatile("fence.mbarrier_init.release.cluster;" ::: "memory");
        issue(kb, kb);
      }
    }
  } else if (!helper) {
    const uint4 v = __ldg((const uint4*)(hg >= 2 ? prm.wv : prm.wk) + tid * 2 + (hg & 1));
#pragma unroll
    for (int i = 0; i < 3; i++) {
      const int key = tid + i * 512;
      sts4(sOne + key * 16, (key % STEPK) < 32 ? 0x00003F80u : 0x00004E80u, 0u, 0u, 0u);
    }
    sts4(sWKV + tid * 16, v.x, v.y, v.z, v.w);
    fence_async();
  }
  __syncthreads();
  if (wg == 4) {
    asm volatile("setmaxnreg.dec.sync.aligned.u32 32;");
    const uint32_t ep = g_epoch[blockIdx.x] + 1;
    if (helper) {
      if (w4 == 0 && elect_one()) {
        flag_wait(FLAG_B(blockIdx.x - 128), ep * 32);
        fence_async_all();
        TS(1, 10);
        mbar_arrive(BAR_GO);
        g_epoch[blockIdx.x] = ep;
      }
      return;
    }
    mbar_wait(BAR_GO, 0);
    if (w4 == 0 && elect_one()) issue(2, 2);
    {
      uint32_t a[4], b[4];
      float c[4];
      lds4(sWKV + (tid - 512) * 16, a);
      lds4(sWKV + 2048 + (tid - 512) * 16, b);
#pragma unroll
      for (int i = 0; i < 4; i++) c[i] = __uint_as_float(a[i]) + __uint_as_float(b[i]);
      lds4(sWKV + 4096 + (tid - 512) * 16, a);
      lds4(sWKV + 6144 + (tid - 512) * 16, b);
#pragma unroll
      for (int i = 0; i < 4; i++) c[i] += __uint_as_float(a[i]) + __uint_as_float(b[i]);
      sts1(sT + w4 * 256 + lane * 4, pack_bf16(c[0], c[1]));
      sts1(sT + w4 * 256 + 128 + lane * 4, pack_bf16(c[2], c[3]));
    }
    named_bar(9, 128);
    {
      const int t = tid - 512;
#pragma unroll
      for (int i = 0; i < 4; i++) {
        const int key = 1536 + t + i * 128;
        sts4(sOne + key * 16, (key % STEPK) < 32 ? 0x00003F80u : 0x00004E80u, 0u, 0u, 0u);
      }
      fence_async();
      __syncwarp();
      if (lane == 0) mbar_arrive(BAR_Q);
    }
    if (w4 == 0) {
      const bool el = elect_one();
      if (el) {
        int s = 0, ph = 0;
#pragma unroll 1
        for (int kb = 3; kb < 8; kb++) {
          mbar_wait(BAR_EMPTY(s), ph);
          issue(kb, s);
          if (++s == 3) { s = 0; ph ^= 1; }
        }
        flag_wait(FLAG_KV, ep * 128);
        fence_async_all();
        TS(0, 11);
        mbar_wait(BAR_EMPTY(2), 1);
        mbar_wait(BAR_EMPTY(0), 0);
#pragma unroll 1
        for (int c = 0; c < 3; c++) {
          const int k0 = c == 0 ? 0 : (c == 1 ? 7 * STEPK : 12 * STEPK), k1 = c == 0 ? 7 * STEPK : (c == 1 ? 12 * STEPK : S_TOK);
          const uint32_t bytes = (k1 - k0) * 16;
          mbar_expect_tx(BAR_KV(c), 4 * bytes);
#pragma unroll 1
          for (int p = 0; p < 4; p++)
            bulk_g2s(sb + (p < 2 ? OFF_K : OFF_V - 65536) + p * 32768 + k0 * 16, g_KV + p * S_TOK + k0, bytes, BAR_KV(c));
        }
      }
#pragma unroll 1
      for (int n = 0; n < 16; n++) {
        if (n == 0 || n == 12) {
          if (n == 0) mbar_wait(BAR_CL(1), 0);
          if (lane < (n == 0 ? 16 : 8))
            flag_wait(lane < 8 ? FLAG_OA(ttO * 8 + lane, n != 0) : FLAG_LM((lane - 8) * 2 + (ttO >> 3)), ep);
          __syncwarp();
          if (el) fence_async_all();
          if (el) TS(2, n == 0 ? 13 : 14);
        }
        if (el) {
          const int gidx = n < 7 ? n : (n < 11 ? n + 2 : (n < 13 ? n - 4 : n));
          const int tr = gidx < 9 ? gidx : gidx - 9;
          if (gidx < 9) mbar_wait(BAR_CL(gidx < 4 ? gidx >> 1 : (gidx == 4 ? 2 : (gidx < 7 ? 3 : 4))), 0);
          else mbar_wait(BAR_TE(tr), 0);
          const uint32_t sl = tail_slots(tr);
          const bool isB = gidx < 8;
          const int kb = isB ? gidx : (gidx == 8 ? 1 : (gidx < 13 ? (gidx - 9) * 2 : (gidx - 13) * 2 + 3));
          const uint32_t fb = BAR_TF(gidx);
          const int row = (isB ? S_TOK : 0) + ttO * 128;
          mbar_expect_tx(fb, 24576);
          tma2d(sb + (sl & 255) * 8192, isB ? &mWoB : &mWoA, ct * 64, kb * 64, fb);
          tma2d(sb + ((sl >> 8) & 255) * 8192, &mO, kb * 64, row, fb);
          tma2d(sb + (sl >> 16) * 8192, &mO, kb * 64, row + 64, fb);
        }
        __syncwarp();
      }
      if (el) g_epoch[blockIdx.x] = ep;
    } else if (w4 == 3) {
      flag_wait(FLAG_KV, ep * 128);
      const uint4 a = *(const uint4*)(g_stats + lane * 4);
      const float kmax2 = __uint_as_float(__reduce_max_sync(~0u, a.x)) + __uint_as_float(__reduce_max_sync(~0u, a.y));
      const float vmax = __uint_as_float(__reduce_max_sync(~0u, max(a.z, a.w)));
      const float lv = vmax > 0.f ? __log2f(vmax) : 0.f;
      const float lim = fminf(90.f, fminf(91.f + lv, 95.f - lv));
      float thr = -1.f;
      if (vmax < 1e27f && kmax2 <= 65536.f && lim > 2.f) thr = fminf(60000.f, (lim * lim - 1.f) / (kmax2 * 1.02f + 1e-30f));
      if (lane == 0) { sts1(sM + 16, __float_as_uint(thr)); mbar_arrive(BAR_Q2); }
    } else {
      const int ch = tbA * 2 + (w4 - 1);
      uint32_t v[4], o[4];
      lds4(sT + (w4 - 1) * 512 + lane * 16, v);
      int kap;
      if (lane < 21) kap = lane * STEPK + 32 + ch;
      else { int idx = ch * 11 + (lane - 21); kap = (idx >> 5) * STEPK + (idx & 31); }
      g_KV[(4 + hg) * S_TOK + kap] = make_uint4(v[0], v[1], v[2], v[3]);
      float st = 0.f;
      if (hg < 2) {
        const float sc = lane < 21 ? 2.f : 1.f;
#pragma unroll
        for (int u = 0; u < 4; u++) {
          uint32_t pv = __shfl_up_sync(~0u, v[u], 1);
          if (lane == 0 || lane >= 21) pv = 0;
          const float x = bf_lo(v[u]), y = bf_hi(v[u]);
          st += x * x + y * y;
          o[u] = pack_f16((x - bf_lo(pv)) * sc, (y - bf_hi(pv)) * sc);
        }
      } else {
        const float sc = lane < 21 ? VSHIFT : 1.f;
#pragma unroll
        for (int u = 0; u < 4; u++) { float x = bf_lo(v[u]), y = bf_hi(v[u]); st += fabsf(x) + fabsf(y); o[u] = pack_bf16(x * sc, y * sc); }
      }
      g_KV[hg * S_TOK + kap] = make_uint4(o[0], o[1], o[2], o[3]);
      const uint32_t um = __reduce_max_sync(~0u, __float_as_uint(st) & 0x7FFFFFFFu);
      if (w4 == 2) { if (lane == 0) sts1(sM + 24, um); named_arrive(10, 64); }
      else {
        named_bar(10, 64);
        if (elect_one()) {
          g_stats[tbA * 4 + hg] = max(um, lds1(sM + 24));
          fence_async_all();
          flag_add(FLAG_KV);
          TS(1, 9);
          mbar_wait(BAR_BDONE, 0);
          tma2d_store(&mQst, sb + OFF_F + 49152, hq * 64, S_TOK + ttB * 128);
          bulk_commit();
          bulk_wait_all();
          fence_async_all();
          flag_add(FLAG_B(hq >> 1));
          TS(0, 12);
          mbar_wait(BAR_Q, 0);
          mbar_arrive(BAR_CL(0));
#pragma unroll 1
          for (int p = 0; p < 2; p++) {
            mbar_wait(BAR_OD(p), 0);
            fence_async_all();
            flag_add(FLAG_OA(blockIdx.x, p));
          }
          TS(2, 0);
        }
      }
    }
    return;
  }
  if (helper) { helper_cta(blockIdx.x - 128, sb, bars, wg, w4, &mQst, &mOst); return; }

  {
    float acc[64];
    if (wg == 0) proj_loop<0>(acc, sb, bars, 16384, 0, wg, sWKV);
    else proj_loop<1>(acc, sb, bars, 16384 + wg * 8192, 49152, wg, sWKV);
    asm volatile("setmaxnreg.inc.sync.aligned.u32 112;");
    if (tid == 0) TS(0, 10);
    const uint32_t sF = sb + OFF_F;
    if (wg == 0) {
      uint32_t r[32];
      const uint32_t qa = sF + w4 * 512 + ((lane >> 3) & 1) * 256 + (lane >> 4) * 128 + (lane & 7) * 16;
#pragma unroll
      for (int hd = 0; hd < 8; hd++) {
#pragma unroll
        for (int i = 0; i < 4; i++) r[4 * hd + i] = pack_f16(acc[8 * hd + 2 * i] * QSCALE, acc[8 * hd + 2 * i + 1] * QSCALE);
        stsm4(qa + hd * 2048, r[4 * hd], r[4 * hd + 1], r[4 * hd + 2], r[4 * hd + 3]);
        if (hd == 3) {
          fence_async();
          __syncwarp();
          if (lane == 0) mbar_arrive(BAR_Q);
        }
      }
      fence_async();
      uint32_t nmax = 0;
#pragma unroll
      for (int hd = 0; hd < 8; hd++) {
        const uint32_t* q = r + 4 * hd;
        const uint32_t t0 = hfma2(q[2], q[2], hfma2(q[0], q[0], 0u)), t1 = hfma2(q[3], q[3], hfma2(q[1], q[1], 0u));
        uint32_t n = hadd2(__byte_perm(t0, t1, 0x5410), __byte_perm(t0, t1, 0x7632));
        n = hadd2(n, __shfl_xor_sync(~0u, n, 1));
        n = hadd2(n, __shfl_xor_sync(~0u, n, 2));
        nmax = __vmaxu2(nmax, n & 0x7FFF7FFFu);
      }
      nmax = __reduce_max_sync(~0u, max(nmax & 0xFFFFu, nmax >> 16));
      if (lane == 0) sts1(sM + w4 * 4, nmax);
      uint4* gq = (uint4*)g_Q + blockIdx.x * 1024 + tid;
#pragma unroll
      for (int hd = 0; hd < 8; hd++)
        gq[hd * 128] = make_uint4(pack_bf16(acc[8 * hd], acc[8 * hd + 1]), pack_bf16(acc[8 * hd + 2], acc[8 * hd + 3]),
                                  pack_bf16(acc[8 * hd + 4], acc[8 * hd + 5]), pack_bf16(acc[8 * hd + 6], acc[8 * hd + 7]));
      __syncwarp();
      if (lane == 0) mbar_arrive(BAR_Q2);
    } else if (wg == 3) {
      named_arrive(8, 384);
      named_bar(6, 384);
      const int t = tid & 127;
#pragma unroll
      for (int j = 0; j < 8; j++)
        sts4(sF + 24576 + j * 2048 + t * 16, pack_bf16(acc[8 * j], acc[8 * j + 1]), pack_bf16(acc[8 * j + 2], acc[8 * j + 3]),
             pack_bf16(acc[8 * j + 4], acc[8 * j + 5]), pack_bf16(acc[8 * j + 6], acc[8 * j + 7]));
      named_arrive(7, 256);
    } else {
      uint32_t p[32];
      named_arrive(6, 384);
      if (wg == 2) named_arrive(8, 384);
#pragma unroll
      for (int i = 0; i < 32; i++) p[i] = phi2(acc[2 * i], acc[2 * i + 1]);
      if (wg == 1) {
        named_bar(8, 384);
        const int m = lane >> 3, r = lane & 7;
#pragma unroll
        for (int j = 0; j < 16; j += 2) {
          const int tok = (j + (m >> 1)) * 8 + r;
          const int chunk = w4 * 2 + (m & 1);
          stsm4t(sF + 49152 + tok * 128 + ((chunk ^ r) << 4), p[2 * j], p[2 * j + 1], p[2 * j + 2], p[2 * j + 3]);
        }
        fence_async();
      } else {
        named_bar(7, 256);
        float kv0[4] = {0, 0, 0, 0}, kv1[4] = {0, 0, 0, 0}, z0[4] = {0, 0, 0, 0}, z1[4] = {0, 0, 0, 0};
        const uint32_t one = 0x3F803F80u;
        const int t = tid & 127;
#pragma unroll
        for (int j = 0; j < 8; j++) {
          uint32_t a[4];
          lds4(sF + 24576 + j * 2048 + t * 16, a);
          mma_bf16(kv0, a[0], a[1], a[2], a[3], p[4 * j], p[4 * j + 2]);
          mma_bf16(kv1, a[0], a[1], a[2], a[3], p[4 * j + 1], p[4 * j + 3]);
          mma_bf16(z0, one, one, one, one, p[4 * j], p[4 * j + 2]);
          mma_bf16(z1, one, one, one, one, p[4 * j + 1], p[4 * j + 3]);
        }
        float4* dst = g_kvp + ((ttB * 32 + hq * 4 + w4) * 3) * 32 + lane;
        dst[0] = make_float4(kv0[0], kv0[1], kv1[0], kv1[1]);
        dst[32] = make_float4(kv0[2], kv0[3], kv1[2], kv1[3]);
        dst[64] = make_float4(z0[0], z0[1], z1[0], z1[1]);
      }
      __syncwarp();
      if (lane == 0) mbar_arrive(BAR_BDONE);
    }
  }

  mbar_wait(BAR_Q, 0);
  if (tid == 0) TS(1, 1);
  __nv_bfloat16* const obase = g_O + (size_t)(tbA * 64) * D_MOD + (hg * 8 + wg) * 16;
  bool safe = true;
  {
    const uint32_t c63 = 0x1F801F80u + (threadIdx.x >> 20);
    const uint32_t m1 = (gridDim.x >> 20) - 1u;
    const uint64_t dK0 = make_desc(sb + OFF_K, 32768, 128, 0);
    const uint64_t dV0 = make_desc(sb + OFF_V, 128, 32768, 0);
    constexpr uint32_t dKV = ((2048u - 8u)  __H0__ ) + STEPK - (OFF_V - OFF_K) / 16;
    mbar_wait(BAR_KV(0), 0);
#pragma unroll 1
    for (int pass = 0; pass < 2; pass++) {
      const uint64_t dQ = make_desc(sb + OFF_F + (pass * 4 + wg) * 2048, 128, 256, 0);
      float Sm[16], Sp[32], O[12];
      uint32_t P[24];
#pragma unroll
      for (int i = 0; i < 32; i++) Sp[i] = SMAGIC;
#pragma unroll
      for (int i = 0; i < 16; i++) Sm[i] = 0.f;
#pragma unroll
      for (int i = 0; i < 12; i++) O[i] = 0.f;
      fence_regs<16>(Sm); fence_regs<32>(Sp); fence_regs<12>(O);
      if (tid == 0) TS(1, 2 + 2 * pass);
      wg_fence();
      wg_qs32<0>(Sm, dQ, dK0);
      wg_qs64<1>(Sp, dQ, dK0 + 32);
      wg_commit();
      wg_wait<0>();
      fence_regs<16>(Sm); fence_regs<32>(Sp);
      uint32_t vlo = (uint32_t)dV0;
#pragma unroll 1
      for (int seg = 0; seg < 4; seg++) {
        if (seg >= 1) {
          if (seg < 3) mbar_wait(BAR_KV(seg), 0);
          if (pass == 1 && (tid & 127) == 0) mbar_arrive(BAR_CL(seg));
          __syncwarp();
        }
        const uint32_t vend = vlo + (seg == 0 ? 6 : 5) * STEPK;
#pragma unroll 1
        for (; vlo != vend; vlo += STEPK) {
          uint64_t dK, dV;
          asm("mov.b64 %0, {%1, %2};" : "=l"(dK) : "r"(vlo + dKV), "r"(8u));
          asm("mov.b64 %0, {%1, %2};" : "=l"(dV) : "r"(vlo), "r"(2048u));
#pragma unroll
          for (int i = 0; i < 8; i++) P[i] = pack_bf16(ex2f(Sm[2 * i]), ex2f(Sm[2 * i + 1]));
#pragma unroll
          for (int i = 0; i < 16; i++) P[8 + i] = exp2_pair_fix(Sp[2 * i], Sp[2 * i + 1], c63, m1);
          fence_regs<24>(P);
          wg_fence();
          wg_qs32<0>(Sm, dQ, dK);
          wg_qs64<1>(Sp, dQ, dK + 32);
#pragma unroll
          for (int k = 0; k < 6; k++) wg_pv24<1>(O, &P[4 * k], dV + k * 16);
          wg_commit();
          wg_wait<0>();
          fence_regs<16>(Sm); fence_regs<32>(Sp); fence_regs<12>(O); fence_regs<24>(P);
        }
      }
#pragma unroll
      for (int i = 0; i < 8; i++) P[i] = pack_bf16(ex2f(Sm[2 * i]), ex2f(Sm[2 * i + 1]));
      fence_regs<8>(P);
      wg_fence();
      wg_pv24<1>(O, &P[0], dV0 + 21 * STEPK);
      wg_pv24<1>(O, &P[4], dV0 + 21 * STEPK + 16);
      wg_commit();
      wg_wait<0>();
      fence_regs<12>(O);
      if (pass == 0) {
        uint32_t n[4];
        mbar_wait(BAR_Q2, 0);
        lds4(sM, n);
        const float qn = __half2float(__ushort_as_half((unsigned short)max(max(n[0], n[1]), max(n[2], n[3]))));
        safe = __all_sync(~0u, qn <= __uint_as_float(lds1(sM + 16)));
        if (!safe) break;
      }
      const float l0 = __shfl_sync(~0u, O[8], lane & ~3), l1 = __shfl_sync(~0u, O[10], lane & ~3);
      const float i0 = rcpf(l0), i1 = rcpf(l1);
      uint32_t* op = (uint32_t*)(obase + pass * 64 + (size_t)(w4 * 16 + (lane >> 2)) * D_MOD) + (lane & 3);
      op[0] = pack_bf16(O[0] * i0, O[1] * i0);
      op[8 * 256] = pack_bf16(O[2] * i1, O[3] * i1);
      op[4] = pack_bf16(O[4] * i0, O[5] * i0);
      op[8 * 256 + 4] = pack_bf16(O[6] * i1, O[7] * i1);
      __syncwarp();
      if (lane == 0) mbar_arrive(BAR_OD(pass));
      if (tid == 0) TS(1, 3 + 2 * pass);
      if ((tid & 127) == 0 && pass == 1 && wg > 0) TS(1, 10 + wg);
    }
  }

  if (!safe) {
    if ((tid & 127) == 0) { mbar_arrive(BAR_CL(1)); mbar_arrive(BAR_CL(2)); mbar_arrive(BAR_CL(3)); }
#pragma unroll 1
    for (int pass = 0; pass < 2; pass++) {
      attn_slow((const uint4*)g_Q + blockIdx.x * 1024 + (pass * 4 + wg) * 128, obase + pass * 64);
      __syncwarp();
      if (lane == 0) mbar_arrive(BAR_OD(pass));
    }
  }

  {
    named_bar(wg + 1, 128);
    if ((tid & 127) == 0) {
      mbar_arrive(BAR_CL(4));
      uint32_t r;
      asm volatile("atom.shared.add.u32 %0, [%1], 1;" : "=r"(r) : "r"(sM + 20) : "memory");
      sts1(sM + 32 + wg * 4, r);
    }
    named_bar(wg + 1, 128);
    const int role = __shfl_sync(~0u, lds1(sM + 32 + wg * 4), 0);
    const int isA = role >> 1, hf = role & 1;
    float acc[32];
    uint32_t xs = 0;
    int prev = 0;
#pragma unroll 1
    for (int n = 0; n < 8; n++) {
      const int gidx = isA ? (n < 4 ? n + 9 : (n == 4 ? 8 : n + 8)) : n;
      const uint32_t sl = tail_slots(gidx < 9 ? gidx : gidx - 9);
      xs = sb + ((sl >> (8 + 8 * hf)) & 255) * 8192;
      const uint64_t da = make_desc(xs, 16, 1024, 1), db = make_desc(sb + (sl & 255) * 8192, 8192, 1024, 1);
      mbar_wait(BAR_TF(gidx), 0);
      if ((tid & 127) == 0 && role == 3) TS(2, 2 + n);
      wg_fence();
#pragma unroll
      for (int k = 0; k < 4; k++) wg_ss64<0, 1>(acc, da + k * 2, db + k * 128, (n | k) != 0);
      wg_commit();
      wg_wait<1>();
      if (!isA && n >= 1 && (tid & 127) == 0) mbar_arrive(BAR_TE(prev));
      __syncwarp();
      prev = n;
    }
    wg_wait<0>();
    fence_regs<32>(acc);
    named_bar(wg + 1, 128);
    const int m = lane >> 3, r = lane & 7;
#pragma unroll
    for (int j = 0; j < 8; j += 2) {
      const int row = w4 * 16 + (m & 1) * 8 + r;
      stsm4(xs + row * 128 + (((j + (m >> 1)) ^ r) << 4),
            pack_bf16(acc[4 * j], acc[4 * j + 1]), pack_bf16(acc[4 * j + 2], acc[4 * j + 3]),
            pack_bf16(acc[4 * j + 4], acc[4 * j + 5]), pack_bf16(acc[4 * j + 6], acc[4 * j + 7]));
    }
    fence_async();
    named_bar(wg + 1, 128);
    if (w4 == 0 && elect_one()) {
      tma2d_store(&mOut, xs, (isA ? 0 : 512) + ct * 64, ttO * 128 + hf * 64);
      bulk_commit();
      asm volatile("cp.async.bulk.wait_group.read 0;" ::: "memory");
      TS(2, 11 + (role >> 1));
    }
  }
}

typedef CUresult (*EncodeFn)(CUtensorMap*, CUtensorMapDataType, cuuint32_t, void*, const cuuint64_t*, const cuuint64_t*,
                             const cuuint32_t*, const cuuint32_t*, CUtensorMapInterleave, CUtensorMapSwizzle,
                             CUtensorMapL2promotion, CUtensorMapFloatOOBfill);

static void make_map(EncodeFn enc, CUtensorMap* m, const void* ptr, uint64_t cols, uint64_t rows, uint32_t bc, uint32_t br) {
  cuuint64_t dims[2] = {cols, rows};
  cuuint64_t strides[1] = {cols * 2};
  cuuint32_t box[2] = {bc, br};
  cuuint32_t es[2] = {1, 1};
  enc(m, CU_TENSOR_MAP_DATA_TYPE_BFLOAT16, 2, (void*)ptr, dims, strides, box, es, CU_TENSOR_MAP_INTERLEAVE_NONE,
      CU_TENSOR_MAP_SWIZZLE_128B, CU_TENSOR_MAP_L2_PROMOTION_L2_256B, CU_TENSOR_MAP_FLOAT_OOB_FILL_NONE);
}

extern "C" void kernel_launch(void* const* d_in, const int* in_sizes, int n_in, void* d_out, int out_size) {
  (void)in_sizes; (void)n_in; (void)out_size;
  static EncodeFn enc = nullptr;
  static void* pQ = nullptr; static void* pO = nullptr;
  if (!enc) {
    void* fn = nullptr; cudaDriverEntryPointQueryResult qr;
    cudaGetDriverEntryPoint("cuTensorMapEncodeTiled", &fn, cudaEnableDefault, &qr);
    enc = (EncodeFn)fn;
    cudaGetSymbolAddress(&pQ, g_Q);
    cudaGetSymbolAddress(&pO, g_O);
    cudaFuncSetAttribute(k1_main, cudaFuncAttributeMaxDynamicSharedMemorySize, SM_TOTAL);
  }
  CUtensorMap mXA64, mXB, mWq, mWqkv, mQst, mO, mOst, mWoA, mWoB, mOut;
  make_map(enc, &mXA64, d_in[0], 512, 2048, 64, 64);
  make_map(enc, &mWq, d_in[1], 512, 512, 64, 64);
  make_map(enc, &mWoA, d_in[4], 512, 512, 64, 64);
  make_map(enc, &mXB, d_in[5], 512, 2048, 64, 128);
  make_map(enc, &mWqkv, d_in[6], 1536, 512, 64, 64);
  make_map(enc, &mWoB, d_in[7], 512, 512, 64, 64);
  make_map(enc, &mQst, pQ, 512, 4096, 64, 128);
  make_map(enc, &mO, pO, 512, 4096, 64, 64);
  make_map(enc, &mOst, pO, 512, 4096, 64, 128);
  make_map(enc, &mOut, d_out, 1024, 2048, 64, 64);
  Params prm{(const __nv_bfloat16*)d_in[2], (const __nv_bfloat16*)d_in[3]};
  k1_main<<<132, 640, SM_TOTAL, cudaStreamPerThread>>>(mXA64, mXB, mWq, mWqkv, mQst, mOst, mO, mWoA, mWoB, mOut, prm);
}
```

```cpp
#include <cuda_runtime.h>
#include <cuda_bf16.h>
#include <cuda_fp16.h>
#include <cuda.h>
#include <stdint.h>

#define S_TOK 2048
#define D_MOD 512

__device__ __align__(1024) __nv_bfloat16 g_Q[2 * S_TOK * D_MOD];
__device__ __align__(1024) __nv_bfloat16 g_O[2 * S_TOK * D_MOD];
__device__ __align__(1024) uint4 g_KV[8 * S_TOK];
__device__ __align__(16) uint32_t g_stats[128];
__device__ __align__(16) float4 g_kvp[16 * 32 * 3 * 32];

#define TS(k, i) do {} while (0)
__device__ __forceinline__ uint32_t smem_u32(const void* p) { return (uint32_t)__cvta_generic_to_shared(p); }
__device__ __forceinline__ void mbar_init(uint32_t bar, int cnt) { asm volatile("mbarrier.init.shared::cta.b64 [%0], %1;" :: "r"(bar), "r"(cnt) : "memory"); }
__device__ __forceinline__ void mbar_expect_tx(uint32_t bar, uint32_t bytes) { asm volatile("mbarrier.arrive.expect_tx.shared::cta.b64 _, [%0], %1;" :: "r"(bar), "r"(bytes) : "memory"); }
__device__ __forceinline__ bool mbar_try(uint32_t bar, uint32_t parity) {
  uint32_t ok;
  asm volatile("{\n.reg .pred p;\nmbarrier.try_wait.parity.shared::cta.b64 p, [%1], %2;\nselp.b32 %0, 1, 0, p;\n}\n" : "=r"(ok) : "r"(bar), "r"(parity) : "memory");
  return ok;
}
__device__ __forceinline__ void mbar_wait(uint32_t bar, uint32_t parity) {
  asm volatile("{\n.reg .pred p;\n.reg .u32 c;\nmov.u32 c, 0;\n"
               "LW_%=:\n"
               "mbarrier.try_wait.parity.shared::cta.b64 p, [%0], %1;\n"
               "@p bra LD_%=;\n"
               "add.u32 c, c, 1;\n"
               "setp.lt.u32 p, c, 4000000;\n"
               "@p bra LW_%=;\n"
               "trap;\n"
               "LD_%=:\n}\n" :: "r"(bar), "r"(parity) : "memory");
}
__device__ __forceinline__ void mbar_arrive_cta(uint32_t bar, uint32_t cta) {
  asm volatile("{\n.reg .b32 ra;\nmapa.shared::cluster.u32 ra, %0, %1;\nmbarrier.arrive.shared::cluster.b64 _, [ra];\n}\n" :: "r"(bar), "r"(cta) : "memory");
}
__device__ __forceinline__ void cluster_sync() {
  asm volatile("barrier.cluster.arrive.relaxed.aligned;\nbarrier.cluster.wait.aligned;" ::: "memory");
}
__device__ __forceinline__ void tma2d(uint32_t dst, const CUtensorMap* m, int c0, int c1, uint32_t bar) {
  asm volatile("cp.async.bulk.tensor.2d.shared::cluster.global.mbarrier::complete_tx::bytes [%0], [%1, {%3, %4}], [%2];"
               :: "r"(dst), "l"(m), "r"(bar), "r"(c0), "r"(c1) : "memory");
}
__device__ __forceinline__ void tma2d_mc(uint32_t dst, const CUtensorMap* m, int c0, int c1, uint32_t bar, uint16_t mask) {
  asm volatile("cp.async.bulk.tensor.2d.shared::cluster.global.mbarrier::complete_tx::bytes.multicast::cluster [%0], [%1, {%3, %4}], [%2], %5;"
               :: "r"(dst), "l"(m), "r"(bar), "r"(c0), "r"(c1), "h"(mask) : "memory");
}
__device__ __forceinline__ void tma2d_store(const CUtensorMap* m, uint32_t src, int c0, int c1) {
  asm volatile("cp.async.bulk.tensor.2d.global.shared::cta.bulk_group [%0, {%2, %3}], [%1];"
               :: "l"(m), "r"(src), "r"(c0), "r"(c1) : "memory");
}
__device__ __forceinline__ void bulk_g2s(uint32_t dst, const void* src, uint32_t bytes, uint32_t bar) {
  asm volatile("cp.async.bulk.shared::cluster.global.mbarrier::complete_tx::bytes [%0], [%1], %2, [%3];"
               :: "r"(dst), "l"(src), "r"(bytes), "r"(bar) : "memory");
}
__device__ __forceinline__ void bulk_commit() { asm volatile("cp.async.bulk.commit_group;" ::: "memory"); }
__device__ __forceinline__ void bulk_wait_all() { asm volatile("cp.async.bulk.wait_group 0;" ::: "memory"); }
__device__ __forceinline__ void fence_async() { asm volatile("fence.proxy.async.shared::cta;" ::: "memory"); }
__device__ __forceinline__ void named_bar(int id, int n) { asm volatile("bar.sync %0, %1;" :: "r"(id), "r"(n) : "memory"); }
__device__ __forceinline__ void pdl_launch() { asm volatile("griddepcontrol.launch_dependents;" ::: "memory"); }
__device__ __forceinline__ void pdl_wait() { asm volatile("griddepcontrol.wait;" ::: "memory"); }
__device__ __forceinline__ void wg_fence() { asm volatile("wgmma.fence.sync.aligned;" ::: "memory"); }
__device__ __forceinline__ void wg_commit() { asm volatile("wgmma.commit_group.sync.aligned;" ::: "memory"); }
template <int n> __device__ __forceinline__ void wg_wait() { asm volatile("wgmma.wait_group.sync.aligned %0;" :: "n"(n) : "memory"); }
template <int n> __device__ __forceinline__ void fence_regs(float* r) {
#pragma unroll
  for (int i = 0; i < n; i++) asm volatile("" : "+f"(r[i]) :: "memory");
}
template <int n> __device__ __forceinline__ void fence_regs(uint32_t* r) {
#pragma unroll
  for (int i = 0; i < n; i++) asm volatile("" : "+r"(r[i]) :: "memory");
}
__device__ __forceinline__ uint64_t make_desc(uint32_t addr, uint32_t lbo, uint32_t sbo, uint32_t swz) {
  return (uint64_t)((addr & 0x3FFFF) >> 4) | ((uint64_t)(lbo >> 4) << 16) | ((uint64_t)(sbo >> 4) << 32) | ((uint64_t)swz << 62);
}
__device__ __forceinline__ float ex2f(float x) { float y; asm("ex2.approx.ftz.f32 %0, %1;" : "=f"(y) : "f"(x)); return y; }
__device__ __forceinline__ uint32_t pack_bf16(float lo, float hi) { uint32_t r; asm("cvt.rn.bf16x2.f32 %0, %1, %2;" : "=r"(r) : "f"(hi), "f"(lo)); return r; }
__device__ __forceinline__ uint32_t pack_f16(float lo, float hi) { uint32_t r; asm("cvt.rn.f16x2.f32 %0, %1, %2;" : "=r"(r) : "f"(hi), "f"(lo)); return r; }
__device__ __forceinline__ float bf_lo(uint32_t v) { return __uint_as_float(v << 16); }
__device__ __forceinline__ float bf_hi(uint32_t v) { return __uint_as_float(v & 0xFFFF0000u); }
__device__ __forceinline__ float rbf(float x) { return __bfloat162float(__float2bfloat16_rn(x)); }
__device__ __forceinline__ void stsm4(uint32_t a, uint32_t r0, uint32_t r1, uint32_t r2, uint32_t r3) {
  asm volatile("stmatrix.sync.aligned.m8n8.x4.shared.b16 [%0], {%1,%2,%3,%4};" :: "r"(a), "r"(r0), "r"(r1), "r"(r2), "r"(r3) : "memory");
}
__device__ __forceinline__ void stsm4t(uint32_t a, uint32_t r0, uint32_t r1, uint32_t r2, uint32_t r3) {
  asm volatile("stmatrix.sync.aligned.m8n8.x4.trans.shared.b16 [%0], {%1,%2,%3,%4};" :: "r"(a), "r"(r0), "r"(r1), "r"(r2), "r"(r3) : "memory");
}
__device__ __forceinline__ void mma_bf16(float* d, uint32_t a0, uint32_t a1, uint32_t a2, uint32_t a3, uint32_t b0, uint32_t b1) {
  asm volatile("mma.sync.aligned.m16n8k16.row.col.f32.bf16.bf16.f32 {%0,%1,%2,%3}, {%4,%5,%6,%7}, {%8,%9}, {%0,%1,%2,%3};"
               : "+f"(d[0]), "+f"(d[1]), "+f"(d[2]), "+f"(d[3]) : "r"(a0), "r"(a1), "r"(a2), "r"(a3), "r"(b0), "r"(b1));
}
template<int SD> __device__ __forceinline__ void wg_qk32(float* d, const uint32_t* a, uint64_t desc) {
  asm volatile("wgmma.mma_async.sync.aligned.m64n32k16.f32.f16.f16 {%0,%1,%2,%3,%4,%5,%6,%7,%8,%9,%10,%11,%12,%13,%14,%15}, {%16,%17,%18,%19}, %20, %21, 1, 1, 0;"
   : "+f"(d[0]),"+f"(d[1]),"+f"(d[2]),"+f"(d[3]),"+f"(d[4]),"+f"(d[5]),"+f"(d[6]),"+f"(d[7]),"+f"(d[8]),"+f"(d[9]),"+f"(d[10]),"+f"(d[11]),"+f"(d[12]),"+f"(d[13]),"+f"(d[14]),"+f"(d[15])
   : "r"(a[0]),"r"(a[1]),"r"(a[2]),"r"(a[3]),"l"(desc),"n"(SD));
}
template<int SD> __device__ __forceinline__ void wg_qk64(float* d, const uint32_t* a, uint64_t desc) {
  asm volatile("wgmma.mma_async.sync.aligned.m64n64k16.f32.f16.f16 {%0,%1,%2,%3,%4,%5,%6,%7,%8,%9,%10,%11,%12,%13,%14,%15,%16,%17,%18,%19,%20,%21,%22,%23,%24,%25,%26,%27,%28,%29,%30,%31}, {%32,%33,%34,%35}, %36, %37, 1, 1, 0;"
   : "+f"(d[0]),"+f"(d[1]),"+f"(d[2]),"+f"(d[3]),"+f"(d[4]),"+f"(d[5]),"+f"(d[6]),"+f"(d[7]),"+f"(d[8]),"+f"(d[9]),"+f"(d[10]),"+f"(d[11]),"+f"(d[12]),"+f"(d[13]),"+f"(d[14]),"+f"(d[15]),"+f"(d[16]),"+f"(d[17]),"+f"(d[18]),"+f"(d[19]),"+f"(d[20]),"+f"(d[21]),"+f"(d[22]),"+f"(d[23]),"+f"(d[24]),"+f"(d[25]),"+f"(d[26]),"+f"(d[27]),"+f"(d[28]),"+f"(d[29]),"+f"(d[30]),"+f"(d[31])
   : "r"(a[0]),"r"(a[1]),"r"(a[2]),"r"(a[3]),"l"(desc),"n"(SD));
}
template<int SD> __device__ __forceinline__ void wg_qs32(float* d, uint64_t da, uint64_t db) {
  asm volatile("wgmma.mma_async.sync.aligned.m64n32k16.f32.f16.f16 {%0,%1,%2,%3,%4,%5,%6,%7,%8,%9,%10,%11,%12,%13,%14,%15}, %16, %17, %18, 1, 1, 0, 0;"
   : "+f"(d[0]),"+f"(d[1]),"+f"(d[2]),"+f"(d[3]),"+f"(d[4]),"+f"(d[5]),"+f"(d[6]),"+f"(d[7]),"+f"(d[8]),"+f"(d[9]),"+f"(d[10]),"+f"(d[11]),"+f"(d[12]),"+f"(d[13]),"+f"(d[14]),"+f"(d[15])
   : "l"(da),"l"(db),"n"(SD));
}
template<int SD> __device__ __forceinline__ void wg_qs64(float* d, uint64_t da, uint64_t db) {
  asm volatile("wgmma.mma_async.sync.aligned.m64n64k16.f32.f16.f16 {%0,%1,%2,%3,%4,%5,%6,%7,%8,%9,%10,%11,%12,%13,%14,%15,%16,%17,%18,%19,%20,%21,%22,%23,%24,%25,%26,%27,%28,%29,%30,%31}, %32, %33, %34, 1, 1, 0, 0;"
   : "+f"(d[0]),"+f"(d[1]),"+f"(d[2]),"+f"(d[3]),"+f"(d[4]),"+f"(d[5]),"+f"(d[6]),"+f"(d[7]),"+f"(d[8]),"+f"(d[9]),"+f"(d[10]),"+f"(d[11]),"+f"(d[12]),"+f"(d[13]),"+f"(d[14]),"+f"(d[15]),"+f"(d[16]),"+f"(d[17]),"+f"(d[18]),"+f"(d[19]),"+f"(d[20]),"+f"(d[21]),"+f"(d[22]),"+f"(d[23]),"+f"(d[24]),"+f"(d[25]),"+f"(d[26]),"+f"(d[27]),"+f"(d[28]),"+f"(d[29]),"+f"(d[30]),"+f"(d[31])
   : "l"(da),"l"(db),"n"(SD));
}
template<int SD> __device__ __forceinline__ void wg_pv24(float* d, const uint32_t* a, uint64_t desc) {
  asm volatile("wgmma.mma_async.sync.aligned.m64n24k16.f32.bf16.bf16 {%0,%1,%2,%3,%4,%5,%6,%7,%8,%9,%10,%11}, {%12,%13,%14,%15}, %16, %17, 1, 1, 1;"
   : "+f"(d[0]),"+f"(d[1]),"+f"(d[2]),"+f"(d[3]),"+f"(d[4]),"+f"(d[5]),"+f"(d[6]),"+f"(d[7]),"+f"(d[8]),"+f"(d[9]),"+f"(d[10]),"+f"(d[11])
   : "r"(a[0]),"r"(a[1]),"r"(a[2]),"r"(a[3]),"l"(desc),"n"(SD));
}
template<int TA, int TB> __device__ __forceinline__ void wg_ss128(float* d, uint64_t da, uint64_t db, int sd) {
  asm volatile("{\n.reg .pred p;\nsetp.ne.b32 p, %66, 0;\n"
   "wgmma.mma_async.sync.aligned.m64n128k16.f32.bf16.bf16 {%0,%1,%2,%3,%4,%5,%6,%7,%8,%9,%10,%11,%12,%13,%14,%15,%16,%17,%18,%19,%20,%21,%22,%23,%24,%25,%26,%27,%28,%29,%30,%31,%32,%33,%34,%35,%36,%37,%38,%39,%40,%41,%42,%43,%44,%45,%46,%47,%48,%49,%50,%51,%52,%53,%54,%55,%56,%57,%58,%59,%60,%61,%62,%63}, %64, %65, p, 1, 1, %67, %68;\n}\n"
   : "+f"(d[0]),"+f"(d[1]),"+f"(d[2]),"+f"(d[3]),"+f"(d[4]),"+f"(d[5]),"+f"(d[6]),"+f"(d[7]),"+f"(d[8]),"+f"(d[9]),"+f"(d[10]),"+f"(d[11]),"+f"(d[12]),"+f"(d[13]),"+f"(d[14]),"+f"(d[15]),"+f"(d[16]),"+f"(d[17]),"+f"(d[18]),"+f"(d[19]),"+f"(d[20]),"+f"(d[21]),"+f"(d[22]),"+f"(d[23]),"+f"(d[24]),"+f"(d[25]),"+f"(d[26]),"+f"(d[27]),"+f"(d[28]),"+f"(d[29]),"+f"(d[30]),"+f"(d[31]),"+f"(d[32]),"+f"(d[33]),"+f"(d[34]),"+f"(d[35]),"+f"(d[36]),"+f"(d[37]),"+f"(d[38]),"+f"(d[39]),"+f"(d[40]),"+f"(d[41]),"+f"(d[42]),"+f"(d[43]),"+f"(d[44]),"+f"(d[45]),"+f"(d[46]),"+f"(d[47]),"+f"(d[48]),"+f"(d[49]),"+f"(d[50]),"+f"(d[51]),"+f"(d[52]),"+f"(d[53]),"+f"(d[54]),"+f"(d[55]),"+f"(d[56]),"+f"(d[57]),"+f"(d[58]),"+f"(d[59]),"+f"(d[60]),"+f"(d[61]),"+f"(d[62]),"+f"(d[63])
   : "l"(da),"l"(db),"r"(sd),"n"(TA),"n"(TB));
}
template<int TA, int TB> __device__ __forceinline__ void wg_ss64(float* d, uint64_t da, uint64_t db, int sd) {
  asm volatile("{\n.reg .pred p;\nsetp.ne.b32 p, %34, 0;\n"
   "wgmma.mma_async.sync.aligned.m64n64k16.f32.bf16.bf16 {%0,%1,%2,%3,%4,%5,%6,%7,%8,%9,%10,%11,%12,%13,%14,%15,%16,%17,%18,%19,%20,%21,%22,%23,%24,%25,%26,%27,%28,%29,%30,%31}, %32, %33, p, 1, 1, %35, %36;\n}\n"
   : "+f"(d[0]),"+f"(d[1]),"+f"(d[2]),"+f"(d[3]),"+f"(d[4]),"+f"(d[5]),"+f"(d[6]),"+f"(d[7]),"+f"(d[8]),"+f"(d[9]),"+f"(d[10]),"+f"(d[11]),"+f"(d[12]),"+f"(d[13]),"+f"(d[14]),"+f"(d[15]),"+f"(d[16]),"+f"(d[17]),"+f"(d[18]),"+f"(d[19]),"+f"(d[20]),"+f"(d[21]),"+f"(d[22]),"+f"(d[23]),"+f"(d[24]),"+f"(d[25]),"+f"(d[26]),"+f"(d[27]),"+f"(d[28]),"+f"(d[29]),"+f"(d[30]),"+f"(d[31])
   : "l"(da),"l"(db),"r"(sd),"n"(TA),"n"(TB));
}

template<int TA, int TB> __device__ __forceinline__ void wg_ss8(float* d, uint64_t da, uint64_t db, int sd) {
  asm volatile("{\n.reg .pred p;\nsetp.ne.b32 p, %6, 0;\n"
   "wgmma.mma_async.sync.aligned.m64n8k16.f32.bf16.bf16 {%0,%1,%2,%3}, %4, %5, p, 1, 1, %7, %8;\n}\n"
   : "+f"(d[0]),"+f"(d[1]),"+f"(d[2]),"+f"(d[3])
   : "l"(da),"l"(db),"r"(sd),"n"(TA),"n"(TB));
}

template<int SD, uint32_t HI> __device__ __forceinline__ void wq32(float* d, uint64_t da, uint32_t lo) {
  asm volatile("{\n.reg .b64 db;\nmov.b64 db, {%17, %19};\n"
   "wgmma.mma_async.sync.aligned.m64n32k16.f32.f16.f16 {%0,%1,%2,%3,%4,%5,%6,%7,%8,%9,%10,%11,%12,%13,%14,%15}, %16, db, %18, 1, 1, 0, 0;\n}\n"
   : "+f"(d[0]),"+f"(d[1]),"+f"(d[2]),"+f"(d[3]),"+f"(d[4]),"+f"(d[5]),"+f"(d[6]),"+f"(d[7]),"+f"(d[8]),"+f"(d[9]),"+f"(d[10]),"+f"(d[11]),"+f"(d[12]),"+f"(d[13]),"+f"(d[14]),"+f"(d[15])
   : "l"(da),"r"(lo),"n"(SD),"r"(HI));
}
template<int SD, uint32_t HI> __device__ __forceinline__ void wq64(float* d, uint64_t da, uint32_t lo) {
  asm volatile("{\n.reg .b64 db;\nmov.b64 db, {%33, %35};\n"
   "wgmma.mma_async.sync.aligned.m64n64k16.f32.f16.f16 {%0,%1,%2,%3,%4,%5,%6,%7,%8,%9,%10,%11,%12,%13,%14,%15,%16,%17,%18,%19,%20,%21,%22,%23,%24,%25,%26,%27,%28,%29,%30,%31}, %32, db, %34, 1, 1, 0, 0;\n}\n"
   : "+f"(d[0]),"+f"(d[1]),"+f"(d[2]),"+f"(d[3]),"+f"(d[4]),"+f"(d[5]),"+f"(d[6]),"+f"(d[7]),"+f"(d[8]),"+f"(d[9]),"+f"(d[10]),"+f"(d[11]),"+f"(d[12]),"+f"(d[13]),"+f"(d[14]),"+f"(d[15]),"+f"(d[16]),"+f"(d[17]),"+f"(d[18]),"+f"(d[19]),"+f"(d[20]),"+f"(d[21]),"+f"(d[22]),"+f"(d[23]),"+f"(d[24]),"+f"(d[25]),"+f"(d[26]),"+f"(d[27]),"+f"(d[28]),"+f"(d[29]),"+f"(d[30]),"+f"(d[31])
   : "l"(da),"r"(lo),"n"(SD),"r"(HI));
}
template<int SD, uint32_t HI> __device__ __forceinline__ void wpv(float* d, const uint32_t* a, uint32_t lo) {
  asm volatile("{\n.reg .b64 db;\nmov.b64 db, {%16, %18};\n"
   "wgmma.mma_async.sync.aligned.m64n24k16.f32.bf16.bf16 {%0,%1,%2,%3,%4,%5,%6,%7,%8,%9,%10,%11}, {%12,%13,%14,%15}, db, %17, 1, 1, 1;\n}\n"
   : "+f"(d[0]),"+f"(d[1]),"+f"(d[2]),"+f"(d[3]),"+f"(d[4]),"+f"(d[5]),"+f"(d[6]),"+f"(d[7]),"+f"(d[8]),"+f"(d[9]),"+f"(d[10]),"+f"(d[11])
   : "r"(a[0]),"r"(a[1]),"r"(a[2]),"r"(a[3]),"r"(lo),"n"(SD),"r"(HI));
}

__device__ __forceinline__ uint32_t phi2(float a, float b) {
  uint32_t r, e;
  asm("cvt.rn.relu.bf16x2.f32 %0, %1, %2;" : "=r"(r) : "f"(b), "f"(a));
  e = pack_bf16(ex2f(a * 1.4426950408889634f), ex2f(b * 1.4426950408889634f));
  asm("add.rn.bf16x2 %0, %0, %1;" : "+r"(e) : "r"(0x35863586u));
  asm("min.NaN.bf16x2 %0, %0, %1;" : "+r"(e) : "r"(0x3F803F80u));
  asm("add.rn.bf16x2 %0, %0, %1;" : "+r"(e) : "r"(r));
  return e;
}

__device__ __forceinline__ void mbar_arrive(uint32_t bar) { asm volatile("mbarrier.arrive.shared::cta.b64 _, [%0];" :: "r"(bar) : "memory"); }
__device__ __forceinline__ void named_arrive(int id, int n) { asm volatile("bar.arrive %0, %1;" :: "r"(id), "r"(n) : "memory"); }
__device__ __forceinline__ void fence_async_all() { asm volatile("fence.proxy.async.global;" ::: "memory"); }
__device__ __forceinline__ void flag_add(uint32_t* f) { asm volatile("fence.acq_rel.gpu;\nred.relaxed.gpu.global.add.u32 [%0], 1;" :: "l"(f) : "memory"); }
__device__ __forceinline__ void flag_wait(const uint32_t* f, uint32_t target) {
  uint32_t v;
#pragma unroll 1
  for (int it = 0;; it++) {
    asm volatile("ld.acquire.gpu.global.u32 %0, [%1];" : "=r"(v) : "l"(f) : "memory");
    if ((int32_t)(v - target) >= 0) break;
    if (it > 2000000) __trap();
    __nanosleep(64);
  }
}
__device__ __forceinline__ bool elect_one() {
  uint32_t p;
  asm volatile("{\n.reg .pred P;\nelect.sync _|P, 0xFFFFFFFF;\nselp.b32 %0, 1, 0, P;\n}\n" : "=r"(p));
  return p;
}
__device__ __forceinline__ void lds4(uint32_t a, uint32_t* r) {
  asm volatile("ld.shared.v4.b32 {%0,%1,%2,%3}, [%4];" : "=r"(r[0]), "=r"(r[1]), "=r"(r[2]), "=r"(r[3]) : "r"(a) : "memory");
}
__device__ __forceinline__ uint32_t lds1(uint32_t a) { uint32_t r; asm volatile("ld.shared.b32 %0, [%1];" : "=r"(r) : "r"(a) : "memory"); return r; }
__device__ __forceinline__ void sts1(uint32_t a, uint32_t v) { asm volatile("st.shared.b32 [%0], %1;" :: "r"(a), "r"(v) : "memory"); }
__device__ __forceinline__ void sts4(uint32_t a, uint32_t r0, uint32_t r1, uint32_t r2, uint32_t r3) {
  asm volatile("st.shared.v4.b32 [%0], {%1,%2,%3,%4};" :: "r"(a), "r"(r0), "r"(r1), "r"(r2), "r"(r3) : "memory");
}
__device__ __forceinline__ void ldsm4(uint32_t a, uint32_t* r) {
  asm volatile("ldmatrix.sync.aligned.m8n8.x4.shared.b16 {%0,%1,%2,%3}, [%4];" : "=r"(r[0]), "=r"(r[1]), "=r"(r[2]), "=r"(r[3]) : "r"(a) : "memory");
}
__device__ __forceinline__ float rcpf(float x) { float y; asm("rcp.approx.ftz.f32 %0, %1;" : "=f"(y) : "f"(x)); return y; }
__device__ __forceinline__ uint32_t hfma2(uint32_t a, uint32_t b, uint32_t c) { uint32_t r; asm("fma.rn.f16x2 %0, %1, %2, %3;" : "=r"(r) : "r"(a), "r"(b), "r"(c)); return r; }
__device__ __forceinline__ uint32_t hadd2(uint32_t a, uint32_t b) { uint32_t r; asm("add.rn.f16x2 %0, %1, %2;" : "=r"(r) : "r"(a), "r"(b)); return r; }

#define STEPK 96
#define QSCALE 0.36067376022224085f
#define SMAGIC (512.0f + 2.0f * (191.0f - 30.0f - 1.5823545f))
#define VSHIFT 1073741824.0f

__device__ uint32_t g_epoch[132];
__device__ uint32_t g_flag[288 * 8];
#define FLAG_KV (g_flag)
#define FLAG_B(h) (g_flag + (4 + (h)) * 8)
#define FLAG_OA(cta, pass) (g_flag + (16 + (cta) * 2 + (pass)) * 8)
#define FLAG_LM(i) (g_flag + (272 + (i)) * 8)

#define SM_TOTAL (224 * 1024 + 2048 + 1024)
#define OFF_K 0
#define OFF_F 65536
#define OFF_V 131072
#define OFF_MISC (224 * 1024)

#define BAR_FULL(s) (bars + 8 * (s))
#define BAR_EMPTY(s) (bars + 24 + 8 * (s))
#define BAR_KV(c) (bars + 48 + 8 * (c))
#define BAR_XA (bars + 72)
#define BAR_BDONE (bars + 80)
#define BAR_Q (bars + 88)
#define BAR_GO (bars + 96)
#define BAR_Q2 (bars + 104)
#define BAR_OD(p) (bars + 112 + 8 * (p))
#define BAR_CL(c) (bars + 128 + 8 * (c))
#define BAR_TE(i) (bars + 168 + 8 * (i))
#define BAR_TF(g) (bars + 224 + 8 * (g))

__device__ __forceinline__ uint32_t exp2_pair_fix(float d0, float d1, uint32_t c63, uint32_t m1) {
  uint32_t w, y, s, r;
  asm("prmt.b32 %0, %1, %2, 0x6521;" : "=r"(w) : "r"(__float_as_uint(d0)), "r"(__float_as_uint(d1)));
  asm("lop3.b32 %0, %1, 0x007F007F, %2, 0xEA;" : "=r"(y) : "r"(w), "r"(c63));
  asm("mad.lo.u32 %0, %1, %2, %3;" : "=r"(s) : "r"(y), "r"(m1), "r"(w));
  asm("fma.rn.bf16x2 %0, %1, %2, %3;" : "=r"(r) : "r"(w), "r"(y), "r"(s));
  return r;
}

__device__ __forceinline__ void attn_slow(const uint4* gq, __nv_bfloat16* dst) {
  const int t = threadIdx.x & 127;
  const int row = t >> 1, half = t & 1;
  float q[16];
#pragma unroll
  for (int i = 0; i < 4; i++) {
    const uint4 v = gq[(row >> 4) * 32 + (row & 7) * 4 + i];
    const uint32_t lo = (row & 8) ? v.y : v.x, hi = (row & 8) ? v.w : v.z;
    q[2 * i] = bf_lo(lo); q[2 * i + 1] = bf_hi(lo); q[2 * i + 8] = bf_lo(hi); q[2 * i + 9] = bf_hi(hi);
  }
  float m = -INFINITY, l = 0.f, o[16];
#pragma unroll
  for (int i = 0; i < 16; i++) o[i] = 0.f;
#pragma unroll 1
  for (int j = half * 1024; j < half * 1024 + 1024; j++) {
    uint4 ka = g_KV[4 * S_TOK + j], kb = g_KV[5 * S_TOK + j];
    uint4 va = g_KV[6 * S_TOK + j], vb = g_KV[7 * S_TOK + j];
    uint32_t kk[8] = {ka.x, ka.y, ka.z, ka.w, kb.x, kb.y, kb.z, kb.w};
    uint32_t vv[8] = {va.x, va.y, va.z, va.w, vb.x, vb.y, vb.z, vb.w};
    float s = 0.f;
#pragma unroll
    for (int i = 0; i < 8; i++) { s = fmaf(q[2 * i], bf_lo(kk[i]), s); s = fmaf(q[2 * i + 1], bf_hi(kk[i]), s); }
    s = rbf(s) * 0.25f;
    if (s > m) {
      float c = __expf(m - s);
      l *= c;
#pragma unroll
      for (int i = 0; i < 16; i++) o[i] *= c;
      m = s;
    }
    float p = __expf(s - m);
    l += p;
#pragma unroll
    for (int i = 0; i < 8; i++) { o[2 * i] = fmaf(p, bf_lo(vv[i]), o[2 * i]); o[2 * i + 1] = fmaf(p, bf_hi(vv[i]), o[2 * i + 1]); }
  }
  float m2 = __shfl_xor_sync(~0u, m, 1);
  float mm = fmaxf(m, m2);
  float c = __expf(m - mm);
  l *= c; l += __shfl_xor_sync(~0u, l, 1);
  float inv = 1.f / l;
  uint32_t r[8];
#pragma unroll
  for (int i = 0; i < 16; i++) { o[i] *= c; o[i] += __shfl_xor_sync(~0u, o[i], 1); o[i] *= inv; }
#pragma unroll
  for (int i = 0; i < 8; i++) r[i] = pack_bf16(o[2 * i], o[2 * i + 1]);
  uint4* d = (uint4*)(dst + (size_t)row * D_MOD);
  if (half == 0) d[0] = make_uint4(r[0], r[1], r[2], r[3]); else d[1] = make_uint4(r[4], r[5], r[6], r[7]);
}

struct Params { const __nv_bfloat16* wk; const __nv_bfloat16* wv; };

__device__ __forceinline__ void helper_cta(const int h, const uint32_t sb, const uint32_t bars, const int wg, const int w4,
                                           const CUtensorMap* mQ, const CUtensorMap* mOs) {
  const int lane = threadIdx.x & 31;
  mbar_wait(BAR_GO, 0);
  const int cb = wg & 1, col = h * 128 + cb * 64, row0 = S_TOK + (wg >> 1) * 1024;
  const uint32_t buf = sb + wg * 49152;
  if (w4 == 0 && elect_one()) {
    fence_async_all();
#pragma unroll 1
    for (int u = 0; u < 3; u++) {
      mbar_expect_tx(BAR_TF(wg * 3 + u), 16384);
      tma2d(buf + u * 16384, mQ, col, row0 + u * 128, BAR_TF(wg * 3 + u));
    }
  }
  const int head = h * 8 + cb * 4 + w4;
  float4 a0 = make_float4(0, 0, 0, 0), a1 = a0, a2 = a0;
#pragma unroll 8
  for (int tt = 0; tt < 16; tt++) {
    const float4* src = g_kvp + ((tt * 32 + head) * 3) * 32 + lane;
    float4 u = src[0], v = src[32], w = src[64];
    a0.x += u.x; a0.y += u.y; a0.z += u.z; a0.w += u.w;
    a1.x += v.x; a1.y += v.y; a1.z += v.z; a1.w += v.w;
    a2.x += w.x; a2.y += w.y; a2.z += w.z; a2.w += w.w;
  }
  const uint32_t b00 = pack_bf16(a0.x, a0.y), b01 = pack_bf16(a0.z, a0.w);
  const uint32_t b10 = pack_bf16(a1.x, a1.y), b11 = pack_bf16(a1.z, a1.w);
  const uint32_t bz0 = pack_bf16(a2.x, a2.y), bz1 = pack_bf16(a2.z, a2.w);
  const int m = lane >> 3, r = lane & 7;
  const uint32_t off = ((m & 1) * 8 + r) * 128 + (((w4 * 2 + (m >> 1)) ^ r) << 4);
  int s = 0, ph = 0;
#pragma unroll 1
  for (int u = 0; u < 8; u++) {
    const uint32_t bb = buf + s * 16384;
    mbar_wait(BAR_TF(wg * 3 + s), ph);
#pragma unroll
    for (int mt = 0; mt < 8; mt++) {
      uint32_t a[4];
      ldsm4(bb + mt * 2048 + off, a);
      float n0[4] = {0, 0, 0, 0}, n1[4] = {0, 0, 0, 0}, dn[4] = {0, 0, 0, 0};
      mma_bf16(dn, a[0], a[1], a[2], a[3], bz0, bz1);
      mma_bf16(n0, a[0], a[1], a[2], a[3], b00, b01);
      mma_bf16(n1, a[0], a[1], a[2], a[3], b10, b11);
      const float i0 = rcpf(dn[0] + 1e-6f), i1 = rcpf(dn[2] + 1e-6f);
      stsm4(bb + mt * 2048 + off, pack_bf16(n0[0] * i0, n0[1] * i0), pack_bf16(n0[2] * i1, n0[3] * i1),
            pack_bf16(n1[0] * i0, n1[1] * i0), pack_bf16(n1[2] * i1, n1[3] * i1));
    }
    fence_async();
    named_bar(wg + 1, 128);
    if (w4 == 0 && lane == 0) {
      tma2d_store(mOs, bb, col, row0 + u * 128);
      bulk_commit();
      if (u >= 1 && u + 2 < 8) {
        asm volatile("cp.async.bulk.wait_group.read 1;" ::: "memory");
        const int sp = s == 0 ? 2 : s - 1;
        mbar_expect_tx(BAR_TF(wg * 3 + sp), 16384);
        tma2d(buf + sp * 16384, mQ, col, row0 + (u + 2) * 128, BAR_TF(wg * 3 + sp));
      }
    }
    __syncwarp();
    if (++s == 3) { s = 0; ph ^= 1; }
  }
  if (w4 == 0 && lane == 0) {
    bulk_wait_all();
    fence_async_all();
    flag_add(FLAG_LM((h * 2 + cb) * 2 + (wg >> 1)));
    if (wg == 0) TS(1, 8);
  }
}

#define STAGE(s) (sb + (2 - (s)) * 65536)
template <int TR> __device__ __forceinline__ void proj_kb(float* acc, uint32_t st, uint32_t offA, uint32_t offB, int first) {
  const uint64_t da = make_desc(st + offA, TR ? 8192 : 16, 1024, 1);
  const uint64_t db = make_desc(st + offB, TR ? 16 : 8192, 1024, 1);
  wg_fence();
#pragma unroll
  for (int k = 0; k < 4; k++) wg_ss128<TR, 1 - TR>(acc, da + k * (TR ? 128 : 2), db + k * (TR ? 2 : 128), k != 0 || !first);
  wg_commit();
}
template <int TR> __device__ __forceinline__ void proj_loop(float* acc, uint32_t sb, uint32_t bars, uint32_t offA, uint32_t offB,
                                                            int wg, uint32_t sWKV) {
  mbar_wait(BAR_FULL(0), 0);
  if (threadIdx.x == 0) TS(0, 2);
  proj_kb<TR>(acc, STAGE(0), offA, offB, 1);
  {
    float kv[4];
    mbar_wait(BAR_XA, 0);
    const uint64_t da = make_desc(STAGE(2) + wg * 16384, 16, 1024, 1), db = make_desc(sWKV + wg * 2048, 128, 128, 0);
    wg_fence();
#pragma unroll
    for (int k = 0; k < 8; k++) wg_ss8<0, 1>(kv, da + (k >> 2) * 512 + (k & 3) * 2, db + k * 16, k != 0);
    wg_commit();
    mbar_wait(BAR_FULL(1), 0);
    if (threadIdx.x == 0) TS(0, 3);
    proj_kb<TR>(acc, STAGE(1), offA, offB, 0);
    wg_wait<1>();
    fence_regs<4>(kv);
    named_bar(wg + 1, 128);
    sts4(sWKV + threadIdx.x * 16, __float_as_uint(kv[0]), __float_as_uint(kv[1]), __float_as_uint(kv[2]), __float_as_uint(kv[3]));
    __syncwarp();
    if ((threadIdx.x & 31) == 0) mbar_arrive(BAR_GO);
    if ((threadIdx.x & 127) == 0) mbar_arrive(BAR_EMPTY(0));
    __syncwarp();
  }
  int s = 2, ph = 0, sp = 1;
#pragma unroll 1
  for (int kb = 2; kb < 8; kb++) {
    mbar_wait(BAR_FULL(s), ph);
    if (threadIdx.x == 0) TS(0, 2 + kb);
    proj_kb<TR>(acc, STAGE(s), offA, offB, 0);
    wg_wait<1>();
    if ((threadIdx.x & 127) == 0) mbar_arrive(BAR_EMPTY(sp));
    __syncwarp();
    sp = s;
    if (++s == 3) { s = 0; ph ^= 1; }
  }
  wg_wait<0>();
  fence_regs<64>(acc);
}

__device__ __forceinline__ uint32_t tail_slots(int t) {
  const uint32_t lo = t < 4 ? (t < 2 ? (t == 0 ? 0x0C0B0Au : 0x0F0E0Du) : (t == 2 ? 0x100400u : 0x081814u))
                            : (t < 6 ? (t == 4 ? 0x110501u : 0x021915u) : (t == 6 ? 0x161206u : (t == 7 ? 0x07031Au : 0x1B1713u)));
  return lo;
}

__global__ void __launch_bounds__(640, 1)
k1_main(const __grid_constant__ CUtensorMap mXA64, const __grid_constant__ CUtensorMap mXB,
        const __grid_constant__ CUtensorMap mWq, const __grid_constant__ CUtensorMap mWqkv,
        const __grid_constant__ CUtensorMap mQst, const __grid_constant__ CUtensorMap mOst,
        const __grid_constant__ CUtensorMap mO, const __grid_constant__ CUtensorMap mWoA,
        const __grid_constant__ CUtensorMap mWoB, const __grid_constant__ CUtensorMap mOut, const Params prm) {
  extern __shared__ uint8_t smem_raw[];
  const uint32_t sb = (smem_u32(smem_raw) + 1023u) & ~1023u;
  const uint32_t bars = sb + OFF_MISC, sM = bars + 512, sT = bars + 1024;
  const int tid = threadIdx.x, warp = __shfl_sync(~0u, tid >> 5, 0), wg = warp >> 2, w4 = warp & 3, lane = tid & 31;
  const bool helper = blockIdx.x >= 128;
  if (tid == 0) TS(0, 0);
  const int G = blockIdx.x >> 4, gi = blockIdx.x & 15;
  const int tbA = G * 4 + (gi >> 2), hg = gi & 3;
  const int ttB = (G >> 1) * 4 + (gi >> 2), hq = (G & 1) * 4 + (gi & 3);
  const int ttO = G * 2 + (gi >> 3), ct = gi & 7;
  auto issue = [&](int kb, int s) {
    const uint32_t fb = BAR_FULL(s), st = STAGE(s);
    mbar_expect_tx(fb, 65536);
    tma2d(st + 16384, &mXA64, kb * 64, tbA * 64, fb);
    tma2d(st, &mWq, hg * 128, kb * 64, fb);
    tma2d(st + 8192, &mWq, hg * 128 + 64, kb * 64, fb);
    tma2d(st + 49152, &mXB, kb * 64, ttB * 128, fb);
    tma2d(st + 24576, &mWqkv, hq * 64, kb * 64, fb);
    tma2d(st + 32768, &mWqkv, 512 + hq * 64, kb * 64, fb);
    tma2d(st + 40960, &mWqkv, 1024 + hq * 64, kb * 64, fb);
  };
  const uint32_t sOne = sb + OFF_V + 65536, sWKV = sOne + 24576;
  if (warp >= 16) {
    if (warp == 17) {
      if (lane == 0) {
        mbar_init(BAR_BDONE, 8); mbar_init(BAR_Q, 8); mbar_init(BAR_GO, helper ? 1 : 16); mbar_init(BAR_Q2, 5);
        mbar_init(BAR_OD(0), 16); mbar_init(BAR_OD(1), 16); mbar_init(BAR_CL(0), 1); mbar_init(BAR_FULL(2), 1);
        sts1(sM + 20, 0);
      }
      if (lane >= 1 && lane < 5) mbar_init(BAR_CL(lane), 4);
      if (lane >= 5 && lane < 8) { mbar_init(BAR_EMPTY(lane - 5), 4); mbar_init(BAR_KV(lane - 5), 1); }
      if (lane >= 8 && lane < 15) mbar_init(BAR_TE(lane - 8), 2);
      if (lane >= 16) mbar_init(BAR_TF(lane - 16), 1);
      asm volatile("fence.mbarrier_init.release.cluster;" ::: "memory");
    } else if (warp == 16 && !helper && elect_one()) {
      mbar_init(BAR_XA, 1); mbar_init(BAR_FULL(0), 1); mbar_init(BAR_FULL(1), 1);
      asm volatile("fence.mbarrier_init.release.cluster;" ::: "memory");
      issue(0, 0);
      mbar_expect_tx(BAR_XA, 65536);
#pragma unroll
      for (int kb = 0; kb < 8; kb++) tma2d(STAGE(2) + kb * 8192, &mXA64, kb * 64, tbA * 64, BAR_XA);
      issue(1, 1);
    }
  } else if (!helper) {
    const uint4 v = __ldg((const uint4*)(hg >= 2 ? prm.wv : prm.wk) + tid * 2 + (hg & 1));
#pragma unroll
    for (int i = 0; i < 3; i++) {
      const int key = tid + i * 512;
      sts4(sOne + key * 16, (key % STEPK) < 32 ? 0x00003F80u : 0x00004E80u, 0u, 0u, 0u);
    }
    sts4(sWKV + tid * 16, v.x, v.y, v.z, v.w);
    fence_async();
  }
  __syncthreads();
  if (wg == 4) {
    asm volatile("setmaxnreg.dec.sync.aligned.u32 32;");
    const uint32_t ep = g_epoch[blockIdx.x] + 1;
    if (helper) {
      if (w4 == 0 && elect_one()) {
        flag_wait(FLAG_B(blockIdx.x - 128), ep * 32);
        fence_async_all();
        TS(1, 10);
        mbar_arrive(BAR_GO);
        g_epoch[blockIdx.x] = ep;
      }
      return;
    }
    mbar_wait(BAR_GO, 0);
    if (w4 == 0 && elect_one()) issue(2, 2);
    {
      uint32_t a[4], b[4];
      float c[4];
      lds4(sWKV + (tid - 512) * 16, a);
      lds4(sWKV + 2048 + (tid - 512) * 16, b);
#pragma unroll
      for (int i = 0; i < 4; i++) c[i] = __uint_as_float(a[i]) + __uint_as_float(b[i]);
      lds4(sWKV + 4096 + (tid - 512) * 16, a);
      lds4(sWKV + 6144 + (tid - 512) * 16, b);
#pragma unroll
      for (int i = 0; i < 4; i++) c[i] += __uint_as_float(a[i]) + __uint_as_float(b[i]);
      sts1(sT + w4 * 256 + lane * 4, pack_bf16(c[0], c[1]));
      sts1(sT + w4 * 256 + 128 + lane * 4, pack_bf16(c[2], c[3]));
    }
    named_bar(9, 128);
    {
      const int t = tid - 512;
#pragma unroll
      for (int i = 0; i < 4; i++) {
        const int key = 1536 + t + i * 128;
        sts4(sOne + key * 16, (key % STEPK) < 32 ? 0x00003F80u : 0x00004E80u, 0u, 0u, 0u);
      }
      fence_async();
      __syncwarp();
      if (lane == 0) mbar_arrive(BAR_Q);
    }
    if (w4 == 0) {
      int s = 0, ph = 0;
#pragma unroll 1
      for (int kb = 3; kb < 8; kb++) {
        mbar_wait(BAR_EMPTY(s), ph);
        if (elect_one()) issue(kb, s);
        if (++s == 3) { s = 0; ph ^= 1; }
      }
      flag_wait(FLAG_KV, ep * 128);
      fence_async_all();
      if (lane == 0) TS(0, 11);
      mbar_wait(BAR_EMPTY(2), 1);
      mbar_wait(BAR_EMPTY(0), 0);
      if (elect_one()) {
#pragma unroll
        for (int c = 0; c < 3; c++) {
          const int k0 = c == 0 ? 0 : (c == 1 ? 7 * STEPK : 12 * STEPK), k1 = c == 0 ? 7 * STEPK : (c == 1 ? 12 * STEPK : S_TOK);
          const uint32_t bytes = (k1 - k0) * 16;
          mbar_expect_tx(BAR_KV(c), 4 * bytes);
#pragma unroll
          for (int p = 0; p < 4; p++)
            bulk_g2s(sb + (p < 2 ? OFF_K : OFF_V - 65536) + p * 32768 + k0 * 16, g_KV + p * S_TOK + k0, bytes, BAR_KV(c));
        }
      }
      mbar_wait(BAR_CL(1), 0);
      flag_wait(FLAG_LM((lane & 7) * 2 + (ttO >> 3)), ep);
      __syncwarp();
      fence_async_all();
      if (lane == 0) TS(2, 13);
#pragma unroll 1
      for (int n = 0; n < 8; n++) {
        mbar_wait(BAR_CL(n < 4 ? n >> 1 : (n == 4 ? 2 : (n < 7 ? 3 : 4))), 0);
        const uint32_t sl = tail_slots(n), fb = BAR_TF(n);
        if (elect_one()) {
          mbar_expect_tx(fb, 24576);
          tma2d(sb + (sl & 255) * 8192, &mWoB, ct * 64, n * 64, fb);
          tma2d(sb + ((sl >> 8) & 255) * 8192, &mO, n * 64, S_TOK + ttO * 128, fb);
          tma2d(sb + (sl >> 16) * 8192, &mO, n * 64, S_TOK + ttO * 128 + 64, fb);
        }
      }
      if (lane == 0) g_epoch[blockIdx.x] = ep;
    } else if (w4 == 3) {
      flag_wait(FLAG_KV, ep * 128);
      const uint4 a = *(const uint4*)(g_stats + lane * 4);
      const float kmax2 = __uint_as_float(__reduce_max_sync(~0u, a.x)) + __uint_as_float(__reduce_max_sync(~0u, a.y));
      const float vmax = __uint_as_float(__reduce_max_sync(~0u, max(a.z, a.w)));
      const float lv = vmax > 0.f ? __log2f(vmax) : 0.f;
      const float lim = fminf(90.f, fminf(91.f + lv, 95.f - lv));
      float thr = -1.f;
      if (vmax < 1e27f && kmax2 <= 65536.f && lim > 2.f) thr = fminf(60000.f, (lim * lim - 1.f) / (kmax2 * 1.02f + 1e-30f));
      if (lane == 0) { sts1(sM + 16, __float_as_uint(thr)); mbar_arrive(BAR_Q2); }
      mbar_wait(BAR_CL(3), 0);
#pragma unroll 1
      for (int n = 0; n < 8; n++) {
        if ((n & 3) == 0) {
          flag_wait(FLAG_OA(ttO * 8 + (lane & 7), n >> 2), ep);
          __syncwarp();
          fence_async_all();
          if (lane == 0 && n == 4) TS(2, 14);
        }
        const int gidx = n < 4 ? n + 9 : (n == 4 ? 8 : n + 8);
        const int kb = n < 4 ? n * 2 : (n - 4) * 2 + 1;
        mbar_wait(n == 4 ? BAR_CL(4) : BAR_TE(gidx - 9), 0);
        const uint32_t sl = tail_slots(n == 4 ? 8 : gidx - 9), fb = BAR_TF(gidx);
        if (elect_one()) {
          mbar_expect_tx(fb, 24576);
          tma2d(sb + (sl & 255) * 8192, &mWoA, ct * 64, kb * 64, fb);
          tma2d(sb + ((sl >> 8) & 255) * 8192, &mO, kb * 64, ttO * 128, fb);
          tma2d(sb + (sl >> 16) * 8192, &mO, kb * 64, ttO * 128 + 64, fb);
        }
      }
    } else {
      const int ch = tbA * 2 + (w4 - 1);
      uint32_t v[4], o[4];
      lds4(sT + (w4 - 1) * 512 + lane * 16, v);
      int kap;
      if (lane < 21) kap = lane * STEPK + 32 + ch;
      else { int idx = ch * 11 + (lane - 21); kap = (idx >> 5) * STEPK + (idx & 31); }
      g_KV[(4 + hg) * S_TOK + kap] = make_uint4(v[0], v[1], v[2], v[3]);
      float st = 0.f;
      if (hg < 2) {
        const float sc = lane < 21 ? 2.f : 1.f;
#pragma unroll
        for (int u = 0; u < 4; u++) {
          uint32_t pv = __shfl_up_sync(~0u, v[u], 1);
          if (lane == 0 || lane >= 21) pv = 0;
          const float x = bf_lo(v[u]), y = bf_hi(v[u]);
          st += x * x + y * y;
          o[u] = pack_f16((x - bf_lo(pv)) * sc, (y - bf_hi(pv)) * sc);
        }
      } else {
        const float sc = lane < 21 ? VSHIFT : 1.f;
#pragma unroll
        for (int u = 0; u < 4; u++) { float x = bf_lo(v[u]), y = bf_hi(v[u]); st += fabsf(x) + fabsf(y); o[u] = pack_bf16(x * sc, y * sc); }
      }
      g_KV[hg * S_TOK + kap] = make_uint4(o[0], o[1], o[2], o[3]);
      const uint32_t um = __reduce_max_sync(~0u, __float_as_uint(st) & 0x7FFFFFFFu);
      if (w4 == 2) { if (lane == 0) sts1(sM + 24, um); named_arrive(10, 64); }
      else {
        named_bar(10, 64);
        if (elect_one()) {
          g_stats[tbA * 4 + hg] = max(um, lds1(sM + 24));
          fence_async_all();
          flag_add(FLAG_KV);
          TS(1, 9);
          mbar_wait(BAR_BDONE, 0);
          tma2d_store(&mQst, sb + OFF_F + 49152, hq * 64, S_TOK + ttB * 128);
          bulk_commit();
          bulk_wait_all();
          fence_async_all();
          flag_add(FLAG_B(hq >> 1));
          TS(0, 12);
          mbar_wait(BAR_Q, 0);
          mbar_arrive(BAR_CL(0));
#pragma unroll 1
          for (int p = 0; p < 2; p++) {
            mbar_wait(BAR_OD(p), 0);
            fence_async_all();
            flag_add(FLAG_OA(blockIdx.x, p));
          }
          TS(2, 0);
        }
      }
    }
    return;
  }
  if (helper) { helper_cta(blockIdx.x - 128, sb, bars, wg, w4, &mQst, &mOst); return; }

  {
    float acc[64];
    if (wg == 0) proj_loop<0>(acc, sb, bars, 16384, 0, wg, sWKV);
    else proj_loop<1>(acc, sb, bars, 16384 + wg * 8192, 49152, wg, sWKV);
    asm volatile("setmaxnreg.inc.sync.aligned.u32 112;");
    if (tid == 0) TS(0, 10);
    const uint32_t sF = sb + OFF_F;
    if (wg == 0) {
      uint32_t r[32];
      const uint32_t qa = sF + w4 * 512 + ((lane >> 3) & 1) * 256 + (lane >> 4) * 128 + (lane & 7) * 16;
#pragma unroll
      for (int hd = 0; hd < 8; hd++) {
#pragma unroll
        for (int i = 0; i < 4; i++) r[4 * hd + i] = pack_f16(acc[8 * hd + 2 * i] * QSCALE, acc[8 * hd + 2 * i + 1] * QSCALE);
        stsm4(qa + hd * 2048, r[4 * hd], r[4 * hd + 1], r[4 * hd + 2], r[4 * hd + 3]);
        if (hd == 3) {
          fence_async();
          __syncwarp();
          if (lane == 0) mbar_arrive(BAR_Q);
        }
      }
      fence_async();
      uint32_t nmax = 0;
#pragma unroll
      for (int hd = 0; hd < 8; hd++) {
        const uint32_t* q = r + 4 * hd;
        const uint32_t t0 = hfma2(q[2], q[2], hfma2(q[0], q[0], 0u)), t1 = hfma2(q[3], q[3], hfma2(q[1], q[1], 0u));
        uint32_t n = hadd2(__byte_perm(t0, t1, 0x5410), __byte_perm(t0, t1, 0x7632));
        n = hadd2(n, __shfl_xor_sync(~0u, n, 1));
        n = hadd2(n, __shfl_xor_sync(~0u, n, 2));
        nmax = __vmaxu2(nmax, n & 0x7FFF7FFFu);
      }
      nmax = __reduce_max_sync(~0u, max(nmax & 0xFFFFu, nmax >> 16));
      if (lane == 0) sts1(sM + w4 * 4, nmax);
      uint4* gq = (uint4*)g_Q + blockIdx.x * 1024 + tid;
#pragma unroll
      for (int hd = 0; hd < 8; hd++)
        gq[hd * 128] = make_uint4(pack_bf16(acc[8 * hd], acc[8 * hd + 1]), pack_bf16(acc[8 * hd + 2], acc[8 * hd + 3]),
                                  pack_bf16(acc[8 * hd + 4], acc[8 * hd + 5]), pack_bf16(acc[8 * hd + 6], acc[8 * hd + 7]));
      __syncwarp();
      if (lane == 0) mbar_arrive(BAR_Q2);
    } else if (wg == 3) {
      named_arrive(8, 384);
      named_bar(6, 384);
      const int t = tid & 127;
#pragma unroll
      for (int j = 0; j < 8; j++)
        sts4(sF + 24576 + j * 2048 + t * 16, pack_bf16(acc[8 * j], acc[8 * j + 1]), pack_bf16(acc[8 * j + 2], acc[8 * j + 3]),
             pack_bf16(acc[8 * j + 4], acc[8 * j + 5]), pack_bf16(acc[8 * j + 6], acc[8 * j + 7]));
      named_arrive(7, 256);
    } else {
      uint32_t p[32];
      named_arrive(6, 384);
      if (wg == 2) named_arrive(8, 384);
#pragma unroll
      for (int i = 0; i < 32; i++) p[i] = phi2(acc[2 * i], acc[2 * i + 1]);
      if (wg == 1) {
        named_bar(8, 384);
        const int m = lane >> 3, r = lane & 7;
#pragma unroll
        for (int j = 0; j < 16; j += 2) {
          const int tok = (j + (m >> 1)) * 8 + r;
          const int chunk = w4 * 2 + (m & 1);
          stsm4t(sF + 49152 + tok * 128 + ((chunk ^ r) << 4), p[2 * j], p[2 * j + 1], p[2 * j + 2], p[2 * j + 3]);
        }
        fence_async();
      } else {
        named_bar(7, 256);
        float kv0[4] = {0, 0, 0, 0}, kv1[4] = {0, 0, 0, 0}, z0[4] = {0, 0, 0, 0}, z1[4] = {0, 0, 0, 0};
        const uint32_t one = 0x3F803F80u;
        const int t = tid & 127;
#pragma unroll
        for (int j = 0; j < 8; j++) {
          uint32_t a[4];
          lds4(sF + 24576 + j * 2048 + t * 16, a);
          mma_bf16(kv0, a[0], a[1], a[2], a[3], p[4 * j], p[4 * j + 2]);
          mma_bf16(kv1, a[0], a[1], a[2], a[3], p[4 * j + 1], p[4 * j + 3]);
          mma_bf16(z0, one, one, one, one, p[4 * j], p[4 * j + 2]);
          mma_bf16(z1, one, one, one, one, p[4 * j + 1], p[4 * j + 3]);
        }
        float4* dst = g_kvp + ((ttB * 32 + hq * 4 + w4) * 3) * 32 + lane;
        dst[0] = make_float4(kv0[0], kv0[1], kv1[0], kv1[1]);
        dst[32] = make_float4(kv0[2], kv0[3], kv1[2], kv1[3]);
        dst[64] = make_float4(z0[0], z0[1], z1[0], z1[1]);
      }
      __syncwarp();
      if (lane == 0) mbar_arrive(BAR_BDONE);
    }
  }

  mbar_wait(BAR_Q, 0);
  if (tid == 0) TS(1, 1);
  __nv_bfloat16* const obase = g_O + (size_t)(tbA * 64) * D_MOD + (hg * 8 + wg) * 16;
  bool safe = true;
  {
    const uint32_t c63 = 0x1F801F80u + (threadIdx.x >> 20);
    const uint32_t m1 = (gridDim.x >> 20) - 1u;
    const uint64_t dK0 = make_desc(sb + OFF_K, 32768, 128, 0);
    const uint64_t dV0 = make_desc(sb + OFF_V, 128, 32768, 0);
    constexpr uint32_t dKV = ((2048u - 8u)  __H0__ ) + STEPK - (OFF_V - OFF_K) / 16;
    mbar_wait(BAR_KV(0), 0);
#pragma unroll 1
    for (int pass = 0; pass < 2; pass++) {
      const uint64_t dQ = make_desc(sb + OFF_F + (pass * 4 + wg) * 2048, 128, 256, 0);
      float Sm[16], Sp[32], O[12];
      uint32_t P[24];
#pragma unroll
      for (int i = 0; i < 32; i++) Sp[i] = SMAGIC;
#pragma unroll
      for (int i = 0; i < 16; i++) Sm[i] = 0.f;
#pragma unroll
      for (int i = 0; i < 12; i++) O[i] = 0.f;
      fence_regs<16>(Sm); fence_regs<32>(Sp); fence_regs<12>(O);
      if (tid == 0) TS(1, 2 + 2 * pass);
      wg_fence();
      wg_qs32<0>(Sm, dQ, dK0);
      wg_qs64<1>(Sp, dQ, dK0 + 32);
      wg_commit();
      wg_wait<0>();
      fence_regs<16>(Sm); fence_regs<32>(Sp);
      uint32_t vlo = (uint32_t)dV0;
#pragma unroll 1
      for (int seg = 0; seg < 4; seg++) {
        if (seg >= 1) {
          if (seg < 3) mbar_wait(BAR_KV(seg), 0);
          if (pass == 1 && (tid & 127) == 0) mbar_arrive(BAR_CL(seg));
          __syncwarp();
        }
        const uint32_t vend = vlo + (seg == 0 ? 6 : 5) * STEPK;
#pragma unroll 1
        for (; vlo != vend; vlo += STEPK) {
          uint64_t dK, dV;
          asm("mov.b64 %0, {%1, %2};" : "=l"(dK) : "r"(vlo + dKV), "r"(8u));
          asm("mov.b64 %0, {%1, %2};" : "=l"(dV) : "r"(vlo), "r"(2048u));
#pragma unroll
          for (int i = 0; i < 8; i++) P[i] = pack_bf16(ex2f(Sm[2 * i]), ex2f(Sm[2 * i + 1]));
#pragma unroll
          for (int i = 0; i < 16; i++) P[8 + i] = exp2_pair_fix(Sp[2 * i], Sp[2 * i + 1], c63, m1);
          fence_regs<24>(P);
          wg_fence();
          wg_qs32<0>(Sm, dQ, dK);
          wg_qs64<1>(Sp, dQ, dK + 32);
#pragma unroll
          for (int k = 0; k < 6; k++) wg_pv24<1>(O, &P[4 * k], dV + k * 16);
          wg_commit();
          wg_wait<0>();
          fence_regs<16>(Sm); fence_regs<32>(Sp); fence_regs<12>(O); fence_regs<24>(P);
        }
      }
#pragma unroll
      for (int i = 0; i < 8; i++) P[i] = pack_bf16(ex2f(Sm[2 * i]), ex2f(Sm[2 * i + 1]));
      fence_regs<8>(P);
      wg_fence();
      wg_pv24<1>(O, &P[0], dV0 + 21 * STEPK);
      wg_pv24<1>(O, &P[4], dV0 + 21 * STEPK + 16);
      wg_commit();
      wg_wait<0>();
      fence_regs<12>(O);
      if (pass == 0) {
        uint32_t n[4];
        mbar_wait(BAR_Q2, 0);
        lds4(sM, n);
        const float qn = __half2float(__ushort_as_half((unsigned short)max(max(n[0], n[1]), max(n[2], n[3]))));
        safe = __all_sync(~0u, qn <= __uint_as_float(lds1(sM + 16)));
        if (!safe) break;
      }
      const float l0 = __shfl_sync(~0u, O[8], lane & ~3), l1 = __shfl_sync(~0u, O[10], lane & ~3);
      const float i0 = rcpf(l0), i1 = rcpf(l1);
      uint32_t* op = (uint32_t*)(obase + pass * 64 + (size_t)(w4 * 16 + (lane >> 2)) * D_MOD) + (lane & 3);
      op[0] = pack_bf16(O[0] * i0, O[1] * i0);
      op[8 * 256] = pack_bf16(O[2] * i1, O[3] * i1);
      op[4] = pack_bf16(O[4] * i0, O[5] * i0);
      op[8 * 256 + 4] = pack_bf16(O[6] * i1, O[7] * i1);
      __syncwarp();
      if (lane == 0) mbar_arrive(BAR_OD(pass));
      if (tid == 0) TS(1, 3 + 2 * pass);
      if ((tid & 127) == 0 && pass == 1 && wg > 0) TS(1, 10 + wg);
    }
  }

  if (!safe) {
    if ((tid & 127) == 0) { mbar_arrive(BAR_CL(1)); mbar_arrive(BAR_CL(2)); mbar_arrive(BAR_CL(3)); }
#pragma unroll 1
    for (int pass = 0; pass < 2; pass++) {
      attn_slow((const uint4*)g_Q + blockIdx.x * 1024 + (pass * 4 + wg) * 128, obase + pass * 64);
      __syncwarp();
      if (lane == 0) mbar_arrive(BAR_OD(pass));
    }
  }

  {
    named_bar(wg + 1, 128);
    if ((tid & 127) == 0) {
      mbar_arrive(BAR_CL(4));
      uint32_t r;
      asm volatile("atom.shared.add.u32 %0, [%1], 1;" : "=r"(r) : "r"(sM + 20) : "memory");
      sts1(sM + 32 + wg * 4, r);
    }
    named_bar(wg + 1, 128);
    const int role = __shfl_sync(~0u, lds1(sM + 32 + wg * 4), 0);
    const int isA = role >> 1, hf = role & 1;
    float acc[32];
    uint32_t xs = 0;
    int prev = 0;
#pragma unroll 1
    for (int n = 0; n < 8; n++) {
      const int gidx = isA ? (n < 4 ? n + 9 : (n == 4 ? 8 : n + 8)) : n;
      const uint32_t sl = tail_slots(gidx < 9 ? gidx : gidx - 9);
      xs = sb + ((sl >> (8 + 8 * hf)) & 255) * 8192;
      const uint64_t da = make_desc(xs, 16, 1024, 1), db = make_desc(sb + (sl & 255) * 8192, 8192, 1024, 1);
      mbar_wait(BAR_TF(gidx), 0);
      if ((tid & 127) == 0 && role == 3) TS(2, 2 + n);
      wg_fence();
#pragma unroll
      for (int k = 0; k < 4; k++) wg_ss64<0, 1>(acc, da + k * 2, db + k * 128, (n | k) != 0);
      wg_commit();
      wg_wait<1>();
      if (!isA && n >= 1 && (tid & 127) == 0) mbar_arrive(BAR_TE(prev));
      __syncwarp();
      prev = n;
    }
    wg_wait<0>();
    fence_regs<32>(acc);
    named_bar(wg + 1, 128);
    const int m = lane >> 3, r = lane & 7;
#pragma unroll
    for (int j = 0; j < 8; j += 2) {
      const int row = w4 * 16 + (m & 1) * 8 + r;
      stsm4(xs + row * 128 + (((j + (m >> 1)) ^ r) << 4),
            pack_bf16(acc[4 * j], acc[4 * j + 1]), pack_bf16(acc[4 * j + 2], acc[4 * j + 3]),
            pack_bf16(acc[4 * j + 4], acc[4 * j + 5]), pack_bf16(acc[4 * j + 6], acc[4 * j + 7]));
    }
    fence_async();
    named_bar(wg + 1, 128);
    if (w4 == 0 && elect_one()) {
      tma2d_store(&mOut, xs, (isA ? 0 : 512) + ct * 64, ttO * 128 + hf * 64);
      bulk_commit();
      asm volatile("cp.async.bulk.wait_group.read 0;" ::: "memory");
      TS(2, 11 + (role >> 1));
    }
  }
}

typedef CUresult (*EncodeFn)(CUtensorMap*, CUtensorMapDataType, cuuint32_t, void*, const cuuint64_t*, const cuuint64_t*,
                             const cuuint32_t*, const cuuint32_t*, CUtensorMapInterleave, CUtensorMapSwizzle,
                             CUtensorMapL2promotion, CUtensorMapFloatOOBfill);

static void make_map(EncodeFn enc, CUtensorMap* m, const void* ptr, uint64_t cols, uint64_t rows, uint32_t bc, uint32_t br) {
  cuuint64_t dims[2] = {cols, rows};
  cuuint64_t strides[1] = {cols * 2};
  cuuint32_t box[2] = {bc, br};
  cuuint32_t es[2] = {1, 1};
  enc(m, CU_TENSOR_MAP_DATA_TYPE_BFLOAT16, 2, (void*)ptr, dims, strides, box, es, CU_TENSOR_MAP_INTERLEAVE_NONE,
      CU_TENSOR_MAP_SWIZZLE_128B, CU_TENSOR_MAP_L2_PROMOTION_L2_256B, CU_TENSOR_MAP_FLOAT_OOB_FILL_NONE);
}

extern "C" void kernel_launch(void* const* d_in, const int* in_sizes, int n_in, void* d_out, int out_size) {
  (void)in_sizes; (void)n_in; (void)out_size;
  static EncodeFn enc = nullptr;
  static void* pQ = nullptr; static void* pO = nullptr;
  if (!enc) {
    void* fn = nullptr; cudaDriverEntryPointQueryResult qr;
    cudaGetDriverEntryPoint("cuTensorMapEncodeTiled", &fn, cudaEnableDefault, &qr);
    enc = (EncodeFn)fn;
    cudaGetSymbolAddress(&pQ, g_Q);
    cudaGetSymbolAddress(&pO, g_O);
    cudaFuncSetAttribute(k1_main, cudaFuncAttributeMaxDynamicSharedMemorySize, SM_TOTAL);
  }
  CUtensorMap mXA64, mXB, mWq, mWqkv, mQst, mO, mOst, mWoA, mWoB, mOut;
  make_map(enc, &mXA64, d_in[0], 512, 2048, 64, 64);
  make_map(enc, &mWq, d_in[1], 512, 512, 64, 64);
  make_map(enc, &mWoA, d_in[4], 512, 512, 64, 64);
  make_map(enc, &mXB, d_in[5], 512, 2048, 64, 128);
  make_map(enc, &mWqkv, d_in[6], 1536, 512, 64, 64);
  make_map(enc, &mWoB, d_in[7], 512, 512, 64, 64);
  make_map(enc, &mQst, pQ, 512, 4096, 64, 128);
  make_map(enc, &mO, pO, 512, 4096, 64, 64);
  make_map(enc, &mOst, pO, 512, 4096, 64, 128);
  make_map(enc, &mOut, d_out, 1024, 2048, 64, 64);
  Params prm{(const __nv_bfloat16*)d_in[2], (const __nv_bfloat16*)d_in[3]};
  k1_main<<<132, 640, SM_TOTAL, cudaStreamPerThread>>>(mXA64, mXB, mWq, mWqkv, mQst, mOst, mO, mWoA, mWoB, mOut, prm);
}
```

```cpp
#include <cuda_runtime.h>
#include <cuda_bf16.h>
#include <cuda_fp16.h>
#include <cuda.h>
#include <stdint.h>

#define S_TOK 2048
#define D_MOD 512

__device__ __align__(1024) __nv_bfloat16 g_Q[2 * S_TOK * D_MOD];
__device__ __align__(1024) __nv_bfloat16 g_O[2 * S_TOK * D_MOD];
__device__ __align__(1024) uint4 g_KV[8 * S_TOK];
__device__ __align__(16) uint32_t g_stats[128];
__device__ __align__(16) float4 g_kvp[16 * 32 * 3 * 32];

#define TS(k, i) do {} while (0)
__device__ __forceinline__ uint32_t smem_u32(const void* p) { return (uint32_t)__cvta_generic_to_shared(p); }
__device__ __forceinline__ void mbar_init(uint32_t bar, int cnt) { asm volatile("mbarrier.init.shared::cta.b64 [%0], %1;" :: "r"(bar), "r"(cnt) : "memory"); }
__device__ __forceinline__ void mbar_expect_tx(uint32_t bar, uint32_t bytes) { asm volatile("mbarrier.arrive.expect_tx.shared::cta.b64 _, [%0], %1;" :: "r"(bar), "r"(bytes) : "memory"); }
__device__ __forceinline__ bool mbar_try(uint32_t bar, uint32_t parity) {
  uint32_t ok;
  asm volatile("{\n.reg .pred p;\nmbarrier.try_wait.parity.shared::cta.b64 p, [%1], %2;\nselp.b32 %0, 1, 0, p;\n}\n" : "=r"(ok) : "r"(bar), "r"(parity) : "memory");
  return ok;
}
__device__ __forceinline__ void mbar_wait(uint32_t bar, uint32_t parity) {
  asm volatile("{\n.reg .pred p;\n.reg .u32 c;\nmov.u32 c, 0;\n"
               "LW_%=:\n"
               "mbarrier.try_wait.parity.shared::cta.b64 p, [%0], %1;\n"
               "@p bra LD_%=;\n"
               "add.u32 c, c, 1;\n"
               "setp.lt.u32 p, c, 4000000;\n"
               "@p bra LW_%=;\n"
               "trap;\n"
               "LD_%=:\n}\n" :: "r"(bar), "r"(parity) : "memory");
}
__device__ __forceinline__ void mbar_arrive_cta(uint32_t bar, uint32_t cta) {
  asm volatile("{\n.reg .b32 ra;\nmapa.shared::cluster.u32 ra, %0, %1;\nmbarrier.arrive.shared::cluster.b64 _, [ra];\n}\n" :: "r"(bar), "r"(cta) : "memory");
}
__device__ __forceinline__ void cluster_sync() {
  asm volatile("barrier.cluster.arrive.relaxed.aligned;\nbarrier.cluster.wait.aligned;" ::: "memory");
}
__device__ __forceinline__ void tma2d(uint32_t dst, const CUtensorMap* m, int c0, int c1, uint32_t bar) {
  asm volatile("cp.async.bulk.tensor.2d.shared::cluster.global.mbarrier::complete_tx::bytes [%0], [%1, {%3, %4}], [%2];"
               :: "r"(dst), "l"(m), "r"(bar), "r"(c0), "r"(c1) : "memory");
}
__device__ __forceinline__ void tma2d_mc(uint32_t dst, const CUtensorMap* m, int c0, int c1, uint32_t bar, uint16_t mask) {
  asm volatile("cp.async.bulk.tensor.2d.shared::cluster.global.mbarrier::complete_tx::bytes.multicast::cluster [%0], [%1, {%3, %4}], [%2], %5;"
               :: "r"(dst), "l"(m), "r"(bar), "r"(c0), "r"(c1), "h"(mask) : "memory");
}
__device__ __forceinline__ void tma2d_store(const CUtensorMap* m, uint32_t src, int c0, int c1) {
  asm volatile("cp.async.bulk.tensor.2d.global.shared::cta.bulk_group [%0, {%2, %3}], [%1];"
               :: "l"(m), "r"(src), "r"(c0), "r"(c1) : "memory");
}
__device__ __forceinline__ void bulk_g2s(uint32_t dst, const void* src, uint32_t bytes, uint32_t bar) {
  asm volatile("cp.async.bulk.shared::cluster.global.mbarrier::complete_tx::bytes [%0], [%1], %2, [%3];"
               :: "r"(dst), "l"(src), "r"(bytes), "r"(bar) : "memory");
}
__device__ __forceinline__ void bulk_commit() { asm volatile("cp.async.bulk.commit_group;" ::: "memory"); }
__device__ __forceinline__ void bulk_wait_all() { asm volatile("cp.async.bulk.wait_group 0;" ::: "memory"); }
__device__ __forceinline__ void fence_async() { asm volatile("fence.proxy.async.shared::cta;" ::: "memory"); }
__device__ __forceinline__ void named_bar(int id, int n) { asm volatile("bar.sync %0, %1;" :: "r"(id), "r"(n) : "memory"); }
__device__ __forceinline__ void pdl_launch() { asm volatile("griddepcontrol.launch_dependents;" ::: "memory"); }
__device__ __forceinline__ void pdl_wait() { asm volatile("griddepcontrol.wait;" ::: "memory"); }
__device__ __forceinline__ void wg_fence() { asm volatile("wgmma.fence.sync.aligned;" ::: "memory"); }
__device__ __forceinline__ void wg_commit() { asm volatile("wgmma.commit_group.sync.aligned;" ::: "memory"); }
template <int n> __device__ __forceinline__ void wg_wait() { asm volatile("wgmma.wait_group.sync.aligned %0;" :: "n"(n) : "memory"); }
template <int n> __device__ __forceinline__ void fence_regs(float* r) {
#pragma unroll
  for (int i = 0; i < n; i++) asm volatile("" : "+f"(r[i]) :: "memory");
}
template <int n> __device__ __forceinline__ void fence_regs(uint32_t* r) {
#pragma unroll
  for (int i = 0; i < n; i++) asm volatile("" : "+r"(r[i]) :: "memory");
}
__device__ __forceinline__ uint64_t make_desc(uint32_t addr, uint32_t lbo, uint32_t sbo, uint32_t swz) {
  return (uint64_t)((addr & 0x3FFFF) >> 4) | ((uint64_t)(lbo >> 4) << 16) | ((uint64_t)(sbo >> 4) << 32) | ((uint64_t)swz << 62);
}
__device__ __forceinline__ float ex2f(float x) { float y; asm("ex2.approx.ftz.f32 %0, %1;" : "=f"(y) : "f"(x)); return y; }
__device__ __forceinline__ uint32_t pack_bf16(float lo, float hi) { uint32_t r; asm("cvt.rn.bf16x2.f32 %0, %1, %2;" : "=r"(r) : "f"(hi), "f"(lo)); return r; }
__device__ __forceinline__ uint32_t pack_f16(float lo, float hi) { uint32_t r; asm("cvt.rn.f16x2.f32 %0, %1, %2;" : "=r"(r) : "f"(hi), "f"(lo)); return r; }
__device__ __forceinline__ float bf_lo(uint32_t v) { return __uint_as_float(v << 16); }
__device__ __forceinline__ float bf_hi(uint32_t v) { return __uint_as_float(v & 0xFFFF0000u); }
__device__ __forceinline__ float rbf(float x) { return __bfloat162float(__float2bfloat16_rn(x)); }
__device__ __forceinline__ void stsm4(uint32_t a, uint32_t r0, uint32_t r1, uint32_t r2, uint32_t r3) {
  asm volatile("stmatrix.sync.aligned.m8n8.x4.shared.b16 [%0], {%1,%2,%3,%4};" :: "r"(a), "r"(r0), "r"(r1), "r"(r2), "r"(r3) : "memory");
}
__device__ __forceinline__ void stsm4t(uint32_t a, uint32_t r0, uint32_t r1, uint32_t r2, uint32_t r3) {
  asm volatile("stmatrix.sync.aligned.m8n8.x4.trans.shared.b16 [%0], {%1,%2,%3,%4};" :: "r"(a), "r"(r0), "r"(r1), "r"(r2), "r"(r3) : "memory");
}
__device__ __forceinline__ void mma_bf16(float* d, uint32_t a0, uint32_t a1, uint32_t a2, uint32_t a3, uint32_t b0, uint32_t b1) {
  asm volatile("mma.sync.aligned.m16n8k16.row.col.f32.bf16.bf16.f32 {%0,%1,%2,%3}, {%4,%5,%6,%7}, {%8,%9}, {%0,%1,%2,%3};"
               : "+f"(d[0]), "+f"(d[1]), "+f"(d[2]), "+f"(d[3]) : "r"(a0), "r"(a1), "r"(a2), "r"(a3), "r"(b0), "r"(b1));
}
template<int SD> __device__ __forceinline__ void wg_qk32(float* d, const uint32_t* a, uint64_t desc) {
  asm volatile("wgmma.mma_async.sync.aligned.m64n32k16.f32.f16.f16 {%0,%1,%2,%3,%4,%5,%6,%7,%8,%9,%10,%11,%12,%13,%14,%15}, {%16,%17,%18,%19}, %20, %21, 1, 1, 0;"
   : "+f"(d[0]),"+f"(d[1]),"+f"(d[2]),"+f"(d[3]),"+f"(d[4]),"+f"(d[5]),"+f"(d[6]),"+f"(d[7]),"+f"(d[8]),"+f"(d[9]),"+f"(d[10]),"+f"(d[11]),"+f"(d[12]),"+f"(d[13]),"+f"(d[14]),"+f"(d[15])
   : "r"(a[0]),"r"(a[1]),"r"(a[2]),"r"(a[3]),"l"(desc),"n"(SD));
}
template<int SD> __device__ __forceinline__ void wg_qk64(float* d, const uint32_t* a, uint64_t desc) {
  asm volatile("wgmma.mma_async.sync.aligned.m64n64k16.f32.f16.f16 {%0,%1,%2,%3,%4,%5,%6,%7,%8,%9,%10,%11,%12,%13,%14,%15,%16,%17,%18,%19,%20,%21,%22,%23,%24,%25,%26,%27,%28,%29,%30,%31}, {%32,%33,%34,%35}, %36, %37, 1, 1, 0;"
   : "+f"(d[0]),"+f"(d[1]),"+f"(d[2]),"+f"(d[3]),"+f"(d[4]),"+f"(d[5]),"+f"(d[6]),"+f"(d[7]),"+f"(d[8]),"+f"(d[9]),"+f"(d[10]),"+f"(d[11]),"+f"(d[12]),"+f"(d[13]),"+f"(d[14]),"+f"(d[15]),"+f"(d[16]),"+f"(d[17]),"+f"(d[18]),"+f"(d[19]),"+f"(d[20]),"+f"(d[21]),"+f"(d[22]),"+f"(d[23]),"+f"(d[24]),"+f"(d[25]),"+f"(d[26]),"+f"(d[27]),"+f"(d[28]),"+f"(d[29]),"+f"(d[30]),"+f"(d[31])
   : "r"(a[0]),"r"(a[1]),"r"(a[2]),"r"(a[3]),"l"(desc),"n"(SD));
}
template<int SD> __device__ __forceinline__ void wg_qs32(float* d, uint64_t da, uint64_t db) {
  asm volatile("wgmma.mma_async.sync.aligned.m64n32k16.f32.f16.f16 {%0,%1,%2,%3,%4,%5,%6,%7,%8,%9,%10,%11,%12,%13,%14,%15}, %16, %17, %18, 1, 1, 0, 0;"
   : "+f"(d[0]),"+f"(d[1]),"+f"(d[2]),"+f"(d[3]),"+f"(d[4]),"+f"(d[5]),"+f"(d[6]),"+f"(d[7]),"+f"(d[8]),"+f"(d[9]),"+f"(d[10]),"+f"(d[11]),"+f"(d[12]),"+f"(d[13]),"+f"(d[14]),"+f"(d[15])
   : "l"(da),"l"(db),"n"(SD));
}
template<int SD> __device__ __forceinline__ void wg_qs64(float* d, uint64_t da, uint64_t db) {
  asm volatile("wgmma.mma_async.sync.aligned.m64n64k16.f32.f16.f16 {%0,%1,%2,%3,%4,%5,%6,%7,%8,%9,%10,%11,%12,%13,%14,%15,%16,%17,%18,%19,%20,%21,%22,%23,%24,%25,%26,%27,%28,%29,%30,%31}, %32, %33, %34, 1, 1, 0, 0;"
   : "+f"(d[0]),"+f"(d[1]),"+f"(d[2]),"+f"(d[3]),"+f"(d[4]),"+f"(d[5]),"+f"(d[6]),"+f"(d[7]),"+f"(d[8]),"+f"(d[9]),"+f"(d[10]),"+f"(d[11]),"+f"(d[12]),"+f"(d[13]),"+f"(d[14]),"+f"(d[15]),"+f"(d[16]),"+f"(d[17]),"+f"(d[18]),"+f"(d[19]),"+f"(d[20]),"+f"(d[21]),"+f"(d[22]),"+f"(d[23]),"+f"(d[24]),"+f"(d[25]),"+f"(d[26]),"+f"(d[27]),"+f"(d[28]),"+f"(d[29]),"+f"(d[30]),"+f"(d[31])
   : "l"(da),"l"(db),"n"(SD));
}
template<int SD> __device__ __forceinline__ void wg_pv24(float* d, const uint32_t* a, uint64_t desc) {
  asm volatile("wgmma.mma_async.sync.aligned.m64n24k16.f32.bf16.bf16 {%0,%1,%2,%3,%4,%5,%6,%7,%8,%9,%10,%11}, {%12,%13,%14,%15}, %16, %17, 1, 1, 1;"
   : "+f"(d[0]),"+f"(d[1]),"+f"(d[2]),"+f"(d[3]),"+f"(d[4]),"+f"(d[5]),"+f"(d[6]),"+f"(d[7]),"+f"(d[8]),"+f"(d[9]),"+f"(d[10]),"+f"(d[11])
   : "r"(a[0]),"r"(a[1]),"r"(a[2]),"r"(a[3]),"l"(desc),"n"(SD));
}
template<int TA, int TB> __device__ __forceinline__ void wg_ss128(float* d, uint64_t da, uint64_t db, int sd) {
  asm volatile("{\n.reg .pred p;\nsetp.ne.b32 p, %66, 0;\n"
   "wgmma.mma_async.sync.aligned.m64n128k16.f32.bf16.bf16 {%0,%1,%2,%3,%4,%5,%6,%7,%8,%9,%10,%11,%12,%13,%14,%15,%16,%17,%18,%19,%20,%21,%22,%23,%24,%25,%26,%27,%28,%29,%30,%31,%32,%33,%34,%35,%36,%37,%38,%39,%40,%41,%42,%43,%44,%45,%46,%47,%48,%49,%50,%51,%52,%53,%54,%55,%56,%57,%58,%59,%60,%61,%62,%63}, %64, %65, p, 1, 1, %67, %68;\n}\n"
   : "+f"(d[0]),"+f"(d[1]),"+f"(d[2]),"+f"(d[3]),"+f"(d[4]),"+f"(d[5]),"+f"(d[6]),"+f"(d[7]),"+f"(d[8]),"+f"(d[9]),"+f"(d[10]),"+f"(d[11]),"+f"(d[12]),"+f"(d[13]),"+f"(d[14]),"+f"(d[15]),"+f"(d[16]),"+f"(d[17]),"+f"(d[18]),"+f"(d[19]),"+f"(d[20]),"+f"(d[21]),"+f"(d[22]),"+f"(d[23]),"+f"(d[24]),"+f"(d[25]),"+f"(d[26]),"+f"(d[27]),"+f"(d[28]),"+f"(d[29]),"+f"(d[30]),"+f"(d[31]),"+f"(d[32]),"+f"(d[33]),"+f"(d[34]),"+f"(d[35]),"+f"(d[36]),"+f"(d[37]),"+f"(d[38]),"+f"(d[39]),"+f"(d[40]),"+f"(d[41]),"+f"(d[42]),"+f"(d[43]),"+f"(d[44]),"+f"(d[45]),"+f"(d[46]),"+f"(d[47]),"+f"(d[48]),"+f"(d[49]),"+f"(d[50]),"+f"(d[51]),"+f"(d[52]),"+f"(d[53]),"+f"(d[54]),"+f"(d[55]),"+f"(d[56]),"+f"(d[57]),"+f"(d[58]),"+f"(d[59]),"+f"(d[60]),"+f"(d[61]),"+f"(d[62]),"+f"(d[63])
   : "l"(da),"l"(db),"r"(sd),"n"(TA),"n"(TB));
}
template<int TA, int TB> __device__ __forceinline__ void wg_ss64(float* d, uint64_t da, uint64_t db, int sd) {
  asm volatile("{\n.reg .pred p;\nsetp.ne.b32 p, %34, 0;\n"
   "wgmma.mma_async.sync.aligned.m64n64k16.f32.bf16.bf16 {%0,%1,%2,%3,%4,%5,%6,%7,%8,%9,%10,%11,%12,%13,%14,%15,%16,%17,%18,%19,%20,%21,%22,%23,%24,%25,%26,%27,%28,%29,%30,%31}, %32, %33, p, 1, 1, %35, %36;\n}\n"
   : "+f"(d[0]),"+f"(d[1]),"+f"(d[2]),"+f"(d[3]),"+f"(d[4]),"+f"(d[5]),"+f"(d[6]),"+f"(d[7]),"+f"(d[8]),"+f"(d[9]),"+f"(d[10]),"+f"(d[11]),"+f"(d[12]),"+f"(d[13]),"+f"(d[14]),"+f"(d[15]),"+f"(d[16]),"+f"(d[17]),"+f"(d[18]),"+f"(d[19]),"+f"(d[20]),"+f"(d[21]),"+f"(d[22]),"+f"(d[23]),"+f"(d[24]),"+f"(d[25]),"+f"(d[26]),"+f"(d[27]),"+f"(d[28]),"+f"(d[29]),"+f"(d[30]),"+f"(d[31])
   : "l"(da),"l"(db),"r"(sd),"n"(TA),"n"(TB));
}

template<int TA, int TB> __device__ __forceinline__ void wg_ss8(float* d, uint64_t da, uint64_t db, int sd) {
  asm volatile("{\n.reg .pred p;\nsetp.ne.b32 p, %6, 0;\n"
   "wgmma.mma_async.sync.aligned.m64n8k16.f32.bf16.bf16 {%0,%1,%2,%3}, %4, %5, p, 1, 1, %7, %8;\n}\n"
   : "+f"(d[0]),"+f"(d[1]),"+f"(d[2]),"+f"(d[3])
   : "l"(da),"l"(db),"r"(sd),"n"(TA),"n"(TB));
}

template<int SD, uint32_t HI> __device__ __forceinline__ void wq32(float* d, uint64_t da, uint32_t lo) {
  asm volatile("{\n.reg .b64 db;\nmov.b64 db, {%17, %19};\n"
   "wgmma.mma_async.sync.aligned.m64n32k16.f32.f16.f16 {%0,%1,%2,%3,%4,%5,%6,%7,%8,%9,%10,%11,%12,%13,%14,%15}, %16, db, %18, 1, 1, 0, 0;\n}\n"
   : "+f"(d[0]),"+f"(d[1]),"+f"(d[2]),"+f"(d[3]),"+f"(d[4]),"+f"(d[5]),"+f"(d[6]),"+f"(d[7]),"+f"(d[8]),"+f"(d[9]),"+f"(d[10]),"+f"(d[11]),"+f"(d[12]),"+f"(d[13]),"+f"(d[14]),"+f"(d[15])
   : "l"(da),"r"(lo),"n"(SD),"r"(HI));
}
template<int SD, uint32_t HI> __device__ __forceinline__ void wq64(float* d, uint64_t da, uint32_t lo) {
  asm volatile("{\n.reg .b64 db;\nmov.b64 db, {%33, %35};\n"
   "wgmma.mma_async.sync.aligned.m64n64k16.f32.f16.f16 {%0,%1,%2,%3,%4,%5,%6,%7,%8,%9,%10,%11,%12,%13,%14,%15,%16,%17,%18,%19,%20,%21,%22,%23,%24,%25,%26,%27,%28,%29,%30,%31}, %32, db, %34, 1, 1, 0, 0;\n}\n"
   : "+f"(d[0]),"+f"(d[1]),"+f"(d[2]),"+f"(d[3]),"+f"(d[4]),"+f"(d[5]),"+f"(d[6]),"+f"(d[7]),"+f"(d[8]),"+f"(d[9]),"+f"(d[10]),"+f"(d[11]),"+f"(d[12]),"+f"(d[13]),"+f"(d[14]),"+f"(d[15]),"+f"(d[16]),"+f"(d[17]),"+f"(d[18]),"+f"(d[19]),"+f"(d[20]),"+f"(d[21]),"+f"(d[22]),"+f"(d[23]),"+f"(d[24]),"+f"(d[25]),"+f"(d[26]),"+f"(d[27]),"+f"(d[28]),"+f"(d[29]),"+f"(d[30]),"+f"(d[31])
   : "l"(da),"r"(lo),"n"(SD),"r"(HI));
}
template<int SD, uint32_t HI> __device__ __forceinline__ void wpv(float* d, const uint32_t* a, uint32_t lo) {
  asm volatile("{\n.reg .b64 db;\nmov.b64 db, {%16, %18};\n"
   "wgmma.mma_async.sync.aligned.m64n24k16.f32.bf16.bf16 {%0,%1,%2,%3,%4,%5,%6,%7,%8,%9,%10,%11}, {%12,%13,%14,%15}, db, %17, 1, 1, 1;\n}\n"
   : "+f"(d[0]),"+f"(d[1]),"+f"(d[2]),"+f"(d[3]),"+f"(d[4]),"+f"(d[5]),"+f"(d[6]),"+f"(d[7]),"+f"(d[8]),"+f"(d[9]),"+f"(d[10]),"+f"(d[11])
   : "r"(a[0]),"r"(a[1]),"r"(a[2]),"r"(a[3]),"r"(lo),"n"(SD),"r"(HI));
}

__device__ __forceinline__ uint32_t phi2(float a, float b) {
  uint32_t r, e;
  asm("cvt.rn.relu.bf16x2.f32 %0, %1, %2;" : "=r"(r) : "f"(b), "f"(a));
  e = pack_bf16(ex2f(a * 1.4426950408889634f), ex2f(b * 1.4426950408889634f));
  asm("add.rn.bf16x2 %0, %0, %1;" : "+r"(e) : "r"(0x35863586u));
  asm("min.NaN.bf16x2 %0, %0, %1;" : "+r"(e) : "r"(0x3F803F80u));
  asm("add.rn.bf16x2 %0, %0, %1;" : "+r"(e) : "r"(r));
  return e;
}

__device__ __forceinline__ void mbar_arrive(uint32_t bar) { asm volatile("mbarrier.arrive.shared::cta.b64 _, [%0];" :: "r"(bar) : "memory"); }
__device__ __forceinline__ void named_arrive(int id, int n) { asm volatile("bar.arrive %0, %1;" :: "r"(id), "r"(n) : "memory"); }
__device__ __forceinline__ void fence_async_all() { asm volatile("fence.proxy.async.global;" ::: "memory"); }
__device__ __forceinline__ void flag_add(uint32_t* f) { asm volatile("fence.acq_rel.gpu;\nred.relaxed.gpu.global.add.u32 [%0], 1;" :: "l"(f) : "memory"); }
__device__ __forceinline__ void flag_wait(const uint32_t* f, uint32_t target) {
  uint32_t v;
#pragma unroll 1
  for (int it = 0;; it++) {
    asm volatile("ld.acquire.gpu.global.u32 %0, [%1];" : "=r"(v) : "l"(f) : "memory");
    if ((int32_t)(v - target) >= 0) break;
    if (it > 2000000) __trap();
    __nanosleep(64);
  }
}
__device__ __forceinline__ bool elect_one() {
  uint32_t p;
  asm volatile("{\n.reg .pred P;\nelect.sync _|P, 0xFFFFFFFF;\nselp.b32 %0, 1, 0, P;\n}\n" : "=r"(p));
  return p;
}
__device__ __forceinline__ void lds4(uint32_t a, uint32_t* r) {
  asm volatile("ld.shared.v4.b32 {%0,%1,%2,%3}, [%4];" : "=r"(r[0]), "=r"(r[1]), "=r"(r[2]), "=r"(r[3]) : "r"(a) : "memory");
}
__device__ __forceinline__ uint32_t lds1(uint32_t a) { uint32_t r; asm volatile("ld.shared.b32 %0, [%1];" : "=r"(r) : "r"(a) : "memory"); return r; }
__device__ __forceinline__ void sts1(uint32_t a, uint32_t v) { asm volatile("st.shared.b32 [%0], %1;" :: "r"(a), "r"(v) : "memory"); }
__device__ __forceinline__ void sts4(uint32_t a, uint32_t r0, uint32_t r1, uint32_t r2, uint32_t r3) {
  asm volatile("st.shared.v4.b32 [%0], {%1,%2,%3,%4};" :: "r"(a), "r"(r0), "r"(r1), "r"(r2), "r"(r3) : "memory");
}
__device__ __forceinline__ void ldsm4(uint32_t a, uint32_t* r) {
  asm volatile("ldmatrix.sync.aligned.m8n8.x4.shared.b16 {%0,%1,%2,%3}, [%4];" : "=r"(r[0]), "=r"(r[1]), "=r"(r[2]), "=r"(r[3]) : "r"(a) : "memory");
}
__device__ __forceinline__ float rcpf(float x) { float y; asm("rcp.approx.ftz.f32 %0, %1;" : "=f"(y) : "f"(x)); return y; }
__device__ __forceinline__ uint32_t hfma2(uint32_t a, uint32_t b, uint32_t c) { uint32_t r; asm("fma.rn.f16x2 %0, %1, %2, %3;" : "=r"(r) : "r"(a), "r"(b), "r"(c)); return r; }
__device__ __forceinline__ uint32_t hadd2(uint32_t a, uint32_t b) { uint32_t r; asm("add.rn.f16x2 %0, %1, %2;" : "=r"(r) : "r"(a), "r"(b)); return r; }

#define STEPK 96
#define QSCALE 0.36067376022224085f
#define SMAGIC (512.0f + 2.0f * (191.0f - 30.0f - 1.5823545f))
#define VSHIFT 1073741824.0f

__device__ uint32_t g_epoch[132];
__device__ uint32_t g_flag[288 * 8];
#define FLAG_KV (g_flag)
#define FLAG_B(h) (g_flag + (4 + (h)) * 8)
#define FLAG_OA(cta, pass) (g_flag + (16 + (cta) * 2 + (pass)) * 8)
#define FLAG_LM(i) (g_flag + (272 + (i)) * 8)

#define SM_TOTAL (224 * 1024 + 2048 + 1024)
#define OFF_K 0
#define OFF_F 65536
#define OFF_V 131072
#define OFF_MISC (224 * 1024)

#define BAR_FULL(s) (bars + 8 * (s))
#define BAR_EMPTY(s) (bars + 24 + 8 * (s))
#define BAR_KV(c) (bars + 48 + 8 * (c))
#define BAR_BDONE (bars + 80)
#define BAR_Q (bars + 88)
#define BAR_GO (bars + 96)
#define BAR_Q2 (bars + 104)
#define BAR_OD(p) (bars + 112 + 8 * (p))
#define BAR_CL(c) (bars + 128 + 8 * (c))
#define BAR_TE(i) (bars + 168 + 8 * (i))
#define BAR_TF(g) (bars + 224 + 8 * (g))
#define BAR_XA(w) (bars + 352 + 8 * (w))
#define BAR_VB(c) (bars + 384 + 8 * (c))

__device__ __forceinline__ uint32_t exp2_pair_fix(float d0, float d1, uint32_t c63, uint32_t m1) {
  uint32_t w, y, s, r;
  asm("prmt.b32 %0, %1, %2, 0x6521;" : "=r"(w) : "r"(__float_as_uint(d0)), "r"(__float_as_uint(d1)));
  asm("lop3.b32 %0, %1, 0x007F007F, %2, 0xEA;" : "=r"(y) : "r"(w), "r"(c63));
  asm("mad.lo.u32 %0, %1, %2, %3;" : "=r"(s) : "r"(y), "r"(m1), "r"(w));
  asm("fma.rn.bf16x2 %0, %1, %2, %3;" : "=r"(r) : "r"(w), "r"(y), "r"(s));
  return r;
}

__device__ __forceinline__ void attn_slow(const uint4* gq, __nv_bfloat16* dst) {
  const int t = threadIdx.x & 127;
  const int row = t >> 1, half = t & 1;
  float q[16];
#pragma unroll
  for (int i = 0; i < 4; i++) {
    const uint4 v = gq[(row >> 4) * 32 + (row & 7) * 4 + i];
    const uint32_t lo = (row & 8) ? v.y : v.x, hi = (row & 8) ? v.w : v.z;
    q[2 * i] = bf_lo(lo); q[2 * i + 1] = bf_hi(lo); q[2 * i + 8] = bf_lo(hi); q[2 * i + 9] = bf_hi(hi);
  }
  float m = -INFINITY, l = 0.f, o[16];
#pragma unroll
  for (int i = 0; i < 16; i++) o[i] = 0.f;
#pragma unroll 1
  for (int j = half * 1024; j < half * 1024 + 1024; j++) {
    uint4 ka = g_KV[4 * S_TOK + j], kb = g_KV[5 * S_TOK + j];
    uint4 va = g_KV[6 * S_TOK + j], vb = g_KV[7 * S_TOK + j];
    uint32_t kk[8] = {ka.x, ka.y, ka.z, ka.w, kb.x, kb.y, kb.z, kb.w};
    uint32_t vv[8] = {va.x, va.y, va.z, va.w, vb.x, vb.y, vb.z, vb.w};
    float s = 0.f;
#pragma unroll
    for (int i = 0; i < 8; i++) { s = fmaf(q[2 * i], bf_lo(kk[i]), s); s = fmaf(q[2 * i + 1], bf_hi(kk[i]), s); }
    s = rbf(s) * 0.25f;
    if (s > m) {
      float c = __expf(m - s);
      l *= c;
#pragma unroll
      for (int i = 0; i < 16; i++) o[i] *= c;
      m = s;
    }
    float p = __expf(s - m);
    l += p;
#pragma unroll
    for (int i = 0; i < 8; i++) { o[2 * i] = fmaf(p, bf_lo(vv[i]), o[2 * i]); o[2 * i + 1] = fmaf(p, bf_hi(vv[i]), o[2 * i + 1]); }
  }
  float m2 = __shfl_xor_sync(~0u, m, 1);
  float mm = fmaxf(m, m2);
  float c = __expf(m - mm);
  l *= c; l += __shfl_xor_sync(~0u, l, 1);
  float inv = 1.f / l;
  uint32_t r[8];
#pragma unroll
  for (int i = 0; i < 16; i++) { o[i] *= c; o[i] += __shfl_xor_sync(~0u, o[i], 1); o[i] *= inv; }
#pragma unroll
  for (int i = 0; i < 8; i++) r[i] = pack_bf16(o[2 * i], o[2 * i + 1]);
  uint4* d = (uint4*)(dst + (size_t)row * D_MOD);
  if (half == 0) d[0] = make_uint4(r[0], r[1], r[2], r[3]); else d[1] = make_uint4(r[4], r[5], r[6], r[7]);
}

struct Params { const __nv_bfloat16* wk; const __nv_bfloat16* wv; };

__device__ __forceinline__ void helper_cta(const int h, const uint32_t sb, const uint32_t bars, const int wg, const int w4,
                                           const CUtensorMap* mQ, const CUtensorMap* mOs) {
  const int lane = threadIdx.x & 31;
  mbar_wait(BAR_GO, 0);
  const int cb = wg & 1, col = h * 128 + cb * 64, row0 = S_TOK + (wg >> 1) * 1024;
  const uint32_t buf = sb + wg * 49152;
  if (w4 == 0 && elect_one()) {
    fence_async_all();
#pragma unroll 1
    for (int u = 0; u < 3; u++) {
      mbar_expect_tx(BAR_TF(wg * 3 + u), 16384);
      tma2d(buf + u * 16384, mQ, col, row0 + u * 128, BAR_TF(wg * 3 + u));
    }
  }
  const int head = h * 8 + cb * 4 + w4;
  float4 a0 = make_float4(0, 0, 0, 0), a1 = a0, a2 = a0;
#pragma unroll 8
  for (int tt = 0; tt < 16; tt++) {
    const float4* src = g_kvp + ((tt * 32 + head) * 3) * 32 + lane;
    float4 u = src[0], v = src[32], w = src[64];
    a0.x += u.x; a0.y += u.y; a0.z += u.z; a0.w += u.w;
    a1.x += v.x; a1.y += v.y; a1.z += v.z; a1.w += v.w;
    a2.x += w.x; a2.y += w.y; a2.z += w.z; a2.w += w.w;
  }
  const uint32_t b00 = pack_bf16(a0.x, a0.y), b01 = pack_bf16(a0.z, a0.w);
  const uint32_t b10 = pack_bf16(a1.x, a1.y), b11 = pack_bf16(a1.z, a1.w);
  const uint32_t bz0 = pack_bf16(a2.x, a2.y), bz1 = pack_bf16(a2.z, a2.w);
  const int m = lane >> 3, r = lane & 7;
  const uint32_t off = ((m & 1) * 8 + r) * 128 + (((w4 * 2 + (m >> 1)) ^ r) << 4);
  int s = 0, ph = 0;
#pragma unroll 1
  for (int u = 0; u < 8; u++) {
    const uint32_t bb = buf + s * 16384;
    mbar_wait(BAR_TF(wg * 3 + s), ph);
#pragma unroll
    for (int mt = 0; mt < 8; mt++) {
      uint32_t a[4];
      ldsm4(bb + mt * 2048 + off, a);
      float n0[4] = {0, 0, 0, 0}, n1[4] = {0, 0, 0, 0}, dn[4] = {0, 0, 0, 0};
      mma_bf16(dn, a[0], a[1], a[2], a[3], bz0, bz1);
      mma_bf16(n0, a[0], a[1], a[2], a[3], b00, b01);
      mma_bf16(n1, a[0], a[1], a[2], a[3], b10, b11);
      const float i0 = rcpf(dn[0] + 1e-6f), i1 = rcpf(dn[2] + 1e-6f);
      stsm4(bb + mt * 2048 + off, pack_bf16(n0[0] * i0, n0[1] * i0), pack_bf16(n0[2] * i1, n0[3] * i1),
            pack_bf16(n1[0] * i0, n1[1] * i0), pack_bf16(n1[2] * i1, n1[3] * i1));
    }
    fence_async();
    named_bar(wg + 1, 128);
    if (w4 == 0 && lane == 0) {
      tma2d_store(mOs, bb, col, row0 + u * 128);
      bulk_commit();
      if (u >= 1 && u + 2 < 8) {
        asm volatile("cp.async.bulk.wait_group.read 1;" ::: "memory");
        const int sp = s == 0 ? 2 : s - 1;
        mbar_expect_tx(BAR_TF(wg * 3 + sp), 16384);
        tma2d(buf + sp * 16384, mQ, col, row0 + (u + 2) * 128, BAR_TF(wg * 3 + sp));
      }
    }
    __syncwarp();
    if (++s == 3) { s = 0; ph ^= 1; }
  }
  if (w4 == 0 && lane == 0) {
    bulk_wait_all();
    fence_async_all();
    flag_add(FLAG_LM((h * 2 + cb) * 2 + (wg >> 1)));
    if (wg == 0) TS(1, 8);
  }
}

#define STAGE(s) (sb + (2 - (s)) * 65536)
template <int TR> __device__ __forceinline__ void proj_kb(float* acc, uint32_t st, uint32_t offA, uint32_t offB, int first) {
  const uint64_t da = make_desc(st + offA, TR ? 8192 : 16, 1024, 1);
  const uint64_t db = make_desc(st + offB, TR ? 16 : 8192, 1024, 1);
  wg_fence();
#pragma unroll
  for (int k = 0; k < 4; k++) wg_ss128<TR, 1 - TR>(acc, da + k * (TR ? 128 : 2), db + k * (TR ? 2 : 128), k != 0 || !first);
  wg_commit();
}
template <int TR> __device__ __forceinline__ void proj_loop(float* acc, uint32_t sb, uint32_t bars, uint32_t offA, uint32_t offB,
                                                            int wg, uint32_t sWKV) {
  {
    float kv[4];
    mbar_wait(BAR_XA(wg), 0);
    if (threadIdx.x == 0) TS(0, 1);
    const uint64_t da = make_desc(STAGE(2) + wg * 16384, 16, 1024, 1), db = make_desc(sWKV + wg * 2048, 128, 128, 0);
    wg_fence();
#pragma unroll
    for (int k = 0; k < 8; k++) wg_ss8<0, 1>(kv, da + (k >> 2) * 512 + (k & 3) * 2, db + k * 16, k != 0);
    wg_commit();
    wg_wait<0>();
    fence_regs<4>(kv);
    named_bar(wg + 1, 128);
    sts4(sWKV + threadIdx.x * 16, __float_as_uint(kv[0]), __float_as_uint(kv[1]), __float_as_uint(kv[2]), __float_as_uint(kv[3]));
    __syncwarp();
    if ((threadIdx.x & 31) == 0) mbar_arrive(BAR_GO);
  }
  int s = 0, ph = 0, sp = 0;
#pragma unroll 1
  for (int kb = 0; kb < 8; kb++) {
    mbar_wait(BAR_FULL(s), ph);
    if (threadIdx.x == 0) TS(0, 2 + kb);
    proj_kb<TR>(acc, STAGE(s), offA, offB, kb == 0);
    wg_wait<1>();
    if (kb >= 1 && (threadIdx.x & 127) == 0) mbar_arrive(BAR_EMPTY(sp));
    __syncwarp();
    sp = s;
    if (++s == 3) { s = 0; ph ^= 1; }
  }
  wg_wait<0>();
  fence_regs<64>(acc);
}

__device__ __forceinline__ uint32_t tail_slots(int t) {
  const uint32_t lo = t < 4 ? (t < 2 ? (t == 0 ? 0x0C0B0Au : 0x0F0E0Du) : (t == 2 ? 0x100400u : 0x081814u))
                            : (t < 6 ? (t == 4 ? 0x110501u : 0x021915u) : (t == 6 ? 0x161206u : (t == 7 ? 0x07031Au : 0x1B1713u)));
  return lo;
}

__global__ void __launch_bounds__(640, 1)
k1_main(const __grid_constant__ CUtensorMap mXA64, const __grid_constant__ CUtensorMap mXB,
        const __grid_constant__ CUtensorMap mWq, const __grid_constant__ CUtensorMap mWqkv,
        const __grid_constant__ CUtensorMap mQst, const __grid_constant__ CUtensorMap mOst,
        const __grid_constant__ CUtensorMap mO, const __grid_constant__ CUtensorMap mWoA,
        const __grid_constant__ CUtensorMap mWoB, const __grid_constant__ CUtensorMap mOut, const Params prm) {
  extern __shared__ uint8_t smem_raw[];
  const uint32_t sb = (smem_u32(smem_raw) + 1023u) & ~1023u;
  const uint32_t bars = sb + OFF_MISC, sM = bars + 512, sT = bars + 1024;
  const int tid = threadIdx.x, warp = __shfl_sync(~0u, tid >> 5, 0), wg = warp >> 2, w4 = warp & 3, lane = tid & 31;
  const bool helper = blockIdx.x >= 128;
  if (tid == 0) TS(0, 0);
  const int G = blockIdx.x >> 4, gi = blockIdx.x & 15;
  const int tbA = G * 4 + (gi >> 2), hg = gi & 3;
  const int ttB = (G >> 1) * 4 + (gi >> 2), hq = (G & 1) * 4 + (gi & 3);
  const int ttO = G * 2 + (gi >> 3), ct = gi & 7;
  auto issue = [&](int kb, int s) {
    const uint32_t fb = BAR_FULL(s), st = STAGE(s);
    mbar_expect_tx(fb, 65536);
    tma2d(st + 16384, &mXA64, kb * 64, tbA * 64, fb);
    tma2d(st, &mWq, hg * 128, kb * 64, fb);
    tma2d(st + 8192, &mWq, hg * 128 + 64, kb * 64, fb);
    tma2d(st + 49152, &mXB, kb * 64, ttB * 128, fb);
    tma2d(st + 24576, &mWqkv, hq * 64, kb * 64, fb);
    tma2d(st + 32768, &mWqkv, 512 + hq * 64, kb * 64, fb);
    tma2d(st + 40960, &mWqkv, 1024 + hq * 64, kb * 64, fb);
  };
  const uint32_t sOne = sb + OFF_V + 65536, sWKV = sOne + 24576;
  if (warp >= 16) {
    if (warp == 17) {
      if (lane == 0) {
        mbar_init(BAR_BDONE, 8); mbar_init(BAR_Q, 8); mbar_init(BAR_GO, helper ? 1 : 16); mbar_init(BAR_Q2, 5);
        mbar_init(BAR_OD(0), 16); mbar_init(BAR_OD(1), 16); mbar_init(BAR_CL(0), 1); mbar_init(BAR_FULL(2), 1);
        sts1(sM + 20, 0);
      }
      if (lane >= 1 && lane < 5) mbar_init(BAR_CL(lane), 4);
      if (lane >= 5 && lane < 8) { mbar_init(BAR_EMPTY(lane - 5), 4); mbar_init(BAR_KV(lane - 5), 1); mbar_init(BAR_VB(lane - 5), 1); }
      if (lane >= 8 && lane < 15) mbar_init(BAR_TE(lane - 8), 2);
      if (lane >= 16) mbar_init(BAR_TF(lane - 16), 1);
      asm volatile("fence.mbarrier_init.release.cluster;" ::: "memory");
    } else if (warp == 16 && !helper && elect_one()) {
#pragma unroll
      for (int w = 0; w < 4; w++) mbar_init(BAR_XA(w), 1);
      mbar_init(BAR_FULL(0), 1); mbar_init(BAR_FULL(1), 1);
      asm volatile("fence.mbarrier_init.release.cluster;" ::: "memory");
#pragma unroll
      for (int w = 0; w < 4; w++) {
        mbar_expect_tx(BAR_XA(w), 16384);
        tma2d(STAGE(2) + w * 16384, &mXA64, w * 128, tbA * 64, BAR_XA(w));
        tma2d(STAGE(2) + w * 16384 + 8192, &mXA64, w * 128 + 64, tbA * 64, BAR_XA(w));
      }
      issue(0, 0);
      issue(1, 1);
    }
  } else if (!helper) {
    const uint4 v = __ldg((const uint4*)(hg >= 2 ? prm.wv : prm.wk) + tid * 2 + (hg & 1));
#pragma unroll
    for (int i = 0; i < 3; i++) {
      const int key = tid + i * 512;
      sts4(sOne + key * 16, (key % STEPK) < 32 ? 0x00003F80u : 0x00004E80u, 0u, 0u, 0u);
    }
    sts4(sWKV + tid * 16, v.x, v.y, v.z, v.w);
    fence_async();
  }
  __syncthreads();
  if (wg == 4) {
    asm volatile("setmaxnreg.dec.sync.aligned.u32 32;");
    const uint32_t ep = g_epoch[blockIdx.x] + 1;
    if (helper) {
      if (w4 == 0 && elect_one()) {
        flag_wait(FLAG_B(blockIdx.x - 128), ep * 32);
        fence_async_all();
        TS(1, 10);
        mbar_arrive(BAR_GO);
        g_epoch[blockIdx.x] = ep;
      }
      return;
    }
    mbar_wait(BAR_GO, 0);
    if (w4 == 0 && elect_one()) issue(2, 2);
    {
      uint32_t a[4], b[4];
      float c[4];
      lds4(sWKV + (tid - 512) * 16, a);
      lds4(sWKV + 2048 + (tid - 512) * 16, b);
#pragma unroll
      for (int i = 0; i < 4; i++) c[i] = __uint_as_float(a[i]) + __uint_as_float(b[i]);
      lds4(sWKV + 4096 + (tid - 512) * 16, a);
      lds4(sWKV + 6144 + (tid - 512) * 16, b);
#pragma unroll
      for (int i = 0; i < 4; i++) c[i] += __uint_as_float(a[i]) + __uint_as_float(b[i]);
      sts1(sT + w4 * 256 + lane * 4, pack_bf16(c[0], c[1]));
      sts1(sT + w4 * 256 + 128 + lane * 4, pack_bf16(c[2], c[3]));
    }
    named_bar(9, 128);
    {
      const int t = tid - 512;
#pragma unroll
      for (int i = 0; i < 4; i++) {
        const int key = 1536 + t + i * 128;
        sts4(sOne + key * 16, (key % STEPK) < 32 ? 0x00003F80u : 0x00004E80u, 0u, 0u, 0u);
      }
      fence_async();
      __syncwarp();
      if (lane == 0) mbar_arrive(BAR_Q);
    }
    if (w4 == 0) {
      int s = 0, ph = 0;
#pragma unroll 1
      for (int kb = 3; kb < 8; kb++) {
        mbar_wait(BAR_EMPTY(s), ph);
        if (elect_one()) issue(kb, s);
        if (++s == 3) { s = 0; ph ^= 1; }
      }
      flag_wait(FLAG_KV, ep * 128);
      fence_async_all();
      if (lane == 0) TS(0, 11);
#pragma unroll 1
      for (int m = 0; m < 2; m++) {
        mbar_wait(m == 0 ? BAR_EMPTY(2) : BAR_EMPTY(0), 1 - m);
        if (elect_one()) {
#pragma unroll
          for (int c = 0; c < 3; c++) {
            const int k0 = c == 0 ? 0 : (c == 1 ? 7 * STEPK : 12 * STEPK), k1 = c == 0 ? 7 * STEPK : (c == 1 ? 12 * STEPK : S_TOK);
            const uint32_t bytes = (k1 - k0) * 16, fb = m == 0 ? BAR_KV(c) : BAR_VB(c);
            mbar_expect_tx(fb, 2 * bytes);
#pragma unroll
            for (int p = 0; p < 2; p++)
              bulk_g2s(sb + m * OFF_V + p * 32768 + k0 * 16, g_KV + (m * 2 + p) * S_TOK + k0, bytes, fb);
          }
        }
      }
      mbar_wait(BAR_CL(1), 0);
      flag_wait(FLAG_LM((lane & 7) * 2 + (ttO >> 3)), ep);
      __syncwarp();
      fence_async_all();
      if (lane == 0) TS(2, 13);
#pragma unroll 1
      for (int n = 0; n < 8; n++) {
        mbar_wait(BAR_CL(n < 4 ? n >> 1 : (n == 4 ? 2 : (n < 7 ? 3 : 4))), 0);
        const uint32_t sl = tail_slots(n), fb = BAR_TF(n);
        if (elect_one()) {
          mbar_expect_tx(fb, 24576);
          tma2d(sb + (sl & 255) * 8192, &mWoB, ct * 64, n * 64, fb);
          tma2d(sb + ((sl >> 8) & 255) * 8192, &mO, n * 64, S_TOK + ttO * 128, fb);
          tma2d(sb + (sl >> 16) * 8192, &mO, n * 64, S_TOK + ttO * 128 + 64, fb);
        }
      }
      if (lane == 0) g_epoch[blockIdx.x] = ep;
    } else if (w4 == 3) {
      flag_wait(FLAG_KV, ep * 128);
      const uint4 a = *(const uint4*)(g_stats + lane * 4);
      const float kmax2 = __uint_as_float(__reduce_max_sync(~0u, a.x)) + __uint_as_float(__reduce_max_sync(~0u, a.y));
      const float vmax = __uint_as_float(__reduce_max_sync(~0u, max(a.z, a.w)));
      const float lv = vmax > 0.f ? __log2f(vmax) : 0.f;
      const float lim = fminf(90.f, fminf(91.f + lv, 95.f - lv));
      float thr = -1.f;
      if (vmax < 1e27f && kmax2 <= 65536.f && lim > 2.f) thr = fminf(60000.f, (lim * lim - 1.f) / (kmax2 * 1.02f + 1e-30f));
      if (lane == 0) { sts1(sM + 16, __float_as_uint(thr)); mbar_arrive(BAR_Q2); }
      mbar_wait(BAR_CL(3), 0);
      flag_wait(FLAG_OA(ttO * 8 + (lane & 7), 0), ep);
      __syncwarp();
      uint32_t pend = 0xF;
#pragma unroll 1
      for (int n = 0; n < 8; n++) {
        const int gidx = n < 4 ? n + 9 : (n == 4 ? 8 : n + 8);
        mbar_wait(n == 4 ? BAR_CL(4) : BAR_TE(gidx - 9), 0);
        int kb = n * 2;
        if (n >= 4) {
          uint32_t rdy;
#pragma unroll 1
          for (int it = 0;; it++) {
            uint32_t v;
            asm volatile("ld.acquire.gpu.global.u32 %0, [%1];" : "=r"(v) : "l"(FLAG_OA(ttO * 8 + (lane & 7), 1)) : "memory");
            const uint32_t b = __ballot_sync(~0u, (int32_t)(v - ep * 16) >= 0);
            rdy = b & (b >> 4) & pend;
            if (rdy) break;
            if (it > 2000000) __trap();
          }
          const int hsel = __ffs(rdy) - 1;
          pend &= ~(1u << hsel);
          kb = hsel * 2 + 1;
          if (lane == 0 && n == 7) TS(2, 14);
        }
        fence_async_all();
        const uint32_t sl = tail_slots(n == 4 ? 8 : gidx - 9), fb = BAR_TF(gidx);
        if (elect_one()) {
          mbar_expect_tx(fb, 24576);
          tma2d(sb + ((sl >> 8) & 255) * 8192, &mO, kb * 64, ttO * 128, fb);
          tma2d(sb + (sl >> 16) * 8192, &mO, kb * 64, ttO * 128 + 64, fb);
          tma2d(sb + (sl & 255) * 8192, &mWoA, ct * 64, kb * 64, fb);
        }
      }
    } else {
      const int ch = tbA * 2 + (w4 - 1);
      uint32_t v[4], o[4];
      lds4(sT + (w4 - 1) * 512 + lane * 16, v);
      int kap;
      if (lane < 21) kap = lane * STEPK + 32 + ch;
      else { int idx = ch * 11 + (lane - 21); kap = (idx >> 5) * STEPK + (idx & 31); }
      g_KV[(4 + hg) * S_TOK + kap] = make_uint4(v[0], v[1], v[2], v[3]);
      float st = 0.f;
      if (hg < 2) {
        const float sc = lane < 21 ? 2.f : 1.f;
#pragma unroll
        for (int u = 0; u < 4; u++) {
          uint32_t pv = __shfl_up_sync(~0u, v[u], 1);
          if (lane == 0 || lane >= 21) pv = 0;
          const float x = bf_lo(v[u]), y = bf_hi(v[u]);
          st += x * x + y * y;
          o[u] = pack_f16((x - bf_lo(pv)) * sc, (y - bf_hi(pv)) * sc);
        }
      } else {
        const float sc = lane < 21 ? VSHIFT : 1.f;
#pragma unroll
        for (int u = 0; u < 4; u++) { float x = bf_lo(v[u]), y = bf_hi(v[u]); st += fabsf(x) + fabsf(y); o[u] = pack_bf16(x * sc, y * sc); }
      }
      g_KV[hg * S_TOK + kap] = make_uint4(o[0], o[1], o[2], o[3]);
      const uint32_t um = __reduce_max_sync(~0u, __float_as_uint(st) & 0x7FFFFFFFu);
      if (w4 == 2) { if (lane == 0) sts1(sM + 24, um); named_arrive(10, 64); }
      else {
        named_bar(10, 64);
        if (elect_one()) {
          g_stats[tbA * 4 + hg] = max(um, lds1(sM + 24));
          fence_async_all();
          flag_add(FLAG_KV);
          TS(1, 9);
          mbar_wait(BAR_BDONE, 0);
          tma2d_store(&mQst, sb + OFF_F + 49152, hq * 64, S_TOK + ttB * 128);
          bulk_commit();
          bulk_wait_all();
          fence_async_all();
          flag_add(FLAG_B(hq >> 1));
          TS(0, 12);
          mbar_wait(BAR_Q, 0);
          mbar_arrive(BAR_CL(0));
          mbar_wait(BAR_OD(0), 0);
          fence_async_all();
          flag_add(FLAG_OA(blockIdx.x, 0));
        }
      }
    }
    return;
  }
  if (helper) { helper_cta(blockIdx.x - 128, sb, bars, wg, w4, &mQst, &mOst); return; }

  {
    float acc[64];
    if (wg == 0) proj_loop<0>(acc, sb, bars, 16384, 0, wg, sWKV);
    else proj_loop<1>(acc, sb, bars, 16384 + wg * 8192, 49152, wg, sWKV);
    asm volatile("setmaxnreg.inc.sync.aligned.u32 112;");
    if (tid == 0) TS(0, 10);
    const uint32_t sF = sb + OFF_F;
    if (wg == 0) {
      uint32_t r[32];
      const uint32_t qa = sF + w4 * 512 + ((lane >> 3) & 1) * 256 + (lane >> 4) * 128 + (lane & 7) * 16;
#pragma unroll
      for (int hd = 0; hd < 8; hd++) {
#pragma unroll
        for (int i = 0; i < 4; i++) r[4 * hd + i] = pack_f16(acc[8 * hd + 2 * i] * QSCALE, acc[8 * hd + 2 * i + 1] * QSCALE);
        stsm4(qa + hd * 2048, r[4 * hd], r[4 * hd + 1], r[4 * hd + 2], r[4 * hd + 3]);
        if (hd == 3) {
          fence_async();
          __syncwarp();
          if (lane == 0) mbar_arrive(BAR_Q);
        }
      }
      fence_async();
      uint32_t nmax = 0;
#pragma unroll
      for (int hd = 0; hd < 8; hd++) {
        const uint32_t* q = r + 4 * hd;
        const uint32_t t0 = hfma2(q[2], q[2], hfma2(q[0], q[0], 0u)), t1 = hfma2(q[3], q[3], hfma2(q[1], q[1], 0u));
        uint32_t n = hadd2(__byte_perm(t0, t1, 0x5410), __byte_perm(t0, t1, 0x7632));
        n = hadd2(n, __shfl_xor_sync(~0u, n, 1));
        n = hadd2(n, __shfl_xor_sync(~0u, n, 2));
        nmax = __vmaxu2(nmax, n & 0x7FFF7FFFu);
      }
      nmax = __reduce_max_sync(~0u, max(nmax & 0xFFFFu, nmax >> 16));
      if (lane == 0) sts1(sM + w4 * 4, nmax);
      uint4* gq = (uint4*)g_Q + blockIdx.x * 1024 + tid;
#pragma unroll
      for (int hd = 0; hd < 8; hd++)
        gq[hd * 128] = make_uint4(pack_bf16(acc[8 * hd], acc[8 * hd + 1]), pack_bf16(acc[8 * hd + 2], acc[8 * hd + 3]),
                                  pack_bf16(acc[8 * hd + 4], acc[8 * hd + 5]), pack_bf16(acc[8 * hd + 6], acc[8 * hd + 7]));
      __syncwarp();
      if (lane == 0) mbar_arrive(BAR_Q2);
    } else if (wg == 3) {
      named_arrive(8, 384);
      named_bar(6, 384);
      const int t = tid & 127;
#pragma unroll
      for (int j = 0; j < 8; j++)
        sts4(sF + 24576 + j * 2048 + t * 16, pack_bf16(acc[8 * j], acc[8 * j + 1]), pack_bf16(acc[8 * j + 2], acc[8 * j + 3]),
             pack_bf16(acc[8 * j + 4], acc[8 * j + 5]), pack_bf16(acc[8 * j + 6], acc[8 * j + 7]));
      named_arrive(7, 256);
    } else {
      uint32_t p[32];
      named_arrive(6, 384);
      if (wg == 2) named_arrive(8, 384);
#pragma unroll
      for (int i = 0; i < 32; i++) p[i] = phi2(acc[2 * i], acc[2 * i + 1]);
      if (wg == 1) {
        named_bar(8, 384);
        const int m = lane >> 3, r = lane & 7;
#pragma unroll
        for (int j = 0; j < 16; j += 2) {
          const int tok = (j + (m >> 1)) * 8 + r;
          const int chunk = w4 * 2 + (m & 1);
          stsm4t(sF + 49152 + tok * 128 + ((chunk ^ r) << 4), p[2 * j], p[2 * j + 1], p[2 * j + 2], p[2 * j + 3]);
        }
        fence_async();
      } else {
        named_bar(7, 256);
        float kv0[4] = {0, 0, 0, 0}, kv1[4] = {0, 0, 0, 0}, z0[4] = {0, 0, 0, 0}, z1[4] = {0, 0, 0, 0};
        const uint32_t one = 0x3F803F80u;
        const int t = tid & 127;
#pragma unroll
        for (int j = 0; j < 8; j++) {
          uint32_t a[4];
          lds4(sF + 24576 + j * 2048 + t * 16, a);
          mma_bf16(kv0, a[0], a[1], a[2], a[3], p[4 * j], p[4 * j + 2]);
          mma_bf16(kv1, a[0], a[1], a[2], a[3], p[4 * j + 1], p[4 * j + 3]);
          mma_bf16(z0, one, one, one, one, p[4 * j], p[4 * j + 2]);
          mma_bf16(z1, one, one, one, one, p[4 * j + 1], p[4 * j + 3]);
        }
        float4* dst = g_kvp + ((ttB * 32 + hq * 4 + w4) * 3) * 32 + lane;
        dst[0] = make_float4(kv0[0], kv0[1], kv1[0], kv1[1]);
        dst[32] = make_float4(kv0[2], kv0[3], kv1[2], kv1[3]);
        dst[64] = make_float4(z0[0], z0[1], z1[0], z1[1]);
      }
      __syncwarp();
      if (lane == 0) mbar_arrive(BAR_BDONE);
    }
  }

  mbar_wait(BAR_Q, 0);
  if (tid == 0) TS(1, 1);
  __nv_bfloat16* const obase = g_O + (size_t)(tbA * 64) * D_MOD + (hg * 8 + wg) * 16;
  bool safe = true;
  {
    const uint32_t c63 = 0x1F801F80u + (threadIdx.x >> 20);
    const uint32_t m1 = (gridDim.x >> 20) - 1u;
    const uint64_t dK0 = make_desc(sb + OFF_K, 32768, 128, 0);
    const uint64_t dV0 = make_desc(sb + OFF_V, 128, 32768, 0);
    constexpr uint32_t dKV = ((2048u - 8u)  __H0__ ) + STEPK - (OFF_V - OFF_K) / 16;
    mbar_wait(BAR_KV(0), 0);
#pragma unroll 1
    for (int pass = 0; pass < 2; pass++) {
      const uint64_t dQ = make_desc(sb + OFF_F + (pass * 4 + wg) * 2048, 128, 256, 0);
      float Sm[16], Sp[32], O[12];
      uint32_t P[24];
#pragma unroll
      for (int i = 0; i < 32; i++) Sp[i] = SMAGIC;
#pragma unroll
      for (int i = 0; i < 16; i++) Sm[i] = 0.f;
#pragma unroll
      for (int i = 0; i < 12; i++) O[i] = 0.f;
      fence_regs<16>(Sm); fence_regs<32>(Sp); fence_regs<12>(O);
      if (tid == 0) TS(1, 2 + 2 * pass);
      wg_fence();
      wg_qs32<0>(Sm, dQ, dK0);
      wg_qs64<1>(Sp, dQ, dK0 + 32);
      wg_commit();
      wg_wait<0>();
      fence_regs<16>(Sm); fence_regs<32>(Sp);
      uint32_t vlo = (uint32_t)dV0;
#pragma unroll 1
      for (int seg = 0; seg < 4; seg++) {
        if (pass == 0) {
          if (seg < 3) { mbar_wait(BAR_KV(seg), 0); mbar_wait(BAR_VB(seg), 0); }
        } else if (seg >= 1) {
          if ((tid & 127) == 0) mbar_arrive(BAR_CL(seg));
          __syncwarp();
        }
        if ((tid & 127) == 0) TS(4 + wg, pass * 5 + seg);
        const uint32_t vend = vlo + (seg == 0 ? 6 : 5) * STEPK;
#pragma unroll 1
        for (; vlo != vend; vlo += STEPK) {
          uint64_t dK, dV;
          asm("mov.b64 %0, {%1, %2};" : "=l"(dK) : "r"(vlo + dKV), "r"(8u));
          asm("mov.b64 %0, {%1, %2};" : "=l"(dV) : "r"(vlo), "r"(2048u));
#pragma unroll
          for (int i = 0; i < 8; i++) P[i] = pack_bf16(ex2f(Sm[2 * i]), ex2f(Sm[2 * i + 1]));
#pragma unroll
          for (int i = 0; i < 16; i++) P[8 + i] = exp2_pair_fix(Sp[2 * i], Sp[2 * i + 1], c63, m1);
          fence_regs<24>(P);
          wg_fence();
#pragma unroll
          for (int k = 0; k < 6; k++) wg_pv24<1>(O, &P[4 * k], dV + k * 16);
          wg_qs64<1>(Sp, dQ, dK + 32);
          wg_qs32<0>(Sm, dQ, dK);
          wg_commit();
          wg_wait<0>();
          fence_regs<16>(Sm); fence_regs<32>(Sp); fence_regs<12>(O); fence_regs<24>(P);
        }
      }
#pragma unroll
      for (int i = 0; i < 8; i++) P[i] = pack_bf16(ex2f(Sm[2 * i]), ex2f(Sm[2 * i + 1]));
      fence_regs<8>(P);
      wg_fence();
      wg_pv24<1>(O, &P[0], dV0 + 21 * STEPK);
      wg_pv24<1>(O, &P[4], dV0 + 21 * STEPK + 16);
      wg_commit();
      wg_wait<0>();
      fence_regs<12>(O);
      if (pass == 0) {
        uint32_t n[4];
        mbar_wait(BAR_Q2, 0);
        lds4(sM, n);
        const float qn = __half2float(__ushort_as_half((unsigned short)max(max(n[0], n[1]), max(n[2], n[3]))));
        safe = __all_sync(~0u, qn <= __uint_as_float(lds1(sM + 16)));
        if (!safe) break;
      }
      const float l0 = __shfl_sync(~0u, O[8], lane & ~3), l1 = __shfl_sync(~0u, O[10], lane & ~3);
      const float i0 = rcpf(l0), i1 = rcpf(l1);
      uint32_t* op = (uint32_t*)(obase + pass * 64 + (size_t)(w4 * 16 + (lane >> 2)) * D_MOD) + (lane & 3);
      op[0] = pack_bf16(O[0] * i0, O[1] * i0);
      op[8 * 256] = pack_bf16(O[2] * i1, O[3] * i1);
      op[4] = pack_bf16(O[4] * i0, O[5] * i0);
      op[8 * 256 + 4] = pack_bf16(O[6] * i1, O[7] * i1);
      __syncwarp();
      if (lane == 0) {
        if (pass == 0) mbar_arrive(BAR_OD(0));
        else { fence_async_all(); flag_add(FLAG_OA(blockIdx.x, 1)); }
      }
      if ((tid & 127) == 0) TS(4 + wg, pass * 5 + 4);
      if (tid == 0) TS(1, 3 + 2 * pass);
      if ((tid & 127) == 0 && pass == 1 && wg > 0) TS(1, 10 + wg);
    }
  }

  if (!safe) {
    if ((tid & 127) == 0) { mbar_arrive(BAR_CL(1)); mbar_arrive(BAR_CL(2)); mbar_arrive(BAR_CL(3)); }
#pragma unroll 1
    for (int pass = 0; pass < 2; pass++) {
      attn_slow((const uint4*)g_Q + blockIdx.x * 1024 + (pass * 4 + wg) * 128, obase + pass * 64);
      __syncwarp();
      if (lane == 0) {
        if (pass == 0) mbar_arrive(BAR_OD(0));
        else { fence_async_all(); flag_add(FLAG_OA(blockIdx.x, 1)); }
      }
    }
  }

  {
    named_bar(wg + 1, 128);
    if ((tid & 127) == 0) {
      mbar_arrive(BAR_CL(4));
      uint32_t r;
      asm volatile("atom.shared.add.u32 %0, [%1], 1;" : "=r"(r) : "r"(sM + 20) : "memory");
      sts1(sM + 32 + wg * 4, r);
    }
    named_bar(wg + 1, 128);
    const int role = __shfl_sync(~0u, lds1(sM + 32 + wg * 4), 0);
    const int isA = role >> 1, hf = role & 1;
    if ((tid & 127) == 0) TS(4 + wg, 10);
    float acc[32];
    uint32_t xs = 0;
    int prev = 0;
#pragma unroll 1
    for (int n = 0; n < 8; n++) {
      const int gidx = isA ? (n < 4 ? n + 9 : (n == 4 ? 8 : n + 8)) : n;
      const uint32_t sl = tail_slots(gidx < 9 ? gidx : gidx - 9);
      xs = sb + ((sl >> (8 + 8 * hf)) & 255) * 8192;
      const uint64_t da = make_desc(xs, 16, 1024, 1), db = make_desc(sb + (sl & 255) * 8192, 8192, 1024, 1);
      mbar_wait(BAR_TF(gidx), 0);
      if ((tid & 127) == 0 && role == 3) TS(2, 2 + n);
      wg_fence();
#pragma unroll
      for (int k = 0; k < 4; k++) wg_ss64<0, 1>(acc, da + k * 2, db + k * 128, (n | k) != 0);
      wg_commit();
      wg_wait<1>();
      if (!isA && n >= 1 && (tid & 127) == 0) mbar_arrive(BAR_TE(prev));
      __syncwarp();
      prev = n;
    }
    wg_wait<0>();
    fence_regs<32>(acc);
    if ((tid & 127) == 0) TS(4 + wg, 11);
    named_bar(wg + 1, 128);
    const int m = lane >> 3, r = lane & 7;
#pragma unroll
    for (int j = 0; j < 8; j += 2) {
      const int row = w4 * 16 + (m & 1) * 8 + r;
      stsm4(xs + row * 128 + (((j + (m >> 1)) ^ r) << 4),
            pack_bf16(acc[4 * j], acc[4 * j + 1]), pack_bf16(acc[4 * j + 2], acc[4 * j + 3]),
            pack_bf16(acc[4 * j + 4], acc[4 * j + 5]), pack_bf16(acc[4 * j + 6], acc[4 * j + 7]));
    }
    fence_async();
    named_bar(wg + 1, 128);
    if (w4 == 0 && elect_one()) {
      tma2d_store(&mOut, xs, (isA ? 0 : 512) + ct * 64, ttO * 128 + hf * 64);
      bulk_commit();
      asm volatile("cp.async.bulk.wait_group.read 0;" ::: "memory");
      TS(2, 11 + (role >> 1));
    }
  }
}

typedef CUresult (*EncodeFn)(CUtensorMap*, CUtensorMapDataType, cuuint32_t, void*, const cuuint64_t*, const cuuint64_t*,
                             const cuuint32_t*, const cuuint32_t*, CUtensorMapInterleave, CUtensorMapSwizzle,
                             CUtensorMapL2promotion, CUtensorMapFloatOOBfill);

static void make_map(EncodeFn enc, CUtensorMap* m, const void* ptr, uint64_t cols, uint64_t rows, uint32_t bc, uint32_t br) {
  cuuint64_t dims[2] = {cols, rows};
  cuuint64_t strides[1] = {cols * 2};
  cuuint32_t box[2] = {bc, br};
  cuuint32_t es[2] = {1, 1};
  enc(m, CU_TENSOR_MAP_DATA_TYPE_BFLOAT16, 2, (void*)ptr, dims, strides, box, es, CU_TENSOR_MAP_INTERLEAVE_NONE,
      CU_TENSOR_MAP_SWIZZLE_128B, CU_TENSOR_MAP_L2_PROMOTION_L2_256B, CU_TENSOR_MAP_FLOAT_OOB_FILL_NONE);
}

extern "C" void kernel_launch(void* const* d_in, const int* in_sizes, int n_in, void* d_out, int out_size) {
  (void)in_sizes; (void)n_in; (void)out_size;
  static EncodeFn enc = nullptr;
  static void* pQ = nullptr; static void* pO = nullptr;
  if (!enc) {
    void* fn = nullptr; cudaDriverEntryPointQueryResult qr;
    cudaGetDriverEntryPoint("cuTensorMapEncodeTiled", &fn, cudaEnableDefault, &qr);
    enc = (EncodeFn)fn;
    cudaGetSymbolAddress(&pQ, g_Q);
    cudaGetSymbolAddress(&pO, g_O);
    cudaFuncSetAttribute(k1_main, cudaFuncAttributeMaxDynamicSharedMemorySize, SM_TOTAL);
  }
  CUtensorMap mXA64, mXB, mWq, mWqkv, mQst, mO, mOst, mWoA, mWoB, mOut;
  make_map(enc, &mXA64, d_in[0], 512, 2048, 64, 64);
  make_map(enc, &mWq, d_in[1], 512, 512, 64, 64);
  make_map(enc, &mWoA, d_in[4], 512, 512, 64, 64);
  make_map(enc, &mXB, d_in[5], 512, 2048, 64, 128);
  make_map(enc, &mWqkv, d_in[6], 1536, 512, 64, 64);
  make_map(enc, &mWoB, d_in[7], 512, 512, 64, 64);
  make_map(enc, &mQst, pQ, 512, 4096, 64, 128);
  make_map(enc, &mO, pO, 512, 4096, 64, 64);
  make_map(enc, &mOst, pO, 512, 4096, 64, 128);
  make_map(enc, &mOut, d_out, 1024, 2048, 64, 64);
  Params prm{(const __nv_bfloat16*)d_in[2], (const __nv_bfloat16*)d_in[3]};
  k1_main<<<132, 640, SM_TOTAL, cudaStreamPerThread>>>(mXA64, mXB, mWq, mWqkv, mQst, mOst, mO, mWoA, mWoB, mOut, prm);
}
```

```cpp
#include <cuda_runtime.h>
#include <cuda_bf16.h>
#include <cuda_fp16.h>
#include <cuda.h>
#include <stdint.h>

#define S_TOK 2048
#define D_MOD 512

__device__ __align__(1024) __nv_bfloat16 g_Q[2 * S_TOK * D_MOD];
__device__ __align__(1024) __nv_bfloat16 g_O[2 * S_TOK * D_MOD];
__device__ __align__(1024) uint4 g_KV[8 * S_TOK];
__device__ __align__(16) uint32_t g_stats[128];
__device__ __align__(16) float4 g_kvp[16 * 32 * 3 * 32];

#define TS(k, i) do {} while (0)
__device__ __forceinline__ uint32_t smem_u32(const void* p) { return (uint32_t)__cvta_generic_to_shared(p); }
__device__ __forceinline__ void mbar_init(uint32_t bar, int cnt) { asm volatile("mbarrier.init.shared::cta.b64 [%0], %1;" :: "r"(bar), "r"(cnt) : "memory"); }
__device__ __forceinline__ void mbar_expect_tx(uint32_t bar, uint32_t bytes) { asm volatile("mbarrier.arrive.expect_tx.shared::cta.b64 _, [%0], %1;" :: "r"(bar), "r"(bytes) : "memory"); }
__device__ __forceinline__ bool mbar_try(uint32_t bar, uint32_t parity) {
  uint32_t ok;
  asm volatile("{\n.reg .pred p;\nmbarrier.try_wait.parity.shared::cta.b64 p, [%1], %2;\nselp.b32 %0, 1, 0, p;\n}\n" : "=r"(ok) : "r"(bar), "r"(parity) : "memory");
  return ok;
}
__device__ __forceinline__ void mbar_wait(uint32_t bar, uint32_t parity) {
  asm volatile("{\n.reg .pred p;\n.reg .u32 c;\nmov.u32 c, 0;\n"
               "LW_%=:\n"
               "mbarrier.try_wait.parity.shared::cta.b64 p, [%0], %1;\n"
               "@p bra LD_%=;\n"
               "add.u32 c, c, 1;\n"
               "setp.lt.u32 p, c, 4000000;\n"
               "@p bra LW_%=;\n"
               "trap;\n"
               "LD_%=:\n}\n" :: "r"(bar), "r"(parity) : "memory");
}
__device__ __forceinline__ void mbar_arrive_cta(uint32_t bar, uint32_t cta) {
  asm volatile("{\n.reg .b32 ra;\nmapa.shared::cluster.u32 ra, %0, %1;\nmbarrier.arrive.shared::cluster.b64 _, [ra];\n}\n" :: "r"(bar), "r"(cta) : "memory");
}
__device__ __forceinline__ void cluster_sync() {
  asm volatile("barrier.cluster.arrive.relaxed.aligned;\nbarrier.cluster.wait.aligned;" ::: "memory");
}
__device__ __forceinline__ void tma2d(uint32_t dst, const CUtensorMap* m, int c0, int c1, uint32_t bar) {
  asm volatile("cp.async.bulk.tensor.2d.shared::cluster.global.mbarrier::complete_tx::bytes [%0], [%1, {%3, %4}], [%2];"
               :: "r"(dst), "l"(m), "r"(bar), "r"(c0), "r"(c1) : "memory");
}
__device__ __forceinline__ void tma2d_mc(uint32_t dst, const CUtensorMap* m, int c0, int c1, uint32_t bar, uint16_t mask) {
  asm volatile("cp.async.bulk.tensor.2d.shared::cluster.global.mbarrier::complete_tx::bytes.multicast::cluster [%0], [%1, {%3, %4}], [%2], %5;"
               :: "r"(dst), "l"(m), "r"(bar), "r"(c0), "r"(c1), "h"(mask) : "memory");
}
__device__ __forceinline__ void tma2d_store(const CUtensorMap* m, uint32_t src, int c0, int c1) {
  asm volatile("cp.async.bulk.tensor.2d.global.shared::cta.bulk_group [%0, {%2, %3}], [%1];"
               :: "l"(m), "r"(src), "r"(c0), "r"(c1) : "memory");
}
__device__ __forceinline__ void bulk_g2s(uint32_t dst, const void* src, uint32_t bytes, uint32_t bar) {
  asm volatile("cp.async.bulk.shared::cluster.global.mbarrier::complete_tx::bytes [%0], [%1], %2, [%3];"
               :: "r"(dst), "l"(src), "r"(bytes), "r"(bar) : "memory");
}
__device__ __forceinline__ void bulk_commit() { asm volatile("cp.async.bulk.commit_group;" ::: "memory"); }
__device__ __forceinline__ void bulk_wait_all() { asm volatile("cp.async.bulk.wait_group 0;" ::: "memory"); }
__device__ __forceinline__ void fence_async() { asm volatile("fence.proxy.async.shared::cta;" ::: "memory"); }
__device__ __forceinline__ void named_bar(int id, int n) { asm volatile("bar.sync %0, %1;" :: "r"(id), "r"(n) : "memory"); }
__device__ __forceinline__ void pdl_launch() { asm volatile("griddepcontrol.launch_dependents;" ::: "memory"); }
__device__ __forceinline__ void pdl_wait() { asm volatile("griddepcontrol.wait;" ::: "memory"); }
__device__ __forceinline__ void wg_fence() { asm volatile("wgmma.fence.sync.aligned;" ::: "memory"); }
__device__ __forceinline__ void wg_commit() { asm volatile("wgmma.commit_group.sync.aligned;" ::: "memory"); }
template <int n> __device__ __forceinline__ void wg_wait() { asm volatile("wgmma.wait_group.sync.aligned %0;" :: "n"(n) : "memory"); }
template <int n> __device__ __forceinline__ void fence_regs(float* r) {
#pragma unroll
  for (int i = 0; i < n; i++) asm volatile("" : "+f"(r[i]) :: "memory");
}
template <int n> __device__ __forceinline__ void fence_regs(uint32_t* r) {
#pragma unroll
  for (int i = 0; i < n; i++) asm volatile("" : "+r"(r[i]) :: "memory");
}
__device__ __forceinline__ uint64_t make_desc(uint32_t addr, uint32_t lbo, uint32_t sbo, uint32_t swz) {
  return (uint64_t)((addr & 0x3FFFF) >> 4) | ((uint64_t)(lbo >> 4) << 16) | ((uint64_t)(sbo >> 4) << 32) | ((uint64_t)swz << 62);
}
__device__ __forceinline__ float ex2f(float x) { float y; asm("ex2.approx.ftz.f32 %0, %1;" : "=f"(y) : "f"(x)); return y; }
__device__ __forceinline__ uint32_t pack_bf16(float lo, float hi) { uint32_t r; asm("cvt.rn.bf16x2.f32 %0, %1, %2;" : "=r"(r) : "f"(hi), "f"(lo)); return r; }
__device__ __forceinline__ uint32_t pack_f16(float lo, float hi) { uint32_t r; asm("cvt.rn.f16x2.f32 %0, %1, %2;" : "=r"(r) : "f"(hi), "f"(lo)); return r; }
__device__ __forceinline__ float bf_lo(uint32_t v) { return __uint_as_float(v << 16); }
__device__ __forceinline__ float bf_hi(uint32_t v) { return __uint_as_float(v & 0xFFFF0000u); }
__device__ __forceinline__ float rbf(float x) { return __bfloat162float(__float2bfloat16_rn(x)); }
__device__ __forceinline__ void stsm4(uint32_t a, uint32_t r0, uint32_t r1, uint32_t r2, uint32_t r3) {
  asm volatile("stmatrix.sync.aligned.m8n8.x4.shared.b16 [%0], {%1,%2,%3,%4};" :: "r"(a), "r"(r0), "r"(r1), "r"(r2), "r"(r3) : "memory");
}
__device__ __forceinline__ void stsm4t(uint32_t a, uint32_t r0, uint32_t r1, uint32_t r2, uint32_t r3) {
  asm volatile("stmatrix.sync.aligned.m8n8.x4.trans.shared.b16 [%0], {%1,%2,%3,%4};" :: "r"(a), "r"(r0), "r"(r1), "r"(r2), "r"(r3) : "memory");
}
__device__ __forceinline__ void mma_bf16(float* d, uint32_t a0, uint32_t a1, uint32_t a2, uint32_t a3, uint32_t b0, uint32_t b1) {
  asm volatile("mma.sync.aligned.m16n8k16.row.col.f32.bf16.bf16.f32 {%0,%1,%2,%3}, {%4,%5,%6,%7}, {%8,%9}, {%0,%1,%2,%3};"
               : "+f"(d[0]), "+f"(d[1]), "+f"(d[2]), "+f"(d[3]) : "r"(a0), "r"(a1), "r"(a2), "r"(a3), "r"(b0), "r"(b1));
}
template<int SD> __device__ __forceinline__ void wg_qk32(float* d, const uint32_t* a, uint64_t desc) {
  asm volatile("wgmma.mma_async.sync.aligned.m64n32k16.f32.f16.f16 {%0,%1,%2,%3,%4,%5,%6,%7,%8,%9,%10,%11,%12,%13,%14,%15}, {%16,%17,%18,%19}, %20, %21, 1, 1, 0;"
   : "+f"(d[0]),"+f"(d[1]),"+f"(d[2]),"+f"(d[3]),"+f"(d[4]),"+f"(d[5]),"+f"(d[6]),"+f"(d[7]),"+f"(d[8]),"+f"(d[9]),"+f"(d[10]),"+f"(d[11]),"+f"(d[12]),"+f"(d[13]),"+f"(d[14]),"+f"(d[15])
   : "r"(a[0]),"r"(a[1]),"r"(a[2]),"r"(a[3]),"l"(desc),"n"(SD));
}
template<int SD> __device__ __forceinline__ void wg_qk64(float* d, const uint32_t* a, uint64_t desc) {
  asm volatile("wgmma.mma_async.sync.aligned.m64n64k16.f32.f16.f16 {%0,%1,%2,%3,%4,%5,%6,%7,%8,%9,%10,%11,%12,%13,%14,%15,%16,%17,%18,%19,%20,%21,%22,%23,%24,%25,%26,%27,%28,%29,%30,%31}, {%32,%33,%34,%35}, %36, %37, 1, 1, 0;"
   : "+f"(d[0]),"+f"(d[1]),"+f"(d[2]),"+f"(d[3]),"+f"(d[4]),"+f"(d[5]),"+f"(d[6]),"+f"(d[7]),"+f"(d[8]),"+f"(d[9]),"+f"(d[10]),"+f"(d[11]),"+f"(d[12]),"+f"(d[13]),"+f"(d[14]),"+f"(d[15]),"+f"(d[16]),"+f"(d[17]),"+f"(d[18]),"+f"(d[19]),"+f"(d[20]),"+f"(d[21]),"+f"(d[22]),"+f"(d[23]),"+f"(d[24]),"+f"(d[25]),"+f"(d[26]),"+f"(d[27]),"+f"(d[28]),"+f"(d[29]),"+f"(d[30]),"+f"(d[31])
   : "r"(a[0]),"r"(a[1]),"r"(a[2]),"r"(a[3]),"l"(desc),"n"(SD));
}
template<int SD> __device__ __forceinline__ void wg_qs32(float* d, uint64_t da, uint64_t db) {
  asm volatile("wgmma.mma_async.sync.aligned.m64n32k16.f32.f16.f16 {%0,%1,%2,%3,%4,%5,%6,%7,%8,%9,%10,%11,%12,%13,%14,%15}, %16, %17, %18, 1, 1, 0, 0;"
   : "+f"(d[0]),"+f"(d[1]),"+f"(d[2]),"+f"(d[3]),"+f"(d[4]),"+f"(d[5]),"+f"(d[6]),"+f"(d[7]),"+f"(d[8]),"+f"(d[9]),"+f"(d[10]),"+f"(d[11]),"+f"(d[12]),"+f"(d[13]),"+f"(d[14]),"+f"(d[15])
   : "l"(da),"l"(db),"n"(SD));
}
template<int SD> __device__ __forceinline__ void wg_qs64(float* d, uint64_t da, uint64_t db) {
  asm volatile("wgmma.mma_async.sync.aligned.m64n64k16.f32.f16.f16 {%0,%1,%2,%3,%4,%5,%6,%7,%8,%9,%10,%11,%12,%13,%14,%15,%16,%17,%18,%19,%20,%21,%22,%23,%24,%25,%26,%27,%28,%29,%30,%31}, %32, %33, %34, 1, 1, 0, 0;"
   : "+f"(d[0]),"+f"(d[1]),"+f"(d[2]),"+f"(d[3]),"+f"(d[4]),"+f"(d[5]),"+f"(d[6]),"+f"(d[7]),"+f"(d[8]),"+f"(d[9]),"+f"(d[10]),"+f"(d[11]),"+f"(d[12]),"+f"(d[13]),"+f"(d[14]),"+f"(d[15]),"+f"(d[16]),"+f"(d[17]),"+f"(d[18]),"+f"(d[19]),"+f"(d[20]),"+f"(d[21]),"+f"(d[22]),"+f"(d[23]),"+f"(d[24]),"+f"(d[25]),"+f"(d[26]),"+f"(d[27]),"+f"(d[28]),"+f"(d[29]),"+f"(d[30]),"+f"(d[31])
   : "l"(da),"l"(db),"n"(SD));
}
template<int SD> __device__ __forceinline__ void wg_pv24(float* d, const uint32_t* a, uint64_t desc) {
  asm volatile("wgmma.mma_async.sync.aligned.m64n24k16.f32.bf16.bf16 {%0,%1,%2,%3,%4,%5,%6,%7,%8,%9,%10,%11}, {%12,%13,%14,%15}, %16, %17, 1, 1, 1;"
   : "+f"(d[0]),"+f"(d[1]),"+f"(d[2]),"+f"(d[3]),"+f"(d[4]),"+f"(d[5]),"+f"(d[6]),"+f"(d[7]),"+f"(d[8]),"+f"(d[9]),"+f"(d[10]),"+f"(d[11])
   : "r"(a[0]),"r"(a[1]),"r"(a[2]),"r"(a[3]),"l"(desc),"n"(SD));
}
template<int TA, int TB> __device__ __forceinline__ void wg_ss128(float* d, uint64_t da, uint64_t db, int sd) {
  asm volatile("{\n.reg .pred p;\nsetp.ne.b32 p, %66, 0;\n"
   "wgmma.mma_async.sync.aligned.m64n128k16.f32.bf16.bf16 {%0,%1,%2,%3,%4,%5,%6,%7,%8,%9,%10,%11,%12,%13,%14,%15,%16,%17,%18,%19,%20,%21,%22,%23,%24,%25,%26,%27,%28,%29,%30,%31,%32,%33,%34,%35,%36,%37,%38,%39,%40,%41,%42,%43,%44,%45,%46,%47,%48,%49,%50,%51,%52,%53,%54,%55,%56,%57,%58,%59,%60,%61,%62,%63}, %64, %65, p, 1, 1, %67, %68;\n}\n"
   : "+f"(d[0]),"+f"(d[1]),"+f"(d[2]),"+f"(d[3]),"+f"(d[4]),"+f"(d[5]),"+f"(d[6]),"+f"(d[7]),"+f"(d[8]),"+f"(d[9]),"+f"(d[10]),"+f"(d[11]),"+f"(d[12]),"+f"(d[13]),"+f"(d[14]),"+f"(d[15]),"+f"(d[16]),"+f"(d[17]),"+f"(d[18]),"+f"(d[19]),"+f"(d[20]),"+f"(d[21]),"+f"(d[22]),"+f"(d[23]),"+f"(d[24]),"+f"(d[25]),"+f"(d[26]),"+f"(d[27]),"+f"(d[28]),"+f"(d[29]),"+f"(d[30]),"+f"(d[31]),"+f"(d[32]),"+f"(d[33]),"+f"(d[34]),"+f"(d[35]),"+f"(d[36]),"+f"(d[37]),"+f"(d[38]),"+f"(d[39]),"+f"(d[40]),"+f"(d[41]),"+f"(d[42]),"+f"(d[43]),"+f"(d[44]),"+f"(d[45]),"+f"(d[46]),"+f"(d[47]),"+f"(d[48]),"+f"(d[49]),"+f"(d[50]),"+f"(d[51]),"+f"(d[52]),"+f"(d[53]),"+f"(d[54]),"+f"(d[55]),"+f"(d[56]),"+f"(d[57]),"+f"(d[58]),"+f"(d[59]),"+f"(d[60]),"+f"(d[61]),"+f"(d[62]),"+f"(d[63])
   : "l"(da),"l"(db),"r"(sd),"n"(TA),"n"(TB));
}
template<int TA, int TB> __device__ __forceinline__ void wg_ss64(float* d, uint64_t da, uint64_t db, int sd) {
  asm volatile("{\n.reg .pred p;\nsetp.ne.b32 p, %34, 0;\n"
   "wgmma.mma_async.sync.aligned.m64n64k16.f32.bf16.bf16 {%0,%1,%2,%3,%4,%5,%6,%7,%8,%9,%10,%11,%12,%13,%14,%15,%16,%17,%18,%19,%20,%21,%22,%23,%24,%25,%26,%27,%28,%29,%30,%31}, %32, %33, p, 1, 1, %35, %36;\n}\n"
   : "+f"(d[0]),"+f"(d[1]),"+f"(d[2]),"+f"(d[3]),"+f"(d[4]),"+f"(d[5]),"+f"(d[6]),"+f"(d[7]),"+f"(d[8]),"+f"(d[9]),"+f"(d[10]),"+f"(d[11]),"+f"(d[12]),"+f"(d[13]),"+f"(d[14]),"+f"(d[15]),"+f"(d[16]),"+f"(d[17]),"+f"(d[18]),"+f"(d[19]),"+f"(d[20]),"+f"(d[21]),"+f"(d[22]),"+f"(d[23]),"+f"(d[24]),"+f"(d[25]),"+f"(d[26]),"+f"(d[27]),"+f"(d[28]),"+f"(d[29]),"+f"(d[30]),"+f"(d[31])
   : "l"(da),"l"(db),"r"(sd),"n"(TA),"n"(TB));
}

template<int TA, int TB> __device__ __forceinline__ void wg_ss8(float* d, uint64_t da, uint64_t db, int sd) {
  asm volatile("{\n.reg .pred p;\nsetp.ne.b32 p, %6, 0;\n"
   "wgmma.mma_async.sync.aligned.m64n8k16.f32.bf16.bf16 {%0,%1,%2,%3}, %4, %5, p, 1, 1, %7, %8;\n}\n"
   : "+f"(d[0]),"+f"(d[1]),"+f"(d[2]),"+f"(d[3])
   : "l"(da),"l"(db),"r"(sd),"n"(TA),"n"(TB));
}

template<int SD, uint32_t HI> __device__ __forceinline__ void wq32(float* d, uint64_t da, uint32_t lo) {
  asm volatile("{\n.reg .b64 db;\nmov.b64 db, {%17, %19};\n"
   "wgmma.mma_async.sync.aligned.m64n32k16.f32.f16.f16 {%0,%1,%2,%3,%4,%5,%6,%7,%8,%9,%10,%11,%12,%13,%14,%15}, %16, db, %18, 1, 1, 0, 0;\n}\n"
   : "+f"(d[0]),"+f"(d[1]),"+f"(d[2]),"+f"(d[3]),"+f"(d[4]),"+f"(d[5]),"+f"(d[6]),"+f"(d[7]),"+f"(d[8]),"+f"(d[9]),"+f"(d[10]),"+f"(d[11]),"+f"(d[12]),"+f"(d[13]),"+f"(d[14]),"+f"(d[15])
   : "l"(da),"r"(lo),"n"(SD),"r"(HI));
}
template<int SD, uint32_t HI> __device__ __forceinline__ void wq64(float* d, uint64_t da, uint32_t lo) {
  asm volatile("{\n.reg .b64 db;\nmov.b64 db, {%33, %35};\n"
   "wgmma.mma_async.sync.aligned.m64n64k16.f32.f16.f16 {%0,%1,%2,%3,%4,%5,%6,%7,%8,%9,%10,%11,%12,%13,%14,%15,%16,%17,%18,%19,%20,%21,%22,%23,%24,%25,%26,%27,%28,%29,%30,%31}, %32, db, %34, 1, 1, 0, 0;\n}\n"
   : "+f"(d[0]),"+f"(d[1]),"+f"(d[2]),"+f"(d[3]),"+f"(d[4]),"+f"(d[5]),"+f"(d[6]),"+f"(d[7]),"+f"(d[8]),"+f"(d[9]),"+f"(d[10]),"+f"(d[11]),"+f"(d[12]),"+f"(d[13]),"+f"(d[14]),"+f"(d[15]),"+f"(d[16]),"+f"(d[17]),"+f"(d[18]),"+f"(d[19]),"+f"(d[20]),"+f"(d[21]),"+f"(d[22]),"+f"(d[23]),"+f"(d[24]),"+f"(d[25]),"+f"(d[26]),"+f"(d[27]),"+f"(d[28]),"+f"(d[29]),"+f"(d[30]),"+f"(d[31])
   : "l"(da),"r"(lo),"n"(SD),"r"(HI));
}
template<int SD, uint32_t HI> __device__ __forceinline__ void wpv(float* d, const uint32_t* a, uint32_t lo) {
  asm volatile("{\n.reg .b64 db;\nmov.b64 db, {%16, %18};\n"
   "wgmma.mma_async.sync.aligned.m64n24k16.f32.bf16.bf16 {%0,%1,%2,%3,%4,%5,%6,%7,%8,%9,%10,%11}, {%12,%13,%14,%15}, db, %17, 1, 1, 1;\n}\n"
   : "+f"(d[0]),"+f"(d[1]),"+f"(d[2]),"+f"(d[3]),"+f"(d[4]),"+f"(d[5]),"+f"(d[6]),"+f"(d[7]),"+f"(d[8]),"+f"(d[9]),"+f"(d[10]),"+f"(d[11])
   : "r"(a[0]),"r"(a[1]),"r"(a[2]),"r"(a[3]),"r"(lo),"n"(SD),"r"(HI));
}

__device__ __forceinline__ uint32_t phi2(float a, float b) {
  uint32_t r, e;
  asm("cvt.rn.relu.bf16x2.f32 %0, %1, %2;" : "=r"(r) : "f"(b), "f"(a));
  e = pack_bf16(ex2f(a * 1.4426950408889634f), ex2f(b * 1.4426950408889634f));
  asm("add.rn.bf16x2 %0, %0, %1;" : "+r"(e) : "r"(0x35863586u));
  asm("min.NaN.bf16x2 %0, %0, %1;" : "+r"(e) : "r"(0x3F803F80u));
  asm("add.rn.bf16x2 %0, %0, %1;" : "+r"(e) : "r"(r));
  return e;
}

__device__ __forceinline__ void mbar_arrive(uint32_t bar) { asm volatile("mbarrier.arrive.shared::cta.b64 _, [%0];" :: "r"(bar) : "memory"); }
__device__ __forceinline__ void named_arrive(int id, int n) { asm volatile("bar.arrive %0, %1;" :: "r"(id), "r"(n) : "memory"); }
__device__ __forceinline__ void fence_async_all() { asm volatile("fence.proxy.async.global;" ::: "memory"); }
__device__ __forceinline__ void flag_add(uint32_t* f) { asm volatile("fence.acq_rel.gpu;\nred.relaxed.gpu.global.add.u32 [%0], 1;" :: "l"(f) : "memory"); }
__device__ __forceinline__ void flag_wait(const uint32_t* f, uint32_t target) {
  uint32_t v;
#pragma unroll 1
  for (int it = 0;; it++) {
    asm volatile("ld.acquire.gpu.global.u32 %0, [%1];" : "=r"(v) : "l"(f) : "memory");
    if ((int32_t)(v - target) >= 0) break;
    if (it > 2000000) __trap();
    __nanosleep(64);
  }
}
__device__ __forceinline__ bool elect_one() {
  uint32_t p;
  asm volatile("{\n.reg .pred P;\nelect.sync _|P, 0xFFFFFFFF;\nselp.b32 %0, 1, 0, P;\n}\n" : "=r"(p));
  return p;
}
__device__ __forceinline__ void lds4(uint32_t a, uint32_t* r) {
  asm volatile("ld.shared.v4.b32 {%0,%1,%2,%3}, [%4];" : "=r"(r[0]), "=r"(r[1]), "=r"(r[2]), "=r"(r[3]) : "r"(a) : "memory");
}
__device__ __forceinline__ uint32_t lds1(uint32_t a) { uint32_t r; asm volatile("ld.shared.b32 %0, [%1];" : "=r"(r) : "r"(a) : "memory"); return r; }
__device__ __forceinline__ void sts1(uint32_t a, uint32_t v) { asm volatile("st.shared.b32 [%0], %1;" :: "r"(a), "r"(v) : "memory"); }
__device__ __forceinline__ void sts4(uint32_t a, uint32_t r0, uint32_t r1, uint32_t r2, uint32_t r3) {
  asm volatile("st.shared.v4.b32 [%0], {%1,%2,%3,%4};" :: "r"(a), "r"(r0), "r"(r1), "r"(r2), "r"(r3) : "memory");
}
__device__ __forceinline__ void ldsm4(uint32_t a, uint32_t* r) {
  asm volatile("ldmatrix.sync.aligned.m8n8.x4.shared.b16 {%0,%1,%2,%3}, [%4];" : "=r"(r[0]), "=r"(r[1]), "=r"(r[2]), "=r"(r[3]) : "r"(a) : "memory");
}
__device__ __forceinline__ float rcpf(float x) { float y; asm("rcp.approx.ftz.f32 %0, %1;" : "=f"(y) : "f"(x)); return y; }
__device__ __forceinline__ uint32_t hfma2(uint32_t a, uint32_t b, uint32_t c) { uint32_t r; asm("fma.rn.f16x2 %0, %1, %2, %3;" : "=r"(r) : "r"(a), "r"(b), "r"(c)); return r; }
__device__ __forceinline__ uint32_t hadd2(uint32_t a, uint32_t b) { uint32_t r; asm("add.rn.f16x2 %0, %1, %2;" : "=r"(r) : "r"(a), "r"(b)); return r; }

#define STEPK 96
#define QSCALE 0.36067376022224085f
#define SMAGIC (512.0f + 2.0f * (191.0f - 30.0f - 1.5823545f))
#define VSHIFT 1073741824.0f

__device__ uint32_t g_epoch[132];
__device__ uint32_t g_flag[288 * 8];
#define FLAG_KV (g_flag)
#define FLAG_B(h) (g_flag + (4 + (h)) * 8)
#define FLAG_OA(cta, pass) (g_flag + (16 + (cta) * 2 + (pass)) * 8)
#define FLAG_LM(i) (g_flag + (272 + (i)) * 8)

#define SM_TOTAL (224 * 1024 + 2048 + 1024)
#define OFF_K 0
#define OFF_F 65536
#define OFF_V 131072
#define OFF_MISC (224 * 1024)

#define BAR_FULL(s) (bars + 8 * (s))
#define BAR_EMPTY(s) (bars + 24 + 8 * (s))
#define BAR_KV(c) (bars + 48 + 8 * (c))
#define BAR_BDONE (bars + 80)
#define BAR_Q (bars + 88)
#define BAR_GO (bars + 96)
#define BAR_Q2 (bars + 104)
#define BAR_OD(p) (bars + 112 + 8 * (p))
#define BAR_CL(c) (bars + 128 + 8 * (c))
#define BAR_TE(i) (bars + 168 + 8 * (i))
#define BAR_TF(g) (bars + 224 + 8 * (g))
#define BAR_O1(w) (bars + 352 + 8 * (w))
#define BAR_VB(c) (bars + 384 + 8 * (c))

__device__ __forceinline__ uint32_t exp2_pair_fix(float d0, float d1, uint32_t c63, uint32_t m1) {
  uint32_t w, y, s, r;
  asm("prmt.b32 %0, %1, %2, 0x6521;" : "=r"(w) : "r"(__float_as_uint(d0)), "r"(__float_as_uint(d1)));
  asm("lop3.b32 %0, %1, 0x007F007F, %2, 0xEA;" : "=r"(y) : "r"(w), "r"(c63));
  asm("mad.lo.u32 %0, %1, %2, %3;" : "=r"(s) : "r"(y), "r"(m1), "r"(w));
  asm("fma.rn.bf16x2 %0, %1, %2, %3;" : "=r"(r) : "r"(w), "r"(y), "r"(s));
  return r;
}

__device__ __forceinline__ void attn_slow(const uint4* gq, __nv_bfloat16* dst) {
  const int t = threadIdx.x & 127;
  const int row = t >> 1, half = t & 1;
  float q[16];
#pragma unroll
  for (int i = 0; i < 4; i++) {
    const uint4 v = gq[(row >> 4) * 32 + (row & 7) * 4 + i];
    const uint32_t lo = (row & 8) ? v.y : v.x, hi = (row & 8) ? v.w : v.z;
    q[2 * i] = bf_lo(lo); q[2 * i + 1] = bf_hi(lo); q[2 * i + 8] = bf_lo(hi); q[2 * i + 9] = bf_hi(hi);
  }
  float m = -INFINITY, l = 0.f, o[16];
#pragma unroll
  for (int i = 0; i < 16; i++) o[i] = 0.f;
#pragma unroll 1
  for (int j = half * 1024; j < half * 1024 + 1024; j++) {
    uint4 ka = g_KV[4 * S_TOK + j], kb = g_KV[5 * S_TOK + j];
    uint4 va = g_KV[6 * S_TOK + j], vb = g_KV[7 * S_TOK + j];
    uint32_t kk[8] = {ka.x, ka.y, ka.z, ka.w, kb.x, kb.y, kb.z, kb.w};
    uint32_t vv[8] = {va.x, va.y, va.z, va.w, vb.x, vb.y, vb.z, vb.w};
    float s = 0.f;
#pragma unroll
    for (int i = 0; i < 8; i++) { s = fmaf(q[2 * i], bf_lo(kk[i]), s); s = fmaf(q[2 * i + 1], bf_hi(kk[i]), s); }
    s = rbf(s) * 0.25f;
    if (s > m) {
      float c = __expf(m - s);
      l *= c;
#pragma unroll
      for (int i = 0; i < 16; i++) o[i] *= c;
      m = s;
    }
    float p = __expf(s - m);
    l += p;
#pragma unroll
    for (int i = 0; i < 8; i++) { o[2 * i] = fmaf(p, bf_lo(vv[i]), o[2 * i]); o[2 * i + 1] = fmaf(p, bf_hi(vv[i]), o[2 * i + 1]); }
  }
  float m2 = __shfl_xor_sync(~0u, m, 1);
  float mm = fmaxf(m, m2);
  float c = __expf(m - mm);
  l *= c; l += __shfl_xor_sync(~0u, l, 1);
  float inv = 1.f / l;
  uint32_t r[8];
#pragma unroll
  for (int i = 0; i < 16; i++) { o[i] *= c; o[i] += __shfl_xor_sync(~0u, o[i], 1); o[i] *= inv; }
#pragma unroll
  for (int i = 0; i < 8; i++) r[i] = pack_bf16(o[2 * i], o[2 * i + 1]);
  uint4* d = (uint4*)(dst + (size_t)row * D_MOD);
  if (half == 0) d[0] = make_uint4(r[0], r[1], r[2], r[3]); else d[1] = make_uint4(r[4], r[5], r[6], r[7]);
}

struct Params { const __nv_bfloat16* wk; const __nv_bfloat16* wv; const __nv_bfloat16* xa; };
__device__ __forceinline__ void cp16(uint32_t dst, const void* src) { asm volatile("cp.async.cg.shared.global [%0], [%1], 16;" :: "r"(dst), "l"(src) : "memory"); }

__device__ __forceinline__ void helper_cta(const int h, const uint32_t sb, const uint32_t bars, const int wg, const int w4,
                                           const CUtensorMap* mQ, const CUtensorMap* mOs) {
  const int lane = threadIdx.x & 31;
  mbar_wait(BAR_GO, 0);
  const int cb = wg & 1, col = h * 128 + cb * 64, row0 = S_TOK + (wg >> 1) * 1024;
  const uint32_t buf = sb + wg * 49152;
  if (w4 == 0 && elect_one()) {
    fence_async_all();
#pragma unroll 1
    for (int u = 0; u < 3; u++) {
      mbar_expect_tx(BAR_TF(wg * 3 + u), 16384);
      tma2d(buf + u * 16384, mQ, col, row0 + u * 128, BAR_TF(wg * 3 + u));
    }
  }
  const int head = h * 8 + cb * 4 + w4;
  float4 a0 = make_float4(0, 0, 0, 0), a1 = a0, a2 = a0;
#pragma unroll 8
  for (int tt = 0; tt < 16; tt++) {
    const float4* src = g_kvp + ((tt * 32 + head) * 3) * 32 + lane;
    float4 u = src[0], v = src[32], w = src[64];
    a0.x += u.x; a0.y += u.y; a0.z += u.z; a0.w += u.w;
    a1.x += v.x; a1.y += v.y; a1.z += v.z; a1.w += v.w;
    a2.x += w.x; a2.y += w.y; a2.z += w.z; a2.w += w.w;
  }
  const uint32_t b00 = pack_bf16(a0.x, a0.y), b01 = pack_bf16(a0.z, a0.w);
  const uint32_t b10 = pack_bf16(a1.x, a1.y), b11 = pack_bf16(a1.z, a1.w);
  const uint32_t bz0 = pack_bf16(a2.x, a2.y), bz1 = pack_bf16(a2.z, a2.w);
  const int m = lane >> 3, r = lane & 7;
  const uint32_t off = ((m & 1) * 8 + r) * 128 + (((w4 * 2 + (m >> 1)) ^ r) << 4);
  int s = 0, ph = 0;
#pragma unroll 1
  for (int u = 0; u < 8; u++) {
    const uint32_t bb = buf + s * 16384;
    mbar_wait(BAR_TF(wg * 3 + s), ph);
#pragma unroll
    for (int mt = 0; mt < 8; mt++) {
      uint32_t a[4];
      ldsm4(bb + mt * 2048 + off, a);
      float n0[4] = {0, 0, 0, 0}, n1[4] = {0, 0, 0, 0}, dn[4] = {0, 0, 0, 0};
      mma_bf16(dn, a[0], a[1], a[2], a[3], bz0, bz1);
      mma_bf16(n0, a[0], a[1], a[2], a[3], b00, b01);
      mma_bf16(n1, a[0], a[1], a[2], a[3], b10, b11);
      const float i0 = rcpf(dn[0] + 1e-6f), i1 = rcpf(dn[2] + 1e-6f);
      stsm4(bb + mt * 2048 + off, pack_bf16(n0[0] * i0, n0[1] * i0), pack_bf16(n0[2] * i1, n0[3] * i1),
            pack_bf16(n1[0] * i0, n1[1] * i0), pack_bf16(n1[2] * i1, n1[3] * i1));
    }
    fence_async();
    named_bar(wg + 1, 128);
    if (w4 == 0 && lane == 0) {
      tma2d_store(mOs, bb, col, row0 + u * 128);
      bulk_commit();
      if (u >= 1 && u + 2 < 8) {
        asm volatile("cp.async.bulk.wait_group.read 1;" ::: "memory");
        const int sp = s == 0 ? 2 : s - 1;
        mbar_expect_tx(BAR_TF(wg * 3 + sp), 16384);
        tma2d(buf + sp * 16384, mQ, col, row0 + (u + 2) * 128, BAR_TF(wg * 3 + sp));
      }
    }
    __syncwarp();
    if (++s == 3) { s = 0; ph ^= 1; }
  }
  if (w4 == 0 && lane == 0) {
    bulk_wait_all();
    fence_async_all();
    flag_add(FLAG_LM((h * 2 + cb) * 2 + (wg >> 1)));
    if (wg == 0) TS(1, 8);
  }
}

#define STAGE(s) (sb + (2 - (s)) * 65536)
template <int TR> __device__ __forceinline__ void proj_kb(float* acc, uint32_t st, uint32_t offA, uint32_t offB, int first) {
  const uint64_t da = make_desc(st + offA, TR ? 8192 : 16, 1024, 1);
  const uint64_t db = make_desc(st + offB, TR ? 16 : 8192, 1024, 1);
  wg_fence();
#pragma unroll
  for (int k = 0; k < 4; k++) wg_ss128<TR, 1 - TR>(acc, da + k * (TR ? 128 : 2), db + k * (TR ? 2 : 128), k != 0 || !first);
  wg_commit();
}
template <int TR> __device__ __forceinline__ void proj_loop(float* acc, uint32_t sb, uint32_t bars, uint32_t offA, uint32_t offB,
                                                            int wg, uint32_t sWKV) {
  {
    float kv[4];
    if (threadIdx.x == 0) TS(0, 1);
    const uint64_t da = make_desc(STAGE(2) + wg * 16384, 16, 1024, 1), db = make_desc(sWKV + wg * 2048, 128, 128, 0);
    wg_fence();
#pragma unroll
    for (int k = 0; k < 8; k++) wg_ss8<0, 1>(kv, da + (k >> 2) * 512 + (k & 3) * 2, db + k * 16, k != 0);
    wg_commit();
    wg_wait<0>();
    fence_regs<4>(kv);
    named_bar(wg + 1, 128);
    sts4(sWKV + threadIdx.x * 16, __float_as_uint(kv[0]), __float_as_uint(kv[1]), __float_as_uint(kv[2]), __float_as_uint(kv[3]));
    __syncwarp();
    if ((threadIdx.x & 31) == 0) mbar_arrive(BAR_GO);
  }
  int s = 0, ph = 0, sp = 0;
#pragma unroll 1
  for (int kb = 0; kb < 8; kb++) {
    mbar_wait(BAR_FULL(s), ph);
    if (threadIdx.x == 0) TS(0, 2 + kb);
    proj_kb<TR>(acc, STAGE(s), offA, offB, kb == 0);
    wg_wait<1>();
    if (kb >= 1 && (threadIdx.x & 127) == 0) mbar_arrive(BAR_EMPTY(sp));
    __syncwarp();
    sp = s;
    if (++s == 3) { s = 0; ph ^= 1; }
  }
  wg_wait<0>();
  fence_regs<64>(acc);
}

__device__ __forceinline__ uint32_t tail_slots(int t) {
  const uint32_t lo = t < 4 ? (t < 2 ? (t == 0 ? 0x0C0B0Au : 0x0F0E0Du) : (t == 2 ? 0x100400u : 0x081814u))
                            : (t < 6 ? (t == 4 ? 0x110501u : 0x021915u) : (t == 6 ? 0x161206u : (t == 7 ? 0x07031Au : 0x1B1713u)));
  return lo;
}

__device__ __forceinline__ void take_role(uint32_t sM, int wg) {
  uint32_t r;
  asm volatile("atom.shared.add.u32 %0, [%1], 1;" : "=r"(r) : "r"(sM + 20) : "memory");
  sts1(sM + 32 + wg * 4, r);
}

__global__ void __launch_bounds__(640, 1)
k1_main(const __grid_constant__ CUtensorMap mXA64, const __grid_constant__ CUtensorMap mXB,
        const __grid_constant__ CUtensorMap mWq, const __grid_constant__ CUtensorMap mWqkv,
        const __grid_constant__ CUtensorMap mQst, const __grid_constant__ CUtensorMap mOst,
        const __grid_constant__ CUtensorMap mO, const __grid_constant__ CUtensorMap mWoA,
        const __grid_constant__ CUtensorMap mWoB, const __grid_constant__ CUtensorMap mOut, const Params prm) {
  extern __shared__ uint8_t smem_raw[];
  const uint32_t sb = (smem_u32(smem_raw) + 1023u) & ~1023u;
  const uint32_t bars = sb + OFF_MISC, sM = bars + 512, sT = bars + 1024;
  const int tid = threadIdx.x, warp = __shfl_sync(~0u, tid >> 5, 0), wg = warp >> 2, w4 = warp & 3, lane = tid & 31;
  const bool helper = blockIdx.x >= 128;
  if (tid == 0) TS(0, 0);
  const int G = blockIdx.x >> 4, gi = blockIdx.x & 15;
  const int tbA = G * 4 + (gi >> 2), hg = gi & 3;
  const int ttB = (G >> 1) * 4 + (gi >> 2), hq = (G & 1) * 4 + (gi & 3);
  const int ttO = G * 2 + (gi >> 3), ct = gi & 7;
  auto issue = [&](int kb, int s) {
    const uint32_t fb = BAR_FULL(s), st = STAGE(s);
    mbar_expect_tx(fb, 65536);
    tma2d(st + 16384, &mXA64, kb * 64, tbA * 64, fb);
    tma2d(st, &mWq, hg * 128, kb * 64, fb);
    tma2d(st + 8192, &mWq, hg * 128 + 64, kb * 64, fb);
    tma2d(st + 49152, &mXB, kb * 64, ttB * 128, fb);
    tma2d(st + 24576, &mWqkv, hq * 64, kb * 64, fb);
    tma2d(st + 32768, &mWqkv, 512 + hq * 64, kb * 64, fb);
    tma2d(st + 40960, &mWqkv, 1024 + hq * 64, kb * 64, fb);
  };
  const uint32_t sOne = sb + OFF_V + 65536, sWKV = sOne + 24576;
  if (warp >= 16) {
    if (warp == 17) {
      if (lane == 0) {
        mbar_init(BAR_BDONE, 8); mbar_init(BAR_Q, 8); mbar_init(BAR_GO, helper ? 1 : 16); mbar_init(BAR_Q2, 5);
        mbar_init(BAR_OD(0), 16); mbar_init(BAR_OD(1), 16); mbar_init(BAR_CL(0), 1); mbar_init(BAR_FULL(2), 1);
        sts1(sM + 20, 0);
      }
      if (lane >= 1 && lane < 5) { mbar_init(BAR_CL(lane), 4); mbar_init(BAR_O1(lane - 1), 4); }
      if (lane >= 5 && lane < 8) { mbar_init(BAR_EMPTY(lane - 5), 4); mbar_init(BAR_KV(lane - 5), 1); mbar_init(BAR_VB(lane - 5), 1); }
      if (lane >= 8 && lane < 15) mbar_init(BAR_TE(lane - 8), 2);
      if (lane >= 16) mbar_init(BAR_TF(lane - 16), 1);
      asm volatile("fence.mbarrier_init.release.cluster;" ::: "memory");
    } else if (warp == 16 && !helper && elect_one()) {
      mbar_init(BAR_FULL(0), 1); mbar_init(BAR_FULL(1), 1);
      asm volatile("fence.mbarrier_init.release.cluster;" ::: "memory");
      issue(0, 0);
      issue(1, 1);
    }
  } else if (!helper) {
    {
      const int t = tid & 127, c = t & 15, r0 = t >> 4;
      const __nv_bfloat16* src = prm.xa + (size_t)(tbA * 64 + r0) * D_MOD + wg * 128 + c * 8;
      const uint32_t dst = STAGE(2) + wg * 16384 + (c >> 3) * 8192 + r0 * 128 + (((c & 7) ^ r0) << 4);
#pragma unroll
      for (int i = 0; i < 8; i++) cp16(dst + i * 1024, src + (size_t)i * 8 * D_MOD);
      cp16(sWKV + tid * 16, (const uint4*)(hg >= 2 ? prm.wv : prm.wk) + tid * 2 + (hg & 1));
      asm volatile("cp.async.commit_group;" ::: "memory");
    }
#pragma unroll
    for (int i = 0; i < 3; i++) {
      const int key = tid + i * 512;
      sts4(sOne + key * 16, (key % STEPK) < 32 ? 0x00003F80u : 0x00004E80u, 0u, 0u, 0u);
    }
    asm volatile("cp.async.wait_group 0;" ::: "memory");
    fence_async();
  }
  __syncthreads();
  if (wg == 4) {
    asm volatile("setmaxnreg.dec.sync.aligned.u32 32;");
    const uint32_t ep = g_epoch[blockIdx.x] + 1;
    if (helper) {
      if (w4 == 0 && elect_one()) {
        flag_wait(FLAG_B(blockIdx.x - 128), ep * 32);
        fence_async_all();
        TS(1, 10);
        mbar_arrive(BAR_GO);
        g_epoch[blockIdx.x] = ep;
      }
      return;
    }
    mbar_wait(BAR_GO, 0);
    if (w4 == 0 && elect_one()) issue(2, 2);
    {
      uint32_t a[4], b[4];
      float c[4];
      lds4(sWKV + (tid - 512) * 16, a);
      lds4(sWKV + 2048 + (tid - 512) * 16, b);
#pragma unroll
      for (int i = 0; i < 4; i++) c[i] = __uint_as_float(a[i]) + __uint_as_float(b[i]);
      lds4(sWKV + 4096 + (tid - 512) * 16, a);
      lds4(sWKV + 6144 + (tid - 512) * 16, b);
#pragma unroll
      for (int i = 0; i < 4; i++) c[i] += __uint_as_float(a[i]) + __uint_as_float(b[i]);
      sts1(sT + w4 * 256 + lane * 4, pack_bf16(c[0], c[1]));
      sts1(sT + w4 * 256 + 128 + lane * 4, pack_bf16(c[2], c[3]));
    }
    named_bar(9, 128);
    {
      const int t = tid - 512;
#pragma unroll
      for (int i = 0; i < 4; i++) {
        const int key = 1536 + t + i * 128;
        sts4(sOne + key * 16, (key % STEPK) < 32 ? 0x00003F80u : 0x00004E80u, 0u, 0u, 0u);
      }
      fence_async();
      __syncwarp();
      if (lane == 0) mbar_arrive(BAR_Q);
    }
    if (w4 == 0) {
      int s = 0, ph = 0;
#pragma unroll 1
      for (int kb = 3; kb < 8; kb++) {
        mbar_wait(BAR_EMPTY(s), ph);
        if (elect_one()) issue(kb, s);
        if (++s == 3) { s = 0; ph ^= 1; }
      }
      flag_wait(FLAG_KV, ep * 128);
      fence_async_all();
      if (lane == 0) TS(0, 11);
#pragma unroll 1
      for (int m = 0; m < 2; m++) {
        mbar_wait(m == 0 ? BAR_EMPTY(2) : BAR_EMPTY(0), 1 - m);
        if (elect_one()) {
#pragma unroll
          for (int c = 0; c < 3; c++) {
            const int k0 = c == 0 ? 0 : (c == 1 ? 7 * STEPK : 12 * STEPK), k1 = c == 0 ? 7 * STEPK : (c == 1 ? 12 * STEPK : S_TOK);
            const uint32_t bytes = (k1 - k0) * 16, fb = m == 0 ? BAR_KV(c) : BAR_VB(c);
            mbar_expect_tx(fb, 2 * bytes);
#pragma unroll
            for (int p = 0; p < 2; p++)
              bulk_g2s(sb + m * OFF_V + p * 32768 + k0 * 16, g_KV + (m * 2 + p) * S_TOK + k0, bytes, fb);
          }
        }
      }
      mbar_wait(BAR_CL(1), 0);
      flag_wait(FLAG_LM((lane & 7) * 2 + (ttO >> 3)), ep);
      __syncwarp();
      fence_async_all();
      if (lane == 0) TS(2, 13);
#pragma unroll 1
      for (int n = 0; n < 8; n++) {
        mbar_wait(BAR_CL(n < 4 ? n >> 1 : (n == 4 ? 2 : (n < 7 ? 3 : 4))), 0);
        const uint32_t sl = tail_slots(n), fb = BAR_TF(n);
        if (elect_one()) {
          mbar_expect_tx(fb, 24576);
          tma2d(sb + (sl & 255) * 8192, &mWoB, ct * 64, n * 64, fb);
          tma2d(sb + ((sl >> 8) & 255) * 8192, &mO, n * 64, S_TOK + ttO * 128, fb);
          tma2d(sb + (sl >> 16) * 8192, &mO, n * 64, S_TOK + ttO * 128 + 64, fb);
        }
      }
      if (lane == 0) g_epoch[blockIdx.x] = ep;
    } else if (w4 == 3) {
      flag_wait(FLAG_KV, ep * 128);
      const uint4 a = *(const uint4*)(g_stats + lane * 4);
      const float kmax2 = __uint_as_float(__reduce_max_sync(~0u, a.x)) + __uint_as_float(__reduce_max_sync(~0u, a.y));
      const float vmax = __uint_as_float(__reduce_max_sync(~0u, max(a.z, a.w)));
      const float lv = vmax > 0.f ? __log2f(vmax) : 0.f;
      const float lim = fminf(90.f, fminf(91.f + lv, 95.f - lv));
      float thr = -1.f;
      if (vmax < 1e27f && kmax2 <= 65536.f && lim > 2.f) thr = fminf(60000.f, (lim * lim - 1.f) / (kmax2 * 1.02f + 1e-30f));
      if (lane == 0) { sts1(sM + 16, __float_as_uint(thr)); mbar_arrive(BAR_Q2); }
      mbar_wait(BAR_CL(3), 0);
      flag_wait(FLAG_OA(ttO * 8 + (lane & 7), 0), ep);
      __syncwarp();
      uint32_t pend = 0xF, rdy = 0;
#pragma unroll 1
      for (int n = 0; n < 8; n++) {
        const int gidx = n < 4 ? n + 9 : (n == 4 ? 8 : n + 8);
        mbar_wait(n == 4 ? BAR_CL(4) : BAR_TE(gidx - 9), 0);
        int kb = n * 2;
        if (n >= 4) {
          rdy &= pend;
#pragma unroll 1
          for (int it = 0; !rdy; it++) {
            uint32_t v;
            asm volatile("ld.acquire.gpu.global.u32 %0, [%1];" : "=r"(v) : "l"(FLAG_OA(ttO * 8 + (lane & 7), 1)) : "memory");
            const uint32_t b = __ballot_sync(~0u, (int32_t)(v - ep * 4) >= 0);
            rdy = b & (b >> 4) & pend;
            if (it > 2000000) __trap();
          }
          const int hsel = __ffs(rdy) - 1;
          pend &= ~(1u << hsel);
          kb = hsel * 2 + 1;
          if (lane == 0 && n == 7) TS(2, 14);
        }
        fence_async_all();
        const uint32_t sl = tail_slots(n == 4 ? 8 : gidx - 9), fb = BAR_TF(gidx);
        if (elect_one()) {
          mbar_expect_tx(fb, 24576);
          tma2d(sb + ((sl >> 8) & 255) * 8192, &mO, kb * 64, ttO * 128, fb);
          tma2d(sb + (sl >> 16) * 8192, &mO, kb * 64, ttO * 128 + 64, fb);
          tma2d(sb + (sl & 255) * 8192, &mWoA, ct * 64, kb * 64, fb);
        }
      }
    } else {
      const int ch = tbA * 2 + (w4 - 1);
      uint32_t v[4], o[4];
      lds4(sT + (w4 - 1) * 512 + lane * 16, v);
      int kap;
      if (lane < 21) kap = lane * STEPK + 32 + ch;
      else { int idx = ch * 11 + (lane - 21); kap = (idx >> 5) * STEPK + (idx & 31); }
      g_KV[(4 + hg) * S_TOK + kap] = make_uint4(v[0], v[1], v[2], v[3]);
      float st = 0.f;
      if (hg < 2) {
        const float sc = lane < 21 ? 2.f : 1.f;
#pragma unroll
        for (int u = 0; u < 4; u++) {
          uint32_t pv = __shfl_up_sync(~0u, v[u], 1);
          if (lane == 0 || lane >= 21) pv = 0;
          const float x = bf_lo(v[u]), y = bf_hi(v[u]);
          st += x * x + y * y;
          o[u] = pack_f16((x - bf_lo(pv)) * sc, (y - bf_hi(pv)) * sc);
        }
      } else {
        const float sc = lane < 21 ? VSHIFT : 1.f;
#pragma unroll
        for (int u = 0; u < 4; u++) { float x = bf_lo(v[u]), y = bf_hi(v[u]); st += fabsf(x) + fabsf(y); o[u] = pack_bf16(x * sc, y * sc); }
      }
      g_KV[hg * S_TOK + kap] = make_uint4(o[0], o[1], o[2], o[3]);
      const uint32_t um = __reduce_max_sync(~0u, __float_as_uint(st) & 0x7FFFFFFFu);
      if (w4 == 2) {
        if (lane == 0) sts1(sM + 24, um);
        named_arrive(10, 64);
        if (lane < 4) {
          mbar_wait(BAR_O1(lane), 0);
          fence_async_all();
          flag_add(FLAG_OA(blockIdx.x, 1));
        }
        __syncwarp();
        if (lane == 0) TS(2, 0);
      }
      else {
        named_bar(10, 64);
        if (elect_one()) {
          g_stats[tbA * 4 + hg] = max(um, lds1(sM + 24));
          fence_async_all();
          flag_add(FLAG_KV);
          TS(1, 9);
          mbar_wait(BAR_BDONE, 0);
          tma2d_store(&mQst, sb + OFF_F + 49152, hq * 64, S_TOK + ttB * 128);
          bulk_commit();
          bulk_wait_all();
          fence_async_all();
          flag_add(FLAG_B(hq >> 1));
          TS(0, 12);
          mbar_wait(BAR_Q, 0);
          mbar_arrive(BAR_CL(0));
          mbar_wait(BAR_OD(0), 0);
          fence_async_all();
          flag_add(FLAG_OA(blockIdx.x, 0));
        }
      }
    }
    return;
  }
  if (helper) { helper_cta(blockIdx.x - 128, sb, bars, wg, w4, &mQst, &mOst); return; }

  {
    float acc[64];
    if (wg == 0) proj_loop<0>(acc, sb, bars, 16384, 0, wg, sWKV);
    else proj_loop<1>(acc, sb, bars, 16384 + wg * 8192, 49152, wg, sWKV);
    asm volatile("setmaxnreg.inc.sync.aligned.u32 112;");
    if (tid == 0) TS(0, 10);
    const uint32_t sF = sb + OFF_F;
    if (wg == 0) {
      uint32_t r[32];
      const uint32_t qa = sF + w4 * 512 + ((lane >> 3) & 1) * 256 + (lane >> 4) * 128 + (lane & 7) * 16;
#pragma unroll
      for (int hd = 0; hd < 8; hd++) {
#pragma unroll
        for (int i = 0; i < 4; i++) r[4 * hd + i] = pack_f16(acc[8 * hd + 2 * i] * QSCALE, acc[8 * hd + 2 * i + 1] * QSCALE);
        stsm4(qa + hd * 2048, r[4 * hd], r[4 * hd + 1], r[4 * hd + 2], r[4 * hd + 3]);
        if (hd == 3) {
          fence_async();
          __syncwarp();
          if (lane == 0) mbar_arrive(BAR_Q);
        }
      }
      fence_async();
      uint32_t nmax = 0;
#pragma unroll
      for (int hd = 0; hd < 8; hd++) {
        const uint32_t* q = r + 4 * hd;
        const uint32_t t0 = hfma2(q[2], q[2], hfma2(q[0], q[0], 0u)), t1 = hfma2(q[3], q[3], hfma2(q[1], q[1], 0u));
        uint32_t n = hadd2(__byte_perm(t0, t1, 0x5410), __byte_perm(t0, t1, 0x7632));
        n = hadd2(n, __shfl_xor_sync(~0u, n, 1));
        n = hadd2(n, __shfl_xor_sync(~0u, n, 2));
        nmax = __vmaxu2(nmax, n & 0x7FFF7FFFu);
      }
      nmax = __reduce_max_sync(~0u, max(nmax & 0xFFFFu, nmax >> 16));
      if (lane == 0) sts1(sM + w4 * 4, nmax);
      uint4* gq = (uint4*)g_Q + blockIdx.x * 1024 + tid;
#pragma unroll
      for (int hd = 0; hd < 8; hd++)
        gq[hd * 128] = make_uint4(pack_bf16(acc[8 * hd], acc[8 * hd + 1]), pack_bf16(acc[8 * hd + 2], acc[8 * hd + 3]),
                                  pack_bf16(acc[8 * hd + 4], acc[8 * hd + 5]), pack_bf16(acc[8 * hd + 6], acc[8 * hd + 7]));
      __syncwarp();
      if (lane == 0) mbar_arrive(BAR_Q2);
    } else if (wg == 3) {
      named_arrive(8, 384);
      named_bar(6, 384);
      const int t = tid & 127;
#pragma unroll
      for (int j = 0; j < 8; j++)
        sts4(sF + 24576 + j * 2048 + t * 16, pack_bf16(acc[8 * j], acc[8 * j + 1]), pack_bf16(acc[8 * j + 2], acc[8 * j + 3]),
             pack_bf16(acc[8 * j + 4], acc[8 * j + 5]), pack_bf16(acc[8 * j + 6], acc[8 * j + 7]));
      named_arrive(7, 256);
    } else {
      uint32_t p[32];
      named_arrive(6, 384);
      if (wg == 2) named_arrive(8, 384);
#pragma unroll
      for (int i = 0; i < 32; i++) p[i] = phi2(acc[2 * i], acc[2 * i + 1]);
      if (wg == 1) {
        named_bar(8, 384);
        const int m = lane >> 3, r = lane & 7;
#pragma unroll
        for (int j = 0; j < 16; j += 2) {
          const int tok = (j + (m >> 1)) * 8 + r;
          const int chunk = w4 * 2 + (m & 1);
          stsm4t(sF + 49152 + tok * 128 + ((chunk ^ r) << 4), p[2 * j], p[2 * j + 1], p[2 * j + 2], p[2 * j + 3]);
        }
        fence_async();
      } else {
        named_bar(7, 256);
        float kv0[4] = {0, 0, 0, 0}, kv1[4] = {0, 0, 0, 0}, z0[4] = {0, 0, 0, 0}, z1[4] = {0, 0, 0, 0};
        const uint32_t one = 0x3F803F80u;
        const int t = tid & 127;
#pragma unroll
        for (int j = 0; j < 8; j++) {
          uint32_t a[4];
          lds4(sF + 24576 + j * 2048 + t * 16, a);
          mma_bf16(kv0, a[0], a[1], a[2], a[3], p[4 * j], p[4 * j + 2]);
          mma_bf16(kv1, a[0], a[1], a[2], a[3], p[4 * j + 1], p[4 * j + 3]);
          mma_bf16(z0, one, one, one, one, p[4 * j], p[4 * j + 2]);
          mma_bf16(z1, one, one, one, one, p[4 * j + 1], p[4 * j + 3]);
        }
        float4* dst = g_kvp + ((ttB * 32 + hq * 4 + w4) * 3) * 32 + lane;
        dst[0] = make_float4(kv0[0], kv0[1], kv1[0], kv1[1]);
        dst[32] = make_float4(kv0[2], kv0[3], kv1[2], kv1[3]);
        dst[64] = make_float4(z0[0], z0[1], z1[0], z1[1]);
      }
      __syncwarp();
      if (lane == 0) mbar_arrive(BAR_BDONE);
    }
  }

  mbar_wait(BAR_Q, 0);
  if (tid == 0) TS(1, 1);
  __nv_bfloat16* const obase = g_O + (size_t)(tbA * 64) * D_MOD + (hg * 8 + wg) * 16;
  bool safe = true;
  {
    const uint32_t c63 = 0x1F801F80u + (threadIdx.x >> 20);
    const uint32_t m1 = (gridDim.x >> 20) - 1u;
    const uint64_t dK0 = make_desc(sb + OFF_K, 32768, 128, 0);
    const uint64_t dV0 = make_desc(sb + OFF_V, 128, 32768, 0);
    constexpr uint32_t dKV = ((2048u - 8u)  __H0__ ) + STEPK - (OFF_V - OFF_K) / 16;
    mbar_wait(BAR_KV(0), 0);
#pragma unroll 1
    for (int pass = 0; pass < 2; pass++) {
      const uint64_t dQ = make_desc(sb + OFF_F + (pass * 4 + wg) * 2048, 128, 256, 0);
      float Sm[16], Sp[32], O[12];
      uint32_t P[24];
#pragma unroll
      for (int i = 0; i < 32; i++) Sp[i] = SMAGIC;
#pragma unroll
      for (int i = 0; i < 16; i++) Sm[i] = 0.f;
#pragma unroll
      for (int i = 0; i < 12; i++) O[i] = 0.f;
      fence_regs<16>(Sm); fence_regs<32>(Sp); fence_regs<12>(O);
      if (tid == 0) TS(1, 2 + 2 * pass);
      wg_fence();
      wg_qs32<0>(Sm, dQ, dK0);
      wg_qs64<1>(Sp, dQ, dK0 + 32);
      wg_commit();
      wg_wait<0>();
      fence_regs<16>(Sm); fence_regs<32>(Sp);
      uint32_t vlo = (uint32_t)dV0;
#pragma unroll 1
      for (int seg = 0; seg < 4; seg++) {
        if (pass == 0) {
          if (seg < 3) { mbar_wait(BAR_KV(seg), 0); mbar_wait(BAR_VB(seg), 0); }
        } else if (seg >= 1) {
          if ((tid & 127) == 0) {
            mbar_arrive(BAR_CL(seg));
            if (seg == 3) take_role(sM, wg);
          }
          __syncwarp();
        }
        if ((tid & 127) == 0) TS(4 + wg, pass * 5 + seg);
        const uint32_t vend = vlo + (seg == 0 ? 6 : 5) * STEPK;
#pragma unroll 1
        for (; vlo != vend; vlo += STEPK) {
          uint64_t dK, dV;
          asm("mov.b64 %0, {%1, %2};" : "=l"(dK) : "r"(vlo + dKV), "r"(8u));
          asm("mov.b64 %0, {%1, %2};" : "=l"(dV) : "r"(vlo), "r"(2048u));
#pragma unroll
          for (int i = 0; i < 8; i++) P[i] = pack_bf16(ex2f(Sm[2 * i]), ex2f(Sm[2 * i + 1]));
#pragma unroll
          for (int i = 0; i < 16; i++) P[8 + i] = exp2_pair_fix(Sp[2 * i], Sp[2 * i + 1], c63, m1);
          fence_regs<24>(P);
          wg_fence();
#pragma unroll
          for (int k = 0; k < 6; k++) wg_pv24<1>(O, &P[4 * k], dV + k * 16);
          wg_qs64<1>(Sp, dQ, dK + 32);
          wg_qs32<0>(Sm, dQ, dK);
          wg_commit();
          wg_wait<0>();
          fence_regs<16>(Sm); fence_regs<32>(Sp); fence_regs<12>(O); fence_regs<24>(P);
        }
      }
#pragma unroll
      for (int i = 0; i < 8; i++) P[i] = pack_bf16(ex2f(Sm[2 * i]), ex2f(Sm[2 * i + 1]));
      fence_regs<8>(P);
      wg_fence();
      wg_pv24<1>(O, &P[0], dV0 + 21 * STEPK);
      wg_pv24<1>(O, &P[4], dV0 + 21 * STEPK + 16);
      wg_commit();
      wg_wait<0>();
      fence_regs<12>(O);
      if (pass == 0) {
        uint32_t n[4];
        mbar_wait(BAR_Q2, 0);
        lds4(sM, n);
        const float qn = __half2float(__ushort_as_half((unsigned short)max(max(n[0], n[1]), max(n[2], n[3]))));
        safe = __all_sync(~0u, qn <= __uint_as_float(lds1(sM + 16)));
        if (!safe) break;
      }
      const float l0 = __shfl_sync(~0u, O[8], lane & ~3), l1 = __shfl_sync(~0u, O[10], lane & ~3);
      const float i0 = rcpf(l0), i1 = rcpf(l1);
      uint32_t* op = (uint32_t*)(obase + pass * 64 + (size_t)(w4 * 16 + (lane >> 2)) * D_MOD) + (lane & 3);
      op[0] = pack_bf16(O[0] * i0, O[1] * i0);
      op[8 * 256] = pack_bf16(O[2] * i1, O[3] * i1);
      op[4] = pack_bf16(O[4] * i0, O[5] * i0);
      op[8 * 256 + 4] = pack_bf16(O[6] * i1, O[7] * i1);
      __syncwarp();
      if (lane == 0) {
        if (pass == 0) mbar_arrive(BAR_OD(0));
        else mbar_arrive(BAR_O1(wg));
      }
      if ((tid & 127) == 0) TS(4 + wg, pass * 5 + 4);
      if (tid == 0) TS(1, 3 + 2 * pass);
      if ((tid & 127) == 0 && pass == 1 && wg > 0) TS(1, 10 + wg);
    }
  }

  if (!safe) {
    if ((tid & 127) == 0) { mbar_arrive(BAR_CL(1)); mbar_arrive(BAR_CL(2)); mbar_arrive(BAR_CL(3)); take_role(sM, wg); }
#pragma unroll 1
    for (int pass = 0; pass < 2; pass++) {
      attn_slow((const uint4*)g_Q + blockIdx.x * 1024 + (pass * 4 + wg) * 128, obase + pass * 64);
      __syncwarp();
      if (lane == 0) {
        if (pass == 0) mbar_arrive(BAR_OD(0));
        else mbar_arrive(BAR_O1(wg));
      }
    }
  }

  {
    named_bar(wg + 1, 128);
    if ((tid & 127) == 0) mbar_arrive(BAR_CL(4));
    const int role = __shfl_sync(~0u, lds1(sM + 32 + wg * 4), 0);
    const int isA = role >> 1, hf = role & 1;
    if ((tid & 127) == 0) TS(4 + wg, 10);
    float acc[32];
    uint32_t xs = 0;
    int prev = 0;
#pragma unroll 1
    for (int n = 0; n < 8; n++) {
      const int gidx = isA ? (n < 4 ? n + 9 : (n == 4 ? 8 : n + 8)) : n;
      const uint32_t sl = tail_slots(gidx < 9 ? gidx : gidx - 9);
      xs = sb + ((sl >> (8 + 8 * hf)) & 255) * 8192;
      const uint64_t da = make_desc(xs, 16, 1024, 1), db = make_desc(sb + (sl & 255) * 8192, 8192, 1024, 1);
      mbar_wait(BAR_TF(gidx), 0);
      if ((tid & 127) == 0 && role == 3) TS(2, 2 + n);
      wg_fence();
#pragma unroll
      for (int k = 0; k < 4; k++) wg_ss64<0, 1>(acc, da + k * 2, db + k * 128, (n | k) != 0);
      wg_commit();
      wg_wait<1>();
      if (!isA && n >= 1 && (tid & 127) == 0) mbar_arrive(BAR_TE(prev));
      __syncwarp();
      prev = n;
    }
    wg_wait<0>();
    fence_regs<32>(acc);
    if ((tid & 127) == 0) TS(4 + wg, 11);
    named_bar(wg + 1, 128);
    const int m = lane >> 3, r = lane & 7;
#pragma unroll
    for (int j = 0; j < 8; j += 2) {
      const int row = w4 * 16 + (m & 1) * 8 + r;
      stsm4(xs + row * 128 + (((j + (m >> 1)) ^ r) << 4),
            pack_bf16(acc[4 * j], acc[4 * j + 1]), pack_bf16(acc[4 * j + 2], acc[4 * j + 3]),
            pack_bf16(acc[4 * j + 4], acc[4 * j + 5]), pack_bf16(acc[4 * j + 6], acc[4 * j + 7]));
    }
    fence_async();
    named_bar(wg + 1, 128);
    if (w4 == 0 && elect_one()) {
      tma2d_store(&mOut, xs, (isA ? 0 : 512) + ct * 64, ttO * 128 + hf * 64);
      bulk_commit();
      asm volatile("cp.async.bulk.wait_group.read 0;" ::: "memory");
      TS(2, 11 + (role >> 1));
    }
  }
}

typedef CUresult (*EncodeFn)(CUtensorMap*, CUtensorMapDataType, cuuint32_t, void*, const cuuint64_t*, const cuuint64_t*,
                             const cuuint32_t*, const cuuint32_t*, CUtensorMapInterleave, CUtensorMapSwizzle,
                             CUtensorMapL2promotion, CUtensorMapFloatOOBfill);

static void make_map(EncodeFn enc, CUtensorMap* m, const void* ptr, uint64_t cols, uint64_t rows, uint32_t bc, uint32_t br) {
  cuuint64_t dims[2] = {cols, rows};
  cuuint64_t strides[1] = {cols * 2};
  cuuint32_t box[2] = {bc, br};
  cuuint32_t es[2] = {1, 1};
  enc(m, CU_TENSOR_MAP_DATA_TYPE_BFLOAT16, 2, (void*)ptr, dims, strides, box, es, CU_TENSOR_MAP_INTERLEAVE_NONE,
      CU_TENSOR_MAP_SWIZZLE_128B, CU_TENSOR_MAP_L2_PROMOTION_L2_256B, CU_TENSOR_MAP_FLOAT_OOB_FILL_NONE);
}

extern "C" void kernel_launch(void* const* d_in, const int* in_sizes, int n_in, void* d_out, int out_size) {
  (void)in_sizes; (void)n_in; (void)out_size;
  static EncodeFn enc = nullptr;
  static void* pQ = nullptr; static void* pO = nullptr;
  if (!enc) {
    void* fn = nullptr; cudaDriverEntryPointQueryResult qr;
    cudaGetDriverEntryPoint("cuTensorMapEncodeTiled", &fn, cudaEnableDefault, &qr);
    enc = (EncodeFn)fn;
    cudaGetSymbolAddress(&pQ, g_Q);
    cudaGetSymbolAddress(&pO, g_O);
    cudaFuncSetAttribute(k1_main, cudaFuncAttributeMaxDynamicSharedMemorySize, SM_TOTAL);
  }
  CUtensorMap mXA64, mXB, mWq, mWqkv, mQst, mO, mOst, mWoA, mWoB, mOut;
  make_map(enc, &mXA64, d_in[0], 512, 2048, 64, 64);
  make_map(enc, &mWq, d_in[1], 512, 512, 64, 64);
  make_map(enc, &mWoA, d_in[4], 512, 512, 64, 64);
  make_map(enc, &mXB, d_in[5], 512, 2048, 64, 128);
  make_map(enc, &mWqkv, d_in[6], 1536, 512, 64, 64);
  make_map(enc, &mWoB, d_in[7], 512, 512, 64, 64);
  make_map(enc, &mQst, pQ, 512, 4096, 64, 128);
  make_map(enc, &mO, pO, 512, 4096, 64, 64);
  make_map(enc, &mOst, pO, 512, 4096, 64, 128);
  make_map(enc, &mOut, d_out, 1024, 2048, 64, 64);
  Params prm{(const __nv_bfloat16*)d_in[2], (const __nv_bfloat16*)d_in[3], (const __nv_bfloat16*)d_in[0]};
  k1_main<<<132, 640, SM_TOTAL, cudaStreamPerThread>>>(mXA64, mXB, mWq, mWqkv, mQst, mOst, mO, mWoA, mWoB, mOut, prm);
}
```

```cpp
#include <cuda_runtime.h>
#include <cuda_bf16.h>
#include <cuda_fp16.h>
#include <cuda.h>
#include <stdint.h>

#define S_TOK 2048
#define D_MOD 512

__device__ __align__(1024) __nv_bfloat16 g_Q[2 * S_TOK * D_MOD];
__device__ __align__(1024) __nv_bfloat16 g_O[2 * S_TOK * D_MOD];
__device__ __align__(1024) uint4 g_KV[8 * S_TOK];
__device__ __align__(16) uint32_t g_stats[128];
__device__ __align__(16) float4 g_kvp[16 * 32 * 3 * 32];

#define TS(k, i) do {} while (0)
__device__ __forceinline__ uint32_t smem_u32(const void* p) { return (uint32_t)__cvta_generic_to_shared(p); }
__device__ __forceinline__ void mbar_init(uint32_t bar, int cnt) { asm volatile("mbarrier.init.shared::cta.b64 [%0], %1;" :: "r"(bar), "r"(cnt) : "memory"); }
__device__ __forceinline__ void mbar_expect_tx(uint32_t bar, uint32_t bytes) { asm volatile("mbarrier.arrive.expect_tx.shared::cta.b64 _, [%0], %1;" :: "r"(bar), "r"(bytes) : "memory"); }
__device__ __forceinline__ bool mbar_try(uint32_t bar, uint32_t parity) {
  uint32_t ok;
  asm volatile("{\n.reg .pred p;\nmbarrier.try_wait.parity.shared::cta.b64 p, [%1], %2;\nselp.b32 %0, 1, 0, p;\n}\n" : "=r"(ok) : "r"(bar), "r"(parity) : "memory");
  return ok;
}
__device__ __forceinline__ void mbar_wait(uint32_t bar, uint32_t parity) {
  asm volatile("{\n.reg .pred p;\n.reg .u32 c;\nmov.u32 c, 0;\n"
               "LW_%=:\n"
               "mbarrier.try_wait.parity.shared::cta.b64 p, [%0], %1;\n"
               "@p bra LD_%=;\n"
               "add.u32 c, c, 1;\n"
               "setp.lt.u32 p, c, 4000000;\n"
               "@p bra LW_%=;\n"
               "trap;\n"
               "LD_%=:\n}\n" :: "r"(bar), "r"(parity) : "memory");
}
__device__ __forceinline__ void mbar_arrive_cta(uint32_t bar, uint32_t cta) {
  asm volatile("{\n.reg .b32 ra;\nmapa.shared::cluster.u32 ra, %0, %1;\nmbarrier.arrive.shared::cluster.b64 _, [ra];\n}\n" :: "r"(bar), "r"(cta) : "memory");
}
__device__ __forceinline__ void cluster_sync() {
  asm volatile("barrier.cluster.arrive.relaxed.aligned;\nbarrier.cluster.wait.aligned;" ::: "memory");
}
__device__ __forceinline__ void tma2d(uint32_t dst, const CUtensorMap* m, int c0, int c1, uint32_t bar) {
  asm volatile("cp.async.bulk.tensor.2d.shared::cluster.global.mbarrier::complete_tx::bytes [%0], [%1, {%3, %4}], [%2];"
               :: "r"(dst), "l"(m), "r"(bar), "r"(c0), "r"(c1) : "memory");
}
__device__ __forceinline__ void tma2d_mc(uint32_t dst, const CUtensorMap* m, int c0, int c1, uint32_t bar, uint16_t mask) {
  asm volatile("cp.async.bulk.tensor.2d.shared::cluster.global.mbarrier::complete_tx::bytes.multicast::cluster [%0], [%1, {%3, %4}], [%2], %5;"
               :: "r"(dst), "l"(m), "r"(bar), "r"(c0), "r"(c1), "h"(mask) : "memory");
}
__device__ __forceinline__ void tma2d_store(const CUtensorMap* m, uint32_t src, int c0, int c1) {
  asm volatile("cp.async.bulk.tensor.2d.global.shared::cta.bulk_group [%0, {%2, %3}], [%1];"
               :: "l"(m), "r"(src), "r"(c0), "r"(c1) : "memory");
}
__device__ __forceinline__ void bulk_g2s(uint32_t dst, const void* src, uint32_t bytes, uint32_t bar) {
  asm volatile("cp.async.bulk.shared::cluster.global.mbarrier::complete_tx::bytes [%0], [%1], %2, [%3];"
               :: "r"(dst), "l"(src), "r"(bytes), "r"(bar) : "memory");
}
__device__ __forceinline__ void bulk_commit() { asm volatile("cp.async.bulk.commit_group;" ::: "memory"); }
__device__ __forceinline__ void bulk_wait_all() { asm volatile("cp.async.bulk.wait_group 0;" ::: "memory"); }
__device__ __forceinline__ void fence_async() { asm volatile("fence.proxy.async.shared::cta;" ::: "memory"); }
__device__ __forceinline__ void named_bar(int id, int n) { asm volatile("bar.sync %0, %1;" :: "r"(id), "r"(n) : "memory"); }
__device__ __forceinline__ void pdl_launch() { asm volatile("griddepcontrol.launch_dependents;" ::: "memory"); }
__device__ __forceinline__ void pdl_wait() { asm volatile("griddepcontrol.wait;" ::: "memory"); }
__device__ __forceinline__ void wg_fence() { asm volatile("wgmma.fence.sync.aligned;" ::: "memory"); }
__device__ __forceinline__ void wg_commit() { asm volatile("wgmma.commit_group.sync.aligned;" ::: "memory"); }
template <int n> __device__ __forceinline__ void wg_wait() { asm volatile("wgmma.wait_group.sync.aligned %0;" :: "n"(n) : "memory"); }
template <int n> __device__ __forceinline__ void fence_regs(float* r) {
#pragma unroll
  for (int i = 0; i < n; i++) asm volatile("" : "+f"(r[i]) :: "memory");
}
template <int n> __device__ __forceinline__ void fence_regs(uint32_t* r) {
#pragma unroll
  for (int i = 0; i < n; i++) asm volatile("" : "+r"(r[i]) :: "memory");
}
__device__ __forceinline__ uint64_t make_desc(uint32_t addr, uint32_t lbo, uint32_t sbo, uint32_t swz) {
  return (uint64_t)((addr & 0x3FFFF) >> 4) | ((uint64_t)(lbo >> 4) << 16) | ((uint64_t)(sbo >> 4) << 32) | ((uint64_t)swz << 62);
}
__device__ __forceinline__ float ex2f(float x) { float y; asm("ex2.approx.ftz.f32 %0, %1;" : "=f"(y) : "f"(x)); return y; }
__device__ __forceinline__ uint32_t pack_bf16(float lo, float hi) { uint32_t r; asm("cvt.rn.bf16x2.f32 %0, %1, %2;" : "=r"(r) : "f"(hi), "f"(lo)); return r; }
__device__ __forceinline__ uint32_t pack_f16(float lo, float hi) { uint32_t r; asm("cvt.rn.f16x2.f32 %0, %1, %2;" : "=r"(r) : "f"(hi), "f"(lo)); return r; }
__device__ __forceinline__ float bf_lo(uint32_t v) { return __uint_as_float(v << 16); }
__device__ __forceinline__ float bf_hi(uint32_t v) { return __uint_as_float(v & 0xFFFF0000u); }
__device__ __forceinline__ float rbf(float x) { return __bfloat162float(__float2bfloat16_rn(x)); }
__device__ __forceinline__ void stsm4(uint32_t a, uint32_t r0, uint32_t r1, uint32_t r2, uint32_t r3) {
  asm volatile("stmatrix.sync.aligned.m8n8.x4.shared.b16 [%0], {%1,%2,%3,%4};" :: "r"(a), "r"(r0), "r"(r1), "r"(r2), "r"(r3) : "memory");
}
__device__ __forceinline__ void stsm4t(uint32_t a, uint32_t r0, uint32_t r1, uint32_t r2, uint32_t r3) {
  asm volatile("stmatrix.sync.aligned.m8n8.x4.trans.shared.b16 [%0], {%1,%2,%3,%4};" :: "r"(a), "r"(r0), "r"(r1), "r"(r2), "r"(r3) : "memory");
}
__device__ __forceinline__ void mma_bf16(float* d, uint32_t a0, uint32_t a1, uint32_t a2, uint32_t a3, uint32_t b0, uint32_t b1) {
  asm volatile("mma.sync.aligned.m16n8k16.row.col.f32.bf16.bf16.f32 {%0,%1,%2,%3}, {%4,%5,%6,%7}, {%8,%9}, {%0,%1,%2,%3};"
               : "+f"(d[0]), "+f"(d[1]), "+f"(d[2]), "+f"(d[3]) : "r"(a0), "r"(a1), "r"(a2), "r"(a3), "r"(b0), "r"(b1));
}
template<int SD> __device__ __forceinline__ void wg_qk32(float* d, const uint32_t* a, uint64_t desc) {
  asm volatile("wgmma.mma_async.sync.aligned.m64n32k16.f32.f16.f16 {%0,%1,%2,%3,%4,%5,%6,%7,%8,%9,%10,%11,%12,%13,%14,%15}, {%16,%17,%18,%19}, %20, %21, 1, 1, 0;"
   : "+f"(d[0]),"+f"(d[1]),"+f"(d[2]),"+f"(d[3]),"+f"(d[4]),"+f"(d[5]),"+f"(d[6]),"+f"(d[7]),"+f"(d[8]),"+f"(d[9]),"+f"(d[10]),"+f"(d[11]),"+f"(d[12]),"+f"(d[13]),"+f"(d[14]),"+f"(d[15])
   : "r"(a[0]),"r"(a[1]),"r"(a[2]),"r"(a[3]),"l"(desc),"n"(SD));
}
template<int SD> __device__ __forceinline__ void wg_qk64(float* d, const uint32_t* a, uint64_t desc) {
  asm volatile("wgmma.mma_async.sync.aligned.m64n64k16.f32.f16.f16 {%0,%1,%2,%3,%4,%5,%6,%7,%8,%9,%10,%11,%12,%13,%14,%15,%16,%17,%18,%19,%20,%21,%22,%23,%24,%25,%26,%27,%28,%29,%30,%31}, {%32,%33,%34,%35}, %36, %37, 1, 1, 0;"
   : "+f"(d[0]),"+f"(d[1]),"+f"(d[2]),"+f"(d[3]),"+f"(d[4]),"+f"(d[5]),"+f"(d[6]),"+f"(d[7]),"+f"(d[8]),"+f"(d[9]),"+f"(d[10]),"+f"(d[11]),"+f"(d[12]),"+f"(d[13]),"+f"(d[14]),"+f"(d[15]),"+f"(d[16]),"+f"(d[17]),"+f"(d[18]),"+f"(d[19]),"+f"(d[20]),"+f"(d[21]),"+f"(d[22]),"+f"(d[23]),"+f"(d[24]),"+f"(d[25]),"+f"(d[26]),"+f"(d[27]),"+f"(d[28]),"+f"(d[29]),"+f"(d[30]),"+f"(d[31])
   : "r"(a[0]),"r"(a[1]),"r"(a[2]),"r"(a[3]),"l"(desc),"n"(SD));
}
template<int SD> __device__ __forceinline__ void wg_qs32(float* d, uint64_t da, uint64_t db) {
  asm volatile("wgmma.mma_async.sync.aligned.m64n32k16.f32.f16.f16 {%0,%1,%2,%3,%4,%5,%6,%7,%8,%9,%10,%11,%12,%13,%14,%15}, %16, %17, %18, 1, 1, 0, 0;"
   : "+f"(d[0]),"+f"(d[1]),"+f"(d[2]),"+f"(d[3]),"+f"(d[4]),"+f"(d[5]),"+f"(d[6]),"+f"(d[7]),"+f"(d[8]),"+f"(d[9]),"+f"(d[10]),"+f"(d[11]),"+f"(d[12]),"+f"(d[13]),"+f"(d[14]),"+f"(d[15])
   : "l"(da),"l"(db),"n"(SD));
}
template<int SD> __device__ __forceinline__ void wg_qs64(float* d, uint64_t da, uint64_t db) {
  asm volatile("wgmma.mma_async.sync.aligned.m64n64k16.f32.f16.f16 {%0,%1,%2,%3,%4,%5,%6,%7,%8,%9,%10,%11,%12,%13,%14,%15,%16,%17,%18,%19,%20,%21,%22,%23,%24,%25,%26,%27,%28,%29,%30,%31}, %32, %33, %34, 1, 1, 0, 0;"
   : "+f"(d[0]),"+f"(d[1]),"+f"(d[2]),"+f"(d[3]),"+f"(d[4]),"+f"(d[5]),"+f"(d[6]),"+f"(d[7]),"+f"(d[8]),"+f"(d[9]),"+f"(d[10]),"+f"(d[11]),"+f"(d[12]),"+f"(d[13]),"+f"(d[14]),"+f"(d[15]),"+f"(d[16]),"+f"(d[17]),"+f"(d[18]),"+f"(d[19]),"+f"(d[20]),"+f"(d[21]),"+f"(d[22]),"+f"(d[23]),"+f"(d[24]),"+f"(d[25]),"+f"(d[26]),"+f"(d[27]),"+f"(d[28]),"+f"(d[29]),"+f"(d[30]),"+f"(d[31])
   : "l"(da),"l"(db),"n"(SD));
}
template<int SD> __device__ __forceinline__ void wg_pv24(float* d, const uint32_t* a, uint64_t desc) {
  asm volatile("wgmma.mma_async.sync.aligned.m64n24k16.f32.bf16.bf16 {%0,%1,%2,%3,%4,%5,%6,%7,%8,%9,%10,%11}, {%12,%13,%14,%15}, %16, %17, 1, 1, 1;"
   : "+f"(d[0]),"+f"(d[1]),"+f"(d[2]),"+f"(d[3]),"+f"(d[4]),"+f"(d[5]),"+f"(d[6]),"+f"(d[7]),"+f"(d[8]),"+f"(d[9]),"+f"(d[10]),"+f"(d[11])
   : "r"(a[0]),"r"(a[1]),"r"(a[2]),"r"(a[3]),"l"(desc),"n"(SD));
}
template<int TA, int TB> __device__ __forceinline__ void wg_ss128(float* d, uint64_t da, uint64_t db, int sd) {
  asm volatile("{\n.reg .pred p;\nsetp.ne.b32 p, %66, 0;\n"
   "wgmma.mma_async.sync.aligned.m64n128k16.f32.bf16.bf16 {%0,%1,%2,%3,%4,%5,%6,%7,%8,%9,%10,%11,%12,%13,%14,%15,%16,%17,%18,%19,%20,%21,%22,%23,%24,%25,%26,%27,%28,%29,%30,%31,%32,%33,%34,%35,%36,%37,%38,%39,%40,%41,%42,%43,%44,%45,%46,%47,%48,%49,%50,%51,%52,%53,%54,%55,%56,%57,%58,%59,%60,%61,%62,%63}, %64, %65, p, 1, 1, %67, %68;\n}\n"
   : "+f"(d[0]),"+f"(d[1]),"+f"(d[2]),"+f"(d[3]),"+f"(d[4]),"+f"(d[5]),"+f"(d[6]),"+f"(d[7]),"+f"(d[8]),"+f"(d[9]),"+f"(d[10]),"+f"(d[11]),"+f"(d[12]),"+f"(d[13]),"+f"(d[14]),"+f"(d[15]),"+f"(d[16]),"+f"(d[17]),"+f"(d[18]),"+f"(d[19]),"+f"(d[20]),"+f"(d[21]),"+f"(d[22]),"+f"(d[23]),"+f"(d[24]),"+f"(d[25]),"+f"(d[26]),"+f"(d[27]),"+f"(d[28]),"+f"(d[29]),"+f"(d[30]),"+f"(d[31]),"+f"(d[32]),"+f"(d[33]),"+f"(d[34]),"+f"(d[35]),"+f"(d[36]),"+f"(d[37]),"+f"(d[38]),"+f"(d[39]),"+f"(d[40]),"+f"(d[41]),"+f"(d[42]),"+f"(d[43]),"+f"(d[44]),"+f"(d[45]),"+f"(d[46]),"+f"(d[47]),"+f"(d[48]),"+f"(d[49]),"+f"(d[50]),"+f"(d[51]),"+f"(d[52]),"+f"(d[53]),"+f"(d[54]),"+f"(d[55]),"+f"(d[56]),"+f"(d[57]),"+f"(d[58]),"+f"(d[59]),"+f"(d[60]),"+f"(d[61]),"+f"(d[62]),"+f"(d[63])
   : "l"(da),"l"(db),"r"(sd),"n"(TA),"n"(TB));
}
template<int TA, int TB> __device__ __forceinline__ void wg_ss64(float* d, uint64_t da, uint64_t db, int sd) {
  asm volatile("{\n.reg .pred p;\nsetp.ne.b32 p, %34, 0;\n"
   "wgmma.mma_async.sync.aligned.m64n64k16.f32.bf16.bf16 {%0,%1,%2,%3,%4,%5,%6,%7,%8,%9,%10,%11,%12,%13,%14,%15,%16,%17,%18,%19,%20,%21,%22,%23,%24,%25,%26,%27,%28,%29,%30,%31}, %32, %33, p, 1, 1, %35, %36;\n}\n"
   : "+f"(d[0]),"+f"(d[1]),"+f"(d[2]),"+f"(d[3]),"+f"(d[4]),"+f"(d[5]),"+f"(d[6]),"+f"(d[7]),"+f"(d[8]),"+f"(d[9]),"+f"(d[10]),"+f"(d[11]),"+f"(d[12]),"+f"(d[13]),"+f"(d[14]),"+f"(d[15]),"+f"(d[16]),"+f"(d[17]),"+f"(d[18]),"+f"(d[19]),"+f"(d[20]),"+f"(d[21]),"+f"(d[22]),"+f"(d[23]),"+f"(d[24]),"+f"(d[25]),"+f"(d[26]),"+f"(d[27]),"+f"(d[28]),"+f"(d[29]),"+f"(d[30]),"+f"(d[31])
   : "l"(da),"l"(db),"r"(sd),"n"(TA),"n"(TB));
}

template<int TA, int TB> __device__ __forceinline__ void wg_ss8(float* d, uint64_t da, uint64_t db, int sd) {
  asm volatile("{\n.reg .pred p;\nsetp.ne.b32 p, %6, 0;\n"
   "wgmma.mma_async.sync.aligned.m64n8k16.f32.bf16.bf16 {%0,%1,%2,%3}, %4, %5, p, 1, 1, %7, %8;\n}\n"
   : "+f"(d[0]),"+f"(d[1]),"+f"(d[2]),"+f"(d[3])
   : "l"(da),"l"(db),"r"(sd),"n"(TA),"n"(TB));
}

template<int SD, uint32_t HI> __device__ __forceinline__ void wq32(float* d, uint64_t da, uint32_t lo) {
  asm volatile("{\n.reg .b64 db;\nmov.b64 db, {%17, %19};\n"
   "wgmma.mma_async.sync.aligned.m64n32k16.f32.f16.f16 {%0,%1,%2,%3,%4,%5,%6,%7,%8,%9,%10,%11,%12,%13,%14,%15}, %16, db, %18, 1, 1, 0, 0;\n}\n"
   : "+f"(d[0]),"+f"(d[1]),"+f"(d[2]),"+f"(d[3]),"+f"(d[4]),"+f"(d[5]),"+f"(d[6]),"+f"(d[7]),"+f"(d[8]),"+f"(d[9]),"+f"(d[10]),"+f"(d[11]),"+f"(d[12]),"+f"(d[13]),"+f"(d[14]),"+f"(d[15])
   : "l"(da),"r"(lo),"n"(SD),"r"(HI));
}
template<int SD, uint32_t HI> __device__ __forceinline__ void wq64(float* d, uint64_t da, uint32_t lo) {
  asm volatile("{\n.reg .b64 db;\nmov.b64 db, {%33, %35};\n"
   "wgmma.mma_async.sync.aligned.m64n64k16.f32.f16.f16 {%0,%1,%2,%3,%4,%5,%6,%7,%8,%9,%10,%11,%12,%13,%14,%15,%16,%17,%18,%19,%20,%21,%22,%23,%24,%25,%26,%27,%28,%29,%30,%31}, %32, db, %34, 1, 1, 0, 0;\n}\n"
   : "+f"(d[0]),"+f"(d[1]),"+f"(d[2]),"+f"(d[3]),"+f"(d[4]),"+f"(d[5]),"+f"(d[6]),"+f"(d[7]),"+f"(d[8]),"+f"(d[9]),"+f"(d[10]),"+f"(d[11]),"+f"(d[12]),"+f"(d[13]),"+f"(d[14]),"+f"(d[15]),"+f"(d[16]),"+f"(d[17]),"+f"(d[18]),"+f"(d[19]),"+f"(d[20]),"+f"(d[21]),"+f"(d[22]),"+f"(d[23]),"+f"(d[24]),"+f"(d[25]),"+f"(d[26]),"+f"(d[27]),"+f"(d[28]),"+f"(d[29]),"+f"(d[30]),"+f"(d[31])
   : "l"(da),"r"(lo),"n"(SD),"r"(HI));
}
template<int SD, uint32_t HI> __device__ __forceinline__ void wpv(float* d, const uint32_t* a, uint32_t lo) {
  asm volatile("{\n.reg .b64 db;\nmov.b64 db, {%16, %18};\n"
   "wgmma.mma_async.sync.aligned.m64n24k16.f32.bf16.bf16 {%0,%1,%2,%3,%4,%5,%6,%7,%8,%9,%10,%11}, {%12,%13,%14,%15}, db, %17, 1, 1, 1;\n}\n"
   : "+f"(d[0]),"+f"(d[1]),"+f"(d[2]),"+f"(d[3]),"+f"(d[4]),"+f"(d[5]),"+f"(d[6]),"+f"(d[7]),"+f"(d[8]),"+f"(d[9]),"+f"(d[10]),"+f"(d[11])
   : "r"(a[0]),"r"(a[1]),"r"(a[2]),"r"(a[3]),"r"(lo),"n"(SD),"r"(HI));
}

__device__ __forceinline__ uint32_t phi2(float a, float b) {
  uint32_t r, e;
  asm("cvt.rn.relu.bf16x2.f32 %0, %1, %2;" : "=r"(r) : "f"(b), "f"(a));
  e = pack_bf16(ex2f(a * 1.4426950408889634f), ex2f(b * 1.4426950408889634f));
  asm("add.rn.bf16x2 %0, %0, %1;" : "+r"(e) : "r"(0x35863586u));
  asm("min.NaN.bf16x2 %0, %0, %1;" : "+r"(e) : "r"(0x3F803F80u));
  asm("add.rn.bf16x2 %0, %0, %1;" : "+r"(e) : "r"(r));
  return e;
}

__device__ __forceinline__ void mbar_arrive(uint32_t bar) { asm volatile("mbarrier.arrive.shared::cta.b64 _, [%0];" :: "r"(bar) : "memory"); }
__device__ __forceinline__ void named_arrive(int id, int n) { asm volatile("bar.arrive %0, %1;" :: "r"(id), "r"(n) : "memory"); }
__device__ __forceinline__ void fence_async_all() { asm volatile("fence.proxy.async.global;" ::: "memory"); }
__device__ __forceinline__ void flag_add(uint32_t* f) { asm volatile("fence.acq_rel.gpu;\nred.relaxed.gpu.global.add.u32 [%0], 1;" :: "l"(f) : "memory"); }
__device__ __forceinline__ void flag_wait(const uint32_t* f, uint32_t target) {
  uint32_t v;
#pragma unroll 1
  for (int it = 0;; it++) {
    asm volatile("ld.acquire.gpu.global.u32 %0, [%1];" : "=r"(v) : "l"(f) : "memory");
    if ((int32_t)(v - target) >= 0) break;
    if (it > 2000000) __trap();
    __nanosleep(64);
  }
}
__device__ __forceinline__ bool elect_one() {
  uint32_t p;
  asm volatile("{\n.reg .pred P;\nelect.sync _|P, 0xFFFFFFFF;\nselp.b32 %0, 1, 0, P;\n}\n" : "=r"(p));
  return p;
}
__device__ __forceinline__ void lds4(uint32_t a, uint32_t* r) {
  asm volatile("ld.shared.v4.b32 {%0,%1,%2,%3}, [%4];" : "=r"(r[0]), "=r"(r[1]), "=r"(r[2]), "=r"(r[3]) : "r"(a) : "memory");
}
__device__ __forceinline__ uint32_t lds1(uint32_t a) { uint32_t r; asm volatile("ld.shared.b32 %0, [%1];" : "=r"(r) : "r"(a) : "memory"); return r; }
__device__ __forceinline__ void sts1(uint32_t a, uint32_t v) { asm volatile("st.shared.b32 [%0], %1;" :: "r"(a), "r"(v) : "memory"); }
__device__ __forceinline__ void sts4(uint32_t a, uint32_t r0, uint32_t r1, uint32_t r2, uint32_t r3) {
  asm volatile("st.shared.v4.b32 [%0], {%1,%2,%3,%4};" :: "r"(a), "r"(r0), "r"(r1), "r"(r2), "r"(r3) : "memory");
}
__device__ __forceinline__ void ldsm4(uint32_t a, uint32_t* r) {
  asm volatile("ldmatrix.sync.aligned.m8n8.x4.shared.b16 {%0,%1,%2,%3}, [%4];" : "=r"(r[0]), "=r"(r[1]), "=r"(r[2]), "=r"(r[3]) : "r"(a) : "memory");
}
__device__ __forceinline__ float rcpf(float x) { float y; asm("rcp.approx.ftz.f32 %0, %1;" : "=f"(y) : "f"(x)); return y; }
__device__ __forceinline__ uint32_t hfma2(uint32_t a, uint32_t b, uint32_t c) { uint32_t r; asm("fma.rn.f16x2 %0, %1, %2, %3;" : "=r"(r) : "r"(a), "r"(b), "r"(c)); return r; }
__device__ __forceinline__ uint32_t hadd2(uint32_t a, uint32_t b) { uint32_t r; asm("add.rn.f16x2 %0, %1, %2;" : "=r"(r) : "r"(a), "r"(b)); return r; }

#define STEPK 96
#define QSCALE 0.36067376022224085f
#define SMAGIC (512.0f + 2.0f * (191.0f - 30.0f - 1.5823545f))
#define VSHIFT 1073741824.0f

__device__ uint32_t g_epoch[132];
__device__ uint32_t g_flag[288 * 8];
#define FLAG_KV (g_flag)
#define FLAG_B(h) (g_flag + (4 + (h)) * 8)
#define FLAG_OA(cta, pass) (g_flag + (16 + (cta) * 2 + (pass)) * 8)
#define FLAG_LM(i) (g_flag + (272 + (i)) * 8)

#define SM_TOTAL (224 * 1024 + 2048 + 1024)
#define OFF_K 0
#define OFF_F 65536
#define OFF_V 131072
#define OFF_MISC (224 * 1024)

#define BAR_FULL(s) (bars + 8 * (s))
#define BAR_EMPTY(s) (bars + 24 + 8 * (s))
#define BAR_KV(c) (bars + 48 + 8 * (c))
#define BAR_BDONE (bars + 80)
#define BAR_Q (bars + 88)
#define BAR_GO (bars + 96)
#define BAR_Q2 (bars + 104)
#define BAR_OD(p) (bars + 112 + 8 * (p))
#define BAR_CL(c) (bars + 128 + 8 * (c))
#define BAR_TE(i) (bars + 168 + 8 * (i))
#define BAR_TF(g) (bars + 224 + 8 * (g))
#define BAR_XA(w) (bars + 352 + 8 * (w))
#define BAR_VB(c) (bars + 384 + 8 * (c))

__device__ __forceinline__ uint32_t exp2_pair_fix(float d0, float d1, uint32_t c63, uint32_t m1) {
  uint32_t w, y, s, r;
  asm("prmt.b32 %0, %1, %2, 0x6521;" : "=r"(w) : "r"(__float_as_uint(d0)), "r"(__float_as_uint(d1)));
  asm("lop3.b32 %0, %1, 0x007F007F, %2, 0xEA;" : "=r"(y) : "r"(w), "r"(c63));
  asm("mad.lo.u32 %0, %1, %2, %3;" : "=r"(s) : "r"(y), "r"(m1), "r"(w));
  asm("fma.rn.bf16x2 %0, %1, %2, %3;" : "=r"(r) : "r"(w), "r"(y), "r"(s));
  return r;
}

__device__ __forceinline__ void attn_slow(const uint4* gq, __nv_bfloat16* dst) {
  const int t = threadIdx.x & 127;
  const int row = t >> 1, half = t & 1;
  float q[16];
#pragma unroll
  for (int i = 0; i < 4; i++) {
    const uint4 v = gq[(row >> 4) * 32 + (row & 7) * 4 + i];
    const uint32_t lo = (row & 8) ? v.y : v.x, hi = (row & 8) ? v.w : v.z;
    q[2 * i] = bf_lo(lo); q[2 * i + 1] = bf_hi(lo); q[2 * i + 8] = bf_lo(hi); q[2 * i + 9] = bf_hi(hi);
  }
  float m = -INFINITY, l = 0.f, o[16];
#pragma unroll
  for (int i = 0; i < 16; i++) o[i] = 0.f;
#pragma unroll 1
  for (int j = half * 1024; j < half * 1024 + 1024; j++) {
    uint4 ka = g_KV[4 * S_TOK + j], kb = g_KV[5 * S_TOK + j];
    uint4 va = g_KV[6 * S_TOK + j], vb = g_KV[7 * S_TOK + j];
    uint32_t kk[8] = {ka.x, ka.y, ka.z, ka.w, kb.x, kb.y, kb.z, kb.w};
    uint32_t vv[8] = {va.x, va.y, va.z, va.w, vb.x, vb.y, vb.z, vb.w};
    float s = 0.f;
#pragma unroll
    for (int i = 0; i < 8; i++) { s = fmaf(q[2 * i], bf_lo(kk[i]), s); s = fmaf(q[2 * i + 1], bf_hi(kk[i]), s); }
    s = rbf(s) * 0.25f;
    if (s > m) {
      float c = __expf(m - s);
      l *= c;
#pragma unroll
      for (int i = 0; i < 16; i++) o[i] *= c;
      m = s;
    }
    float p = __expf(s - m);
    l += p;
#pragma unroll
    for (int i = 0; i < 8; i++) { o[2 * i] = fmaf(p, bf_lo(vv[i]), o[2 * i]); o[2 * i + 1] = fmaf(p, bf_hi(vv[i]), o[2 * i + 1]); }
  }
  float m2 = __shfl_xor_sync(~0u, m, 1);
  float mm = fmaxf(m, m2);
  float c = __expf(m - mm);
  l *= c; l += __shfl_xor_sync(~0u, l, 1);
  float inv = 1.f / l;
  uint32_t r[8];
#pragma unroll
  for (int i = 0; i < 16; i++) { o[i] *= c; o[i] += __shfl_xor_sync(~0u, o[i], 1); o[i] *= inv; }
#pragma unroll
  for (int i = 0; i < 8; i++) r[i] = pack_bf16(o[2 * i], o[2 * i + 1]);
  uint4* d = (uint4*)(dst + (size_t)row * D_MOD);
  if (half == 0) d[0] = make_uint4(r[0], r[1], r[2], r[3]); else d[1] = make_uint4(r[4], r[5], r[6], r[7]);
}

struct Params { const __nv_bfloat16* wk; const __nv_bfloat16* wv; const __nv_bfloat16* xa; };
__device__ __forceinline__ void cp16(uint32_t dst, const void* src) { asm volatile("cp.async.cg.shared.global [%0], [%1], 16;" :: "r"(dst), "l"(src) : "memory"); }

__device__ __forceinline__ void helper_cta(const int h, const uint32_t sb, const uint32_t bars, const int wg, const int w4,
                                           const CUtensorMap* mQ, const CUtensorMap* mOs) {
  const int lane = threadIdx.x & 31;
  mbar_wait(BAR_GO, 0);
  const int cb = wg & 1, col = h * 128 + cb * 64, row0 = S_TOK + (wg >> 1) * 1024;
  const uint32_t buf = sb + wg * 49152;
  if (w4 == 0 && elect_one()) {
    fence_async_all();
#pragma unroll 1
    for (int u = 0; u < 3; u++) {
      mbar_expect_tx(BAR_TF(wg * 3 + u), 16384);
      tma2d(buf + u * 16384, mQ, col, row0 + u * 128, BAR_TF(wg * 3 + u));
    }
  }
  const int head = h * 8 + cb * 4 + w4;
  float4 a0 = make_float4(0, 0, 0, 0), a1 = a0, a2 = a0;
#pragma unroll 8
  for (int tt = 0; tt < 16; tt++) {
    const float4* src = g_kvp + ((tt * 32 + head) * 3) * 32 + lane;
    float4 u = src[0], v = src[32], w = src[64];
    a0.x += u.x; a0.y += u.y; a0.z += u.z; a0.w += u.w;
    a1.x += v.x; a1.y += v.y; a1.z += v.z; a1.w += v.w;
    a2.x += w.x; a2.y += w.y; a2.z += w.z; a2.w += w.w;
  }
  const uint32_t b00 = pack_bf16(a0.x, a0.y), b01 = pack_bf16(a0.z, a0.w);
  const uint32_t b10 = pack_bf16(a1.x, a1.y), b11 = pack_bf16(a1.z, a1.w);
  const uint32_t bz0 = pack_bf16(a2.x, a2.y), bz1 = pack_bf16(a2.z, a2.w);
  const int m = lane >> 3, r = lane & 7;
  const uint32_t off = ((m & 1) * 8 + r) * 128 + (((w4 * 2 + (m >> 1)) ^ r) << 4);
  int s = 0, ph = 0;
#pragma unroll 1
  for (int u = 0; u < 8; u++) {
    const uint32_t bb = buf + s * 16384;
    mbar_wait(BAR_TF(wg * 3 + s), ph);
#pragma unroll
    for (int mt = 0; mt < 8; mt++) {
      uint32_t a[4];
      ldsm4(bb + mt * 2048 + off, a);
      float n0[4] = {0, 0, 0, 0}, n1[4] = {0, 0, 0, 0}, dn[4] = {0, 0, 0, 0};
      mma_bf16(dn, a[0], a[1], a[2], a[3], bz0, bz1);
      mma_bf16(n0, a[0], a[1], a[2], a[3], b00, b01);
      mma_bf16(n1, a[0], a[1], a[2], a[3], b10, b11);
      const float i0 = rcpf(dn[0] + 1e-6f), i1 = rcpf(dn[2] + 1e-6f);
      stsm4(bb + mt * 2048 + off, pack_bf16(n0[0] * i0, n0[1] * i0), pack_bf16(n0[2] * i1, n0[3] * i1),
            pack_bf16(n1[0] * i0, n1[1] * i0), pack_bf16(n1[2] * i1, n1[3] * i1));
    }
    fence_async();
    named_bar(wg + 1, 128);
    if (w4 == 0 && lane == 0) {
      tma2d_store(mOs, bb, col, row0 + u * 128);
      bulk_commit();
      if (u >= 1 && u + 2 < 8) {
        asm volatile("cp.async.bulk.wait_group.read 1;" ::: "memory");
        const int sp = s == 0 ? 2 : s - 1;
        mbar_expect_tx(BAR_TF(wg * 3 + sp), 16384);
        tma2d(buf + sp * 16384, mQ, col, row0 + (u + 2) * 128, BAR_TF(wg * 3 + sp));
      }
    }
    __syncwarp();
    if (++s == 3) { s = 0; ph ^= 1; }
  }
  if (w4 == 0 && lane == 0) {
    bulk_wait_all();
    fence_async_all();
    flag_add(FLAG_LM((h * 2 + cb) * 2 + (wg >> 1)));
    if (wg == 0) TS(1, 8);
  }
}

#define STAGE(s) (sb + (2 - (s)) * 65536)
template <int TR> __device__ __forceinline__ void proj_kb(float* acc, uint32_t st, uint32_t offA, uint32_t offB, int first) {
  const uint64_t da = make_desc(st + offA, TR ? 8192 : 16, 1024, 1);
  const uint64_t db = make_desc(st + offB, TR ? 16 : 8192, 1024, 1);
  wg_fence();
#pragma unroll
  for (int k = 0; k < 4; k++) wg_ss128<TR, 1 - TR>(acc, da + k * (TR ? 128 : 2), db + k * (TR ? 2 : 128), k != 0 || !first);
  wg_commit();
}
template <int TR> __device__ __forceinline__ void proj_loop(float* acc, uint32_t sb, uint32_t bars, uint32_t offA, uint32_t offB,
                                                            int wg, uint32_t sWKV) {
  {
    float kv[4];
    if (threadIdx.x == 0) TS(0, 13);
    mbar_wait(BAR_XA(wg), 0);
    if (threadIdx.x == 0) TS(0, 1);
    const uint64_t da = make_desc(STAGE(2) + wg * 16384, 16, 1024, 1), db = make_desc(sWKV + wg * 2048, 128, 128, 0);
    wg_fence();
#pragma unroll
    for (int k = 0; k < 8; k++) wg_ss8<0, 1>(kv, da + (k >> 2) * 512 + (k & 3) * 2, db + k * 16, k != 0);
    wg_commit();
    wg_wait<0>();
    fence_regs<4>(kv);
    named_bar(wg + 1, 128);
    sts4(sWKV + threadIdx.x * 16, __float_as_uint(kv[0]), __float_as_uint(kv[1]), __float_as_uint(kv[2]), __float_as_uint(kv[3]));
    __syncwarp();
    if ((threadIdx.x & 31) == 0) mbar_arrive(BAR_GO);
  }
  int s = 0, ph = 0, sp = 0;
#pragma unroll 1
  for (int kb = 0; kb < 8; kb++) {
    mbar_wait(BAR_FULL(s), ph);
    if (threadIdx.x == 0) TS(0, 2 + kb);
    proj_kb<TR>(acc, STAGE(s), offA, offB, kb == 0);
    wg_wait<1>();
    if (kb >= 1 && (threadIdx.x & 127) == 0) mbar_arrive(BAR_EMPTY(sp));
    __syncwarp();
    sp = s;
    if (++s == 3) { s = 0; ph ^= 1; }
  }
  wg_wait<0>();
  fence_regs<64>(acc);
}

__device__ __forceinline__ uint32_t tail_slots(int t) {
  const uint32_t lo = t < 4 ? (t < 2 ? (t == 0 ? 0x0C0B0Au : 0x0F0E0Du) : (t == 2 ? 0x100400u : 0x081814u))
                            : (t < 6 ? (t == 4 ? 0x110501u : 0x021915u) : (t == 6 ? 0x161206u : (t == 7 ? 0x07031Au : 0x1B1713u)));
  return lo;
}

__device__ __forceinline__ void take_role(uint32_t sM, int wg) {
  uint32_t r;
  asm volatile("atom.shared.add.u32 %0, [%1], 1;" : "=r"(r) : "r"(sM + 20) : "memory");
  sts1(sM + 32 + wg * 4, r);
}

__global__ void __launch_bounds__(640, 1)
k1_main(const __grid_constant__ CUtensorMap mXA64, const __grid_constant__ CUtensorMap mXB,
        const __grid_constant__ CUtensorMap mWq, const __grid_constant__ CUtensorMap mWqkv,
        const __grid_constant__ CUtensorMap mQst, const __grid_constant__ CUtensorMap mOst,
        const __grid_constant__ CUtensorMap mO, const __grid_constant__ CUtensorMap mWoA,
        const __grid_constant__ CUtensorMap mWoB, const __grid_constant__ CUtensorMap mOut, const Params prm) {
  extern __shared__ uint8_t smem_raw[];
  const uint32_t sb = (smem_u32(smem_raw) + 1023u) & ~1023u;
  const uint32_t bars = sb + OFF_MISC, sM = bars + 512, sT = bars + 1024;
  const int tid = threadIdx.x, warp = __shfl_sync(~0u, tid >> 5, 0), wg = warp >> 2, w4 = warp & 3, lane = tid & 31;
  const bool helper = blockIdx.x >= 128;
  if (tid == 0) TS(0, 0);
  const int G = blockIdx.x >> 4, gi = blockIdx.x & 15;
  const int tbA = G * 4 + (gi >> 2), hg = gi & 3;
  const int ttB = (G >> 1) * 4 + (gi >> 2), hq = (G & 1) * 4 + (gi & 3);
  const int ttO = G * 2 + (gi >> 3), ct = gi & 7;
  auto issue = [&](int kb, int s) {
    const uint32_t fb = BAR_FULL(s), st = STAGE(s);
    mbar_expect_tx(fb, 65536);
    tma2d(st + 16384, &mXA64, kb * 64, tbA * 64, fb);
    tma2d(st, &mWq, hg * 128, kb * 64, fb);
    tma2d(st + 8192, &mWq, hg * 128 + 64, kb * 64, fb);
    tma2d(st + 49152, &mXB, kb * 64, ttB * 128, fb);
    tma2d(st + 24576, &mWqkv, hq * 64, kb * 64, fb);
    tma2d(st + 32768, &mWqkv, 512 + hq * 64, kb * 64, fb);
    tma2d(st + 40960, &mWqkv, 1024 + hq * 64, kb * 64, fb);
  };
  const uint32_t sOne = sb + OFF_V + 65536, sWKV = sOne + 24576;
  if (warp >= 16) {
    if (warp == 17) {
      if (lane == 0) {
        mbar_init(BAR_BDONE, 8); mbar_init(BAR_Q, 8); mbar_init(BAR_GO, helper ? 1 : 16); mbar_init(BAR_Q2, 5);
        mbar_init(BAR_OD(0), 16); mbar_init(BAR_OD(1), 16); mbar_init(BAR_CL(0), 1); mbar_init(BAR_FULL(2), 1);
        sts1(sM + 20, 0);
      }
      if (lane >= 1 && lane < 5) mbar_init(BAR_CL(lane), 4);
      if (lane >= 5 && lane < 8) { mbar_init(BAR_EMPTY(lane - 5), 4); mbar_init(BAR_KV(lane - 5), 1); mbar_init(BAR_VB(lane - 5), 1); }
      if (lane >= 8 && lane < 15) mbar_init(BAR_TE(lane - 8), 2);
      if (lane >= 16) mbar_init(BAR_TF(lane - 16), 1);
      asm volatile("fence.mbarrier_init.release.cluster;" ::: "memory");
    } else if (warp == 16 && !helper && elect_one()) {
#pragma unroll
      for (int w = 0; w < 4; w++) mbar_init(BAR_XA(w), 1);
      mbar_init(BAR_FULL(0), 1); mbar_init(BAR_FULL(1), 1);
      asm volatile("fence.mbarrier_init.release.cluster;" ::: "memory");
#pragma unroll
      for (int w = 0; w < 4; w++) {
        mbar_expect_tx(BAR_XA(w), 16384);
        tma2d(STAGE(2) + w * 16384, &mXA64, w * 128, tbA * 64, BAR_XA(w));
        tma2d(STAGE(2) + w * 16384 + 8192, &mXA64, w * 128 + 64, tbA * 64, BAR_XA(w));
      }
      TS(0, 14);
      issue(0, 0);
      issue(1, 1);
      TS(0, 15);
    }
  } else if (!helper) {
    const uint4 v = __ldg((const uint4*)(hg >= 2 ? prm.wv : prm.wk) + tid * 2 + (hg & 1));
#pragma unroll
    for (int i = 0; i < 3; i++) {
      const int key = tid + i * 512;
      sts4(sOne + key * 16, (key % STEPK) < 32 ? 0x00003F80u : 0x00004E80u, 0u, 0u, 0u);
    }
    sts4(sWKV + tid * 16, v.x, v.y, v.z, v.w);
    fence_async();
  }
  __syncthreads();
  if (wg == 4) {
    asm volatile("setmaxnreg.dec.sync.aligned.u32 32;");
    const uint32_t ep = g_epoch[blockIdx.x] + 1;
    if (helper) {
      if (w4 == 0 && elect_one()) {
        flag_wait(FLAG_B(blockIdx.x - 128), ep * 32);
        fence_async_all();
        TS(1, 10);
        mbar_arrive(BAR_GO);
        g_epoch[blockIdx.x] = ep;
      }
      return;
    }
    mbar_wait(BAR_GO, 0);
    if (w4 == 0 && elect_one()) issue(2, 2);
    {
      uint32_t a[4], b[4];
      float c[4];
      lds4(sWKV + (tid - 512) * 16, a);
      lds4(sWKV + 2048 + (tid - 512) * 16, b);
#pragma unroll
      for (int i = 0; i < 4; i++) c[i] = __uint_as_float(a[i]) + __uint_as_float(b[i]);
      lds4(sWKV + 4096 + (tid - 512) * 16, a);
      lds4(sWKV + 6144 + (tid - 512) * 16, b);
#pragma unroll
      for (int i = 0; i < 4; i++) c[i] += __uint_as_float(a[i]) + __uint_as_float(b[i]);
      sts1(sT + w4 * 256 + lane * 4, pack_bf16(c[0], c[1]));
      sts1(sT + w4 * 256 + 128 + lane * 4, pack_bf16(c[2], c[3]));
    }
    named_bar(9, 128);
    {
      const int t = tid - 512;
#pragma unroll
      for (int i = 0; i < 4; i++) {
        const int key = 1536 + t + i * 128;
        sts4(sOne + key * 16, (key % STEPK) < 32 ? 0x00003F80u : 0x00004E80u, 0u, 0u, 0u);
      }
      fence_async();
      __syncwarp();
      if (lane == 0) mbar_arrive(BAR_Q);
    }
    if (w4 == 0) {
      int s = 0, ph = 0;
#pragma unroll 1
      for (int kb = 3; kb < 8; kb++) {
        mbar_wait(BAR_EMPTY(s), ph);
        if (elect_one()) issue(kb, s);
        if (++s == 3) { s = 0; ph ^= 1; }
      }
      flag_wait(FLAG_KV, ep * 128);
      fence_async_all();
      if (lane == 0) TS(0, 11);
#pragma unroll 1
      for (int m = 0; m < 2; m++) {
        mbar_wait(m == 0 ? BAR_EMPTY(2) : BAR_EMPTY(0), 1 - m);
        if (elect_one()) {
#pragma unroll
          for (int c = 0; c < 3; c++) {
            const int k0 = c == 0 ? 0 : (c == 1 ? 7 * STEPK : 12 * STEPK), k1 = c == 0 ? 7 * STEPK : (c == 1 ? 12 * STEPK : S_TOK);
            const uint32_t bytes = (k1 - k0) * 16, fb = m == 0 ? BAR_KV(c) : BAR_VB(c);
            mbar_expect_tx(fb, 2 * bytes);
#pragma unroll
            for (int p = 0; p < 2; p++)
              bulk_g2s(sb + m * OFF_V + p * 32768 + k0 * 16, g_KV + (m * 2 + p) * S_TOK + k0, bytes, fb);
          }
        }
      }
      mbar_wait(BAR_CL(1), 0);
      flag_wait(FLAG_LM((lane & 7) * 2 + (ttO >> 3)), ep);
      __syncwarp();
      fence_async_all();
      if (lane == 0) TS(2, 13);
#pragma unroll 1
      for (int n = 0; n < 8; n++) {
        mbar_wait(BAR_CL(n < 4 ? n >> 1 : (n == 4 ? 2 : (n < 7 ? 3 : 4))), 0);
        const uint32_t sl = tail_slots(n), fb = BAR_TF(n);
        if (elect_one()) {
          mbar_expect_tx(fb, 24576);
          tma2d(sb + (sl & 255) * 8192, &mWoB, ct * 64, n * 64, fb);
          tma2d(sb + ((sl >> 8) & 255) * 8192, &mO, n * 64, S_TOK + ttO * 128, fb);
          tma2d(sb + (sl >> 16) * 8192, &mO, n * 64, S_TOK + ttO * 128 + 64, fb);
        }
      }
      if (lane == 0) g_epoch[blockIdx.x] = ep;
    } else if (w4 == 3) {
      flag_wait(FLAG_KV, ep * 128);
      const uint4 a = *(const uint4*)(g_stats + lane * 4);
      const float kmax2 = __uint_as_float(__reduce_max_sync(~0u, a.x)) + __uint_as_float(__reduce_max_sync(~0u, a.y));
      const float vmax = __uint_as_float(__reduce_max_sync(~0u, max(a.z, a.w)));
      const float lv = vmax > 0.f ? __log2f(vmax) : 0.f;
      const float lim = fminf(90.f, fminf(91.f + lv, 95.f - lv));
      float thr = -1.f;
      if (vmax < 1e27f && kmax2 <= 65536.f && lim > 2.f) thr = fminf(60000.f, (lim * lim - 1.f) / (kmax2 * 1.02f + 1e-30f));
      if (lane == 0) { sts1(sM + 16, __float_as_uint(thr)); mbar_arrive(BAR_Q2); }
      mbar_wait(BAR_CL(3), 0);
      flag_wait(FLAG_OA(ttO * 8 + (lane & 7), 0), ep);
      __syncwarp();
      uint32_t pend = 0xF, rdy = 0;
#pragma unroll 1
      for (int n = 0; n < 8; n++) {
        const int gidx = n < 4 ? n + 9 : (n == 4 ? 8 : n + 8);
        mbar_wait(n == 4 ? BAR_CL(4) : BAR_TE(gidx - 9), 0);
        int kb = n * 2;
        if (n >= 4) {
          rdy &= pend;
#pragma unroll 1
          for (int it = 0; !rdy; it++) {
            uint32_t v;
            asm volatile("ld.acquire.gpu.global.u32 %0, [%1];" : "=r"(v) : "l"(FLAG_OA(ttO * 8 + (lane & 7), 1)) : "memory");
            const uint32_t b = __ballot_sync(~0u, (int32_t)(v - ep) >= 0);
            rdy = b & (b >> 4) & pend;
            if (it > 2000000) __trap();
          }
          const int hsel = __ffs(rdy) - 1;
          pend &= ~(1u << hsel);
          kb = hsel * 2 + 1;
          if (lane == 0 && n == 7) TS(2, 14);
        }
        fence_async_all();
        const uint32_t sl = tail_slots(n == 4 ? 8 : gidx - 9), fb = BAR_TF(gidx);
        if (elect_one()) {
          mbar_expect_tx(fb, 24576);
          tma2d(sb + ((sl >> 8) & 255) * 8192, &mO, kb * 64, ttO * 128, fb);
          tma2d(sb + (sl >> 16) * 8192, &mO, kb * 64, ttO * 128 + 64, fb);
          tma2d(sb + (sl & 255) * 8192, &mWoA, ct * 64, kb * 64, fb);
        }
      }
    } else {
      const int ch = tbA * 2 + (w4 - 1);
      uint32_t v[4], o[4];
      lds4(sT + (w4 - 1) * 512 + lane * 16, v);
      int kap;
      if (lane < 21) kap = lane * STEPK + 32 + ch;
      else { int idx = ch * 11 + (lane - 21); kap = (idx >> 5) * STEPK + (idx & 31); }
      g_KV[(4 + hg) * S_TOK + kap] = make_uint4(v[0], v[1], v[2], v[3]);
      float st = 0.f;
      if (hg < 2) {
        const float sc = lane < 21 ? 2.f : 1.f;
#pragma unroll
        for (int u = 0; u < 4; u++) {
          uint32_t pv = __shfl_up_sync(~0u, v[u], 1);
          if (lane == 0 || lane >= 21) pv = 0;
          const float x = bf_lo(v[u]), y = bf_hi(v[u]);
          st += x * x + y * y;
          o[u] = pack_f16((x - bf_lo(pv)) * sc, (y - bf_hi(pv)) * sc);
        }
      } else {
        const float sc = lane < 21 ? VSHIFT : 1.f;
#pragma unroll
        for (int u = 0; u < 4; u++) { float x = bf_lo(v[u]), y = bf_hi(v[u]); st += fabsf(x) + fabsf(y); o[u] = pack_bf16(x * sc, y * sc); }
      }
      g_KV[hg * S_TOK + kap] = make_uint4(o[0], o[1], o[2], o[3]);
      const uint32_t um = __reduce_max_sync(~0u, __float_as_uint(st) & 0x7FFFFFFFu);
      if (w4 == 2) {
        if (lane == 0) sts1(sM + 24, um);
        named_arrive(10, 64);
      }
      else {
        named_bar(10, 64);
        if (elect_one()) {
          g_stats[tbA * 4 + hg] = max(um, lds1(sM + 24));
          fence_async_all();
          flag_add(FLAG_KV);
          TS(1, 9);
          mbar_wait(BAR_BDONE, 0);
          tma2d_store(&mQst, sb + OFF_F + 49152, hq * 64, S_TOK + ttB * 128);
          bulk_commit();
          bulk_wait_all();
          fence_async_all();
          flag_add(FLAG_B(hq >> 1));
          TS(0, 12);
          mbar_wait(BAR_Q, 0);
          mbar_arrive(BAR_CL(0));
#pragma unroll 1
          for (int p = 0; p < 2; p++) {
            mbar_wait(BAR_OD(p), 0);
            TS(2, 1);
            fence_async_all();
            flag_add(FLAG_OA(blockIdx.x, p));
          }
          TS(2, 0);
        }
      }
    }
    return;
  }
  if (helper) { helper_cta(blockIdx.x - 128, sb, bars, wg, w4, &mQst, &mOst); return; }

  {
    float acc[64];
    if (wg == 0) proj_loop<0>(acc, sb, bars, 16384, 0, wg, sWKV);
    else proj_loop<1>(acc, sb, bars, 16384 + wg * 8192, 49152, wg, sWKV);
    asm volatile("setmaxnreg.inc.sync.aligned.u32 112;");
    if (tid == 0) TS(0, 10);
    const uint32_t sF = sb + OFF_F;
    if (wg == 0) {
      uint32_t r[32];
      const uint32_t qa = sF + w4 * 512 + ((lane >> 3) & 1) * 256 + (lane >> 4) * 128 + (lane & 7) * 16;
#pragma unroll
      for (int hd = 0; hd < 8; hd++) {
#pragma unroll
        for (int i = 0; i < 4; i++) r[4 * hd + i] = pack_f16(acc[8 * hd + 2 * i] * QSCALE, acc[8 * hd + 2 * i + 1] * QSCALE);
        stsm4(qa + hd * 2048, r[4 * hd], r[4 * hd + 1], r[4 * hd + 2], r[4 * hd + 3]);
        if (hd == 3) {
          fence_async();
          __syncwarp();
          if (lane == 0) mbar_arrive(BAR_Q);
        }
      }
      fence_async();
      uint32_t nmax = 0;
#pragma unroll
      for (int hd = 0; hd < 8; hd++) {
        const uint32_t* q = r + 4 * hd;
        const uint32_t t0 = hfma2(q[2], q[2], hfma2(q[0], q[0], 0u)), t1 = hfma2(q[3], q[3], hfma2(q[1], q[1], 0u));
        uint32_t n = hadd2(__byte_perm(t0, t1, 0x5410), __byte_perm(t0, t1, 0x7632));
        n = hadd2(n, __shfl_xor_sync(~0u, n, 1));
        n = hadd2(n, __shfl_xor_sync(~0u, n, 2));
        nmax = __vmaxu2(nmax, n & 0x7FFF7FFFu);
      }
      nmax = __reduce_max_sync(~0u, max(nmax & 0xFFFFu, nmax >> 16));
      if (lane == 0) sts1(sM + w4 * 4, nmax);
      uint4* gq = (uint4*)g_Q + blockIdx.x * 1024 + tid;
#pragma unroll
      for (int hd = 0; hd < 8; hd++)
        gq[hd * 128] = make_uint4(pack_bf16(acc[8 * hd], acc[8 * hd + 1]), pack_bf16(acc[8 * hd + 2], acc[8 * hd + 3]),
                                  pack_bf16(acc[8 * hd + 4], acc[8 * hd + 5]), pack_bf16(acc[8 * hd + 6], acc[8 * hd + 7]));
      __syncwarp();
      if (lane == 0) mbar_arrive(BAR_Q2);
    } else if (wg == 3) {
      named_arrive(8, 384);
      named_bar(6, 384);
      const int t = tid & 127;
#pragma unroll
      for (int j = 0; j < 8; j++)
        sts4(sF + 24576 + j * 2048 + t * 16, pack_bf16(acc[8 * j], acc[8 * j + 1]), pack_bf16(acc[8 * j + 2], acc[8 * j + 3]),
             pack_bf16(acc[8 * j + 4], acc[8 * j + 5]), pack_bf16(acc[8 * j + 6], acc[8 * j + 7]));
      named_arrive(7, 256);
    } else {
      uint32_t p[32];
      named_arrive(6, 384);
      if (wg == 2) named_arrive(8, 384);
#pragma unroll
      for (int i = 0; i < 32; i++) p[i] = phi2(acc[2 * i], acc[2 * i + 1]);
      if (wg == 1) {
        named_bar(8, 384);
        const int m = lane >> 3, r = lane & 7;
#pragma unroll
        for (int j = 0; j < 16; j += 2) {
          const int tok = (j + (m >> 1)) * 8 + r;
          const int chunk = w4 * 2 + (m & 1);
          stsm4t(sF + 49152 + tok * 128 + ((chunk ^ r) << 4), p[2 * j], p[2 * j + 1], p[2 * j + 2], p[2 * j + 3]);
        }
        fence_async();
      } else {
        named_bar(7, 256);
        float kv0[4] = {0, 0, 0, 0}, kv1[4] = {0, 0, 0, 0}, z0[4] = {0, 0, 0, 0}, z1[4] = {0, 0, 0, 0};
        const uint32_t one = 0x3F803F80u;
        const int t = tid & 127;
#pragma unroll
        for (int j = 0; j < 8; j++) {
          uint32_t a[4];
          lds4(sF + 24576 + j * 2048 + t * 16, a);
          mma_bf16(kv0, a[0], a[1], a[2], a[3], p[4 * j], p[4 * j + 2]);
          mma_bf16(kv1, a[0], a[1], a[2], a[3], p[4 * j + 1], p[4 * j + 3]);
          mma_bf16(z0, one, one, one, one, p[4 * j], p[4 * j + 2]);
          mma_bf16(z1, one, one, one, one, p[4 * j + 1], p[4 * j + 3]);
        }
        float4* dst = g_kvp + ((ttB * 32 + hq * 4 + w4) * 3) * 32 + lane;
        dst[0] = make_float4(kv0[0], kv0[1], kv1[0], kv1[1]);
        dst[32] = make_float4(kv0[2], kv0[3], kv1[2], kv1[3]);
        dst[64] = make_float4(z0[0], z0[1], z1[0], z1[1]);
      }
      __syncwarp();
      if (lane == 0) mbar_arrive(BAR_BDONE);
    }
  }

  mbar_wait(BAR_Q, 0);
  if (tid == 0) TS(1, 1);
  __nv_bfloat16* const obase = g_O + (size_t)(tbA * 64) * D_MOD + (hg * 8 + wg) * 16;
  bool safe = true;
  {
    const uint32_t c63 = 0x1F801F80u + (threadIdx.x >> 20);
    const uint32_t m1 = (gridDim.x >> 20) - 1u;
    const uint64_t dK0 = make_desc(sb + OFF_K, 32768, 128, 0);
    const uint64_t dV0 = make_desc(sb + OFF_V, 128, 32768, 0);
    constexpr uint32_t dKV = ((2048u - 8u)  __H0__ ) + STEPK - (OFF_V - OFF_K) / 16;
    mbar_wait(BAR_KV(0), 0);
#pragma unroll 1
    for (int pass = 0; pass < 2; pass++) {
      const uint64_t dQ = make_desc(sb + OFF_F + (pass * 4 + wg) * 2048, 128, 256, 0);
      float Sm[16], Sp[32], O[12];
      uint32_t P[24];
#pragma unroll
      for (int i = 0; i < 32; i++) Sp[i] = SMAGIC;
#pragma unroll
      for (int i = 0; i < 16; i++) Sm[i] = 0.f;
#pragma unroll
      for (int i = 0; i < 12; i++) O[i] = 0.f;
      fence_regs<16>(Sm); fence_regs<32>(Sp); fence_regs<12>(O);
      if (tid == 0) TS(1, 2 + 2 * pass);
      wg_fence();
      wg_qs32<0>(Sm, dQ, dK0);
      wg_qs64<1>(Sp, dQ, dK0 + 32);
      wg_commit();
      wg_wait<0>();
      fence_regs<16>(Sm); fence_regs<32>(Sp);
      uint32_t vlo = (uint32_t)dV0;
#pragma unroll 1
      for (int seg = 0; seg < 4; seg++) {
        if (pass == 0) {
          if (seg < 3) { mbar_wait(BAR_KV(seg), 0); mbar_wait(BAR_VB(seg), 0); }
        } else if (seg >= 1) {
          if ((tid & 127) == 0) {
            mbar_arrive(BAR_CL(seg));
            if (seg == 3) take_role(sM, wg);
          }
          __syncwarp();
        }
        if ((tid & 127) == 0) TS(4 + wg, pass * 5 + seg);
        const uint32_t vend = vlo + (seg == 0 ? 6 : 5) * STEPK;
#pragma unroll 1
        for (; vlo != vend; vlo += STEPK) {
          uint64_t dK, dV;
          asm("mov.b64 %0, {%1, %2};" : "=l"(dK) : "r"(vlo + dKV), "r"(8u));
          asm("mov.b64 %0, {%1, %2};" : "=l"(dV) : "r"(vlo), "r"(2048u));
#pragma unroll
          for (int i = 0; i < 8; i++) P[i] = pack_bf16(ex2f(Sm[2 * i]), ex2f(Sm[2 * i + 1]));
#pragma unroll
          for (int i = 0; i < 16; i++) P[8 + i] = exp2_pair_fix(Sp[2 * i], Sp[2 * i + 1], c63, m1);
          fence_regs<24>(P);
          wg_fence();
#pragma unroll
          for (int k = 0; k < 6; k++) wg_pv24<1>(O, &P[4 * k], dV + k * 16);
          wg_qs64<1>(Sp, dQ, dK + 32);
          wg_qs32<0>(Sm, dQ, dK);
          wg_commit();
          wg_wait<0>();
          fence_regs<16>(Sm); fence_regs<32>(Sp); fence_regs<12>(O); fence_regs<24>(P);
        }
      }
#pragma unroll
      for (int i = 0; i < 8; i++) P[i] = pack_bf16(ex2f(Sm[2 * i]), ex2f(Sm[2 * i + 1]));
      fence_regs<8>(P);
      wg_fence();
      wg_pv24<1>(O, &P[0], dV0 + 21 * STEPK);
      wg_pv24<1>(O, &P[4], dV0 + 21 * STEPK + 16);
      wg_commit();
      wg_wait<0>();
      fence_regs<12>(O);
      if (pass == 0) {
        uint32_t n[4];
        mbar_wait(BAR_Q2, 0);
        lds4(sM, n);
        const float qn = __half2float(__ushort_as_half((unsigned short)max(max(n[0], n[1]), max(n[2], n[3]))));
        safe = __all_sync(~0u, qn <= __uint_as_float(lds1(sM + 16)));
        if (!safe) break;
      }
      const float l0 = __shfl_sync(~0u, O[8], lane & ~3), l1 = __shfl_sync(~0u, O[10], lane & ~3);
      const float i0 = rcpf(l0), i1 = rcpf(l1);
      uint32_t* op = (uint32_t*)(obase + pass * 64 + (size_t)(w4 * 16 + (lane >> 2)) * D_MOD) + (lane & 3);
      op[0] = pack_bf16(O[0] * i0, O[1] * i0);
      op[8 * 256] = pack_bf16(O[2] * i1, O[3] * i1);
      op[4] = pack_bf16(O[4] * i0, O[5] * i0);
      op[8 * 256 + 4] = pack_bf16(O[6] * i1, O[7] * i1);
      __syncwarp();
      if (lane == 0) mbar_arrive(BAR_OD(pass));
      if ((tid & 127) == 0) TS(4 + wg, pass * 5 + 4);
      if (tid == 0) TS(1, 3 + 2 * pass);
      if ((tid & 127) == 0 && pass == 1 && wg > 0) TS(1, 10 + wg);
    }
  }

  if (!safe) {
    if ((tid & 127) == 0) { mbar_arrive(BAR_CL(1)); mbar_arrive(BAR_CL(2)); mbar_arrive(BAR_CL(3)); take_role(sM, wg); }
#pragma unroll 1
    for (int pass = 0; pass < 2; pass++) {
      attn_slow((const uint4*)g_Q + blockIdx.x * 1024 + (pass * 4 + wg) * 128, obase + pass * 64);
      __syncwarp();
      if (lane == 0) mbar_arrive(BAR_OD(pass));
    }
  }

  {
    named_bar(wg + 1, 128);
    if ((tid & 127) == 0) mbar_arrive(BAR_CL(4));
    const int role = __shfl_sync(~0u, lds1(sM + 32 + wg * 4), 0);
    const int isA = role >> 1, hf = role & 1;
    if ((tid & 127) == 0) TS(4 + wg, 10);
    float acc[32];
    uint32_t xs = 0;
    int prev = 0;
#pragma unroll 1
    for (int n = 0; n < 8; n++) {
      const int gidx = isA ? (n < 4 ? n + 9 : (n == 4 ? 8 : n + 8)) : n;
      const uint32_t sl = tail_slots(gidx < 9 ? gidx : gidx - 9);
      xs = sb + ((sl >> (8 + 8 * hf)) & 255) * 8192;
      const uint64_t da = make_desc(xs, 16, 1024, 1), db = make_desc(sb + (sl & 255) * 8192, 8192, 1024, 1);
      mbar_wait(BAR_TF(gidx), 0);
      if ((tid & 127) == 0 && role == 3) TS(2, 2 + n);
      wg_fence();
#pragma unroll
      for (int k = 0; k < 4; k++) wg_ss64<0, 1>(acc, da + k * 2, db + k * 128, (n | k) != 0);
      wg_commit();
      wg_wait<1>();
      if (!isA && n >= 1 && (tid & 127) == 0) mbar_arrive(BAR_TE(prev));
      __syncwarp();
      prev = n;
    }
    wg_wait<0>();
    fence_regs<32>(acc);
    if ((tid & 127) == 0) TS(4 + wg, 11);
    named_bar(wg + 1, 128);
    const int m = lane >> 3, r = lane & 7;
#pragma unroll
    for (int j = 0; j < 8; j += 2) {
      const int row = w4 * 16 + (m & 1) * 8 + r;
      stsm4(xs + row * 128 + (((j + (m >> 1)) ^ r) << 4),
            pack_bf16(acc[4 * j], acc[4 * j + 1]), pack_bf16(acc[4 * j + 2], acc[4 * j + 3]),
            pack_bf16(acc[4 * j + 4], acc[4 * j + 5]), pack_bf16(acc[4 * j + 6], acc[4 * j + 7]));
    }
    fence_async();
    named_bar(wg + 1, 128);
    if (w4 == 0 && elect_one()) {
      tma2d_store(&mOut, xs, (isA ? 0 : 512) + ct * 64, ttO * 128 + hf * 64);
      bulk_commit();
      asm volatile("cp.async.bulk.wait_group.read 0;" ::: "memory");
      TS(2, 11 + (role >> 1));
    }
  }
}

typedef CUresult (*EncodeFn)(CUtensorMap*, CUtensorMapDataType, cuuint32_t, void*, const cuuint64_t*, const cuuint64_t*,
                             const cuuint32_t*, const cuuint32_t*, CUtensorMapInterleave, CUtensorMapSwizzle,
                             CUtensorMapL2promotion, CUtensorMapFloatOOBfill);

static void make_map(EncodeFn enc, CUtensorMap* m, const void* ptr, uint64_t cols, uint64_t rows, uint32_t bc, uint32_t br) {
  cuuint64_t dims[2] = {cols, rows};
  cuuint64_t strides[1] = {cols * 2};
  cuuint32_t box[2] = {bc, br};
  cuuint32_t es[2] = {1, 1};
  enc(m, CU_TENSOR_MAP_DATA_TYPE_BFLOAT16, 2, (void*)ptr, dims, strides, box, es, CU_TENSOR_MAP_INTERLEAVE_NONE,
      CU_TENSOR_MAP_SWIZZLE_128B, CU_TENSOR_MAP_L2_PROMOTION_L2_256B, CU_TENSOR_MAP_FLOAT_OOB_FILL_NONE);
}

extern "C" void kernel_launch(void* const* d_in, const int* in_sizes, int n_in, void* d_out, int out_size) {
  (void)in_sizes; (void)n_in; (void)out_size;
  static EncodeFn enc = nullptr;
  static void* pQ = nullptr; static void* pO = nullptr;
  if (!enc) {
    void* fn = nullptr; cudaDriverEntryPointQueryResult qr;
    cudaGetDriverEntryPoint("cuTensorMapEncodeTiled", &fn, cudaEnableDefault, &qr);
    enc = (EncodeFn)fn;
    cudaGetSymbolAddress(&pQ, g_Q);
    cudaGetSymbolAddress(&pO, g_O);
    cudaFuncSetAttribute(k1_main, cudaFuncAttributeMaxDynamicSharedMemorySize, SM_TOTAL);
  }
  CUtensorMap mXA64, mXB, mWq, mWqkv, mQst, mO, mOst, mWoA, mWoB, mOut;
  make_map(enc, &mXA64, d_in[0], 512, 2048, 64, 64);
  make_map(enc, &mWq, d_in[1], 512, 512, 64, 64);
  make_map(enc, &mWoA, d_in[4], 512, 512, 64, 64);
  make_map(enc, &mXB, d_in[5], 512, 2048, 64, 128);
  make_map(enc, &mWqkv, d_in[6], 1536, 512, 64, 64);
  make_map(enc, &mWoB, d_in[7], 512, 512, 64, 64);
  make_map(enc, &mQst, pQ, 512, 4096, 64, 128);
  make_map(enc, &mO, pO, 512, 4096, 64, 64);
  make_map(enc, &mOst, pO, 512, 4096, 64, 128);
  make_map(enc, &mOut, d_out, 1024, 2048, 64, 64);
  Params prm{(const __nv_bfloat16*)d_in[2], (const __nv_bfloat16*)d_in[3], (const __nv_bfloat16*)d_in[0]};
  k1_main<<<132, 640, SM_TOTAL, cudaStreamPerThread>>>(mXA64, mXB, mWq, mWqkv, mQst, mOst, mO, mWoA, mWoB, mOut, prm);
}
```

```cpp
#include <cuda_runtime.h>
#include <cuda_bf16.h>
#include <cuda_fp16.h>
#include <cuda.h>
#include <stdint.h>

#define S_TOK 2048
#define D_MOD 512

__device__ __align__(1024) __nv_bfloat16 g_Q[2 * S_TOK * D_MOD];
__device__ __align__(1024) __nv_bfloat16 g_O[2 * S_TOK * D_MOD];
__device__ __align__(1024) uint4 g_KV[8 * S_TOK];
__device__ __align__(16) uint32_t g_stats[128];
__device__ __align__(16) float4 g_kvp[16 * 32 * 3 * 32];

#define TS(k, i) do {} while (0)
__device__ __forceinline__ uint32_t smem_u32(const void* p) { return (uint32_t)__cvta_generic_to_shared(p); }
__device__ __forceinline__ void mbar_init(uint32_t bar, int cnt) { asm volatile("mbarrier.init.shared::cta.b64 [%0], %1;" :: "r"(bar), "r"(cnt) : "memory"); }
__device__ __forceinline__ void mbar_expect_tx(uint32_t bar, uint32_t bytes) { asm volatile("mbarrier.arrive.expect_tx.shared::cta.b64 _, [%0], %1;" :: "r"(bar), "r"(bytes) : "memory"); }
__device__ __forceinline__ bool mbar_try(uint32_t bar, uint32_t parity) {
  uint32_t ok;
  asm volatile("{\n.reg .pred p;\nmbarrier.try_wait.parity.shared::cta.b64 p, [%1], %2;\nselp.b32 %0, 1, 0, p;\n}\n" : "=r"(ok) : "r"(bar), "r"(parity) : "memory");
  return ok;
}
__device__ __forceinline__ void mbar_wait(uint32_t bar, uint32_t parity) {
  asm volatile("{\n.reg .pred p;\n.reg .u32 c;\nmov.u32 c, 0;\n"
               "LW_%=:\n"
               "mbarrier.try_wait.parity.shared::cta.b64 p, [%0], %1;\n"
               "@p bra LD_%=;\n"
               "add.u32 c, c, 1;\n"
               "setp.lt.u32 p, c, 4000000;\n"
               "@p bra LW_%=;\n"
               "trap;\n"
               "LD_%=:\n}\n" :: "r"(bar), "r"(parity) : "memory");
}
__device__ __forceinline__ void mbar_arrive_cta(uint32_t bar, uint32_t cta) {
  asm volatile("{\n.reg .b32 ra;\nmapa.shared::cluster.u32 ra, %0, %1;\nmbarrier.arrive.shared::cluster.b64 _, [ra];\n}\n" :: "r"(bar), "r"(cta) : "memory");
}
__device__ __forceinline__ void cluster_sync() {
  asm volatile("barrier.cluster.arrive.relaxed.aligned;\nbarrier.cluster.wait.aligned;" ::: "memory");
}
__device__ __forceinline__ void tma2d(uint32_t dst, const CUtensorMap* m, int c0, int c1, uint32_t bar) {
  asm volatile("cp.async.bulk.tensor.2d.shared::cluster.global.mbarrier::complete_tx::bytes [%0], [%1, {%3, %4}], [%2];"
               :: "r"(dst), "l"(m), "r"(bar), "r"(c0), "r"(c1) : "memory");
}
__device__ __forceinline__ void tma2d_mc(uint32_t dst, const CUtensorMap* m, int c0, int c1, uint32_t bar, uint16_t mask) {
  asm volatile("cp.async.bulk.tensor.2d.shared::cluster.global.mbarrier::complete_tx::bytes.multicast::cluster [%0], [%1, {%3, %4}], [%2], %5;"
               :: "r"(dst), "l"(m), "r"(bar), "r"(c0), "r"(c1), "h"(mask) : "memory");
}
__device__ __forceinline__ void tma2d_store(const CUtensorMap* m, uint32_t src, int c0, int c1) {
  asm volatile("cp.async.bulk.tensor.2d.global.shared::cta.bulk_group [%0, {%2, %3}], [%1];"
               :: "l"(m), "r"(src), "r"(c0), "r"(c1) : "memory");
}
__device__ __forceinline__ void bulk_g2s(uint32_t dst, const void* src, uint32_t bytes, uint32_t bar) {
  asm volatile("cp.async.bulk.shared::cluster.global.mbarrier::complete_tx::bytes [%0], [%1], %2, [%3];"
               :: "r"(dst), "l"(src), "r"(bytes), "r"(bar) : "memory");
}
__device__ __forceinline__ void bulk_commit() { asm volatile("cp.async.bulk.commit_group;" ::: "memory"); }
__device__ __forceinline__ void bulk_wait_all() { asm volatile("cp.async.bulk.wait_group 0;" ::: "memory"); }
__device__ __forceinline__ void fence_async() { asm volatile("fence.proxy.async.shared::cta;" ::: "memory"); }
__device__ __forceinline__ void named_bar(int id, int n) { asm volatile("bar.sync %0, %1;" :: "r"(id), "r"(n) : "memory"); }
__device__ __forceinline__ void pdl_launch() { asm volatile("griddepcontrol.launch_dependents;" ::: "memory"); }
__device__ __forceinline__ void pdl_wait() { asm volatile("griddepcontrol.wait;" ::: "memory"); }
__device__ __forceinline__ void wg_fence() { asm volatile("wgmma.fence.sync.aligned;" ::: "memory"); }
__device__ __forceinline__ void wg_commit() { asm volatile("wgmma.commit_group.sync.aligned;" ::: "memory"); }
template <int n> __device__ __forceinline__ void wg_wait() { asm volatile("wgmma.wait_group.sync.aligned %0;" :: "n"(n) : "memory"); }
template <int n> __device__ __forceinline__ void fence_regs(float* r) {
#pragma unroll
  for (int i = 0; i < n; i++) asm volatile("" : "+f"(r[i]) :: "memory");
}
template <int n> __device__ __forceinline__ void fence_regs(uint32_t* r) {
#pragma unroll
  for (int i = 0; i < n; i++) asm volatile("" : "+r"(r[i]) :: "memory");
}
__device__ __forceinline__ uint64_t make_desc(uint32_t addr, uint32_t lbo, uint32_t sbo, uint32_t swz) {
  return (uint64_t)((addr & 0x3FFFF) >> 4) | ((uint64_t)(lbo >> 4) << 16) | ((uint64_t)(sbo >> 4) << 32) | ((uint64_t)swz << 62);
}
__device__ __forceinline__ float ex2f(float x) { float y; asm("ex2.approx.ftz.f32 %0, %1;" : "=f"(y) : "f"(x)); return y; }
__device__ __forceinline__ uint32_t pack_bf16(float lo, float hi) { uint32_t r; asm("cvt.rn.bf16x2.f32 %0, %1, %2;" : "=r"(r) : "f"(hi), "f"(lo)); return r; }
__device__ __forceinline__ uint32_t pack_f16(float lo, float hi) { uint32_t r; asm("cvt.rn.f16x2.f32 %0, %1, %2;" : "=r"(r) : "f"(hi), "f"(lo)); return r; }
__device__ __forceinline__ float bf_lo(uint32_t v) { return __uint_as_float(v << 16); }
__device__ __forceinline__ float bf_hi(uint32_t v) { return __uint_as_float(v & 0xFFFF0000u); }
__device__ __forceinline__ float rbf(float x) { return __bfloat162float(__float2bfloat16_rn(x)); }
__device__ __forceinline__ void stsm4(uint32_t a, uint32_t r0, uint32_t r1, uint32_t r2, uint32_t r3) {
  asm volatile("stmatrix.sync.aligned.m8n8.x4.shared.b16 [%0], {%1,%2,%3,%4};" :: "r"(a), "r"(r0), "r"(r1), "r"(r2), "r"(r3) : "memory");
}
__device__ __forceinline__ void stsm4t(uint32_t a, uint32_t r0, uint32_t r1, uint32_t r2, uint32_t r3) {
  asm volatile("stmatrix.sync.aligned.m8n8.x4.trans.shared.b16 [%0], {%1,%2,%3,%4};" :: "r"(a), "r"(r0), "r"(r1), "r"(r2), "r"(r3) : "memory");
}
__device__ __forceinline__ void mma_bf16(float* d, uint32_t a0, uint32_t a1, uint32_t a2, uint32_t a3, uint32_t b0, uint32_t b1) {
  asm volatile("mma.sync.aligned.m16n8k16.row.col.f32.bf16.bf16.f32 {%0,%1,%2,%3}, {%4,%5,%6,%7}, {%8,%9}, {%0,%1,%2,%3};"
               : "+f"(d[0]), "+f"(d[1]), "+f"(d[2]), "+f"(d[3]) : "r"(a0), "r"(a1), "r"(a2), "r"(a3), "r"(b0), "r"(b1));
}
template<int SD> __device__ __forceinline__ void wg_qk32(float* d, const uint32_t* a, uint64_t desc) {
  asm volatile("wgmma.mma_async.sync.aligned.m64n32k16.f32.f16.f16 {%0,%1,%2,%3,%4,%5,%6,%7,%8,%9,%10,%11,%12,%13,%14,%15}, {%16,%17,%18,%19}, %20, %21, 1, 1, 0;"
   : "+f"(d[0]),"+f"(d[1]),"+f"(d[2]),"+f"(d[3]),"+f"(d[4]),"+f"(d[5]),"+f"(d[6]),"+f"(d[7]),"+f"(d[8]),"+f"(d[9]),"+f"(d[10]),"+f"(d[11]),"+f"(d[12]),"+f"(d[13]),"+f"(d[14]),"+f"(d[15])
   : "r"(a[0]),"r"(a[1]),"r"(a[2]),"r"(a[3]),"l"(desc),"n"(SD));
}
template<int SD> __device__ __forceinline__ void wg_qk64(float* d, const uint32_t* a, uint64_t desc) {
  asm volatile("wgmma.mma_async.sync.aligned.m64n64k16.f32.f16.f16 {%0,%1,%2,%3,%4,%5,%6,%7,%8,%9,%10,%11,%12,%13,%14,%15,%16,%17,%18,%19,%20,%21,%22,%23,%24,%25,%26,%27,%28,%29,%30,%31}, {%32,%33,%34,%35}, %36, %37, 1, 1, 0;"
   : "+f"(d[0]),"+f"(d[1]),"+f"(d[2]),"+f"(d[3]),"+f"(d[4]),"+f"(d[5]),"+f"(d[6]),"+f"(d[7]),"+f"(d[8]),"+f"(d[9]),"+f"(d[10]),"+f"(d[11]),"+f"(d[12]),"+f"(d[13]),"+f"(d[14]),"+f"(d[15]),"+f"(d[16]),"+f"(d[17]),"+f"(d[18]),"+f"(d[19]),"+f"(d[20]),"+f"(d[21]),"+f"(d[22]),"+f"(d[23]),"+f"(d[24]),"+f"(d[25]),"+f"(d[26]),"+f"(d[27]),"+f"(d[28]),"+f"(d[29]),"+f"(d[30]),"+f"(d[31])
   : "r"(a[0]),"r"(a[1]),"r"(a[2]),"r"(a[3]),"l"(desc),"n"(SD));
}
template<int SD> __device__ __forceinline__ void wg_qs32(float* d, uint64_t da, uint64_t db) {
  asm volatile("wgmma.mma_async.sync.aligned.m64n32k16.f32.f16.f16 {%0,%1,%2,%3,%4,%5,%6,%7,%8,%9,%10,%11,%12,%13,%14,%15}, %16, %17, %18, 1, 1, 0, 0;"
   : "+f"(d[0]),"+f"(d[1]),"+f"(d[2]),"+f"(d[3]),"+f"(d[4]),"+f"(d[5]),"+f"(d[6]),"+f"(d[7]),"+f"(d[8]),"+f"(d[9]),"+f"(d[10]),"+f"(d[11]),"+f"(d[12]),"+f"(d[13]),"+f"(d[14]),"+f"(d[15])
   : "l"(da),"l"(db),"n"(SD));
}
template<int SD> __device__ __forceinline__ void wg_qs64(float* d, uint64_t da, uint64_t db) {
  asm volatile("wgmma.mma_async.sync.aligned.m64n64k16.f32.f16.f16 {%0,%1,%2,%3,%4,%5,%6,%7,%8,%9,%10,%11,%12,%13,%14,%15,%16,%17,%18,%19,%20,%21,%22,%23,%24,%25,%26,%27,%28,%29,%30,%31}, %32, %33, %34, 1, 1, 0, 0;"
   : "+f"(d[0]),"+f"(d[1]),"+f"(d[2]),"+f"(d[3]),"+f"(d[4]),"+f"(d[5]),"+f"(d[6]),"+f"(d[7]),"+f"(d[8]),"+f"(d[9]),"+f"(d[10]),"+f"(d[11]),"+f"(d[12]),"+f"(d[13]),"+f"(d[14]),"+f"(d[15]),"+f"(d[16]),"+f"(d[17]),"+f"(d[18]),"+f"(d[19]),"+f"(d[20]),"+f"(d[21]),"+f"(d[22]),"+f"(d[23]),"+f"(d[24]),"+f"(d[25]),"+f"(d[26]),"+f"(d[27]),"+f"(d[28]),"+f"(d[29]),"+f"(d[30]),"+f"(d[31])
   : "l"(da),"l"(db),"n"(SD));
}
template<int SD> __device__ __forceinline__ void wg_pv24(float* d, const uint32_t* a, uint64_t desc) {
  asm volatile("wgmma.mma_async.sync.aligned.m64n24k16.f32.bf16.bf16 {%0,%1,%2,%3,%4,%5,%6,%7,%8,%9,%10,%11}, {%12,%13,%14,%15}, %16, %17, 1, 1, 1;"
   : "+f"(d[0]),"+f"(d[1]),"+f"(d[2]),"+f"(d[3]),"+f"(d[4]),"+f"(d[5]),"+f"(d[6]),"+f"(d[7]),"+f"(d[8]),"+f"(d[9]),"+f"(d[10]),"+f"(d[11])
   : "r"(a[0]),"r"(a[1]),"r"(a[2]),"r"(a[3]),"l"(desc),"n"(SD));
}
template<int TA, int TB> __device__ __forceinline__ void wg_ss128(float* d, uint64_t da, uint64_t db, int sd) {
  asm volatile("{\n.reg .pred p;\nsetp.ne.b32 p, %66, 0;\n"
   "wgmma.mma_async.sync.aligned.m64n128k16.f32.bf16.bf16 {%0,%1,%2,%3,%4,%5,%6,%7,%8,%9,%10,%11,%12,%13,%14,%15,%16,%17,%18,%19,%20,%21,%22,%23,%24,%25,%26,%27,%28,%29,%30,%31,%32,%33,%34,%35,%36,%37,%38,%39,%40,%41,%42,%43,%44,%45,%46,%47,%48,%49,%50,%51,%52,%53,%54,%55,%56,%57,%58,%59,%60,%61,%62,%63}, %64, %65, p, 1, 1, %67, %68;\n}\n"
   : "+f"(d[0]),"+f"(d[1]),"+f"(d[2]),"+f"(d[3]),"+f"(d[4]),"+f"(d[5]),"+f"(d[6]),"+f"(d[7]),"+f"(d[8]),"+f"(d[9]),"+f"(d[10]),"+f"(d[11]),"+f"(d[12]),"+f"(d[13]),"+f"(d[14]),"+f"(d[15]),"+f"(d[16]),"+f"(d[17]),"+f"(d[18]),"+f"(d[19]),"+f"(d[20]),"+f"(d[21]),"+f"(d[22]),"+f"(d[23]),"+f"(d[24]),"+f"(d[25]),"+f"(d[26]),"+f"(d[27]),"+f"(d[28]),"+f"(d[29]),"+f"(d[30]),"+f"(d[31]),"+f"(d[32]),"+f"(d[33]),"+f"(d[34]),"+f"(d[35]),"+f"(d[36]),"+f"(d[37]),"+f"(d[38]),"+f"(d[39]),"+f"(d[40]),"+f"(d[41]),"+f"(d[42]),"+f"(d[43]),"+f"(d[44]),"+f"(d[45]),"+f"(d[46]),"+f"(d[47]),"+f"(d[48]),"+f"(d[49]),"+f"(d[50]),"+f"(d[51]),"+f"(d[52]),"+f"(d[53]),"+f"(d[54]),"+f"(d[55]),"+f"(d[56]),"+f"(d[57]),"+f"(d[58]),"+f"(d[59]),"+f"(d[60]),"+f"(d[61]),"+f"(d[62]),"+f"(d[63])
   : "l"(da),"l"(db),"r"(sd),"n"(TA),"n"(TB));
}
template<int TA, int TB> __device__ __forceinline__ void wg_ss64(float* d, uint64_t da, uint64_t db, int sd) {
  asm volatile("{\n.reg .pred p;\nsetp.ne.b32 p, %34, 0;\n"
   "wgmma.mma_async.sync.aligned.m64n64k16.f32.bf16.bf16 {%0,%1,%2,%3,%4,%5,%6,%7,%8,%9,%10,%11,%12,%13,%14,%15,%16,%17,%18,%19,%20,%21,%22,%23,%24,%25,%26,%27,%28,%29,%30,%31}, %32, %33, p, 1, 1, %35, %36;\n}\n"
   : "+f"(d[0]),"+f"(d[1]),"+f"(d[2]),"+f"(d[3]),"+f"(d[4]),"+f"(d[5]),"+f"(d[6]),"+f"(d[7]),"+f"(d[8]),"+f"(d[9]),"+f"(d[10]),"+f"(d[11]),"+f"(d[12]),"+f"(d[13]),"+f"(d[14]),"+f"(d[15]),"+f"(d[16]),"+f"(d[17]),"+f"(d[18]),"+f"(d[19]),"+f"(d[20]),"+f"(d[21]),"+f"(d[22]),"+f"(d[23]),"+f"(d[24]),"+f"(d[25]),"+f"(d[26]),"+f"(d[27]),"+f"(d[28]),"+f"(d[29]),"+f"(d[30]),"+f"(d[31])
   : "l"(da),"l"(db),"r"(sd),"n"(TA),"n"(TB));
}

template<int TA, int TB> __device__ __forceinline__ void wg_ss8(float* d, uint64_t da, uint64_t db, int sd) {
  asm volatile("{\n.reg .pred p;\nsetp.ne.b32 p, %6, 0;\n"
   "wgmma.mma_async.sync.aligned.m64n8k16.f32.bf16.bf16 {%0,%1,%2,%3}, %4, %5, p, 1, 1, %7, %8;\n}\n"
   : "+f"(d[0]),"+f"(d[1]),"+f"(d[2]),"+f"(d[3])
   : "l"(da),"l"(db),"r"(sd),"n"(TA),"n"(TB));
}

template<int SD, uint32_t HI> __device__ __forceinline__ void wq32(float* d, uint64_t da, uint32_t lo) {
  asm volatile("{\n.reg .b64 db;\nmov.b64 db, {%17, %19};\n"
   "wgmma.mma_async.sync.aligned.m64n32k16.f32.f16.f16 {%0,%1,%2,%3,%4,%5,%6,%7,%8,%9,%10,%11,%12,%13,%14,%15}, %16, db, %18, 1, 1, 0, 0;\n}\n"
   : "+f"(d[0]),"+f"(d[1]),"+f"(d[2]),"+f"(d[3]),"+f"(d[4]),"+f"(d[5]),"+f"(d[6]),"+f"(d[7]),"+f"(d[8]),"+f"(d[9]),"+f"(d[10]),"+f"(d[11]),"+f"(d[12]),"+f"(d[13]),"+f"(d[14]),"+f"(d[15])
   : "l"(da),"r"(lo),"n"(SD),"r"(HI));
}
template<int SD, uint32_t HI> __device__ __forceinline__ void wq64(float* d, uint64_t da, uint32_t lo) {
  asm volatile("{\n.reg .b64 db;\nmov.b64 db, {%33, %35};\n"
   "wgmma.mma_async.sync.aligned.m64n64k16.f32.f16.f16 {%0,%1,%2,%3,%4,%5,%6,%7,%8,%9,%10,%11,%12,%13,%14,%15,%16,%17,%18,%19,%20,%21,%22,%23,%24,%25,%26,%27,%28,%29,%30,%31}, %32, db, %34, 1, 1, 0, 0;\n}\n"
   : "+f"(d[0]),"+f"(d[1]),"+f"(d[2]),"+f"(d[3]),"+f"(d[4]),"+f"(d[5]),"+f"(d[6]),"+f"(d[7]),"+f"(d[8]),"+f"(d[9]),"+f"(d[10]),"+f"(d[11]),"+f"(d[12]),"+f"(d[13]),"+f"(d[14]),"+f"(d[15]),"+f"(d[16]),"+f"(d[17]),"+f"(d[18]),"+f"(d[19]),"+f"(d[20]),"+f"(d[21]),"+f"(d[22]),"+f"(d[23]),"+f"(d[24]),"+f"(d[25]),"+f"(d[26]),"+f"(d[27]),"+f"(d[28]),"+f"(d[29]),"+f"(d[30]),"+f"(d[31])
   : "l"(da),"r"(lo),"n"(SD),"r"(HI));
}
template<int SD, uint32_t HI> __device__ __forceinline__ void wpv(float* d, const uint32_t* a, uint32_t lo) {
  asm volatile("{\n.reg .b64 db;\nmov.b64 db, {%16, %18};\n"
   "wgmma.mma_async.sync.aligned.m64n24k16.f32.bf16.bf16 {%0,%1,%2,%3,%4,%5,%6,%7,%8,%9,%10,%11}, {%12,%13,%14,%15}, db, %17, 1, 1, 1;\n}\n"
   : "+f"(d[0]),"+f"(d[1]),"+f"(d[2]),"+f"(d[3]),"+f"(d[4]),"+f"(d[5]),"+f"(d[6]),"+f"(d[7]),"+f"(d[8]),"+f"(d[9]),"+f"(d[10]),"+f"(d[11])
   : "r"(a[0]),"r"(a[1]),"r"(a[2]),"r"(a[3]),"r"(lo),"n"(SD),"r"(HI));
}

__device__ __forceinline__ uint32_t phi2(float a, float b) {
  uint32_t r, e;
  asm("cvt.rn.relu.bf16x2.f32 %0, %1, %2;" : "=r"(r) : "f"(b), "f"(a));
  e = pack_bf16(ex2f(a * 1.4426950408889634f), ex2f(b * 1.4426950408889634f));
  asm("add.rn.bf16x2 %0, %0, %1;" : "+r"(e) : "r"(0x35863586u));
  asm("min.NaN.bf16x2 %0, %0, %1;" : "+r"(e) : "r"(0x3F803F80u));
  asm("add.rn.bf16x2 %0, %0, %1;" : "+r"(e) : "r"(r));
  return e;
}

__device__ __forceinline__ void mbar_arrive(uint32_t bar) { asm volatile("mbarrier.arrive.shared::cta.b64 _, [%0];" :: "r"(bar) : "memory"); }
__device__ __forceinline__ void named_arrive(int id, int n) { asm volatile("bar.arrive %0, %1;" :: "r"(id), "r"(n) : "memory"); }
__device__ __forceinline__ void fence_async_all() { asm volatile("fence.proxy.async.global;" ::: "memory"); }
__device__ __forceinline__ void flag_add(uint32_t* f) { asm volatile("fence.acq_rel.gpu;\nred.relaxed.gpu.global.add.u32 [%0], 1;" :: "l"(f) : "memory"); }
#define PUBLISH(f) do { fence_async_all(); flag_add(f); } while (0)
__device__ __forceinline__ void flag_wait(const uint32_t* f, uint32_t target) {
  uint32_t v;
#pragma unroll 1
  for (int it = 0;; it++) {
    asm volatile("ld.acquire.gpu.global.u32 %0, [%1];" : "=r"(v) : "l"(f) : "memory");
    if ((int32_t)(v - target) >= 0) break;
    if (it > 2000000) __trap();
    __nanosleep(64);
  }
}
__device__ __forceinline__ bool elect_one() {
  uint32_t p;
  asm volatile("{\n.reg .pred P;\nelect.sync _|P, 0xFFFFFFFF;\nselp.b32 %0, 1, 0, P;\n}\n" : "=r"(p));
  return p;
}
__device__ __forceinline__ void lds4(uint32_t a, uint32_t* r) {
  asm volatile("ld.shared.v4.b32 {%0,%1,%2,%3}, [%4];" : "=r"(r[0]), "=r"(r[1]), "=r"(r[2]), "=r"(r[3]) : "r"(a) : "memory");
}
__device__ __forceinline__ uint32_t lds1(uint32_t a) { uint32_t r; asm volatile("ld.shared.b32 %0, [%1];" : "=r"(r) : "r"(a) : "memory"); return r; }
__device__ __forceinline__ void sts1(uint32_t a, uint32_t v) { asm volatile("st.shared.b32 [%0], %1;" :: "r"(a), "r"(v) : "memory"); }
__device__ __forceinline__ void sts4(uint32_t a, uint32_t r0, uint32_t r1, uint32_t r2, uint32_t r3) {
  asm volatile("st.shared.v4.b32 [%0], {%1,%2,%3,%4};" :: "r"(a), "r"(r0), "r"(r1), "r"(r2), "r"(r3) : "memory");
}
__device__ __forceinline__ void ldsm4(uint32_t a, uint32_t* r) {
  asm volatile("ldmatrix.sync.aligned.m8n8.x4.shared.b16 {%0,%1,%2,%3}, [%4];" : "=r"(r[0]), "=r"(r[1]), "=r"(r[2]), "=r"(r[3]) : "r"(a) : "memory");
}
__device__ __forceinline__ float rcpf(float x) { float y; asm("rcp.approx.ftz.f32 %0, %1;" : "=f"(y) : "f"(x)); return y; }
__device__ __forceinline__ uint32_t hfma2(uint32_t a, uint32_t b, uint32_t c) { uint32_t r; asm("fma.rn.f16x2 %0, %1, %2, %3;" : "=r"(r) : "r"(a), "r"(b), "r"(c)); return r; }
__device__ __forceinline__ uint32_t hadd2(uint32_t a, uint32_t b) { uint32_t r; asm("add.rn.f16x2 %0, %1, %2;" : "=r"(r) : "r"(a), "r"(b)); return r; }

#define STEPK 96
#define QSCALE 0.36067376022224085f
#define SMAGIC (512.0f + 2.0f * (191.0f - 30.0f - 1.5823545f))
#define VSHIFT 1073741824.0f

__device__ uint32_t g_epoch[132];
__device__ uint32_t g_flag[288 * 8];
#define FLAG_KV (g_flag)
#define FLAG_B(h) (g_flag + (4 + (h)) * 8)
#define FLAG_OA(cta, pass) (g_flag + (16 + (cta) * 2 + (pass)) * 8)
#define FLAG_LM(i) (g_flag + (272 + (i)) * 8)

#define SM_TOTAL (224 * 1024 + 2048 + 1024)
#define OFF_K 0
#define OFF_F 65536
#define OFF_V 131072
#define OFF_MISC (224 * 1024)

#define BAR_FULL(s) (bars + 8 * (s))
#define BAR_EMPTY(s) (bars + 24 + 8 * (s))
#define BAR_KV(c) (bars + 48 + 8 * (c))
#define BAR_BDONE (bars + 80)
#define BAR_Q (bars + 88)
#define BAR_GO (bars + 96)
#define BAR_Q2 (bars + 104)
#define BAR_OD(p) (bars + 112 + 8 * (p))
#define BAR_CL(c) (bars + 128 + 8 * (c))
#define BAR_TE(i) (bars + 168 + 8 * (i))
#define BAR_TF(g) (bars + 224 + 8 * (g))
#define BAR_XA(w) (bars + 352 + 8 * (w))
#define BAR_VB(c) (bars + 384 + 8 * (c))

__device__ __forceinline__ uint32_t exp2_pair_fix(float d0, float d1, uint32_t c63, uint32_t m1) {
  uint32_t w, y, s, r;
  asm("prmt.b32 %0, %1, %2, 0x6521;" : "=r"(w) : "r"(__float_as_uint(d0)), "r"(__float_as_uint(d1)));
  asm("lop3.b32 %0, %1, 0x007F007F, %2, 0xEA;" : "=r"(y) : "r"(w), "r"(c63));
  asm("mad.lo.u32 %0, %1, %2, %3;" : "=r"(s) : "r"(y), "r"(m1), "r"(w));
  asm("fma.rn.bf16x2 %0, %1, %2, %3;" : "=r"(r) : "r"(w), "r"(y), "r"(s));
  return r;
}

__device__ __forceinline__ void attn_slow(const uint4* gq, uint32_t dst) {
  const int t = threadIdx.x & 127;
  const int row = t >> 1, half = t & 1;
  float q[16];
#pragma unroll
  for (int i = 0; i < 4; i++) {
    const uint4 v = gq[(row >> 4) * 32 + (row & 7) * 4 + i];
    const uint32_t lo = (row & 8) ? v.y : v.x, hi = (row & 8) ? v.w : v.z;
    q[2 * i] = bf_lo(lo); q[2 * i + 1] = bf_hi(lo); q[2 * i + 8] = bf_lo(hi); q[2 * i + 9] = bf_hi(hi);
  }
  float m = -INFINITY, l = 0.f, o[16];
#pragma unroll
  for (int i = 0; i < 16; i++) o[i] = 0.f;
#pragma unroll 1
  for (int j = half * 1024; j < half * 1024 + 1024; j++) {
    uint4 ka = g_KV[4 * S_TOK + j], kb = g_KV[5 * S_TOK + j];
    uint4 va = g_KV[6 * S_TOK + j], vb = g_KV[7 * S_TOK + j];
    uint32_t kk[8] = {ka.x, ka.y, ka.z, ka.w, kb.x, kb.y, kb.z, kb.w};
    uint32_t vv[8] = {va.x, va.y, va.z, va.w, vb.x, vb.y, vb.z, vb.w};
    float s = 0.f;
#pragma unroll
    for (int i = 0; i < 8; i++) { s = fmaf(q[2 * i], bf_lo(kk[i]), s); s = fmaf(q[2 * i + 1], bf_hi(kk[i]), s); }
    s = rbf(s) * 0.25f;
    if (s > m) {
      float c = __expf(m - s);
      l *= c;
#pragma unroll
      for (int i = 0; i < 16; i++) o[i] *= c;
      m = s;
    }
    float p = __expf(s - m);
    l += p;
#pragma unroll
    for (int i = 0; i < 8; i++) { o[2 * i] = fmaf(p, bf_lo(vv[i]), o[2 * i]); o[2 * i + 1] = fmaf(p, bf_hi(vv[i]), o[2 * i + 1]); }
  }
  float m2 = __shfl_xor_sync(~0u, m, 1);
  float mm = fmaxf(m, m2);
  float c = __expf(m - mm);
  l *= c; l += __shfl_xor_sync(~0u, l, 1);
  float inv = 1.f / l;
  uint32_t r[8];
#pragma unroll
  for (int i = 0; i < 16; i++) { o[i] *= c; o[i] += __shfl_xor_sync(~0u, o[i], 1); o[i] *= inv; }
#pragma unroll
  for (int i = 0; i < 8; i++) r[i] = pack_bf16(o[2 * i], o[2 * i + 1]);
  if (half == 0) sts4(dst + t * 16, r[0], r[1], r[2], r[3]); else sts4(dst + t * 16, r[4], r[5], r[6], r[7]);
  fence_async();
}

struct Params { const __nv_bfloat16* wk; const __nv_bfloat16* wv; const __nv_bfloat16* xa; };
__device__ __forceinline__ void cp16(uint32_t dst, const void* src) { asm volatile("cp.async.cg.shared.global [%0], [%1], 16;" :: "r"(dst), "l"(src) : "memory"); }

__device__ __forceinline__ void helper_cta(const int h, const uint32_t sb, const uint32_t bars, const int wg, const int w4,
                                           const CUtensorMap* mQ, const CUtensorMap* mOs) {
  const int lane = threadIdx.x & 31;
  mbar_wait(BAR_GO, 0);
  const int cb = wg & 1, col = h * 128 + cb * 64, row0 = S_TOK + (wg >> 1) * 1024;
  const uint32_t buf = sb + wg * 49152;
  if (w4 == 0 && elect_one()) {
    fence_async_all();
#pragma unroll 1
    for (int u = 0; u < 3; u++) {
      mbar_expect_tx(BAR_TF(wg * 3 + u), 16384);
      tma2d(buf + u * 16384, mQ, col, row0 + u * 128, BAR_TF(wg * 3 + u));
    }
  }
  const int head = h * 8 + cb * 4 + w4;
  float4 a0 = make_float4(0, 0, 0, 0), a1 = a0, a2 = a0;
#pragma unroll 8
  for (int tt = 0; tt < 16; tt++) {
    const float4* src = g_kvp + ((tt * 32 + head) * 3) * 32 + lane;
    float4 u = src[0], v = src[32], w = src[64];
    a0.x += u.x; a0.y += u.y; a0.z += u.z; a0.w += u.w;
    a1.x += v.x; a1.y += v.y; a1.z += v.z; a1.w += v.w;
    a2.x += w.x; a2.y += w.y; a2.z += w.z; a2.w += w.w;
  }
  const uint32_t b00 = pack_bf16(a0.x, a0.y), b01 = pack_bf16(a0.z, a0.w);
  const uint32_t b10 = pack_bf16(a1.x, a1.y), b11 = pack_bf16(a1.z, a1.w);
  const uint32_t bz0 = pack_bf16(a2.x, a2.y), bz1 = pack_bf16(a2.z, a2.w);
  const int m = lane >> 3, r = lane & 7;
  const uint32_t off = ((m & 1) * 8 + r) * 128 + (((w4 * 2 + (m >> 1)) ^ r) << 4);
  int s = 0, ph = 0;
#pragma unroll 1
  for (int u = 0; u < 8; u++) {
    const uint32_t bb = buf + s * 16384;
    mbar_wait(BAR_TF(wg * 3 + s), ph);
#pragma unroll
    for (int mt = 0; mt < 8; mt++) {
      uint32_t a[4];
      ldsm4(bb + mt * 2048 + off, a);
      float n0[4] = {0, 0, 0, 0}, n1[4] = {0, 0, 0, 0}, dn[4] = {0, 0, 0, 0};
      mma_bf16(dn, a[0], a[1], a[2], a[3], bz0, bz1);
      mma_bf16(n0, a[0], a[1], a[2], a[3], b00, b01);
      mma_bf16(n1, a[0], a[1], a[2], a[3], b10, b11);
      const float i0 = rcpf(dn[0] + 1e-6f), i1 = rcpf(dn[2] + 1e-6f);
      stsm4(bb + mt * 2048 + off, pack_bf16(n0[0] * i0, n0[1] * i0), pack_bf16(n0[2] * i1, n0[3] * i1),
            pack_bf16(n1[0] * i0, n1[1] * i0), pack_bf16(n1[2] * i1, n1[3] * i1));
    }
    fence_async();
    named_bar(wg + 1, 128);
    if (w4 == 0 && lane == 0) {
      tma2d_store(mOs, bb, col, row0 + u * 128);
      bulk_commit();
      if (u >= 1 && u + 2 < 8) {
        asm volatile("cp.async.bulk.wait_group.read 1;" ::: "memory");
        const int sp = s == 0 ? 2 : s - 1;
        mbar_expect_tx(BAR_TF(wg * 3 + sp), 16384);
        tma2d(buf + sp * 16384, mQ, col, row0 + (u + 2) * 128, BAR_TF(wg * 3 + sp));
      }
    }
    __syncwarp();
    if (++s == 3) { s = 0; ph ^= 1; }
  }
  if (w4 == 0 && lane == 0) {
    bulk_wait_all();
    fence_async_all();
    flag_add(FLAG_LM((h * 2 + cb) * 2 + (wg >> 1)));
    if (wg == 0) TS(1, 8);
  }
}

#define STAGE(s) (sb + (2 - (s)) * 65536)
template <int TR> __device__ __forceinline__ void proj_kb(float* acc, uint32_t st, uint32_t offA, uint32_t offB, int first) {
  const uint64_t da = make_desc(st + offA, TR ? 8192 : 16, 1024, 1);
  const uint64_t db = make_desc(st + offB, TR ? 16 : 8192, 1024, 1);
  wg_fence();
#pragma unroll
  for (int k = 0; k < 4; k++) wg_ss128<TR, 1 - TR>(acc, da + k * (TR ? 128 : 2), db + k * (TR ? 2 : 128), k != 0 || !first);
  wg_commit();
}
template <int TR> __device__ __forceinline__ void proj_loop(float* acc, uint32_t sb, uint32_t bars, uint32_t offA, uint32_t offB,
                                                            int wg, uint32_t sWKV) {
  {
    float kv[4];
    if (threadIdx.x == 0) TS(0, 13);
    mbar_wait(BAR_XA(wg), 0);
    if (threadIdx.x == 0) TS(0, 1);
    const uint64_t da = make_desc(STAGE(2) + wg * 16384, 16, 1024, 1), db = make_desc(sWKV + wg * 2048, 128, 128, 0);
    wg_fence();
#pragma unroll
    for (int k = 0; k < 8; k++) wg_ss8<0, 1>(kv, da + (k >> 2) * 512 + (k & 3) * 2, db + k * 16, k != 0);
    wg_commit();
    wg_wait<0>();
    fence_regs<4>(kv);
    named_bar(wg + 1, 128);
    sts4(sWKV + threadIdx.x * 16, __float_as_uint(kv[0]), __float_as_uint(kv[1]), __float_as_uint(kv[2]), __float_as_uint(kv[3]));
    __syncwarp();
    if ((threadIdx.x & 31) == 0) mbar_arrive(BAR_GO);
  }
  int s = 0, ph = 0, sp = 0;
#pragma unroll 1
  for (int kb = 0; kb < 8; kb++) {
    mbar_wait(BAR_FULL(s), ph);
    if (threadIdx.x == 0) TS(0, 2 + kb);
    proj_kb<TR>(acc, STAGE(s), offA, offB, kb == 0);
    wg_wait<1>();
    if (kb >= 1 && (threadIdx.x & 127) == 0) mbar_arrive(BAR_EMPTY(sp));
    __syncwarp();
    sp = s;
    if (++s == 3) { s = 0; ph ^= 1; }
  }
  wg_wait<0>();
  fence_regs<64>(acc);
}

__device__ __forceinline__ uint32_t tail_slots(int t) {
  const uint32_t lo = t < 4 ? (t < 2 ? (t == 0 ? 0x0C0B0Au : 0x0F0E0Du) : (t == 2 ? 0x100400u : 0x081814u))
                            : (t < 6 ? (t == 4 ? 0x110501u : 0x021915u) : (t == 6 ? 0x161206u : (t == 7 ? 0x07031Au : 0x1B1713u)));
  return lo;
}

__device__ __forceinline__ void take_role(uint32_t sM, int wg) {
  uint32_t r;
  asm volatile("atom.shared.add.u32 %0, [%1], 1;" : "=r"(r) : "r"(sM + 20) : "memory");
  sts1(sM + 32 + wg * 4, r);
}

__global__ void __launch_bounds__(640, 1)
k1_main(const __grid_constant__ CUtensorMap mXA64, const __grid_constant__ CUtensorMap mXB,
        const __grid_constant__ CUtensorMap mWq, const __grid_constant__ CUtensorMap mWqkv,
        const __grid_constant__ CUtensorMap mQst, const __grid_constant__ CUtensorMap mOst,
        const __grid_constant__ CUtensorMap mO, const __grid_constant__ CUtensorMap mWoA,
        const __grid_constant__ CUtensorMap mWoB, const __grid_constant__ CUtensorMap mOut,
        const __grid_constant__ CUtensorMap mO16, const Params prm) {
  extern __shared__ uint8_t smem_raw[];
  const uint32_t sb = (smem_u32(smem_raw) + 1023u) & ~1023u;
  const uint32_t bars = sb + OFF_MISC, sM = bars + 512, sT = bars + 1024;
  const int tid = threadIdx.x, warp = __shfl_sync(~0u, tid >> 5, 0), wg = warp >> 2, w4 = warp & 3, lane = tid & 31;
  const bool helper = blockIdx.x >= 128;
  if (tid == 0) TS(0, 0);
  const int G = blockIdx.x >> 4, gi = blockIdx.x & 15;
  const int tbA = G * 4 + (gi >> 2), hg = gi & 3;
  const int ttB = (G >> 1) * 4 + (gi >> 2), hq = (G & 1) * 4 + (gi & 3);
  const int ttO = G * 2 + (gi >> 3), ct = gi & 7;
  auto issue = [&](int kb, int s) {
    const uint32_t fb = BAR_FULL(s), st = STAGE(s);
    mbar_expect_tx(fb, 65536);
    tma2d(st + 16384, &mXA64, kb * 64, tbA * 64, fb);
    tma2d(st, &mWq, hg * 128, kb * 64, fb);
    tma2d(st + 8192, &mWq, hg * 128 + 64, kb * 64, fb);
    tma2d(st + 49152, &mXB, kb * 64, ttB * 128, fb);
    tma2d(st + 24576, &mWqkv, hq * 64, kb * 64, fb);
    tma2d(st + 32768, &mWqkv, 512 + hq * 64, kb * 64, fb);
    tma2d(st + 40960, &mWqkv, 1024 + hq * 64, kb * 64, fb);
  };
  const uint32_t sOne = sb + OFF_V + 65536, sWKV = sOne + 24576;
  if (warp >= 16) {
    if (warp == 17) {
      if (elect_one()) {
        mbar_init(BAR_BDONE, 8); mbar_init(BAR_Q, 8); mbar_init(BAR_GO, helper ? 1 : 16); mbar_init(BAR_Q2, 5);
        mbar_init(BAR_OD(0), 16); mbar_init(BAR_OD(1), 16); mbar_init(BAR_CL(0), 1); mbar_init(BAR_FULL(2), 1);
#pragma unroll
        for (int i = 0; i < 4; i++) mbar_init(BAR_CL(i + 1), i == 0 ? 5 : 4);
#pragma unroll
        for (int i = 0; i < 3; i++) { mbar_init(BAR_EMPTY(i), 4); mbar_init(BAR_KV(i), 1); mbar_init(BAR_VB(i), 1); }
        sts1(sM + 20, 0);
        asm volatile("fence.mbarrier_init.release.cluster;" ::: "memory");
      }
    } else if (warp == 18) {
      if (elect_one()) {
#pragma unroll
        for (int i = 0; i < 7; i++) mbar_init(BAR_TE(i), 2);
#pragma unroll
        for (int i = 0; i < 16; i++) mbar_init(BAR_TF(i), 1);
        asm volatile("fence.mbarrier_init.release.cluster;" ::: "memory");
      }
    } else if (warp == 16 && !helper && elect_one()) {
#pragma unroll
      for (int w = 0; w < 4; w++) mbar_init(BAR_XA(w), 1);
      mbar_init(BAR_FULL(0), 1); mbar_init(BAR_FULL(1), 1);
      asm volatile("fence.mbarrier_init.release.cluster;" ::: "memory");
#pragma unroll
      for (int w = 0; w < 4; w++) {
        mbar_expect_tx(BAR_XA(w), 16384);
        tma2d(STAGE(2) + w * 16384, &mXA64, w * 128, tbA * 64, BAR_XA(w));
        tma2d(STAGE(2) + w * 16384 + 8192, &mXA64, w * 128 + 64, tbA * 64, BAR_XA(w));
      }
      TS(0, 14);
      issue(0, 0);
    }
  } else if (!helper) {
    const uint4 v = __ldg((const uint4*)(hg >= 2 ? prm.wv : prm.wk) + tid * 2 + (hg & 1));
#pragma unroll
    for (int i = 0; i < 3; i++) {
      const int key = tid + i * 512;
      sts4(sOne + key * 16, (key % STEPK) < 32 ? 0x00003F80u : 0x00004E80u, 0u, 0u, 0u);
    }
    sts4(sWKV + tid * 16, v.x, v.y, v.z, v.w);
    fence_async();
  }
  __syncthreads();
  if (wg == 4) {
    if (w4 == 0 && !helper && elect_one()) { issue(1, 1); TS(0, 15); }
    asm volatile("setmaxnreg.dec.sync.aligned.u32 32;");
    const uint32_t ep = g_epoch[blockIdx.x] + 1;
    if (helper) {
      if (w4 == 0 && elect_one()) {
        flag_wait(FLAG_B(blockIdx.x - 128), ep * 32);
        fence_async_all();
        TS(1, 10);
        mbar_arrive(BAR_GO);
        g_epoch[blockIdx.x] = ep;
      }
      return;
    }
    mbar_wait(BAR_GO, 0);
    if (w4 == 0 && elect_one()) issue(2, 2);
    {
      uint32_t a[4], b[4];
      float c[4];
      lds4(sWKV + (tid - 512) * 16, a);
      lds4(sWKV + 2048 + (tid - 512) * 16, b);
#pragma unroll
      for (int i = 0; i < 4; i++) c[i] = __uint_as_float(a[i]) + __uint_as_float(b[i]);
      lds4(sWKV + 4096 + (tid - 512) * 16, a);
      lds4(sWKV + 6144 + (tid - 512) * 16, b);
#pragma unroll
      for (int i = 0; i < 4; i++) c[i] += __uint_as_float(a[i]) + __uint_as_float(b[i]);
      sts1(sT + w4 * 256 + lane * 4, pack_bf16(c[0], c[1]));
      sts1(sT + w4 * 256 + 128 + lane * 4, pack_bf16(c[2], c[3]));
    }
    named_bar(9, 128);
    {
      const int t = tid - 512;
#pragma unroll
      for (int i = 0; i < 4; i++) {
        const int key = 1536 + t + i * 128;
        sts4(sOne + key * 16, (key % STEPK) < 32 ? 0x00003F80u : 0x00004E80u, 0u, 0u, 0u);
      }
      fence_async();
      __syncwarp();
      if (lane == 0) mbar_arrive(BAR_Q);
    }
    if (w4 == 0) {
      int s = 0, ph = 0;
#pragma unroll 1
      for (int kb = 3; kb < 8; kb++) {
        mbar_wait(BAR_EMPTY(s), ph);
        if (elect_one()) issue(kb, s);
        if (++s == 3) { s = 0; ph ^= 1; }
      }
      flag_wait(FLAG_KV, ep * 128);
      fence_async_all();
      if (lane == 0) TS(0, 11);
#pragma unroll 1
      for (int m = 0; m < 2; m++) {
        mbar_wait(m == 0 ? BAR_EMPTY(2) : BAR_EMPTY(0), 1 - m);
        if (elect_one()) {
#pragma unroll
          for (int c = 0; c < 3; c++) {
            const int k0 = c == 0 ? 0 : (c == 1 ? 7 * STEPK : 12 * STEPK), k1 = c == 0 ? 7 * STEPK : (c == 1 ? 12 * STEPK : S_TOK);
            const uint32_t bytes = (k1 - k0) * 16, fb = m == 0 ? BAR_KV(c) : BAR_VB(c);
            mbar_expect_tx(fb, 2 * bytes);
#pragma unroll
            for (int p = 0; p < 2; p++)
              bulk_g2s(sb + m * OFF_V + p * 32768 + k0 * 16, g_KV + (m * 2 + p) * S_TOK + k0, bytes, fb);
          }
        }
      }
      mbar_wait(BAR_CL(1), 0);
      flag_wait(FLAG_LM((lane & 7) * 2 + (ttO >> 3)), ep);
      __syncwarp();
      fence_async_all();
      if (lane == 0) TS(2, 13);
#pragma unroll 1
      for (int n = 0; n < 8; n++) {
        mbar_wait(BAR_CL(n < 4 ? n >> 1 : (n == 4 ? 2 : (n < 7 ? 3 : 4))), 0);
        const uint32_t sl = tail_slots(n), fb = BAR_TF(n);
        if (elect_one()) {
          mbar_expect_tx(fb, 24576);
          tma2d(sb + (sl & 255) * 8192, &mWoB, ct * 64, n * 64, fb);
          tma2d(sb + ((sl >> 8) & 255) * 8192, &mO, n * 64, S_TOK + ttO * 128, fb);
          tma2d(sb + (sl >> 16) * 8192, &mO, n * 64, S_TOK + ttO * 128 + 64, fb);
        }
      }
      if (lane == 0) g_epoch[blockIdx.x] = ep;
    } else if (w4 == 3) {
      flag_wait(FLAG_KV, ep * 128);
      const uint4 a = *(const uint4*)(g_stats + lane * 4);
      const float kmax2 = __uint_as_float(__reduce_max_sync(~0u, a.x)) + __uint_as_float(__reduce_max_sync(~0u, a.y));
      const float vmax = __uint_as_float(__reduce_max_sync(~0u, max(a.z, a.w)));
      const float lv = vmax > 0.f ? __log2f(vmax) : 0.f;
      const float lim = fminf(90.f, fminf(91.f + lv, 95.f - lv));
      float thr = -1.f;
      if (vmax < 1e27f && kmax2 <= 65536.f && lim > 2.f) thr = fminf(60000.f, (lim * lim - 1.f) / (kmax2 * 1.02f + 1e-30f));
      if (lane == 0) { sts1(sM + 16, __float_as_uint(thr)); mbar_arrive(BAR_Q2); }
      mbar_wait(BAR_CL(3), 0);
      flag_wait(FLAG_OA(ttO * 8 + (lane & 7), 0), ep);
      __syncwarp();
      uint32_t pend = 0xF, rdy = 0;
#pragma unroll 1
      for (int n = 0; n < 8; n++) {
        const int gidx = n < 4 ? n + 9 : (n == 4 ? 8 : n + 8);
        mbar_wait(n == 4 ? BAR_CL(4) : BAR_TE(gidx - 9), 0);
        int kb = n * 2;
        if (n >= 4) {
          rdy &= pend;
#pragma unroll 1
          for (int it = 0; !rdy; it++) {
            uint32_t v;
            asm volatile("ld.acquire.gpu.global.u32 %0, [%1];" : "=r"(v) : "l"(FLAG_OA(ttO * 8 + (lane & 7), 1)) : "memory");
            const uint32_t b = __ballot_sync(~0u, (int32_t)(v - ep) >= 0);
            rdy = b & (b >> 4) & pend;
            if (it > 2000000) __trap();
          }
          const int hsel = __ffs(rdy) - 1;
          pend &= ~(1u << hsel);
          kb = hsel * 2 + 1;
          if (lane == 0 && n == 7) TS(2, 14);
        }
        fence_async_all();
        const uint32_t sl = tail_slots(n == 4 ? 8 : gidx - 9), fb = BAR_TF(gidx);
        if (elect_one()) {
          mbar_expect_tx(fb, 24576);
          tma2d(sb + ((sl >> 8) & 255) * 8192, &mO, kb * 64, ttO * 128, fb);
          tma2d(sb + (sl >> 16) * 8192, &mO, kb * 64, ttO * 128 + 64, fb);
          tma2d(sb + (sl & 255) * 8192, &mWoA, ct * 64, kb * 64, fb);
        }
      }
    } else {
      const int ch = tbA * 2 + (w4 - 1);
      uint32_t v[4], o[4];
      lds4(sT + (w4 - 1) * 512 + lane * 16, v);
      int kap;
      if (lane < 21) kap = lane * STEPK + 32 + ch;
      else { int idx = ch * 11 + (lane - 21); kap = (idx >> 5) * STEPK + (idx & 31); }
      g_KV[(4 + hg) * S_TOK + kap] = make_uint4(v[0], v[1], v[2], v[3]);
      float st = 0.f;
      if (hg < 2) {
        const float sc = lane < 21 ? 2.f : 1.f;
#pragma unroll
        for (int u = 0; u < 4; u++) {
          uint32_t pv = __shfl_up_sync(~0u, v[u], 1);
          if (lane == 0 || lane >= 21) pv = 0;
          const float x = bf_lo(v[u]), y = bf_hi(v[u]);
          st += x * x + y * y;
          o[u] = pack_f16((x - bf_lo(pv)) * sc, (y - bf_hi(pv)) * sc);
        }
      } else {
        const float sc = lane < 21 ? VSHIFT : 1.f;
#pragma unroll
        for (int u = 0; u < 4; u++) { float x = bf_lo(v[u]), y = bf_hi(v[u]); st += fabsf(x) + fabsf(y); o[u] = pack_bf16(x * sc, y * sc); }
      }
      g_KV[hg * S_TOK + kap] = make_uint4(o[0], o[1], o[2], o[3]);
      const uint32_t um = __reduce_max_sync(~0u, __float_as_uint(st) & 0x7FFFFFFFu);
      if (w4 == 2) {
        if (lane == 0) sts1(sM + 24, um);
        named_arrive(10, 64);
      }
      else {
        named_bar(10, 64);
        if (elect_one()) {
          g_stats[tbA * 4 + hg] = max(um, lds1(sM + 24));
          fence_async_all();
          flag_add(FLAG_KV);
          TS(1, 9);
          mbar_wait(BAR_BDONE, 0);
          tma2d_store(&mQst, sb + OFF_F + 49152, hq * 64, S_TOK + ttB * 128);
          bulk_commit();
          bulk_wait_all();
          fence_async_all();
          flag_add(FLAG_B(hq >> 1));
          TS(0, 12);
          mbar_wait(BAR_Q, 0);
          mbar_arrive(BAR_CL(0));
#pragma unroll 1
          for (int p = 0; p < 2; p++) {
            mbar_wait(BAR_OD(p), 0);
#pragma unroll
            for (int w = 0; w < 4; w++) tma2d_store(&mO16, sb + OFF_F + (p * 4 + w) * 2048, hg * 128 + p * 64 + w * 16, tbA * 64);
            bulk_commit();
            bulk_wait_all();
            if (p == 0) mbar_arrive(BAR_CL(1));
            PUBLISH(FLAG_OA(blockIdx.x, p));
          }
          TS(2, 0);
        }
      }
    }
    return;
  }
  if (helper) { helper_cta(blockIdx.x - 128, sb, bars, wg, w4, &mQst, &mOst); return; }

  {
    float acc[64];
    if (wg == 0) proj_loop<0>(acc, sb, bars, 16384, 0, wg, sWKV);
    else proj_loop<1>(acc, sb, bars, 16384 + wg * 8192, 49152, wg, sWKV);
    asm volatile("setmaxnreg.inc.sync.aligned.u32 112;");
    if (tid == 0) TS(0, 10);
    const uint32_t sF = sb + OFF_F;
    if (wg == 0) {
      uint32_t r[32];
      const uint32_t qa = sF + w4 * 512 + ((lane >> 3) & 1) * 256 + (lane >> 4) * 128 + (lane & 7) * 16;
#pragma unroll
      for (int hd = 0; hd < 8; hd++) {
#pragma unroll
        for (int i = 0; i < 4; i++) r[4 * hd + i] = pack_f16(acc[8 * hd + 2 * i] * QSCALE, acc[8 * hd + 2 * i + 1] * QSCALE);
        stsm4(qa + hd * 2048, r[4 * hd], r[4 * hd + 1], r[4 * hd + 2], r[4 * hd + 3]);
        if (hd == 3) {
          fence_async();
          __syncwarp();
          if (lane == 0) mbar_arrive(BAR_Q);
        }
      }
      fence_async();
      uint32_t nmax = 0;
#pragma unroll
      for (int hd = 0; hd < 8; hd++) {
        const uint32_t* q = r + 4 * hd;
        const uint32_t t0 = hfma2(q[2], q[2], hfma2(q[0], q[0], 0u)), t1 = hfma2(q[3], q[3], hfma2(q[1], q[1], 0u));
        uint32_t n = hadd2(__byte_perm(t0, t1, 0x5410), __byte_perm(t0, t1, 0x7632));
        n = hadd2(n, __shfl_xor_sync(~0u, n, 1));
        n = hadd2(n, __shfl_xor_sync(~0u, n, 2));
        nmax = __vmaxu2(nmax, n & 0x7FFF7FFFu);
      }
      nmax = __reduce_max_sync(~0u, max(nmax & 0xFFFFu, nmax >> 16));
      if (lane == 0) sts1(sM + w4 * 4, nmax);
      uint4* gq = (uint4*)g_Q + blockIdx.x * 1024 + tid;
#pragma unroll
      for (int hd = 0; hd < 8; hd++)
        gq[hd * 128] = make_uint4(pack_bf16(acc[8 * hd], acc[8 * hd + 1]), pack_bf16(acc[8 * hd + 2], acc[8 * hd + 3]),
                                  pack_bf16(acc[8 * hd + 4], acc[8 * hd + 5]), pack_bf16(acc[8 * hd + 6], acc[8 * hd + 7]));
      __syncwarp();
      if (lane == 0) mbar_arrive(BAR_Q2);
    } else if (wg == 3) {
      named_arrive(8, 384);
      named_bar(6, 384);
      const int t = tid & 127;
#pragma unroll
      for (int j = 0; j < 8; j++)
        sts4(sF + 24576 + j * 2048 + t * 16, pack_bf16(acc[8 * j], acc[8 * j + 1]), pack_bf16(acc[8 * j + 2], acc[8 * j + 3]),
             pack_bf16(acc[8 * j + 4], acc[8 * j + 5]), pack_bf16(acc[8 * j + 6], acc[8 * j + 7]));
      named_arrive(7, 256);
    } else {
      uint32_t p[32];
      named_arrive(6, 384);
      if (wg == 2) named_arrive(8, 384);
#pragma unroll
      for (int i = 0; i < 32; i++) p[i] = phi2(acc[2 * i], acc[2 * i + 1]);
      if (wg == 1) {
        named_bar(8, 384);
        const int m = lane >> 3, r = lane & 7;
#pragma unroll
        for (int j = 0; j < 16; j += 2) {
          const int tok = (j + (m >> 1)) * 8 + r;
          const int chunk = w4 * 2 + (m & 1);
          stsm4t(sF + 49152 + tok * 128 + ((chunk ^ r) << 4), p[2 * j], p[2 * j + 1], p[2 * j + 2], p[2 * j + 3]);
        }
        fence_async();
      } else {
        named_bar(7, 256);
        float kv0[4] = {0, 0, 0, 0}, kv1[4] = {0, 0, 0, 0}, z0[4] = {0, 0, 0, 0}, z1[4] = {0, 0, 0, 0};
        const uint32_t one = 0x3F803F80u;
        const int t = tid & 127;
#pragma unroll
        for (int j = 0; j < 8; j++) {
          uint32_t a[4];
          lds4(sF + 24576 + j * 2048 + t * 16, a);
          mma_bf16(kv0, a[0], a[1], a[2], a[3], p[4 * j], p[4 * j + 2]);
          mma_bf16(kv1, a[0], a[1], a[2], a[3], p[4 * j + 1], p[4 * j + 3]);
          mma_bf16(z0, one, one, one, one, p[4 * j], p[4 * j + 2]);
          mma_bf16(z1, one, one, one, one, p[4 * j + 1], p[4 * j + 3]);
        }
        float4* dst = g_kvp + ((ttB * 32 + hq * 4 + w4) * 3) * 32 + lane;
        dst[0] = make_float4(kv0[0], kv0[1], kv1[0], kv1[1]);
        dst[32] = make_float4(kv0[2], kv0[3], kv1[2], kv1[3]);
        dst[64] = make_float4(z0[0], z0[1], z1[0], z1[1]);
      }
      __syncwarp();
      if (lane == 0) mbar_arrive(BAR_BDONE);
    }
  }

  mbar_wait(BAR_Q, 0);
  if (tid == 0) TS(1, 1);
  bool safe = true;
  {
    const uint32_t c63 = 0x1F801F80u + (threadIdx.x >> 20);
    const uint32_t m1 = (gridDim.x >> 20) - 1u;
    const uint64_t dK0 = make_desc(sb + OFF_K, 32768, 128, 0);
    const uint64_t dV0 = make_desc(sb + OFF_V, 128, 32768, 0);
    constexpr uint32_t dKV = ((2048u - 8u)  __H0__ ) + STEPK - (OFF_V - OFF_K) / 16;
    mbar_wait(BAR_KV(0), 0);
#pragma unroll 1
    for (int pass = 0; pass < 2; pass++) {
      const uint64_t dQ = make_desc(sb + OFF_F + (pass * 4 + wg) * 2048, 128, 256, 0);
      float Sm[16], Sp[32], O[12];
      uint32_t P[24];
#pragma unroll
      for (int i = 0; i < 32; i++) Sp[i] = SMAGIC;
#pragma unroll
      for (int i = 0; i < 16; i++) Sm[i] = 0.f;
#pragma unroll
      for (int i = 0; i < 12; i++) O[i] = 0.f;
      fence_regs<16>(Sm); fence_regs<32>(Sp); fence_regs<12>(O);
      if (tid == 0) TS(1, 2 + 2 * pass);
      wg_fence();
      wg_qs32<0>(Sm, dQ, dK0);
      wg_qs64<1>(Sp, dQ, dK0 + 32);
      wg_commit();
      wg_wait<0>();
      fence_regs<16>(Sm); fence_regs<32>(Sp);
      uint32_t vlo = (uint32_t)dV0;
#pragma unroll 1
      for (int seg = 0; seg < 4; seg++) {
        if (pass == 0) {
          if (seg < 3) { mbar_wait(BAR_KV(seg), 0); mbar_wait(BAR_VB(seg), 0); }
        } else if (seg >= 1) {
          if ((tid & 127) == 0) {
            mbar_arrive(BAR_CL(seg));
            if (seg == 3) take_role(sM, wg);
          }
          __syncwarp();
        }
        if ((tid & 127) == 0) TS(4 + wg, pass * 5 + seg);
        const uint32_t vend = vlo + (seg == 0 ? 6 : 5) * STEPK;
#pragma unroll 1
        for (; vlo != vend; vlo += STEPK) {
          uint64_t dK, dV;
          asm("mov.b64 %0, {%1, %2};" : "=l"(dK) : "r"(vlo + dKV), "r"(8u));
          asm("mov.b64 %0, {%1, %2};" : "=l"(dV) : "r"(vlo), "r"(2048u));
#pragma unroll
          for (int i = 0; i < 8; i++) P[i] = pack_bf16(ex2f(Sm[2 * i]), ex2f(Sm[2 * i + 1]));
#pragma unroll
          for (int i = 0; i < 16; i++) P[8 + i] = exp2_pair_fix(Sp[2 * i], Sp[2 * i + 1], c63, m1);
          fence_regs<24>(P);
          wg_fence();
#pragma unroll
          for (int k = 0; k < 6; k++) wg_pv24<1>(O, &P[4 * k], dV + k * 16);
          wg_qs64<1>(Sp, dQ, dK + 32);
          wg_qs32<0>(Sm, dQ, dK);
          wg_commit();
          wg_wait<0>();
          fence_regs<16>(Sm); fence_regs<32>(Sp); fence_regs<12>(O); fence_regs<24>(P);
        }
      }
#pragma unroll
      for (int i = 0; i < 8; i++) P[i] = pack_bf16(ex2f(Sm[2 * i]), ex2f(Sm[2 * i + 1]));
      fence_regs<8>(P);
      wg_fence();
      wg_pv24<1>(O, &P[0], dV0 + 21 * STEPK);
      wg_pv24<1>(O, &P[4], dV0 + 21 * STEPK + 16);
      wg_commit();
      wg_wait<0>();
      fence_regs<12>(O);
      if (pass == 0) {
        uint32_t n[4];
        mbar_wait(BAR_Q2, 0);
        lds4(sM, n);
        const float qn = __half2float(__ushort_as_half((unsigned short)max(max(n[0], n[1]), max(n[2], n[3]))));
        safe = __all_sync(~0u, qn <= __uint_as_float(lds1(sM + 16)));
        if (!safe) break;
      }
      const float l0 = __shfl_sync(~0u, O[8], lane & ~3), l1 = __shfl_sync(~0u, O[10], lane & ~3);
      const float i0 = rcpf(l0), i1 = rcpf(l1);
      stsm4(sb + OFF_F + (pass * 4 + wg) * 2048 + w4 * 512 + (lane & 15) * 32 + (lane >> 4) * 16,
            pack_bf16(O[0] * i0, O[1] * i0), pack_bf16(O[2] * i1, O[3] * i1),
            pack_bf16(O[4] * i0, O[5] * i0), pack_bf16(O[6] * i1, O[7] * i1));
      fence_async();
      __syncwarp();
      if (lane == 0) mbar_arrive(BAR_OD(pass));
      if ((tid & 127) == 0) TS(4 + wg, pass * 5 + 4);
      if (tid == 0) TS(1, 3 + 2 * pass);
      if ((tid & 127) == 0 && pass == 1 && wg > 0) TS(1, 10 + wg);
    }
  }

  if (!safe) {
    if ((tid & 127) == 0) { mbar_arrive(BAR_CL(1)); mbar_arrive(BAR_CL(2)); mbar_arrive(BAR_CL(3)); take_role(sM, wg); }
#pragma unroll 1
    for (int pass = 0; pass < 2; pass++) {
      attn_slow((const uint4*)g_Q + blockIdx.x * 1024 + (pass * 4 + wg) * 128, sb + OFF_F + (pass * 4 + wg) * 2048);
      __syncwarp();
      if (lane == 0) mbar_arrive(BAR_OD(pass));
    }
  }

  {
    named_bar(wg + 1, 128);
    if ((tid & 127) == 0) mbar_arrive(BAR_CL(4));
    const int role = __shfl_sync(~0u, lds1(sM + 32 + wg * 4), 0);
    const int isA = role >> 1, hf = role & 1;
    if ((tid & 127) == 0) TS(4 + wg, 10);
    float acc[32];
    uint32_t xs = 0;
    int prev = 0;
#pragma unroll 1
    for (int n = 0; n < 8; n++) {
      const int gidx = isA ? (n < 4 ? n + 9 : (n == 4 ? 8 : n + 8)) : n;
      const uint32_t sl = tail_slots(gidx < 9 ? gidx : gidx - 9);
      xs = sb + ((sl >> (8 + 8 * hf)) & 255) * 8192;
      const uint64_t da = make_desc(xs, 16, 1024, 1), db = make_desc(sb + (sl & 255) * 8192, 8192, 1024, 1);
      mbar_wait(BAR_TF(gidx), 0);
      if ((tid & 127) == 0 && role == 3) TS(2, 2 + n);
      wg_fence();
#pragma unroll
      for (int k = 0; k < 4; k++) wg_ss64<0, 1>(acc, da + k * 2, db + k * 128, (n | k) != 0);
      wg_commit();
      wg_wait<1>();
      if (!isA && n >= 1 && (tid & 127) == 0) mbar_arrive(BAR_TE(prev));
      __syncwarp();
      prev = n;
    }
    wg_wait<0>();
    fence_regs<32>(acc);
    if ((tid & 127) == 0) TS(4 + wg, 11);
    named_bar(wg + 1, 128);
    const int m = lane >> 3, r = lane & 7;
#pragma unroll
    for (int j = 0; j < 8; j += 2) {
      const int row = w4 * 16 + (m & 1) * 8 + r;
      stsm4(xs + row * 128 + (((j + (m >> 1)) ^ r) << 4),
            pack_bf16(acc[4 * j], acc[4 * j + 1]), pack_bf16(acc[4 * j + 2], acc[4 * j + 3]),
            pack_bf16(acc[4 * j + 4], acc[4 * j + 5]), pack_bf16(acc[4 * j + 6], acc[4 * j + 7]));
    }
    fence_async();
    named_bar(wg + 1, 128);
    if (w4 == 0 && elect_one()) {
      tma2d_store(&mOut, xs, (isA ? 0 : 512) + ct * 64, ttO * 128 + hf * 64);
      bulk_commit();
      asm volatile("cp.async.bulk.wait_group.read 0;" ::: "memory");
      TS(2, 11 + (role >> 1));
    }
  }
}

typedef CUresult (*EncodeFn)(CUtensorMap*, CUtensorMapDataType, cuuint32_t, void*, const cuuint64_t*, const cuuint64_t*,
                             const cuuint32_t*, const cuuint32_t*, CUtensorMapInterleave, CUtensorMapSwizzle,
                             CUtensorMapL2promotion, CUtensorMapFloatOOBfill);

static void make_map(EncodeFn enc, CUtensorMap* m, const void* ptr, uint64_t cols, uint64_t rows, uint32_t bc, uint32_t br,
                     CUtensorMapSwizzle sw = CU_TENSOR_MAP_SWIZZLE_128B) {
  cuuint64_t dims[2] = {cols, rows};
  cuuint64_t strides[1] = {cols * 2};
  cuuint32_t box[2] = {bc, br};
  cuuint32_t es[2] = {1, 1};
  enc(m, CU_TENSOR_MAP_DATA_TYPE_BFLOAT16, 2, (void*)ptr, dims, strides, box, es, CU_TENSOR_MAP_INTERLEAVE_NONE,
      sw, CU_TENSOR_MAP_L2_PROMOTION_L2_256B, CU_TENSOR_MAP_FLOAT_OOB_FILL_NONE);
}

extern "C" void kernel_launch(void* const* d_in, const int* in_sizes, int n_in, void* d_out, int out_size) {
  (void)in_sizes; (void)n_in; (void)out_size;
  static EncodeFn enc = nullptr;
  static void* pQ = nullptr; static void* pO = nullptr;
  if (!enc) {
    void* fn = nullptr; cudaDriverEntryPointQueryResult qr;
    cudaGetDriverEntryPoint("cuTensorMapEncodeTiled", &fn, cudaEnableDefault, &qr);
    enc = (EncodeFn)fn;
    cudaGetSymbolAddress(&pQ, g_Q);
    cudaGetSymbolAddress(&pO, g_O);
    cudaFuncSetAttribute(k1_main, cudaFuncAttributeMaxDynamicSharedMemorySize, SM_TOTAL);
  }
  CUtensorMap mXA64, mXB, mWq, mWqkv, mQst, mO, mOst, mWoA, mWoB, mOut, mO16;
  make_map(enc, &mXA64, d_in[0], 512, 2048, 64, 64);
  make_map(enc, &mWq, d_in[1], 512, 512, 64, 64);
  make_map(enc, &mWoA, d_in[4], 512, 512, 64, 64);
  make_map(enc, &mXB, d_in[5], 512, 2048, 64, 128);
  make_map(enc, &mWqkv, d_in[6], 1536, 512, 64, 64);
  make_map(enc, &mWoB, d_in[7], 512, 512, 64, 64);
  make_map(enc, &mQst, pQ, 512, 4096, 64, 128);
  make_map(enc, &mO, pO, 512, 4096, 64, 64);
  make_map(enc, &mOst, pO, 512, 4096, 64, 128);
  make_map(enc, &mOut, d_out, 1024, 2048, 64, 64);
  make_map(enc, &mO16, pO, 512, 4096, 16, 64, CU_TENSOR_MAP_SWIZZLE_NONE);
  Params prm{(const __nv_bfloat16*)d_in[2], (const __nv_bfloat16*)d_in[3], (const __nv_bfloat16*)d_in[0]};
  k1_main<<<132, 640, SM_TOTAL, cudaStreamPerThread>>>(mXA64, mXB, mWq, mWqkv, mQst, mOst, mO, mWoA, mWoB, mOut, mO16, prm);
}
```

```cpp
#include <cuda_runtime.h>
#include <cuda_bf16.h>
#include <cuda_fp16.h>
#include <cuda.h>
#include <stdint.h>

#define S_TOK 2048
#define D_MOD 512

__device__ __align__(1024) __nv_bfloat16 g_Q[2 * S_TOK * D_MOD];
__device__ __align__(1024) __nv_bfloat16 g_O[2 * S_TOK * D_MOD];
__device__ __align__(1024) uint4 g_KV[8 * S_TOK];
__device__ __align__(16) uint32_t g_stats[128];
__device__ __align__(16) float4 g_kvp[16 * 32 * 3 * 32];

#define TS(k, i) do {} while (0)
__device__ __forceinline__ uint32_t smem_u32(const void* p) { return (uint32_t)__cvta_generic_to_shared(p); }
__device__ __forceinline__ void mbar_init(uint32_t bar, int cnt) { asm volatile("mbarrier.init.shared::cta.b64 [%0], %1;" :: "r"(bar), "r"(cnt) : "memory"); }
__device__ __forceinline__ void mbar_expect_tx(uint32_t bar, uint32_t bytes) { asm volatile("mbarrier.arrive.expect_tx.shared::cta.b64 _, [%0], %1;" :: "r"(bar), "r"(bytes) : "memory"); }
__device__ __forceinline__ bool mbar_try(uint32_t bar, uint32_t parity) {
  uint32_t ok;
  asm volatile("{\n.reg .pred p;\nmbarrier.try_wait.parity.shared::cta.b64 p, [%1], %2;\nselp.b32 %0, 1, 0, p;\n}\n" : "=r"(ok) : "r"(bar), "r"(parity) : "memory");
  return ok;
}
__device__ __forceinline__ void mbar_wait(uint32_t bar, uint32_t parity) {
  asm volatile("{\n.reg .pred p;\n.reg .u32 c;\nmov.u32 c, 0;\n"
               "LW_%=:\n"
               "mbarrier.try_wait.parity.shared::cta.b64 p, [%0], %1;\n"
               "@p bra LD_%=;\n"
               "add.u32 c, c, 1;\n"
               "setp.lt.u32 p, c, 4000000;\n"
               "@p bra LW_%=;\n"
               "trap;\n"
               "LD_%=:\n}\n" :: "r"(bar), "r"(parity) : "memory");
}
__device__ __forceinline__ void mbar_arrive_cta(uint32_t bar, uint32_t cta) {
  asm volatile("{\n.reg .b32 ra;\nmapa.shared::cluster.u32 ra, %0, %1;\nmbarrier.arrive.shared::cluster.b64 _, [ra];\n}\n" :: "r"(bar), "r"(cta) : "memory");
}
__device__ __forceinline__ void cluster_sync() {
  asm volatile("barrier.cluster.arrive.relaxed.aligned;\nbarrier.cluster.wait.aligned;" ::: "memory");
}
__device__ __forceinline__ void tma2d(uint32_t dst, const CUtensorMap* m, int c0, int c1, uint32_t bar) {
  asm volatile("cp.async.bulk.tensor.2d.shared::cluster.global.mbarrier::complete_tx::bytes [%0], [%1, {%3, %4}], [%2];"
               :: "r"(dst), "l"(m), "r"(bar), "r"(c0), "r"(c1) : "memory");
}
__device__ __forceinline__ void tma2d_mc(uint32_t dst, const CUtensorMap* m, int c0, int c1, uint32_t bar, uint16_t mask) {
  asm volatile("cp.async.bulk.tensor.2d.shared::cluster.global.mbarrier::complete_tx::bytes.multicast::cluster [%0], [%1, {%3, %4}], [%2], %5;"
               :: "r"(dst), "l"(m), "r"(bar), "r"(c0), "r"(c1), "h"(mask) : "memory");
}
__device__ __forceinline__ void tma2d_store(const CUtensorMap* m, uint32_t src, int c0, int c1) {
  asm volatile("cp.async.bulk.tensor.2d.global.shared::cta.bulk_group [%0, {%2, %3}], [%1];"
               :: "l"(m), "r"(src), "r"(c0), "r"(c1) : "memory");
}
__device__ __forceinline__ void bulk_g2s(uint32_t dst, const void* src, uint32_t bytes, uint32_t bar) {
  asm volatile("cp.async.bulk.shared::cluster.global.mbarrier::complete_tx::bytes [%0], [%1], %2, [%3];"
               :: "r"(dst), "l"(src), "r"(bytes), "r"(bar) : "memory");
}
__device__ __forceinline__ void bulk_commit() { asm volatile("cp.async.bulk.commit_group;" ::: "memory"); }
__device__ __forceinline__ void bulk_wait_all() { asm volatile("cp.async.bulk.wait_group 0;" ::: "memory"); }
__device__ __forceinline__ void fence_async() { asm volatile("fence.proxy.async.shared::cta;" ::: "memory"); }
__device__ __forceinline__ void named_bar(int id, int n) { asm volatile("bar.sync %0, %1;" :: "r"(id), "r"(n) : "memory"); }
__device__ __forceinline__ void pdl_launch() { asm volatile("griddepcontrol.launch_dependents;" ::: "memory"); }
__device__ __forceinline__ void pdl_wait() { asm volatile("griddepcontrol.wait;" ::: "memory"); }
__device__ __forceinline__ void wg_fence() { asm volatile("wgmma.fence.sync.aligned;" ::: "memory"); }
__device__ __forceinline__ void wg_commit() { asm volatile("wgmma.commit_group.sync.aligned;" ::: "memory"); }
template <int n> __device__ __forceinline__ void wg_wait() { asm volatile("wgmma.wait_group.sync.aligned %0;" :: "n"(n) : "memory"); }
template <int n> __device__ __forceinline__ void fence_regs(float* r) {
#pragma unroll
  for (int i = 0; i < n; i++) asm volatile("" : "+f"(r[i]) :: "memory");
}
template <int n> __device__ __forceinline__ void fence_regs(uint32_t* r) {
#pragma unroll
  for (int i = 0; i < n; i++) asm volatile("" : "+r"(r[i]) :: "memory");
}
__device__ __forceinline__ uint64_t make_desc(uint32_t addr, uint32_t lbo, uint32_t sbo, uint32_t swz) {
  return (uint64_t)((addr & 0x3FFFF) >> 4) | ((uint64_t)(lbo >> 4) << 16) | ((uint64_t)(sbo >> 4) << 32) | ((uint64_t)swz << 62);
}
__device__ __forceinline__ float ex2f(float x) { float y; asm("ex2.approx.ftz.f32 %0, %1;" : "=f"(y) : "f"(x)); return y; }
__device__ __forceinline__ uint32_t pack_bf16(float lo, float hi) { uint32_t r; asm("cvt.rn.bf16x2.f32 %0, %1, %2;" : "=r"(r) : "f"(hi), "f"(lo)); return r; }
__device__ __forceinline__ uint32_t pack_f16(float lo, float hi) { uint32_t r; asm("cvt.rn.f16x2.f32 %0, %1, %2;" : "=r"(r) : "f"(hi), "f"(lo)); return r; }
__device__ __forceinline__ float bf_lo(uint32_t v) { return __uint_as_float(v << 16); }
__device__ __forceinline__ float bf_hi(uint32_t v) { return __uint_as_float(v & 0xFFFF0000u); }
__device__ __forceinline__ float rbf(float x) { return __bfloat162float(__float2bfloat16_rn(x)); }
__device__ __forceinline__ void stsm4(uint32_t a, uint32_t r0, uint32_t r1, uint32_t r2, uint32_t r3) {
  asm volatile("stmatrix.sync.aligned.m8n8.x4.shared.b16 [%0], {%1,%2,%3,%4};" :: "r"(a), "r"(r0), "r"(r1), "r"(r2), "r"(r3) : "memory");
}
__device__ __forceinline__ void stsm4t(uint32_t a, uint32_t r0, uint32_t r1, uint32_t r2, uint32_t r3) {
  asm volatile("stmatrix.sync.aligned.m8n8.x4.trans.shared.b16 [%0], {%1,%2,%3,%4};" :: "r"(a), "r"(r0), "r"(r1), "r"(r2), "r"(r3) : "memory");
}
__device__ __forceinline__ void mma_bf16(float* d, uint32_t a0, uint32_t a1, uint32_t a2, uint32_t a3, uint32_t b0, uint32_t b1) {
  asm volatile("mma.sync.aligned.m16n8k16.row.col.f32.bf16.bf16.f32 {%0,%1,%2,%3}, {%4,%5,%6,%7}, {%8,%9}, {%0,%1,%2,%3};"
               : "+f"(d[0]), "+f"(d[1]), "+f"(d[2]), "+f"(d[3]) : "r"(a0), "r"(a1), "r"(a2), "r"(a3), "r"(b0), "r"(b1));
}
template<int SD> __device__ __forceinline__ void wg_qk32(float* d, const uint32_t* a, uint64_t desc) {
  asm volatile("wgmma.mma_async.sync.aligned.m64n32k16.f32.f16.f16 {%0,%1,%2,%3,%4,%5,%6,%7,%8,%9,%10,%11,%12,%13,%14,%15}, {%16,%17,%18,%19}, %20, %21, 1, 1, 0;"
   : "+f"(d[0]),"+f"(d[1]),"+f"(d[2]),"+f"(d[3]),"+f"(d[4]),"+f"(d[5]),"+f"(d[6]),"+f"(d[7]),"+f"(d[8]),"+f"(d[9]),"+f"(d[10]),"+f"(d[11]),"+f"(d[12]),"+f"(d[13]),"+f"(d[14]),"+f"(d[15])
   : "r"(a[0]),"r"(a[1]),"r"(a[2]),"r"(a[3]),"l"(desc),"n"(SD));
}
template<int SD> __device__ __forceinline__ void wg_qk64(float* d, const uint32_t* a, uint64_t desc) {
  asm volatile("wgmma.mma_async.sync.aligned.m64n64k16.f32.f16.f16 {%0,%1,%2,%3,%4,%5,%6,%7,%8,%9,%10,%11,%12,%13,%14,%15,%16,%17,%18,%19,%20,%21,%22,%23,%24,%25,%26,%27,%28,%29,%30,%31}, {%32,%33,%34,%35}, %36, %37, 1, 1, 0;"
   : "+f"(d[0]),"+f"(d[1]),"+f"(d[2]),"+f"(d[3]),"+f"(d[4]),"+f"(d[5]),"+f"(d[6]),"+f"(d[7]),"+f"(d[8]),"+f"(d[9]),"+f"(d[10]),"+f"(d[11]),"+f"(d[12]),"+f"(d[13]),"+f"(d[14]),"+f"(d[15]),"+f"(d[16]),"+f"(d[17]),"+f"(d[18]),"+f"(d[19]),"+f"(d[20]),"+f"(d[21]),"+f"(d[22]),"+f"(d[23]),"+f"(d[24]),"+f"(d[25]),"+f"(d[26]),"+f"(d[27]),"+f"(d[28]),"+f"(d[29]),"+f"(d[30]),"+f"(d[31])
   : "r"(a[0]),"r"(a[1]),"r"(a[2]),"r"(a[3]),"l"(desc),"n"(SD));
}
template<int SD> __device__ __forceinline__ void wg_qs32(float* d, uint64_t da, uint64_t db) {
  asm volatile("wgmma.mma_async.sync.aligned.m64n32k16.f32.f16.f16 {%0,%1,%2,%3,%4,%5,%6,%7,%8,%9,%10,%11,%12,%13,%14,%15}, %16, %17, %18, 1, 1, 0, 0;"
   : "+f"(d[0]),"+f"(d[1]),"+f"(d[2]),"+f"(d[3]),"+f"(d[4]),"+f"(d[5]),"+f"(d[6]),"+f"(d[7]),"+f"(d[8]),"+f"(d[9]),"+f"(d[10]),"+f"(d[11]),"+f"(d[12]),"+f"(d[13]),"+f"(d[14]),"+f"(d[15])
   : "l"(da),"l"(db),"n"(SD));
}
template<int SD> __device__ __forceinline__ void wg_qs64(float* d, uint64_t da, uint64_t db) {
  asm volatile("wgmma.mma_async.sync.aligned.m64n64k16.f32.f16.f16 {%0,%1,%2,%3,%4,%5,%6,%7,%8,%9,%10,%11,%12,%13,%14,%15,%16,%17,%18,%19,%20,%21,%22,%23,%24,%25,%26,%27,%28,%29,%30,%31}, %32, %33, %34, 1, 1, 0, 0;"
   : "+f"(d[0]),"+f"(d[1]),"+f"(d[2]),"+f"(d[3]),"+f"(d[4]),"+f"(d[5]),"+f"(d[6]),"+f"(d[7]),"+f"(d[8]),"+f"(d[9]),"+f"(d[10]),"+f"(d[11]),"+f"(d[12]),"+f"(d[13]),"+f"(d[14]),"+f"(d[15]),"+f"(d[16]),"+f"(d[17]),"+f"(d[18]),"+f"(d[19]),"+f"(d[20]),"+f"(d[21]),"+f"(d[22]),"+f"(d[23]),"+f"(d[24]),"+f"(d[25]),"+f"(d[26]),"+f"(d[27]),"+f"(d[28]),"+f"(d[29]),"+f"(d[30]),"+f"(d[31])
   : "l"(da),"l"(db),"n"(SD));
}
template<int SD> __device__ __forceinline__ void wg_pv24(float* d, const uint32_t* a, uint64_t desc) {
  asm volatile("wgmma.mma_async.sync.aligned.m64n24k16.f32.bf16.bf16 {%0,%1,%2,%3,%4,%5,%6,%7,%8,%9,%10,%11}, {%12,%13,%14,%15}, %16, %17, 1, 1, 1;"
   : "+f"(d[0]),"+f"(d[1]),"+f"(d[2]),"+f"(d[3]),"+f"(d[4]),"+f"(d[5]),"+f"(d[6]),"+f"(d[7]),"+f"(d[8]),"+f"(d[9]),"+f"(d[10]),"+f"(d[11])
   : "r"(a[0]),"r"(a[1]),"r"(a[2]),"r"(a[3]),"l"(desc),"n"(SD));
}
template<int TA, int TB> __device__ __forceinline__ void wg_ss128(float* d, uint64_t da, uint64_t db, int sd) {
  asm volatile("{\n.reg .pred p;\nsetp.ne.b32 p, %66, 0;\n"
   "wgmma.mma_async.sync.aligned.m64n128k16.f32.bf16.bf16 {%0,%1,%2,%3,%4,%5,%6,%7,%8,%9,%10,%11,%12,%13,%14,%15,%16,%17,%18,%19,%20,%21,%22,%23,%24,%25,%26,%27,%28,%29,%30,%31,%32,%33,%34,%35,%36,%37,%38,%39,%40,%41,%42,%43,%44,%45,%46,%47,%48,%49,%50,%51,%52,%53,%54,%55,%56,%57,%58,%59,%60,%61,%62,%63}, %64, %65, p, 1, 1, %67, %68;\n}\n"
   : "+f"(d[0]),"+f"(d[1]),"+f"(d[2]),"+f"(d[3]),"+f"(d[4]),"+f"(d[5]),"+f"(d[6]),"+f"(d[7]),"+f"(d[8]),"+f"(d[9]),"+f"(d[10]),"+f"(d[11]),"+f"(d[12]),"+f"(d[13]),"+f"(d[14]),"+f"(d[15]),"+f"(d[16]),"+f"(d[17]),"+f"(d[18]),"+f"(d[19]),"+f"(d[20]),"+f"(d[21]),"+f"(d[22]),"+f"(d[23]),"+f"(d[24]),"+f"(d[25]),"+f"(d[26]),"+f"(d[27]),"+f"(d[28]),"+f"(d[29]),"+f"(d[30]),"+f"(d[31]),"+f"(d[32]),"+f"(d[33]),"+f"(d[34]),"+f"(d[35]),"+f"(d[36]),"+f"(d[37]),"+f"(d[38]),"+f"(d[39]),"+f"(d[40]),"+f"(d[41]),"+f"(d[42]),"+f"(d[43]),"+f"(d[44]),"+f"(d[45]),"+f"(d[46]),"+f"(d[47]),"+f"(d[48]),"+f"(d[49]),"+f"(d[50]),"+f"(d[51]),"+f"(d[52]),"+f"(d[53]),"+f"(d[54]),"+f"(d[55]),"+f"(d[56]),"+f"(d[57]),"+f"(d[58]),"+f"(d[59]),"+f"(d[60]),"+f"(d[61]),"+f"(d[62]),"+f"(d[63])
   : "l"(da),"l"(db),"r"(sd),"n"(TA),"n"(TB));
}
template<int TA, int TB> __device__ __forceinline__ void wg_ss64(float* d, uint64_t da, uint64_t db, int sd) {
  asm volatile("{\n.reg .pred p;\nsetp.ne.b32 p, %34, 0;\n"
   "wgmma.mma_async.sync.aligned.m64n64k16.f32.bf16.bf16 {%0,%1,%2,%3,%4,%5,%6,%7,%8,%9,%10,%11,%12,%13,%14,%15,%16,%17,%18,%19,%20,%21,%22,%23,%24,%25,%26,%27,%28,%29,%30,%31}, %32, %33, p, 1, 1, %35, %36;\n}\n"
   : "+f"(d[0]),"+f"(d[1]),"+f"(d[2]),"+f"(d[3]),"+f"(d[4]),"+f"(d[5]),"+f"(d[6]),"+f"(d[7]),"+f"(d[8]),"+f"(d[9]),"+f"(d[10]),"+f"(d[11]),"+f"(d[12]),"+f"(d[13]),"+f"(d[14]),"+f"(d[15]),"+f"(d[16]),"+f"(d[17]),"+f"(d[18]),"+f"(d[19]),"+f"(d[20]),"+f"(d[21]),"+f"(d[22]),"+f"(d[23]),"+f"(d[24]),"+f"(d[25]),"+f"(d[26]),"+f"(d[27]),"+f"(d[28]),"+f"(d[29]),"+f"(d[30]),"+f"(d[31])
   : "l"(da),"l"(db),"r"(sd),"n"(TA),"n"(TB));
}

template<int TA, int TB> __device__ __forceinline__ void wg_ss8(float* d, uint64_t da, uint64_t db, int sd) {
  asm volatile("{\n.reg .pred p;\nsetp.ne.b32 p, %6, 0;\n"
   "wgmma.mma_async.sync.aligned.m64n8k16.f32.bf16.bf16 {%0,%1,%2,%3}, %4, %5, p, 1, 1, %7, %8;\n}\n"
   : "+f"(d[0]),"+f"(d[1]),"+f"(d[2]),"+f"(d[3])
   : "l"(da),"l"(db),"r"(sd),"n"(TA),"n"(TB));
}

template<int SD, uint32_t HI> __device__ __forceinline__ void wq32(float* d, uint64_t da, uint32_t lo) {
  asm volatile("{\n.reg .b64 db;\nmov.b64 db, {%17, %19};\n"
   "wgmma.mma_async.sync.aligned.m64n32k16.f32.f16.f16 {%0,%1,%2,%3,%4,%5,%6,%7,%8,%9,%10,%11,%12,%13,%14,%15}, %16, db, %18, 1, 1, 0, 0;\n}\n"
   : "+f"(d[0]),"+f"(d[1]),"+f"(d[2]),"+f"(d[3]),"+f"(d[4]),"+f"(d[5]),"+f"(d[6]),"+f"(d[7]),"+f"(d[8]),"+f"(d[9]),"+f"(d[10]),"+f"(d[11]),"+f"(d[12]),"+f"(d[13]),"+f"(d[14]),"+f"(d[15])
   : "l"(da),"r"(lo),"n"(SD),"r"(HI));
}
template<int SD, uint32_t HI> __device__ __forceinline__ void wq64(float* d, uint64_t da, uint32_t lo) {
  asm volatile("{\n.reg .b64 db;\nmov.b64 db, {%33, %35};\n"
   "wgmma.mma_async.sync.aligned.m64n64k16.f32.f16.f16 {%0,%1,%2,%3,%4,%5,%6,%7,%8,%9,%10,%11,%12,%13,%14,%15,%16,%17,%18,%19,%20,%21,%22,%23,%24,%25,%26,%27,%28,%29,%30,%31}, %32, db, %34, 1, 1, 0, 0;\n}\n"
   : "+f"(d[0]),"+f"(d[1]),"+f"(d[2]),"+f"(d[3]),"+f"(d[4]),"+f"(d[5]),"+f"(d[6]),"+f"(d[7]),"+f"(d[8]),"+f"(d[9]),"+f"(d[10]),"+f"(d[11]),"+f"(d[12]),"+f"(d[13]),"+f"(d[14]),"+f"(d[15]),"+f"(d[16]),"+f"(d[17]),"+f"(d[18]),"+f"(d[19]),"+f"(d[20]),"+f"(d[21]),"+f"(d[22]),"+f"(d[23]),"+f"(d[24]),"+f"(d[25]),"+f"(d[26]),"+f"(d[27]),"+f"(d[28]),"+f"(d[29]),"+f"(d[30]),"+f"(d[31])
   : "l"(da),"r"(lo),"n"(SD),"r"(HI));
}
template<int SD, uint32_t HI> __device__ __forceinline__ void wpv(float* d, const uint32_t* a, uint32_t lo) {
  asm volatile("{\n.reg .b64 db;\nmov.b64 db, {%16, %18};\n"
   "wgmma.mma_async.sync.aligned.m64n24k16.f32.bf16.bf16 {%0,%1,%2,%3,%4,%5,%6,%7,%8,%9,%10,%11}, {%12,%13,%14,%15}, db, %17, 1, 1, 1;\n}\n"
   : "+f"(d[0]),"+f"(d[1]),"+f"(d[2]),"+f"(d[3]),"+f"(d[4]),"+f"(d[5]),"+f"(d[6]),"+f"(d[7]),"+f"(d[8]),"+f"(d[9]),"+f"(d[10]),"+f"(d[11])
   : "r"(a[0]),"r"(a[1]),"r"(a[2]),"r"(a[3]),"r"(lo),"n"(SD),"r"(HI));
}

__device__ __forceinline__ uint32_t phi2(float a, float b) {
  uint32_t r, e;
  asm("cvt.rn.relu.bf16x2.f32 %0, %1, %2;" : "=r"(r) : "f"(b), "f"(a));
  e = pack_bf16(ex2f(a * 1.4426950408889634f), ex2f(b * 1.4426950408889634f));
  asm("add.rn.bf16x2 %0, %0, %1;" : "+r"(e) : "r"(0x35863586u));
  asm("min.NaN.bf16x2 %0, %0, %1;" : "+r"(e) : "r"(0x3F803F80u));
  asm("add.rn.bf16x2 %0, %0, %1;" : "+r"(e) : "r"(r));
  return e;
}

__device__ __forceinline__ void mbar_arrive(uint32_t bar) { asm volatile("mbarrier.arrive.shared::cta.b64 _, [%0];" :: "r"(bar) : "memory"); }
__device__ __forceinline__ void named_arrive(int id, int n) { asm volatile("bar.arrive %0, %1;" :: "r"(id), "r"(n) : "memory"); }
__device__ __forceinline__ void fence_async_all() { asm volatile("fence.proxy.async.global;" ::: "memory"); }
__device__ __forceinline__ void flag_add(uint32_t* f) { asm volatile("fence.acq_rel.gpu;\nred.relaxed.gpu.global.add.u32 [%0], 1;" :: "l"(f) : "memory"); }
#define PUBLISH(f) asm volatile("fence.proxy.async.global;\nred.relaxed.gpu.global.add.u32 [%0], 1;" :: "l"(f) : "memory")
__device__ __forceinline__ void flag_wait(const uint32_t* f, uint32_t target) {
  uint32_t v;
#pragma unroll 1
  for (int it = 0;; it++) {
    asm volatile("ld.acquire.gpu.global.u32 %0, [%1];" : "=r"(v) : "l"(f) : "memory");
    if ((int32_t)(v - target) >= 0) break;
    if (it > 2000000) __trap();
    __nanosleep(64);
  }
}
__device__ __forceinline__ bool elect_one() {
  uint32_t p;
  asm volatile("{\n.reg .pred P;\nelect.sync _|P, 0xFFFFFFFF;\nselp.b32 %0, 1, 0, P;\n}\n" : "=r"(p));
  return p;
}
__device__ __forceinline__ void lds4(uint32_t a, uint32_t* r) {
  asm volatile("ld.shared.v4.b32 {%0,%1,%2,%3}, [%4];" : "=r"(r[0]), "=r"(r[1]), "=r"(r[2]), "=r"(r[3]) : "r"(a) : "memory");
}
__device__ __forceinline__ uint32_t lds1(uint32_t a) { uint32_t r; asm volatile("ld.shared.b32 %0, [%1];" : "=r"(r) : "r"(a) : "memory"); return r; }
__device__ __forceinline__ void sts1(uint32_t a, uint32_t v) { asm volatile("st.shared.b32 [%0], %1;" :: "r"(a), "r"(v) : "memory"); }
__device__ __forceinline__ void sts4(uint32_t a, uint32_t r0, uint32_t r1, uint32_t r2, uint32_t r3) {
  asm volatile("st.shared.v4.b32 [%0], {%1,%2,%3,%4};" :: "r"(a), "r"(r0), "r"(r1), "r"(r2), "r"(r3) : "memory");
}
__device__ __forceinline__ void ldsm4(uint32_t a, uint32_t* r) {
  asm volatile("ldmatrix.sync.aligned.m8n8.x4.shared.b16 {%0,%1,%2,%3}, [%4];" : "=r"(r[0]), "=r"(r[1]), "=r"(r[2]), "=r"(r[3]) : "r"(a) : "memory");
}
__device__ __forceinline__ float rcpf(float x) { float y; asm("rcp.approx.ftz.f32 %0, %1;" : "=f"(y) : "f"(x)); return y; }
__device__ __forceinline__ uint32_t hfma2(uint32_t a, uint32_t b, uint32_t c) { uint32_t r; asm("fma.rn.f16x2 %0, %1, %2, %3;" : "=r"(r) : "r"(a), "r"(b), "r"(c)); return r; }
__device__ __forceinline__ uint32_t hadd2(uint32_t a, uint32_t b) { uint32_t r; asm("add.rn.f16x2 %0, %1, %2;" : "=r"(r) : "r"(a), "r"(b)); return r; }

#define STEPK 96
#define QSCALE 0.36067376022224085f
#define SMAGIC (512.0f + 2.0f * (191.0f - 30.0f - 1.5823545f))
#define VSHIFT 1073741824.0f

__device__ uint32_t g_epoch[132];
__device__ uint32_t g_flag[288 * 8];
#define FLAG_KV (g_flag)
#define FLAG_B(h) (g_flag + (4 + (h)) * 8)
#define FLAG_OA(cta, pass) (g_flag + (16 + (cta) * 2 + (pass)) * 8)
#define FLAG_LM(i) (g_flag + (272 + (i)) * 8)

#define SM_TOTAL (224 * 1024 + 2048 + 1024)
#define OFF_K 0
#define OFF_F 65536
#define OFF_V 131072
#define OFF_MISC (224 * 1024)

#define BAR_FULL(s) (bars + 8 * (s))
#define BAR_EMPTY(s) (bars + 24 + 8 * (s))
#define BAR_KV(c) (bars + 48 + 8 * (c))
#define BAR_BDONE (bars + 80)
#define BAR_Q (bars + 88)
#define BAR_GO (bars + 96)
#define BAR_Q2 (bars + 104)
#define BAR_OD(p) (bars + 112 + 8 * (p))
#define BAR_CL(c) (bars + 128 + 8 * (c))
#define BAR_TE(i) (bars + 168 + 8 * (i))
#define BAR_TF(g) (bars + 224 + 8 * (g))
#define BAR_XA(w) (bars + 352 + 8 * (w))
#define BAR_VB(c) (bars + 384 + 8 * (c))

__device__ __forceinline__ uint32_t exp2_pair_fix(float d0, float d1, uint32_t c63, uint32_t m1) {
  uint32_t w, y, s, r;
  asm("prmt.b32 %0, %1, %2, 0x6521;" : "=r"(w) : "r"(__float_as_uint(d0)), "r"(__float_as_uint(d1)));
  asm("lop3.b32 %0, %1, 0x007F007F, %2, 0xEA;" : "=r"(y) : "r"(w), "r"(c63));
  asm("mad.lo.u32 %0, %1, %2, %3;" : "=r"(s) : "r"(y), "r"(m1), "r"(w));
  asm("fma.rn.bf16x2 %0, %1, %2, %3;" : "=r"(r) : "r"(w), "r"(y), "r"(s));
  return r;
}

__device__ __forceinline__ void attn_slow(const uint4* gq, uint32_t dst) {
  const int t = threadIdx.x & 127;
  const int row = t >> 1, half = t & 1;
  float q[16];
#pragma unroll
  for (int i = 0; i < 4; i++) {
    const uint4 v = gq[(row >> 4) * 32 + (row & 7) * 4 + i];
    const uint32_t lo = (row & 8) ? v.y : v.x, hi = (row & 8) ? v.w : v.z;
    q[2 * i] = bf_lo(lo); q[2 * i + 1] = bf_hi(lo); q[2 * i + 8] = bf_lo(hi); q[2 * i + 9] = bf_hi(hi);
  }
  float m = -INFINITY, l = 0.f, o[16];
#pragma unroll
  for (int i = 0; i < 16; i++) o[i] = 0.f;
#pragma unroll 1
  for (int j = half * 1024; j < half * 1024 + 1024; j++) {
    uint4 ka = g_KV[4 * S_TOK + j], kb = g_KV[5 * S_TOK + j];
    uint4 va = g_KV[6 * S_TOK + j], vb = g_KV[7 * S_TOK + j];
    uint32_t kk[8] = {ka.x, ka.y, ka.z, ka.w, kb.x, kb.y, kb.z, kb.w};
    uint32_t vv[8] = {va.x, va.y, va.z, va.w, vb.x, vb.y, vb.z, vb.w};
    float s = 0.f;
#pragma unroll
    for (int i = 0; i < 8; i++) { s = fmaf(q[2 * i], bf_lo(kk[i]), s); s = fmaf(q[2 * i + 1], bf_hi(kk[i]), s); }
    s = rbf(s) * 0.25f;
    if (s > m) {
      float c = __expf(m - s);
      l *= c;
#pragma unroll
      for (int i = 0; i < 16; i++) o[i] *= c;
      m = s;
    }
    float p = __expf(s - m);
    l += p;
#pragma unroll
    for (int i = 0; i < 8; i++) { o[2 * i] = fmaf(p, bf_lo(vv[i]), o[2 * i]); o[2 * i + 1] = fmaf(p, bf_hi(vv[i]), o[2 * i + 1]); }
  }
  float m2 = __shfl_xor_sync(~0u, m, 1);
  float mm = fmaxf(m, m2);
  float c = __expf(m - mm);
  l *= c; l += __shfl_xor_sync(~0u, l, 1);
  float inv = 1.f / l;
  uint32_t r[8];
#pragma unroll
  for (int i = 0; i < 16; i++) { o[i] *= c; o[i] += __shfl_xor_sync(~0u, o[i], 1); o[i] *= inv; }
#pragma unroll
  for (int i = 0; i < 8; i++) r[i] = pack_bf16(o[2 * i], o[2 * i + 1]);
  if (half == 0) sts4(dst + t * 16, r[0], r[1], r[2], r[3]); else sts4(dst + t * 16, r[4], r[5], r[6], r[7]);
  fence_async();
}

struct Params { const __nv_bfloat16* wk; const __nv_bfloat16* wv; const __nv_bfloat16* xa; };
__device__ __forceinline__ void cp16(uint32_t dst, const void* src) { asm volatile("cp.async.cg.shared.global [%0], [%1], 16;" :: "r"(dst), "l"(src) : "memory"); }

__device__ __forceinline__ void helper_cta(const int h, const uint32_t sb, const uint32_t bars, const int wg, const int w4,
                                           const CUtensorMap* mQ, const CUtensorMap* mOs) {
  const int lane = threadIdx.x & 31;
  mbar_wait(BAR_GO, 0);
  const int cb = wg & 1, col = h * 128 + cb * 64, row0 = S_TOK + (wg >> 1) * 1024;
  const uint32_t buf = sb + wg * 49152;
  if (w4 == 0 && elect_one()) {
    fence_async_all();
#pragma unroll 1
    for (int u = 0; u < 3; u++) {
      mbar_expect_tx(BAR_TF(wg * 3 + u), 16384);
      tma2d(buf + u * 16384, mQ, col, row0 + u * 128, BAR_TF(wg * 3 + u));
    }
  }
  const int head = h * 8 + cb * 4 + w4;
  float4 a0 = make_float4(0, 0, 0, 0), a1 = a0, a2 = a0;
#pragma unroll 8
  for (int tt = 0; tt < 16; tt++) {
    const float4* src = g_kvp + ((tt * 32 + head) * 3) * 32 + lane;
    float4 u = src[0], v = src[32], w = src[64];
    a0.x += u.x; a0.y += u.y; a0.z += u.z; a0.w += u.w;
    a1.x += v.x; a1.y += v.y; a1.z += v.z; a1.w += v.w;
    a2.x += w.x; a2.y += w.y; a2.z += w.z; a2.w += w.w;
  }
  const uint32_t b00 = pack_bf16(a0.x, a0.y), b01 = pack_bf16(a0.z, a0.w);
  const uint32_t b10 = pack_bf16(a1.x, a1.y), b11 = pack_bf16(a1.z, a1.w);
  const uint32_t bz0 = pack_bf16(a2.x, a2.y), bz1 = pack_bf16(a2.z, a2.w);
  const int m = lane >> 3, r = lane & 7;
  const uint32_t off = ((m & 1) * 8 + r) * 128 + (((w4 * 2 + (m >> 1)) ^ r) << 4);
  int s = 0, ph = 0;
#pragma unroll 1
  for (int u = 0; u < 8; u++) {
    const uint32_t bb = buf + s * 16384;
    mbar_wait(BAR_TF(wg * 3 + s), ph);
#pragma unroll
    for (int mt = 0; mt < 8; mt++) {
      uint32_t a[4];
      ldsm4(bb + mt * 2048 + off, a);
      float n0[4] = {0, 0, 0, 0}, n1[4] = {0, 0, 0, 0}, dn[4] = {0, 0, 0, 0};
      mma_bf16(dn, a[0], a[1], a[2], a[3], bz0, bz1);
      mma_bf16(n0, a[0], a[1], a[2], a[3], b00, b01);
      mma_bf16(n1, a[0], a[1], a[2], a[3], b10, b11);
      const float i0 = rcpf(dn[0] + 1e-6f), i1 = rcpf(dn[2] + 1e-6f);
      stsm4(bb + mt * 2048 + off, pack_bf16(n0[0] * i0, n0[1] * i0), pack_bf16(n0[2] * i1, n0[3] * i1),
            pack_bf16(n1[0] * i0, n1[1] * i0), pack_bf16(n1[2] * i1, n1[3] * i1));
    }
    fence_async();
    named_bar(wg + 1, 128);
    if (w4 == 0 && lane == 0) {
      tma2d_store(mOs, bb, col, row0 + u * 128);
      bulk_commit();
      if (u >= 1 && u + 2 < 8) {
        asm volatile("cp.async.bulk.wait_group.read 1;" ::: "memory");
        const int sp = s == 0 ? 2 : s - 1;
        mbar_expect_tx(BAR_TF(wg * 3 + sp), 16384);
        tma2d(buf + sp * 16384, mQ, col, row0 + (u + 2) * 128, BAR_TF(wg * 3 + sp));
      }
    }
    __syncwarp();
    if (++s == 3) { s = 0; ph ^= 1; }
  }
  if (w4 == 0 && lane == 0) {
    bulk_wait_all();
    fence_async_all();
    flag_add(FLAG_LM((h * 2 + cb) * 2 + (wg >> 1)));
    if (wg == 0) TS(1, 8);
  }
}

#define STAGE(s) (sb + (2 - (s)) * 65536)
template <int TR> __device__ __forceinline__ void proj_kb(float* acc, uint32_t st, uint32_t offA, uint32_t offB, int first) {
  const uint64_t da = make_desc(st + offA, TR ? 8192 : 16, 1024, 1);
  const uint64_t db = make_desc(st + offB, TR ? 16 : 8192, 1024, 1);
  wg_fence();
#pragma unroll
  for (int k = 0; k < 4; k++) wg_ss128<TR, 1 - TR>(acc, da + k * (TR ? 128 : 2), db + k * (TR ? 2 : 128), k != 0 || !first);
  wg_commit();
}
template <int TR> __device__ __forceinline__ void proj_loop(float* acc, uint32_t sb, uint32_t bars, uint32_t offA, uint32_t offB,
                                                            int wg, uint32_t sWKV) {
  {
    float kv[4];
    if (threadIdx.x == 0) TS(0, 13);
    mbar_wait(BAR_XA(wg), 0);
    if (threadIdx.x == 0) TS(0, 1);
    const uint64_t da = make_desc(STAGE(2) + wg * 16384, 16, 1024, 1), db = make_desc(sWKV + wg * 2048, 128, 128, 0);
    wg_fence();
#pragma unroll
    for (int k = 0; k < 8; k++) wg_ss8<0, 1>(kv, da + (k >> 2) * 512 + (k & 3) * 2, db + k * 16, k != 0);
    wg_commit();
    wg_wait<0>();
    fence_regs<4>(kv);
    named_bar(wg + 1, 128);
    sts4(sWKV + threadIdx.x * 16, __float_as_uint(kv[0]), __float_as_uint(kv[1]), __float_as_uint(kv[2]), __float_as_uint(kv[3]));
    __syncwarp();
    if ((threadIdx.x & 31) == 0) mbar_arrive(BAR_GO);
  }
  int s = 0, ph = 0, sp = 0;
#pragma unroll 1
  for (int kb = 0; kb < 8; kb++) {
    mbar_wait(BAR_FULL(s), ph);
    if (threadIdx.x == 0) TS(0, 2 + kb);
    proj_kb<TR>(acc, STAGE(s), offA, offB, kb == 0);
    wg_wait<1>();
    if (kb >= 1 && (threadIdx.x & 127) == 0) mbar_arrive(BAR_EMPTY(sp));
    __syncwarp();
    sp = s;
    if (++s == 3) { s = 0; ph ^= 1; }
  }
  wg_wait<0>();
  fence_regs<64>(acc);
}

__device__ __forceinline__ uint32_t tail_slots(int t) {
  const uint32_t lo = t < 4 ? (t < 2 ? (t == 0 ? 0x0C0B0Au : 0x0F0E0Du) : (t == 2 ? 0x100400u : 0x081814u))
                            : (t < 6 ? (t == 4 ? 0x110501u : 0x021915u) : (t == 6 ? 0x161206u : (t == 7 ? 0x07031Au : 0x1B1713u)));
  return lo;
}

__device__ __forceinline__ void take_role(uint32_t sM, int wg) {
  uint32_t r;
  asm volatile("atom.shared.add.u32 %0, [%1], 1;" : "=r"(r) : "r"(sM + 20) : "memory");
  sts1(sM + 32 + wg * 4, r);
}

__global__ void __launch_bounds__(640, 1)
k1_main(const __grid_constant__ CUtensorMap mXA64, const __grid_constant__ CUtensorMap mXB,
        const __grid_constant__ CUtensorMap mWq, const __grid_constant__ CUtensorMap mWqkv,
        const __grid_constant__ CUtensorMap mQst, const __grid_constant__ CUtensorMap mOst,
        const __grid_constant__ CUtensorMap mO, const __grid_constant__ CUtensorMap mWoA,
        const __grid_constant__ CUtensorMap mWoB, const __grid_constant__ CUtensorMap mOut,
        const __grid_constant__ CUtensorMap mO16, const Params prm) {
  extern __shared__ uint8_t smem_raw[];
  const uint32_t sb = (smem_u32(smem_raw) + 1023u) & ~1023u;
  const uint32_t bars = sb + OFF_MISC, sM = bars + 512, sT = bars + 1024;
  const int tid = threadIdx.x, warp = __shfl_sync(~0u, tid >> 5, 0), wg = warp >> 2, w4 = warp & 3, lane = tid & 31;
  const bool helper = blockIdx.x >= 128;
  if (tid == 0) TS(0, 0);
  const int G = blockIdx.x >> 4, gi = blockIdx.x & 15;
  const int tbA = G * 4 + (gi >> 2), hg = gi & 3;
  const int ttB = (G >> 1) * 4 + (gi >> 2), hq = (G & 1) * 4 + (gi & 3);
  const int ttO = G * 2 + (gi >> 3), ct = gi & 7;
  auto issue = [&](int kb, int s) {
    const uint32_t fb = BAR_FULL(s), st = STAGE(s);
    mbar_expect_tx(fb, 65536);
    tma2d(st + 16384, &mXA64, kb * 64, tbA * 64, fb);
    tma2d(st, &mWq, hg * 128, kb * 64, fb);
    tma2d(st + 8192, &mWq, hg * 128 + 64, kb * 64, fb);
    tma2d(st + 49152, &mXB, kb * 64, ttB * 128, fb);
    tma2d(st + 24576, &mWqkv, hq * 64, kb * 64, fb);
    tma2d(st + 32768, &mWqkv, 512 + hq * 64, kb * 64, fb);
    tma2d(st + 40960, &mWqkv, 1024 + hq * 64, kb * 64, fb);
  };
  const uint32_t sOne = sb + OFF_V + 65536, sWKV = sOne + 24576;
  if (warp >= 16) {
    if (warp == 17) {
      if (elect_one()) {
        mbar_init(BAR_BDONE, 8); mbar_init(BAR_Q, 8); mbar_init(BAR_GO, helper ? 1 : 16); mbar_init(BAR_Q2, 5);
        mbar_init(BAR_OD(0), 16); mbar_init(BAR_OD(1), 16); mbar_init(BAR_CL(0), 1); mbar_init(BAR_FULL(2), 1);
#pragma unroll
        for (int i = 0; i < 4; i++) mbar_init(BAR_CL(i + 1), i == 0 ? 5 : 4);
#pragma unroll
        for (int i = 0; i < 3; i++) { mbar_init(BAR_EMPTY(i), 4); mbar_init(BAR_KV(i), 1); mbar_init(BAR_VB(i), 1); }
        sts1(sM + 20, 0);
        asm volatile("fence.mbarrier_init.release.cluster;" ::: "memory");
      }
    } else if (warp == 18) {
      if (elect_one()) {
#pragma unroll
        for (int i = 0; i < 7; i++) mbar_init(BAR_TE(i), 1);
#pragma unroll
        for (int i = 0; i < 16; i++) mbar_init(BAR_TF(i), 1);
        asm volatile("fence.mbarrier_init.release.cluster;" ::: "memory");
      }
    } else if (warp == 16 && !helper && elect_one()) {
#pragma unroll
      for (int w = 0; w < 4; w++) mbar_init(BAR_XA(w), 1);
      mbar_init(BAR_FULL(0), 1); mbar_init(BAR_FULL(1), 1);
      asm volatile("fence.mbarrier_init.release.cluster;" ::: "memory");
#pragma unroll
      for (int w = 0; w < 4; w++) {
        mbar_expect_tx(BAR_XA(w), 16384);
        tma2d(STAGE(2) + w * 16384, &mXA64, w * 128, tbA * 64, BAR_XA(w));
        tma2d(STAGE(2) + w * 16384 + 8192, &mXA64, w * 128 + 64, tbA * 64, BAR_XA(w));
      }
      TS(0, 14);
      issue(0, 0);
    }
  } else if (!helper) {
    const uint4 v = __ldg((const uint4*)(hg >= 2 ? prm.wv : prm.wk) + tid * 2 + (hg & 1));
#pragma unroll
    for (int i = 0; i < 3; i++) {
      const int key = tid + i * 512;
      sts4(sOne + key * 16, (key % STEPK) < 32 ? 0x00003F80u : 0x00004E80u, 0u, 0u, 0u);
    }
    sts4(sWKV + tid * 16, v.x, v.y, v.z, v.w);
    fence_async();
  }
  __syncthreads();
  if (wg == 4) {
    if (w4 == 0 && !helper && elect_one()) { issue(1, 1); TS(0, 15); }
    asm volatile("setmaxnreg.dec.sync.aligned.u32 32;");
    const uint32_t ep = g_epoch[blockIdx.x] + 1;
    if (helper) {
      if (w4 == 0 && elect_one()) {
        flag_wait(FLAG_B(blockIdx.x - 128), ep * 32);
        fence_async_all();
        TS(1, 10);
        mbar_arrive(BAR_GO);
        g_epoch[blockIdx.x] = ep;
      }
      return;
    }
    mbar_wait(BAR_GO, 0);
    if (w4 == 0 && elect_one()) issue(2, 2);
    {
      uint32_t a[4], b[4];
      float c[4];
      lds4(sWKV + (tid - 512) * 16, a);
      lds4(sWKV + 2048 + (tid - 512) * 16, b);
#pragma unroll
      for (int i = 0; i < 4; i++) c[i] = __uint_as_float(a[i]) + __uint_as_float(b[i]);
      lds4(sWKV + 4096 + (tid - 512) * 16, a);
      lds4(sWKV + 6144 + (tid - 512) * 16, b);
#pragma unroll
      for (int i = 0; i < 4; i++) c[i] += __uint_as_float(a[i]) + __uint_as_float(b[i]);
      sts1(sT + w4 * 256 + lane * 4, pack_bf16(c[0], c[1]));
      sts1(sT + w4 * 256 + 128 + lane * 4, pack_bf16(c[2], c[3]));
    }
    named_bar(9, 128);
    {
      const int t = tid - 512;
#pragma unroll
      for (int i = 0; i < 4; i++) {
        const int key = 1536 + t + i * 128;
        sts4(sOne + key * 16, (key % STEPK) < 32 ? 0x00003F80u : 0x00004E80u, 0u, 0u, 0u);
      }
      fence_async();
      __syncwarp();
      if (lane == 0) mbar_arrive(BAR_Q);
    }
    if (w4 == 0) {
      int s = 0, ph = 0;
#pragma unroll 1
      for (int kb = 3; kb < 8; kb++) {
        mbar_wait(BAR_EMPTY(s), ph);
        if (elect_one()) issue(kb, s);
        if (++s == 3) { s = 0; ph ^= 1; }
      }
      flag_wait(FLAG_KV, ep * 128);
      fence_async_all();
      if (lane == 0) TS(0, 11);
#pragma unroll 1
      for (int m = 0; m < 2; m++) {
        mbar_wait(m == 0 ? BAR_EMPTY(2) : BAR_EMPTY(0), 1 - m);
        if (elect_one()) {
#pragma unroll
          for (int c = 0; c < 3; c++) {
            const int k0 = c == 0 ? 0 : (c == 1 ? 7 * STEPK : 12 * STEPK), k1 = c == 0 ? 7 * STEPK : (c == 1 ? 12 * STEPK : S_TOK);
            const uint32_t bytes = (k1 - k0) * 16, fb = m == 0 ? BAR_KV(c) : BAR_VB(c);
            mbar_expect_tx(fb, 2 * bytes);
#pragma unroll
            for (int p = 0; p < 2; p++)
              bulk_g2s(sb + m * OFF_V + p * 32768 + k0 * 16, g_KV + (m * 2 + p) * S_TOK + k0, bytes, fb);
          }
        }
      }
      mbar_wait(BAR_CL(1), 0);
      flag_wait(FLAG_LM((lane & 7) * 2 + (ttO >> 3)), ep);
      __syncwarp();
      fence_async_all();
      if (lane == 0) TS(2, 13);
#pragma unroll 1
      for (int n = 0; n < 8; n++) {
        mbar_wait(BAR_CL(n < 4 ? n >> 1 : (n == 4 ? 2 : (n < 7 ? 3 : 4))), 0);
        const uint32_t sl = tail_slots(n), fb = BAR_TF(n);
        if (elect_one()) {
          mbar_expect_tx(fb, 24576);
          tma2d(sb + (sl & 255) * 8192, &mWoB, ct * 64, n * 64, fb);
          tma2d(sb + ((sl >> 8) & 255) * 8192, &mO, n * 64, S_TOK + ttO * 128, fb);
          tma2d(sb + (sl >> 16) * 8192, &mO, n * 64, S_TOK + ttO * 128 + 64, fb);
        }
      }
      if (lane == 0) g_epoch[blockIdx.x] = ep;
    } else if (w4 == 3) {
      flag_wait(FLAG_KV, ep * 128);
      const uint4 a = *(const uint4*)(g_stats + lane * 4);
      const float kmax2 = __uint_as_float(__reduce_max_sync(~0u, a.x)) + __uint_as_float(__reduce_max_sync(~0u, a.y));
      const float vmax = __uint_as_float(__reduce_max_sync(~0u, max(a.z, a.w)));
      const float lv = vmax > 0.f ? __log2f(vmax) : 0.f;
      const float lim = fminf(90.f, fminf(91.f + lv, 95.f - lv));
      float thr = -1.f;
      if (vmax < 1e27f && kmax2 <= 65536.f && lim > 2.f) thr = fminf(60000.f, (lim * lim - 1.f) / (kmax2 * 1.02f + 1e-30f));
      if (lane == 0) { sts1(sM + 16, __float_as_uint(thr)); mbar_arrive(BAR_Q2); }
      mbar_wait(BAR_CL(3), 0);
      flag_wait(FLAG_OA(ttO * 8 + (lane & 7), 0), ep);
      __syncwarp();
      fence_async_all();
#pragma unroll 1
      for (int n = 0; n < 4; n++) {
        mbar_wait(BAR_TE(n), 0);
        const uint32_t sl = tail_slots(n), fb = BAR_TF(n + 9);
        if (elect_one()) {
          mbar_expect_tx(fb, 24576);
          tma2d(sb + ((sl >> 8) & 255) * 8192, &mO, n * 128, ttO * 128, fb);
          tma2d(sb + (sl >> 16) * 8192, &mO, n * 128, ttO * 128 + 64, fb);
          tma2d(sb + (sl & 255) * 8192, &mWoA, ct * 64, n * 128, fb);
        }
      }
    } else {
      const int ch = tbA * 2 + (w4 - 1);
      uint32_t v[4], o[4];
      lds4(sT + (w4 - 1) * 512 + lane * 16, v);
      int kap;
      if (lane < 21) kap = lane * STEPK + 32 + ch;
      else { int idx = ch * 11 + (lane - 21); kap = (idx >> 5) * STEPK + (idx & 31); }
      g_KV[(4 + hg) * S_TOK + kap] = make_uint4(v[0], v[1], v[2], v[3]);
      float st = 0.f;
      if (hg < 2) {
        const float sc = lane < 21 ? 2.f : 1.f;
#pragma unroll
        for (int u = 0; u < 4; u++) {
          uint32_t pv = __shfl_up_sync(~0u, v[u], 1);
          if (lane == 0 || lane >= 21) pv = 0;
          const float x = bf_lo(v[u]), y = bf_hi(v[u]);
          st += x * x + y * y;
          o[u] = pack_f16((x - bf_lo(pv)) * sc, (y - bf_hi(pv)) * sc);
        }
      } else {
        const float sc = lane < 21 ? VSHIFT : 1.f;
#pragma unroll
        for (int u = 0; u < 4; u++) { float x = bf_lo(v[u]), y = bf_hi(v[u]); st += fabsf(x) + fabsf(y); o[u] = pack_bf16(x * sc, y * sc); }
      }
      g_KV[hg * S_TOK + kap] = make_uint4(o[0], o[1], o[2], o[3]);
      const uint32_t um = __reduce_max_sync(~0u, __float_as_uint(st) & 0x7FFFFFFFu);
      if (w4 == 2) {
        if (lane == 0) sts1(sM + 24, um);
        named_arrive(10, 64);
        uint32_t pend = 0xF, rdy = 0;
#pragma unroll 1
        for (int n = 0; n < 4; n++) {
          mbar_wait(n == 0 ? BAR_CL(4) : BAR_TE(n + 3), 0);
          rdy &= pend;
#pragma unroll 1
          for (int it = 0; !rdy; it++) {
            uint32_t fv;
            asm volatile("ld.acquire.gpu.global.u32 %0, [%1];" : "=r"(fv) : "l"(FLAG_OA(ttO * 8 + (lane & 7), 1)) : "memory");
            const uint32_t b = __ballot_sync(~0u, (int32_t)(fv - ep) >= 0);
            rdy = b & (b >> 4) & pend;
            if (it > 2000000) __trap();
          }
          const int hsel = __ffs(rdy) - 1;
          pend &= ~(1u << hsel);
          if (lane == 0 && n == 3) TS(2, 14);
          fence_async_all();
          const uint32_t sl = tail_slots(n == 0 ? 8 : n + 3), fb = BAR_TF(n == 0 ? 8 : n + 12);
          if (elect_one()) {
            mbar_expect_tx(fb, 24576);
            tma2d(sb + ((sl >> 8) & 255) * 8192, &mO, hsel * 128 + 64, ttO * 128, fb);
            tma2d(sb + (sl >> 16) * 8192, &mO, hsel * 128 + 64, ttO * 128 + 64, fb);
            tma2d(sb + (sl & 255) * 8192, &mWoA, ct * 64, hsel * 128 + 64, fb);
          }
        }
      }
      else {
        named_bar(10, 64);
        if (elect_one()) {
          g_stats[tbA * 4 + hg] = max(um, lds1(sM + 24));
          fence_async_all();
          flag_add(FLAG_KV);
          TS(1, 9);
          mbar_wait(BAR_BDONE, 0);
          tma2d_store(&mQst, sb + OFF_F + 49152, hq * 64, S_TOK + ttB * 128);
          bulk_commit();
          bulk_wait_all();
          fence_async_all();
          flag_add(FLAG_B(hq >> 1));
          TS(0, 12);
          mbar_wait(BAR_Q, 0);
          mbar_arrive(BAR_CL(0));
#pragma unroll 1
          for (int p = 0; p < 2; p++) {
            mbar_wait(BAR_OD(p), 0);
#pragma unroll
            for (int w = 0; w < 4; w++) tma2d_store(&mO16, sb + OFF_F + (p * 4 + w) * 2048, hg * 128 + p * 64 + w * 16, tbA * 64);
            bulk_commit();
            bulk_wait_all();
            if (p == 0) mbar_arrive(BAR_CL(1));
            PUBLISH(FLAG_OA(blockIdx.x, p));
          }
          TS(2, 0);
        }
      }
    }
    return;
  }
  if (helper) { helper_cta(blockIdx.x - 128, sb, bars, wg, w4, &mQst, &mOst); return; }

  {
    float acc[64];
    if (wg == 0) proj_loop<0>(acc, sb, bars, 16384, 0, wg, sWKV);
    else proj_loop<1>(acc, sb, bars, 16384 + wg * 8192, 49152, wg, sWKV);
    asm volatile("setmaxnreg.inc.sync.aligned.u32 112;");
    if (tid == 0) TS(0, 10);
    const uint32_t sF = sb + OFF_F;
    if (wg == 0) {
      uint32_t r[32];
      const uint32_t qa = sF + w4 * 512 + ((lane >> 3) & 1) * 256 + (lane >> 4) * 128 + (lane & 7) * 16;
#pragma unroll
      for (int hd = 0; hd < 8; hd++) {
#pragma unroll
        for (int i = 0; i < 4; i++) r[4 * hd + i] = pack_f16(acc[8 * hd + 2 * i] * QSCALE, acc[8 * hd + 2 * i + 1] * QSCALE);
        stsm4(qa + hd * 2048, r[4 * hd], r[4 * hd + 1], r[4 * hd + 2], r[4 * hd + 3]);
        if (hd == 3) {
          fence_async();
          __syncwarp();
          if (lane == 0) mbar_arrive(BAR_Q);
        }
      }
      fence_async();
      uint32_t nmax = 0;
#pragma unroll
      for (int hd = 0; hd < 8; hd++) {
        const uint32_t* q = r + 4 * hd;
        const uint32_t t0 = hfma2(q[2], q[2], hfma2(q[0], q[0], 0u)), t1 = hfma2(q[3], q[3], hfma2(q[1], q[1], 0u));
        uint32_t n = hadd2(__byte_perm(t0, t1, 0x5410), __byte_perm(t0, t1, 0x7632));
        n = hadd2(n, __shfl_xor_sync(~0u, n, 1));
        n = hadd2(n, __shfl_xor_sync(~0u, n, 2));
        nmax = __vmaxu2(nmax, n & 0x7FFF7FFFu);
      }
      nmax = __reduce_max_sync(~0u, max(nmax & 0xFFFFu, nmax >> 16));
      if (lane == 0) sts1(sM + w4 * 4, nmax);
      uint4* gq = (uint4*)g_Q + blockIdx.x * 1024 + tid;
#pragma unroll
      for (int hd = 0; hd < 8; hd++)
        gq[hd * 128] = make_uint4(pack_bf16(acc[8 * hd], acc[8 * hd + 1]), pack_bf16(acc[8 * hd + 2], acc[8 * hd + 3]),
                                  pack_bf16(acc[8 * hd + 4], acc[8 * hd + 5]), pack_bf16(acc[8 * hd + 6], acc[8 * hd + 7]));
      __syncwarp();
      if (lane == 0) mbar_arrive(BAR_Q2);
    } else if (wg == 3) {
      named_arrive(8, 384);
      named_bar(6, 384);
      const int t = tid & 127;
#pragma unroll
      for (int j = 0; j < 8; j++)
        sts4(sF + 24576 + j * 2048 + t * 16, pack_bf16(acc[8 * j], acc[8 * j + 1]), pack_bf16(acc[8 * j + 2], acc[8 * j + 3]),
             pack_bf16(acc[8 * j + 4], acc[8 * j + 5]), pack_bf16(acc[8 * j + 6], acc[8 * j + 7]));
      named_arrive(7, 256);
    } else {
      uint32_t p[32];
      named_arrive(6, 384);
      if (wg == 2) named_arrive(8, 384);
#pragma unroll
      for (int i = 0; i < 32; i++) p[i] = phi2(acc[2 * i], acc[2 * i + 1]);
      if (wg == 1) {
        named_bar(8, 384);
        const int m = lane >> 3, r = lane & 7;
#pragma unroll
        for (int j = 0; j < 16; j += 2) {
          const int tok = (j + (m >> 1)) * 8 + r;
          const int chunk = w4 * 2 + (m & 1);
          stsm4t(sF + 49152 + tok * 128 + ((chunk ^ r) << 4), p[2 * j], p[2 * j + 1], p[2 * j + 2], p[2 * j + 3]);
        }
        fence_async();
      } else {
        named_bar(7, 256);
        float kv0[4] = {0, 0, 0, 0}, kv1[4] = {0, 0, 0, 0}, z0[4] = {0, 0, 0, 0}, z1[4] = {0, 0, 0, 0};
        const uint32_t one = 0x3F803F80u;
        const int t = tid & 127;
#pragma unroll
        for (int j = 0; j < 8; j++) {
          uint32_t a[4];
          lds4(sF + 24576 + j * 2048 + t * 16, a);
          mma_bf16(kv0, a[0], a[1], a[2], a[3], p[4 * j], p[4 * j + 2]);
          mma_bf16(kv1, a[0], a[1], a[2], a[3], p[4 * j + 1], p[4 * j + 3]);
          mma_bf16(z0, one, one, one, one, p[4 * j], p[4 * j + 2]);
          mma_bf16(z1, one, one, one, one, p[4 * j + 1], p[4 * j + 3]);
        }
        float4* dst = g_kvp + ((ttB * 32 + hq * 4 + w4) * 3) * 32 + lane;
        dst[0] = make_float4(kv0[0], kv0[1], kv1[0], kv1[1]);
        dst[32] = make_float4(kv0[2], kv0[3], kv1[2], kv1[3]);
        dst[64] = make_float4(z0[0], z0[1], z1[0], z1[1]);
      }
      __syncwarp();
      if (lane == 0) mbar_arrive(BAR_BDONE);
    }
  }

  mbar_wait(BAR_Q, 0);
  if (tid == 0) TS(1, 1);
  bool safe = true;
  {
    const uint32_t c63 = 0x1F801F80u + (threadIdx.x >> 20);
    const uint32_t m1 = (gridDim.x >> 20) - 1u;
    const uint64_t dK0 = make_desc(sb + OFF_K, 32768, 128, 0);
    const uint64_t dV0 = make_desc(sb + OFF_V, 128, 32768, 0);
    constexpr uint32_t dKV = ((2048u - 8u)  __H0__ ) + STEPK - (OFF_V - OFF_K) / 16;
    mbar_wait(BAR_KV(0), 0);
#pragma unroll 1
    for (int pass = 0; pass < 2; pass++) {
      const uint64_t dQ = make_desc(sb + OFF_F + (pass * 4 + wg) * 2048, 128, 256, 0);
      float Sm[16], Sp[32], O[12];
      uint32_t P[24];
#pragma unroll
      for (int i = 0; i < 32; i++) Sp[i] = SMAGIC;
#pragma unroll
      for (int i = 0; i < 16; i++) Sm[i] = 0.f;
#pragma unroll
      for (int i = 0; i < 12; i++) O[i] = 0.f;
      fence_regs<16>(Sm); fence_regs<32>(Sp); fence_regs<12>(O);
      if (tid == 0) TS(1, 2 + 2 * pass);
      wg_fence();
      wg_qs32<0>(Sm, dQ, dK0);
      wg_qs64<1>(Sp, dQ, dK0 + 32);
      wg_commit();
      wg_wait<0>();
      fence_regs<16>(Sm); fence_regs<32>(Sp);
      uint32_t vlo = (uint32_t)dV0;
#pragma unroll 1
      for (int seg = 0; seg < 4; seg++) {
        if (pass == 0) {
          if (seg < 3) { mbar_wait(BAR_KV(seg), 0); mbar_wait(BAR_VB(seg), 0); }
        } else if (seg >= 1) {
          if ((tid & 127) == 0) {
            mbar_arrive(BAR_CL(seg));
            if (seg == 3) take_role(sM, wg);
          }
          __syncwarp();
        }
        if ((tid & 127) == 0) TS(4 + wg, pass * 5 + seg);
        const uint32_t vend = vlo + (seg == 0 ? 6 : 5) * STEPK;
#pragma unroll 1
        for (; vlo != vend; vlo += STEPK) {
          uint64_t dK, dV;
          asm("mov.b64 %0, {%1, %2};" : "=l"(dK) : "r"(vlo + dKV), "r"(8u));
          asm("mov.b64 %0, {%1, %2};" : "=l"(dV) : "r"(vlo), "r"(2048u));
#pragma unroll
          for (int i = 0; i < 8; i++) P[i] = pack_bf16(ex2f(Sm[2 * i]), ex2f(Sm[2 * i + 1]));
#pragma unroll
          for (int i = 0; i < 16; i++) P[8 + i] = exp2_pair_fix(Sp[2 * i], Sp[2 * i + 1], c63, m1);
          fence_regs<24>(P);
          wg_fence();
#pragma unroll
          for (int k = 0; k < 6; k++) wg_pv24<1>(O, &P[4 * k], dV + k * 16);
          wg_qs64<1>(Sp, dQ, dK + 32);
          wg_qs32<0>(Sm, dQ, dK);
          wg_commit();
          wg_wait<0>();
          fence_regs<16>(Sm); fence_regs<32>(Sp); fence_regs<12>(O); fence_regs<24>(P);
        }
      }
#pragma unroll
      for (int i = 0; i < 8; i++) P[i] = pack_bf16(ex2f(Sm[2 * i]), ex2f(Sm[2 * i + 1]));
      fence_regs<8>(P);
      wg_fence();
      wg_pv24<1>(O, &P[0], dV0 + 21 * STEPK);
      wg_pv24<1>(O, &P[4], dV0 + 21 * STEPK + 16);
      wg_commit();
      wg_wait<0>();
      fence_regs<12>(O);
      if (pass == 0) {
        uint32_t n[4];
        mbar_wait(BAR_Q2, 0);
        lds4(sM, n);
        const float qn = __half2float(__ushort_as_half((unsigned short)max(max(n[0], n[1]), max(n[2], n[3]))));
        safe = __all_sync(~0u, qn <= __uint_as_float(lds1(sM + 16)));
        if (!safe) break;
      }
      const float l0 = __shfl_sync(~0u, O[8], lane & ~3), l1 = __shfl_sync(~0u, O[10], lane & ~3);
      const float i0 = rcpf(l0), i1 = rcpf(l1);
      stsm4(sb + OFF_F + (pass * 4 + wg) * 2048 + w4 * 512 + (lane & 15) * 32 + (lane >> 4) * 16,
            pack_bf16(O[0] * i0, O[1] * i0), pack_bf16(O[2] * i1, O[3] * i1),
            pack_bf16(O[4] * i0, O[5] * i0), pack_bf16(O[6] * i1, O[7] * i1));
      fence_async();
      __syncwarp();
      if (lane == 0) mbar_arrive(BAR_OD(pass));
      if ((tid & 127) == 0) TS(4 + wg, pass * 5 + 4);
      if (tid == 0) TS(1, 3 + 2 * pass);
      if ((tid & 127) == 0 && pass == 1 && wg > 0) TS(1, 10 + wg);
    }
  }

  if (!safe) {
    if ((tid & 127) == 0) { mbar_arrive(BAR_CL(1)); mbar_arrive(BAR_CL(2)); mbar_arrive(BAR_CL(3)); take_role(sM, wg); }
#pragma unroll 1
    for (int pass = 0; pass < 2; pass++) {
      attn_slow((const uint4*)g_Q + blockIdx.x * 1024 + (pass * 4 + wg) * 128, sb + OFF_F + (pass * 4 + wg) * 2048);
      __syncwarp();
      if (lane == 0) mbar_arrive(BAR_OD(pass));
    }
  }

  {
    named_bar(wg + 1, 128);
    if ((tid & 127) == 0) mbar_arrive(BAR_CL(4));
    const int role = __shfl_sync(~0u, lds1(sM + 32 + wg * 4), 0);
    if ((tid & 127) == 0) TS(4 + wg, 10);
    const int m = lane >> 3, r = lane & 7;
    const uint32_t stoff = (w4 * 16 + (m & 1) * 8 + r) * 128;
    if (role == 0) {
      float acc0[32], acc1[32];
      uint32_t sl = 0;
#pragma unroll 1
      for (int n = 0; n < 8; n++) {
        sl = tail_slots(n);
        const uint64_t da0 = make_desc(sb + ((sl >> 8) & 255) * 8192, 16, 1024, 1), da1 = make_desc(sb + (sl >> 16) * 8192, 16, 1024, 1);
        const uint64_t db = make_desc(sb + (sl & 255) * 8192, 8192, 1024, 1);
        mbar_wait(BAR_TF(n), 0);
        wg_fence();
#pragma unroll
        for (int k = 0; k < 4; k++) {
          wg_ss64<0, 1>(acc0, da0 + k * 2, db + k * 128, (n | k) != 0);
          wg_ss64<0, 1>(acc1, da1 + k * 2, db + k * 128, (n | k) != 0);
        }
        wg_commit();
        wg_wait<0>();
        if (n < 7 && (tid & 127) == 0) mbar_arrive(BAR_TE(n));
        __syncwarp();
      }
      fence_regs<32>(acc0); fence_regs<32>(acc1);
      if ((tid & 127) == 0) TS(4 + wg, 11);
      const uint32_t x0 = sb + ((sl >> 8) & 255) * 8192, x1 = sb + (sl >> 16) * 8192;
#pragma unroll
      for (int j = 0; j < 8; j += 2) {
        const uint32_t o = stoff + (((j + (m >> 1)) ^ r) << 4);
        stsm4(x0 + o, pack_bf16(acc0[4 * j], acc0[4 * j + 1]), pack_bf16(acc0[4 * j + 2], acc0[4 * j + 3]),
              pack_bf16(acc0[4 * j + 4], acc0[4 * j + 5]), pack_bf16(acc0[4 * j + 6], acc0[4 * j + 7]));
        stsm4(x1 + o, pack_bf16(acc1[4 * j], acc1[4 * j + 1]), pack_bf16(acc1[4 * j + 2], acc1[4 * j + 3]),
              pack_bf16(acc1[4 * j + 4], acc1[4 * j + 5]), pack_bf16(acc1[4 * j + 6], acc1[4 * j + 7]));
      }
      fence_async();
      named_bar(wg + 1, 128);
      if (w4 == 0 && elect_one()) {
        tma2d_store(&mOut, x0, 512 + ct * 64, ttO * 128);
        tma2d_store(&mOut, x1, 512 + ct * 64, ttO * 128 + 64);
        bulk_commit();
        asm volatile("cp.async.bulk.wait_group.read 0;" ::: "memory");
        TS(2, 11);
      }
    } else if (role < 3) {
      const int hf = role - 1;
      float acc[32];
      uint32_t xs = 0;
#pragma unroll 1
      for (int n = 0; n < 8; n++) {
        const int gidx = n < 4 ? n + 9 : (n == 4 ? 8 : n + 8);
        const uint32_t sl = tail_slots(n == 4 ? 8 : gidx - 9);
        xs = sb + ((sl >> (8 + 8 * hf)) & 255) * 8192;
        const uint64_t da = make_desc(xs, 16, 1024, 1), db = make_desc(sb + (sl & 255) * 8192, 8192, 1024, 1);
        mbar_wait(BAR_TF(gidx), 0);
        if ((tid & 127) == 0 && role == 2) TS(2, 2 + n);
        wg_fence();
#pragma unroll
        for (int k = 0; k < 4; k++) wg_ss64<0, 1>(acc, da + k * 2, db + k * 128, (n | k) != 0);
        wg_commit();
      }
      wg_wait<0>();
      fence_regs<32>(acc);
      if ((tid & 127) == 0) TS(4 + wg, 11);
#pragma unroll
      for (int j = 0; j < 8; j += 2)
        stsm4(xs + stoff + (((j + (m >> 1)) ^ r) << 4),
              pack_bf16(acc[4 * j], acc[4 * j + 1]), pack_bf16(acc[4 * j + 2], acc[4 * j + 3]),
              pack_bf16(acc[4 * j + 4], acc[4 * j + 5]), pack_bf16(acc[4 * j + 6], acc[4 * j + 7]));
      fence_async();
      named_bar(wg + 1, 128);
      if (w4 == 0 && elect_one()) {
        tma2d_store(&mOut, xs, ct * 64, ttO * 128 + hf * 64);
        bulk_commit();
        asm volatile("cp.async.bulk.wait_group.read 0;" ::: "memory");
        TS(2, 12);
      }
    }
  }
}

typedef CUresult (*EncodeFn)(CUtensorMap*, CUtensorMapDataType, cuuint32_t, void*, const cuuint64_t*, const cuuint64_t*,
                             const cuuint32_t*, const cuuint32_t*, CUtensorMapInterleave, CUtensorMapSwizzle,
                             CUtensorMapL2promotion, CUtensorMapFloatOOBfill);

static void make_map(EncodeFn enc, CUtensorMap* m, const void* ptr, uint64_t cols, uint64_t rows, uint32_t bc, uint32_t br,
                     CUtensorMapSwizzle sw = CU_TENSOR_MAP_SWIZZLE_128B) {
  cuuint64_t dims[2] = {cols, rows};
  cuuint64_t strides[1] = {cols * 2};
  cuuint32_t box[2] = {bc, br};
  cuuint32_t es[2] = {1, 1};
  enc(m, CU_TENSOR_MAP_DATA_TYPE_BFLOAT16, 2, (void*)ptr, dims, strides, box, es, CU_TENSOR_MAP_INTERLEAVE_NONE,
      sw, CU_TENSOR_MAP_L2_PROMOTION_L2_256B, CU_TENSOR_MAP_FLOAT_OOB_FILL_NONE);
}

extern "C" void kernel_launch(void* const* d_in, const int* in_sizes, int n_in, void* d_out, int out_size) {
  (void)in_sizes; (void)n_in; (void)out_size;
  static EncodeFn enc = nullptr;
  static void* pQ = nullptr; static void* pO = nullptr;
  if (!enc) {
    void* fn = nullptr; cudaDriverEntryPointQueryResult qr;
    cudaGetDriverEntryPoint("cuTensorMapEncodeTiled", &fn, cudaEnableDefault, &qr);
    enc = (EncodeFn)fn;
    cudaGetSymbolAddress(&pQ, g_Q);
    cudaGetSymbolAddress(&pO, g_O);
    cudaFuncSetAttribute(k1_main, cudaFuncAttributeMaxDynamicSharedMemorySize, SM_TOTAL);
  }
  CUtensorMap mXA64, mXB, mWq, mWqkv, mQst, mO, mOst, mWoA, mWoB, mOut, mO16;
  make_map(enc, &mXA64, d_in[0], 512, 2048, 64, 64);
  make_map(enc, &mWq, d_in[1], 512, 512, 64, 64);
  make_map(enc, &mWoA, d_in[4], 512, 512, 64, 64);
  make_map(enc, &mXB, d_in[5], 512, 2048, 64, 128);
  make_map(enc, &mWqkv, d_in[6], 1536, 512, 64, 64);
  make_map(enc, &mWoB, d_in[7], 512, 512, 64, 64);
  make_map(enc, &mQst, pQ, 512, 4096, 64, 128);
  make_map(enc, &mO, pO, 512, 4096, 64, 64);
  make_map(enc, &mOst, pO, 512, 4096, 64, 128);
  make_map(enc, &mOut, d_out, 1024, 2048, 64, 64);
  make_map(enc, &mO16, pO, 512, 4096, 16, 64, CU_TENSOR_MAP_SWIZZLE_NONE);
  Params prm{(const __nv_bfloat16*)d_in[2], (const __nv_bfloat16*)d_in[3], (const __nv_bfloat16*)d_in[0]};
  k1_main<<<132, 640, SM_TOTAL, cudaStreamPerThread>>>(mXA64, mXB, mWq, mWqkv, mQst, mOst, mO, mWoA, mWoB, mOut, mO16, prm);
}
```

```cpp
#include <cuda_runtime.h>
#include <cuda_bf16.h>
#include <cuda_fp16.h>
#include <cuda.h>
#include <stdint.h>

#define S_TOK 2048
#define D_MOD 512

__device__ __align__(1024) __nv_bfloat16 g_Q[2 * S_TOK * D_MOD];
__device__ __align__(1024) __nv_bfloat16 g_O[2 * S_TOK * D_MOD];
__device__ __align__(1024) uint4 g_KV[8 * S_TOK];
__device__ __align__(16) uint32_t g_stats[128];
__device__ __align__(16) float4 g_kvp[16 * 32 * 3 * 32];

#define TS(k, i) do {} while (0)
__device__ __forceinline__ uint32_t smem_u32(const void* p) { return (uint32_t)__cvta_generic_to_shared(p); }
__device__ __forceinline__ void mbar_init(uint32_t bar, int cnt) { asm volatile("mbarrier.init.shared::cta.b64 [%0], %1;" :: "r"(bar), "r"(cnt) : "memory"); }
__device__ __forceinline__ void mbar_expect_tx(uint32_t bar, uint32_t bytes) { asm volatile("mbarrier.arrive.expect_tx.shared::cta.b64 _, [%0], %1;" :: "r"(bar), "r"(bytes) : "memory"); }
__device__ __forceinline__ bool mbar_try(uint32_t bar, uint32_t parity) {
  uint32_t ok;
  asm volatile("{\n.reg .pred p;\nmbarrier.try_wait.parity.shared::cta.b64 p, [%1], %2;\nselp.b32 %0, 1, 0, p;\n}\n" : "=r"(ok) : "r"(bar), "r"(parity) : "memory");
  return ok;
}
__device__ __forceinline__ void mbar_wait(uint32_t bar, uint32_t parity) {
  asm volatile("{\n.reg .pred p;\n.reg .u32 c;\nmov.u32 c, 0;\n"
               "LW_%=:\n"
               "mbarrier.try_wait.parity.shared::cta.b64 p, [%0], %1;\n"
               "@p bra LD_%=;\n"
               "add.u32 c, c, 1;\n"
               "setp.lt.u32 p, c, 4000000;\n"
               "@p bra LW_%=;\n"
               "trap;\n"
               "LD_%=:\n}\n" :: "r"(bar), "r"(parity) : "memory");
}
__device__ __forceinline__ void mbar_arrive_cta(uint32_t bar, uint32_t cta) {
  asm volatile("{\n.reg .b32 ra;\nmapa.shared::cluster.u32 ra, %0, %1;\nmbarrier.arrive.shared::cluster.b64 _, [ra];\n}\n" :: "r"(bar), "r"(cta) : "memory");
}
__device__ __forceinline__ void cluster_sync() {
  asm volatile("barrier.cluster.arrive.relaxed.aligned;\nbarrier.cluster.wait.aligned;" ::: "memory");
}
__device__ __forceinline__ void tma2d(uint32_t dst, const CUtensorMap* m, int c0, int c1, uint32_t bar) {
  asm volatile("cp.async.bulk.tensor.2d.shared::cluster.global.mbarrier::complete_tx::bytes [%0], [%1, {%3, %4}], [%2];"
               :: "r"(dst), "l"(m), "r"(bar), "r"(c0), "r"(c1) : "memory");
}
__device__ __forceinline__ void tma2d_mc(uint32_t dst, const CUtensorMap* m, int c0, int c1, uint32_t bar, uint16_t mask) {
  asm volatile("cp.async.bulk.tensor.2d.shared::cluster.global.mbarrier::complete_tx::bytes.multicast::cluster [%0], [%1, {%3, %4}], [%2], %5;"
               :: "r"(dst), "l"(m), "r"(bar), "r"(c0), "r"(c1), "h"(mask) : "memory");
}
__device__ __forceinline__ void tma2d_store(const CUtensorMap* m, uint32_t src, int c0, int c1) {
  asm volatile("cp.async.bulk.tensor.2d.global.shared::cta.bulk_group [%0, {%2, %3}], [%1];"
               :: "l"(m), "r"(src), "r"(c0), "r"(c1) : "memory");
}
__device__ __forceinline__ void bulk_g2s(uint32_t dst, const void* src, uint32_t bytes, uint32_t bar) {
  asm volatile("cp.async.bulk.shared::cluster.global.mbarrier::complete_tx::bytes [%0], [%1], %2, [%3];"
               :: "r"(dst), "l"(src), "r"(bytes), "r"(bar) : "memory");
}
__device__ __forceinline__ void bulk_commit() { asm volatile("cp.async.bulk.commit_group;" ::: "memory"); }
__device__ __forceinline__ void bulk_wait_all() { asm volatile("cp.async.bulk.wait_group 0;" ::: "memory"); }
__device__ __forceinline__ void fence_async() { asm volatile("fence.proxy.async.shared::cta;" ::: "memory"); }
__device__ __forceinline__ void named_bar(int id, int n) { asm volatile("bar.sync %0, %1;" :: "r"(id), "r"(n) : "memory"); }
__device__ __forceinline__ void pdl_launch() { asm volatile("griddepcontrol.launch_dependents;" ::: "memory"); }
__device__ __forceinline__ void pdl_wait() { asm volatile("griddepcontrol.wait;" ::: "memory"); }
__device__ __forceinline__ void wg_fence() { asm volatile("wgmma.fence.sync.aligned;" ::: "memory"); }
__device__ __forceinline__ void wg_commit() { asm volatile("wgmma.commit_group.sync.aligned;" ::: "memory"); }
template <int n> __device__ __forceinline__ void wg_wait() { asm volatile("wgmma.wait_group.sync.aligned %0;" :: "n"(n) : "memory"); }
template <int n> __device__ __forceinline__ void fence_regs(float* r) {
#pragma unroll
  for (int i = 0; i < n; i++) asm volatile("" : "+f"(r[i]) :: "memory");
}
template <int n> __device__ __forceinline__ void fence_regs(uint32_t* r) {
#pragma unroll
  for (int i = 0; i < n; i++) asm volatile("" : "+r"(r[i]) :: "memory");
}
__device__ __forceinline__ uint64_t make_desc(uint32_t addr, uint32_t lbo, uint32_t sbo, uint32_t swz) {
  return (uint64_t)((addr & 0x3FFFF) >> 4) | ((uint64_t)(lbo >> 4) << 16) | ((uint64_t)(sbo >> 4) << 32) | ((uint64_t)swz << 62);
}
__device__ __forceinline__ float ex2f(float x) { float y; asm("ex2.approx.ftz.f32 %0, %1;" : "=f"(y) : "f"(x)); return y; }
__device__ __forceinline__ uint32_t pack_bf16(float lo, float hi) { uint32_t r; asm("cvt.rn.bf16x2.f32 %0, %1, %2;" : "=r"(r) : "f"(hi), "f"(lo)); return r; }
__device__ __forceinline__ uint32_t pack_f16(float lo, float hi) { uint32_t r; asm("cvt.rn.f16x2.f32 %0, %1, %2;" : "=r"(r) : "f"(hi), "f"(lo)); return r; }
__device__ __forceinline__ float bf_lo(uint32_t v) { return __uint_as_float(v << 16); }
__device__ __forceinline__ float bf_hi(uint32_t v) { return __uint_as_float(v & 0xFFFF0000u); }
__device__ __forceinline__ float rbf(float x) { return __bfloat162float(__float2bfloat16_rn(x)); }
__device__ __forceinline__ void stsm4(uint32_t a, uint32_t r0, uint32_t r1, uint32_t r2, uint32_t r3) {
  asm volatile("stmatrix.sync.aligned.m8n8.x4.shared.b16 [%0], {%1,%2,%3,%4};" :: "r"(a), "r"(r0), "r"(r1), "r"(r2), "r"(r3) : "memory");
}
__device__ __forceinline__ void stsm4t(uint32_t a, uint32_t r0, uint32_t r1, uint32_t r2, uint32_t r3) {
  asm volatile("stmatrix.sync.aligned.m8n8.x4.trans.shared.b16 [%0], {%1,%2,%3,%4};" :: "r"(a), "r"(r0), "r"(r1), "r"(r2), "r"(r3) : "memory");
}
__device__ __forceinline__ void mma_bf16(float* d, uint32_t a0, uint32_t a1, uint32_t a2, uint32_t a3, uint32_t b0, uint32_t b1) {
  asm volatile("mma.sync.aligned.m16n8k16.row.col.f32.bf16.bf16.f32 {%0,%1,%2,%3}, {%4,%5,%6,%7}, {%8,%9}, {%0,%1,%2,%3};"
               : "+f"(d[0]), "+f"(d[1]), "+f"(d[2]), "+f"(d[3]) : "r"(a0), "r"(a1), "r"(a2), "r"(a3), "r"(b0), "r"(b1));
}
template<int SD> __device__ __forceinline__ void wg_qk32(float* d, const uint32_t* a, uint64_t desc) {
  asm volatile("wgmma.mma_async.sync.aligned.m64n32k16.f32.f16.f16 {%0,%1,%2,%3,%4,%5,%6,%7,%8,%9,%10,%11,%12,%13,%14,%15}, {%16,%17,%18,%19}, %20, %21, 1, 1, 0;"
   : "+f"(d[0]),"+f"(d[1]),"+f"(d[2]),"+f"(d[3]),"+f"(d[4]),"+f"(d[5]),"+f"(d[6]),"+f"(d[7]),"+f"(d[8]),"+f"(d[9]),"+f"(d[10]),"+f"(d[11]),"+f"(d[12]),"+f"(d[13]),"+f"(d[14]),"+f"(d[15])
   : "r"(a[0]),"r"(a[1]),"r"(a[2]),"r"(a[3]),"l"(desc),"n"(SD));
}
template<int SD> __device__ __forceinline__ void wg_qk64(float* d, const uint32_t* a, uint64_t desc) {
  asm volatile("wgmma.mma_async.sync.aligned.m64n64k16.f32.f16.f16 {%0,%1,%2,%3,%4,%5,%6,%7,%8,%9,%10,%11,%12,%13,%14,%15,%16,%17,%18,%19,%20,%21,%22,%23,%24,%25,%26,%27,%28,%29,%30,%31}, {%32,%33,%34,%35}, %36, %37, 1, 1, 0;"
   : "+f"(d[0]),"+f"(d[1]),"+f"(d[2]),"+f"(d[3]),"+f"(d[4]),"+f"(d[5]),"+f"(d[6]),"+f"(d[7]),"+f"(d[8]),"+f"(d[9]),"+f"(d[10]),"+f"(d[11]),"+f"(d[12]),"+f"(d[13]),"+f"(d[14]),"+f"(d[15]),"+f"(d[16]),"+f"(d[17]),"+f"(d[18]),"+f"(d[19]),"+f"(d[20]),"+f"(d[21]),"+f"(d[22]),"+f"(d[23]),"+f"(d[24]),"+f"(d[25]),"+f"(d[26]),"+f"(d[27]),"+f"(d[28]),"+f"(d[29]),"+f"(d[30]),"+f"(d[31])
   : "r"(a[0]),"r"(a[1]),"r"(a[2]),"r"(a[3]),"l"(desc),"n"(SD));
}
template<int SD> __device__ __forceinline__ void wg_qs32(float* d, uint64_t da, uint64_t db) {
  asm volatile("wgmma.mma_async.sync.aligned.m64n32k16.f32.f16.f16 {%0,%1,%2,%3,%4,%5,%6,%7,%8,%9,%10,%11,%12,%13,%14,%15}, %16, %17, %18, 1, 1, 0, 0;"
   : "+f"(d[0]),"+f"(d[1]),"+f"(d[2]),"+f"(d[3]),"+f"(d[4]),"+f"(d[5]),"+f"(d[6]),"+f"(d[7]),"+f"(d[8]),"+f"(d[9]),"+f"(d[10]),"+f"(d[11]),"+f"(d[12]),"+f"(d[13]),"+f"(d[14]),"+f"(d[15])
   : "l"(da),"l"(db),"n"(SD));
}
template<int SD> __device__ __forceinline__ void wg_qs64(float* d, uint64_t da, uint64_t db) {
  asm volatile("wgmma.mma_async.sync.aligned.m64n64k16.f32.f16.f16 {%0,%1,%2,%3,%4,%5,%6,%7,%8,%9,%10,%11,%12,%13,%14,%15,%16,%17,%18,%19,%20,%21,%22,%23,%24,%25,%26,%27,%28,%29,%30,%31}, %32, %33, %34, 1, 1, 0, 0;"
   : "+f"(d[0]),"+f"(d[1]),"+f"(d[2]),"+f"(d[3]),"+f"(d[4]),"+f"(d[5]),"+f"(d[6]),"+f"(d[7]),"+f"(d[8]),"+f"(d[9]),"+f"(d[10]),"+f"(d[11]),"+f"(d[12]),"+f"(d[13]),"+f"(d[14]),"+f"(d[15]),"+f"(d[16]),"+f"(d[17]),"+f"(d[18]),"+f"(d[19]),"+f"(d[20]),"+f"(d[21]),"+f"(d[22]),"+f"(d[23]),"+f"(d[24]),"+f"(d[25]),"+f"(d[26]),"+f"(d[27]),"+f"(d[28]),"+f"(d[29]),"+f"(d[30]),"+f"(d[31])
   : "l"(da),"l"(db),"n"(SD));
}
template<int SD> __device__ __forceinline__ void wg_pv24(float* d, const uint32_t* a, uint64_t desc) {
  asm volatile("wgmma.mma_async.sync.aligned.m64n24k16.f32.bf16.bf16 {%0,%1,%2,%3,%4,%5,%6,%7,%8,%9,%10,%11}, {%12,%13,%14,%15}, %16, %17, 1, 1, 1;"
   : "+f"(d[0]),"+f"(d[1]),"+f"(d[2]),"+f"(d[3]),"+f"(d[4]),"+f"(d[5]),"+f"(d[6]),"+f"(d[7]),"+f"(d[8]),"+f"(d[9]),"+f"(d[10]),"+f"(d[11])
   : "r"(a[0]),"r"(a[1]),"r"(a[2]),"r"(a[3]),"l"(desc),"n"(SD));
}
template<int TA, int TB> __device__ __forceinline__ void wg_ss128(float* d, uint64_t da, uint64_t db, int sd) {
  asm volatile("{\n.reg .pred p;\nsetp.ne.b32 p, %66, 0;\n"
   "wgmma.mma_async.sync.aligned.m64n128k16.f32.bf16.bf16 {%0,%1,%2,%3,%4,%5,%6,%7,%8,%9,%10,%11,%12,%13,%14,%15,%16,%17,%18,%19,%20,%21,%22,%23,%24,%25,%26,%27,%28,%29,%30,%31,%32,%33,%34,%35,%36,%37,%38,%39,%40,%41,%42,%43,%44,%45,%46,%47,%48,%49,%50,%51,%52,%53,%54,%55,%56,%57,%58,%59,%60,%61,%62,%63}, %64, %65, p, 1, 1, %67, %68;\n}\n"
   : "+f"(d[0]),"+f"(d[1]),"+f"(d[2]),"+f"(d[3]),"+f"(d[4]),"+f"(d[5]),"+f"(d[6]),"+f"(d[7]),"+f"(d[8]),"+f"(d[9]),"+f"(d[10]),"+f"(d[11]),"+f"(d[12]),"+f"(d[13]),"+f"(d[14]),"+f"(d[15]),"+f"(d[16]),"+f"(d[17]),"+f"(d[18]),"+f"(d[19]),"+f"(d[20]),"+f"(d[21]),"+f"(d[22]),"+f"(d[23]),"+f"(d[24]),"+f"(d[25]),"+f"(d[26]),"+f"(d[27]),"+f"(d[28]),"+f"(d[29]),"+f"(d[30]),"+f"(d[31]),"+f"(d[32]),"+f"(d[33]),"+f"(d[34]),"+f"(d[35]),"+f"(d[36]),"+f"(d[37]),"+f"(d[38]),"+f"(d[39]),"+f"(d[40]),"+f"(d[41]),"+f"(d[42]),"+f"(d[43]),"+f"(d[44]),"+f"(d[45]),"+f"(d[46]),"+f"(d[47]),"+f"(d[48]),"+f"(d[49]),"+f"(d[50]),"+f"(d[51]),"+f"(d[52]),"+f"(d[53]),"+f"(d[54]),"+f"(d[55]),"+f"(d[56]),"+f"(d[57]),"+f"(d[58]),"+f"(d[59]),"+f"(d[60]),"+f"(d[61]),"+f"(d[62]),"+f"(d[63])
   : "l"(da),"l"(db),"r"(sd),"n"(TA),"n"(TB));
}
template<int TA, int TB> __device__ __forceinline__ void wg_ss64(float* d, uint64_t da, uint64_t db, int sd) {
  asm volatile("{\n.reg .pred p;\nsetp.ne.b32 p, %34, 0;\n"
   "wgmma.mma_async.sync.aligned.m64n64k16.f32.bf16.bf16 {%0,%1,%2,%3,%4,%5,%6,%7,%8,%9,%10,%11,%12,%13,%14,%15,%16,%17,%18,%19,%20,%21,%22,%23,%24,%25,%26,%27,%28,%29,%30,%31}, %32, %33, p, 1, 1, %35, %36;\n}\n"
   : "+f"(d[0]),"+f"(d[1]),"+f"(d[2]),"+f"(d[3]),"+f"(d[4]),"+f"(d[5]),"+f"(d[6]),"+f"(d[7]),"+f"(d[8]),"+f"(d[9]),"+f"(d[10]),"+f"(d[11]),"+f"(d[12]),"+f"(d[13]),"+f"(d[14]),"+f"(d[15]),"+f"(d[16]),"+f"(d[17]),"+f"(d[18]),"+f"(d[19]),"+f"(d[20]),"+f"(d[21]),"+f"(d[22]),"+f"(d[23]),"+f"(d[24]),"+f"(d[25]),"+f"(d[26]),"+f"(d[27]),"+f"(d[28]),"+f"(d[29]),"+f"(d[30]),"+f"(d[31])
   : "l"(da),"l"(db),"r"(sd),"n"(TA),"n"(TB));
}

template<int TA, int TB> __device__ __forceinline__ void wg_ss8(float* d, uint64_t da, uint64_t db, int sd) {
  asm volatile("{\n.reg .pred p;\nsetp.ne.b32 p, %6, 0;\n"
   "wgmma.mma_async.sync.aligned.m64n8k16.f32.bf16.bf16 {%0,%1,%2,%3}, %4, %5, p, 1, 1, %7, %8;\n}\n"
   : "+f"(d[0]),"+f"(d[1]),"+f"(d[2]),"+f"(d[3])
   : "l"(da),"l"(db),"r"(sd),"n"(TA),"n"(TB));
}

template<int SD, uint32_t HI> __device__ __forceinline__ void wq32(float* d, uint64_t da, uint32_t lo) {
  asm volatile("{\n.reg .b64 db;\nmov.b64 db, {%17, %19};\n"
   "wgmma.mma_async.sync.aligned.m64n32k16.f32.f16.f16 {%0,%1,%2,%3,%4,%5,%6,%7,%8,%9,%10,%11,%12,%13,%14,%15}, %16, db, %18, 1, 1, 0, 0;\n}\n"
   : "+f"(d[0]),"+f"(d[1]),"+f"(d[2]),"+f"(d[3]),"+f"(d[4]),"+f"(d[5]),"+f"(d[6]),"+f"(d[7]),"+f"(d[8]),"+f"(d[9]),"+f"(d[10]),"+f"(d[11]),"+f"(d[12]),"+f"(d[13]),"+f"(d[14]),"+f"(d[15])
   : "l"(da),"r"(lo),"n"(SD),"r"(HI));
}
template<int SD, uint32_t HI> __device__ __forceinline__ void wq64(float* d, uint64_t da, uint32_t lo) {
  asm volatile("{\n.reg .b64 db;\nmov.b64 db, {%33, %35};\n"
   "wgmma.mma_async.sync.aligned.m64n64k16.f32.f16.f16 {%0,%1,%2,%3,%4,%5,%6,%7,%8,%9,%10,%11,%12,%13,%14,%15,%16,%17,%18,%19,%20,%21,%22,%23,%24,%25,%26,%27,%28,%29,%30,%31}, %32, db, %34, 1, 1, 0, 0;\n}\n"
   : "+f"(d[0]),"+f"(d[1]),"+f"(d[2]),"+f"(d[3]),"+f"(d[4]),"+f"(d[5]),"+f"(d[6]),"+f"(d[7]),"+f"(d[8]),"+f"(d[9]),"+f"(d[10]),"+f"(d[11]),"+f"(d[12]),"+f"(d[13]),"+f"(d[14]),"+f"(d[15]),"+f"(d[16]),"+f"(d[17]),"+f"(d[18]),"+f"(d[19]),"+f"(d[20]),"+f"(d[21]),"+f"(d[22]),"+f"(d[23]),"+f"(d[24]),"+f"(d[25]),"+f"(d[26]),"+f"(d[27]),"+f"(d[28]),"+f"(d[29]),"+f"(d[30]),"+f"(d[31])
   : "l"(da),"r"(lo),"n"(SD),"r"(HI));
}
template<int SD, uint32_t HI> __device__ __forceinline__ void wpv(float* d, const uint32_t* a, uint32_t lo) {
  asm volatile("{\n.reg .b64 db;\nmov.b64 db, {%16, %18};\n"
   "wgmma.mma_async.sync.aligned.m64n24k16.f32.bf16.bf16 {%0,%1,%2,%3,%4,%5,%6,%7,%8,%9,%10,%11}, {%12,%13,%14,%15}, db, %17, 1, 1, 1;\n}\n"
   : "+f"(d[0]),"+f"(d[1]),"+f"(d[2]),"+f"(d[3]),"+f"(d[4]),"+f"(d[5]),"+f"(d[6]),"+f"(d[7]),"+f"(d[8]),"+f"(d[9]),"+f"(d[10]),"+f"(d[11])
   : "r"(a[0]),"r"(a[1]),"r"(a[2]),"r"(a[3]),"r"(lo),"n"(SD),"r"(HI));
}

__device__ __forceinline__ uint32_t phi2(float a, float b) {
  uint32_t r, e;
  asm("cvt.rn.relu.bf16x2.f32 %0, %1, %2;" : "=r"(r) : "f"(b), "f"(a));
  e = pack_bf16(ex2f(a * 1.4426950408889634f), ex2f(b * 1.4426950408889634f));
  asm("add.rn.bf16x2 %0, %0, %1;" : "+r"(e) : "r"(0x35863586u));
  asm("min.NaN.bf16x2 %0, %0, %1;" : "+r"(e) : "r"(0x3F803F80u));
  asm("add.rn.bf16x2 %0, %0, %1;" : "+r"(e) : "r"(r));
  return e;
}

__device__ __forceinline__ void mbar_arrive(uint32_t bar) { asm volatile("mbarrier.arrive.shared::cta.b64 _, [%0];" :: "r"(bar) : "memory"); }
__device__ __forceinline__ void named_arrive(int id, int n) { asm volatile("bar.arrive %0, %1;" :: "r"(id), "r"(n) : "memory"); }
__device__ __forceinline__ void fence_async_all() { asm volatile("fence.proxy.async.global;" ::: "memory"); }
__device__ __forceinline__ void flag_add(uint32_t* f) { asm volatile("fence.acq_rel.gpu;\nred.relaxed.gpu.global.add.u32 [%0], 1;" :: "l"(f) : "memory"); }
#define PUBLISH(f) asm volatile("fence.proxy.async.global;\nred.relaxed.gpu.global.add.u32 [%0], 1;" :: "l"(f) : "memory")
__device__ __forceinline__ void flag_wait(const uint32_t* f, uint32_t target) {
  uint32_t v;
#pragma unroll 1
  for (int it = 0;; it++) {
    asm volatile("ld.acquire.gpu.global.u32 %0, [%1];" : "=r"(v) : "l"(f) : "memory");
    if ((int32_t)(v - target) >= 0) break;
    if (it > 2000000) __trap();
    __nanosleep(64);
  }
}
__device__ __forceinline__ bool elect_one() {
  uint32_t p;
  asm volatile("{\n.reg .pred P;\nelect.sync _|P, 0xFFFFFFFF;\nselp.b32 %0, 1, 0, P;\n}\n" : "=r"(p));
  return p;
}
__device__ __forceinline__ void lds4(uint32_t a, uint32_t* r) {
  asm volatile("ld.shared.v4.b32 {%0,%1,%2,%3}, [%4];" : "=r"(r[0]), "=r"(r[1]), "=r"(r[2]), "=r"(r[3]) : "r"(a) : "memory");
}
__device__ __forceinline__ uint32_t lds1(uint32_t a) { uint32_t r; asm volatile("ld.shared.b32 %0, [%1];" : "=r"(r) : "r"(a) : "memory"); return r; }
__device__ __forceinline__ void sts1(uint32_t a, uint32_t v) { asm volatile("st.shared.b32 [%0], %1;" :: "r"(a), "r"(v) : "memory"); }
__device__ __forceinline__ void sts4(uint32_t a, uint32_t r0, uint32_t r1, uint32_t r2, uint32_t r3) {
  asm volatile("st.shared.v4.b32 [%0], {%1,%2,%3,%4};" :: "r"(a), "r"(r0), "r"(r1), "r"(r2), "r"(r3) : "memory");
}
__device__ __forceinline__ void ldsm4(uint32_t a, uint32_t* r) {
  asm volatile("ldmatrix.sync.aligned.m8n8.x4.shared.b16 {%0,%1,%2,%3}, [%4];" : "=r"(r[0]), "=r"(r[1]), "=r"(r[2]), "=r"(r[3]) : "r"(a) : "memory");
}
__device__ __forceinline__ float rcpf(float x) { float y; asm("rcp.approx.ftz.f32 %0, %1;" : "=f"(y) : "f"(x)); return y; }
__device__ __forceinline__ uint32_t hfma2(uint32_t a, uint32_t b, uint32_t c) { uint32_t r; asm("fma.rn.f16x2 %0, %1, %2, %3;" : "=r"(r) : "r"(a), "r"(b), "r"(c)); return r; }
__device__ __forceinline__ uint32_t hadd2(uint32_t a, uint32_t b) { uint32_t r; asm("add.rn.f16x2 %0, %1, %2;" : "=r"(r) : "r"(a), "r"(b)); return r; }

#define STEPK 96
#define QSCALE 0.36067376022224085f
#define SMAGIC (512.0f + 2.0f * (191.0f - 30.0f - 1.5823545f))
#define VSHIFT 1073741824.0f

__device__ uint32_t g_epoch[132];
__device__ uint32_t g_flag[288 * 8];
#define FLAG_KV (g_flag)
#define FLAG_B(h) (g_flag + (4 + (h)) * 8)
#define FLAG_OA(cta, pass) (g_flag + (16 + (cta) * 2 + (pass)) * 8)
#define FLAG_LM(i) (g_flag + (272 + (i)) * 8)

#define SM_TOTAL (224 * 1024 + 2048 + 1024)
#define OFF_K 0
#define OFF_F 65536
#define OFF_V 131072
#define OFF_MISC (224 * 1024)

#define BAR_FULL(s) (bars + 8 * (s))
#define BAR_EMPTY(s) (bars + 24 + 8 * (s))
#define BAR_KV(c) (bars + 48 + 8 * (c))
#define BAR_BDONE (bars + 80)
#define BAR_Q (bars + 88)
#define BAR_GO (bars + 96)
#define BAR_Q2 (bars + 104)
#define BAR_OD(p) (bars + 112 + 8 * (p))
#define BAR_CL(c) (bars + 128 + 8 * (c))
#define BAR_TE(i) (bars + 168 + 8 * (i))
#define BAR_TF(g) (bars + 224 + 8 * (g))
#define BAR_XA(w) (bars + 352 + 8 * (w))
#define BAR_VB(c) (bars + 384 + 8 * (c))

__device__ __forceinline__ uint32_t exp2_pair_fix(float d0, float d1, uint32_t c63, uint32_t m1) {
  uint32_t w, y, s, r;
  asm("prmt.b32 %0, %1, %2, 0x6521;" : "=r"(w) : "r"(__float_as_uint(d0)), "r"(__float_as_uint(d1)));
  asm("lop3.b32 %0, %1, 0x007F007F, %2, 0xEA;" : "=r"(y) : "r"(w), "r"(c63));
  asm("mad.lo.u32 %0, %1, %2, %3;" : "=r"(s) : "r"(y), "r"(m1), "r"(w));
  asm("fma.rn.bf16x2 %0, %1, %2, %3;" : "=r"(r) : "r"(w), "r"(y), "r"(s));
  return r;
}

__device__ __forceinline__ void attn_slow(const uint4* gq, uint32_t dst) {
  const int t = threadIdx.x & 127;
  const int row = t >> 1, half = t & 1;
  float q[16];
#pragma unroll
  for (int i = 0; i < 4; i++) {
    const uint4 v = gq[(row >> 4) * 32 + (row & 7) * 4 + i];
    const uint32_t lo = (row & 8) ? v.y : v.x, hi = (row & 8) ? v.w : v.z;
    q[2 * i] = bf_lo(lo); q[2 * i + 1] = bf_hi(lo); q[2 * i + 8] = bf_lo(hi); q[2 * i + 9] = bf_hi(hi);
  }
  float m = -INFINITY, l = 0.f, o[16];
#pragma unroll
  for (int i = 0; i < 16; i++) o[i] = 0.f;
#pragma unroll 1
  for (int j = half * 1024; j < half * 1024 + 1024; j++) {
    uint4 ka = g_KV[4 * S_TOK + j], kb = g_KV[5 * S_TOK + j];
    uint4 va = g_KV[6 * S_TOK + j], vb = g_KV[7 * S_TOK + j];
    uint32_t kk[8] = {ka.x, ka.y, ka.z, ka.w, kb.x, kb.y, kb.z, kb.w};
    uint32_t vv[8] = {va.x, va.y, va.z, va.w, vb.x, vb.y, vb.z, vb.w};
    float s = 0.f;
#pragma unroll
    for (int i = 0; i < 8; i++) { s = fmaf(q[2 * i], bf_lo(kk[i]), s); s = fmaf(q[2 * i + 1], bf_hi(kk[i]), s); }
    s = rbf(s) * 0.25f;
    if (s > m) {
      float c = __expf(m - s);
      l *= c;
#pragma unroll
      for (int i = 0; i < 16; i++) o[i] *= c;
      m = s;
    }
    float p = __expf(s - m);
    l += p;
#pragma unroll
    for (int i = 0; i < 8; i++) { o[2 * i] = fmaf(p, bf_lo(vv[i]), o[2 * i]); o[2 * i + 1] = fmaf(p, bf_hi(vv[i]), o[2 * i + 1]); }
  }
  float m2 = __shfl_xor_sync(~0u, m, 1);
  float mm = fmaxf(m, m2);
  float c = __expf(m - mm);
  l *= c; l += __shfl_xor_sync(~0u, l, 1);
  float inv = 1.f / l;
  uint32_t r[8];
#pragma unroll
  for (int i = 0; i < 16; i++) { o[i] *= c; o[i] += __shfl_xor_sync(~0u, o[i], 1); o[i] *= inv; }
#pragma unroll
  for (int i = 0; i < 8; i++) r[i] = pack_bf16(o[2 * i], o[2 * i + 1]);
  if (half == 0) sts4(dst + t * 16, r[0], r[1], r[2], r[3]); else sts4(dst + t * 16, r[4], r[5], r[6], r[7]);
  fence_async();
}

struct Params { const __nv_bfloat16* wk; const __nv_bfloat16* wv; const __nv_bfloat16* xa; };
__device__ __forceinline__ void cp16(uint32_t dst, const void* src) { asm volatile("cp.async.cg.shared.global [%0], [%1], 16;" :: "r"(dst), "l"(src) : "memory"); }

__device__ __forceinline__ void helper_cta(const int h, const uint32_t sb, const uint32_t bars, const int wg, const int w4,
                                           const CUtensorMap* mQ, const CUtensorMap* mOs) {
  const int lane = threadIdx.x & 31;
  mbar_wait(BAR_GO, 0);
  const int cb = wg & 1, col = h * 128 + cb * 64, row0 = S_TOK + (wg >> 1) * 1024;
  const uint32_t buf = sb + wg * 49152;
  if (w4 == 0 && elect_one()) {
    fence_async_all();
#pragma unroll 1
    for (int u = 0; u < 3; u++) {
      mbar_expect_tx(BAR_TF(wg * 3 + u), 16384);
      tma2d(buf + u * 16384, mQ, col, row0 + u * 128, BAR_TF(wg * 3 + u));
    }
  }
  const int head = h * 8 + cb * 4 + w4;
  float4 a0 = make_float4(0, 0, 0, 0), a1 = a0, a2 = a0;
#pragma unroll 8
  for (int tt = 0; tt < 16; tt++) {
    const float4* src = g_kvp + ((tt * 32 + head) * 3) * 32 + lane;
    float4 u = src[0], v = src[32], w = src[64];
    a0.x += u.x; a0.y += u.y; a0.z += u.z; a0.w += u.w;
    a1.x += v.x; a1.y += v.y; a1.z += v.z; a1.w += v.w;
    a2.x += w.x; a2.y += w.y; a2.z += w.z; a2.w += w.w;
  }
  const uint32_t b00 = pack_bf16(a0.x, a0.y), b01 = pack_bf16(a0.z, a0.w);
  const uint32_t b10 = pack_bf16(a1.x, a1.y), b11 = pack_bf16(a1.z, a1.w);
  const uint32_t bz0 = pack_bf16(a2.x, a2.y), bz1 = pack_bf16(a2.z, a2.w);
  const int m = lane >> 3, r = lane & 7;
  const uint32_t off = ((m & 1) * 8 + r) * 128 + (((w4 * 2 + (m >> 1)) ^ r) << 4);
  int s = 0, ph = 0;
#pragma unroll 1
  for (int u = 0; u < 8; u++) {
    const uint32_t bb = buf + s * 16384;
    mbar_wait(BAR_TF(wg * 3 + s), ph);
#pragma unroll
    for (int mt = 0; mt < 8; mt++) {
      uint32_t a[4];
      ldsm4(bb + mt * 2048 + off, a);
      float n0[4] = {0, 0, 0, 0}, n1[4] = {0, 0, 0, 0}, dn[4] = {0, 0, 0, 0};
      mma_bf16(dn, a[0], a[1], a[2], a[3], bz0, bz1);
      mma_bf16(n0, a[0], a[1], a[2], a[3], b00, b01);
      mma_bf16(n1, a[0], a[1], a[2], a[3], b10, b11);
      const float i0 = rcpf(dn[0] + 1e-6f), i1 = rcpf(dn[2] + 1e-6f);
      stsm4(bb + mt * 2048 + off, pack_bf16(n0[0] * i0, n0[1] * i0), pack_bf16(n0[2] * i1, n0[3] * i1),
            pack_bf16(n1[0] * i0, n1[1] * i0), pack_bf16(n1[2] * i1, n1[3] * i1));
    }
    fence_async();
    named_bar(wg + 1, 128);
    if (w4 == 0 && lane == 0) {
      tma2d_store(mOs, bb, col, row0 + u * 128);
      bulk_commit();
      if (u >= 1 && u + 2 < 8) {
        asm volatile("cp.async.bulk.wait_group.read 1;" ::: "memory");
        const int sp = s == 0 ? 2 : s - 1;
        mbar_expect_tx(BAR_TF(wg * 3 + sp), 16384);
        tma2d(buf + sp * 16384, mQ, col, row0 + (u + 2) * 128, BAR_TF(wg * 3 + sp));
      }
    }
    __syncwarp();
    if (++s == 3) { s = 0; ph ^= 1; }
  }
  if (w4 == 0 && lane == 0) {
    bulk_wait_all();
    fence_async_all();
    flag_add(FLAG_LM((h * 2 + cb) * 2 + (wg >> 1)));
    if (wg == 0) TS(1, 8);
  }
}

#define STAGE(s) (sb + (2 - (s)) * 65536)
template <int TR> __device__ __forceinline__ void proj_kb(float* acc, uint32_t st, uint32_t offA, uint32_t offB, int first) {
  const uint64_t da = make_desc(st + offA, TR ? 8192 : 16, 1024, 1);
  const uint64_t db = make_desc(st + offB, TR ? 16 : 8192, 1024, 1);
  wg_fence();
#pragma unroll
  for (int k = 0; k < 4; k++) wg_ss128<TR, 1 - TR>(acc, da + k * (TR ? 128 : 2), db + k * (TR ? 2 : 128), k != 0 || !first);
  wg_commit();
}
template <int TR> __device__ __forceinline__ void proj_loop(float* acc, uint32_t sb, uint32_t bars, uint32_t offA, uint32_t offB,
                                                            int wg, uint32_t sWKV) {
  {
    float kv[4];
    if (threadIdx.x == 0) TS(0, 13);
    mbar_wait(BAR_XA(wg), 0);
    if (threadIdx.x == 0) TS(0, 1);
    const uint64_t da = make_desc(STAGE(2) + wg * 16384, 16, 1024, 1), db = make_desc(sWKV + wg * 2048, 128, 128, 0);
    wg_fence();
#pragma unroll
    for (int k = 0; k < 8; k++) wg_ss8<0, 1>(kv, da + (k >> 2) * 512 + (k & 3) * 2, db + k * 16, k != 0);
    wg_commit();
    wg_wait<0>();
    fence_regs<4>(kv);
    named_bar(wg + 1, 128);
    sts4(sWKV + threadIdx.x * 16, __float_as_uint(kv[0]), __float_as_uint(kv[1]), __float_as_uint(kv[2]), __float_as_uint(kv[3]));
    __syncwarp();
    if ((threadIdx.x & 31) == 0) mbar_arrive(BAR_GO);
  }
  int s = 0, ph = 0, sp = 0;
#pragma unroll 1
  for (int kb = 0; kb < 8; kb++) {
    mbar_wait(BAR_FULL(s), ph);
    if (threadIdx.x == 0) TS(0, 2 + kb);
    proj_kb<TR>(acc, STAGE(s), offA, offB, kb == 0);
    wg_wait<1>();
    if (kb >= 1 && (threadIdx.x & 127) == 0) mbar_arrive(BAR_EMPTY(sp));
    __syncwarp();
    sp = s;
    if (++s == 3) { s = 0; ph ^= 1; }
  }
  wg_wait<0>();
  fence_regs<64>(acc);
}

__device__ __forceinline__ uint32_t tail_slots(int t) {
  const uint32_t lo = t < 4 ? (t < 2 ? (t == 0 ? 0x0C0B0Au : 0x0F0E0Du) : (t == 2 ? 0x100400u : 0x181408u))
                            : (t < 6 ? (t == 4 ? 0x110501u : 0x191502u) : (t == 6 ? 0x161206u : (t == 7 ? 0x1A0703u : 0x1B1713u)));
  return lo;
}

__device__ __forceinline__ void take_role(uint32_t sM, int wg) {
  uint32_t r;
  asm volatile("atom.shared.add.u32 %0, [%1], 1;" : "=r"(r) : "r"(sM + 20) : "memory");
  sts1(sM + 32 + wg * 4, r);
}

__global__ void __launch_bounds__(640, 1)
k1_main(const __grid_constant__ CUtensorMap mXA64, const __grid_constant__ CUtensorMap mXB,
        const __grid_constant__ CUtensorMap mWq, const __grid_constant__ CUtensorMap mWqkv,
        const __grid_constant__ CUtensorMap mQst, const __grid_constant__ CUtensorMap mOst,
        const __grid_constant__ CUtensorMap mO, const __grid_constant__ CUtensorMap mWoA,
        const __grid_constant__ CUtensorMap mWoB, const __grid_constant__ CUtensorMap mOut,
        const __grid_constant__ CUtensorMap mO16, const Params prm) {
  extern __shared__ uint8_t smem_raw[];
  const uint32_t sb = (smem_u32(smem_raw) + 1023u) & ~1023u;
  const uint32_t bars = sb + OFF_MISC, sM = bars + 512, sT = bars + 1024;
  const int tid = threadIdx.x, warp = __shfl_sync(~0u, tid >> 5, 0), wg = warp >> 2, w4 = warp & 3, lane = tid & 31;
  const bool helper = blockIdx.x >= 128;
  if (tid == 0) TS(0, 0);
  const int G = blockIdx.x >> 4, gi = blockIdx.x & 15;
  const int tbA = G * 4 + (gi >> 2), hg = gi & 3;
  const int ttB = (G >> 1) * 4 + (gi >> 2), hq = (G & 1) * 4 + (gi & 3);
  auto issue = [&](int kb, int s) {
    const uint32_t fb = BAR_FULL(s), st = STAGE(s);
    mbar_expect_tx(fb, 65536);
    tma2d(st + 16384, &mXA64, kb * 64, tbA * 64, fb);
    tma2d(st, &mWq, hg * 128, kb * 64, fb);
    tma2d(st + 8192, &mWq, hg * 128 + 64, kb * 64, fb);
    tma2d(st + 49152, &mXB, kb * 64, ttB * 128, fb);
    tma2d(st + 24576, &mWqkv, hq * 64, kb * 64, fb);
    tma2d(st + 32768, &mWqkv, 512 + hq * 64, kb * 64, fb);
    tma2d(st + 40960, &mWqkv, 1024 + hq * 64, kb * 64, fb);
  };
  const uint32_t sOne = sb + OFF_V + 65536, sWKV = sOne + 24576;
  if (warp >= 16) {
    if (warp == 17) {
      if (elect_one()) {
        mbar_init(BAR_BDONE, 8); mbar_init(BAR_Q, 8); mbar_init(BAR_GO, helper ? 1 : 16); mbar_init(BAR_Q2, 5);
        mbar_init(BAR_OD(0), 16); mbar_init(BAR_OD(1), 16); mbar_init(BAR_CL(0), 1); mbar_init(BAR_FULL(2), 1);
#pragma unroll
        for (int i = 0; i < 4; i++) mbar_init(BAR_CL(i + 1), i == 0 ? 5 : 4);
#pragma unroll
        for (int i = 0; i < 3; i++) { mbar_init(BAR_EMPTY(i), 4); mbar_init(BAR_KV(i), 1); mbar_init(BAR_VB(i), 1); }
        sts1(sM + 20, 0);
        asm volatile("fence.mbarrier_init.release.cluster;" ::: "memory");
      }
    } else if (warp == 18) {
      if (elect_one()) {
#pragma unroll
        for (int i = 0; i < 7; i++) mbar_init(BAR_TE(i), 1);
#pragma unroll
        for (int i = 0; i < 16; i++) mbar_init(BAR_TF(i), i < 12 ? 1 : 2);
        asm volatile("fence.mbarrier_init.release.cluster;" ::: "memory");
      }
    } else if (warp == 16 && !helper && elect_one()) {
#pragma unroll
      for (int w = 0; w < 4; w++) mbar_init(BAR_XA(w), 1);
      mbar_init(BAR_FULL(0), 1); mbar_init(BAR_FULL(1), 1);
      asm volatile("fence.mbarrier_init.release.cluster;" ::: "memory");
#pragma unroll
      for (int w = 0; w < 4; w++) {
        mbar_expect_tx(BAR_XA(w), 16384);
        tma2d(STAGE(2) + w * 16384, &mXA64, w * 128, tbA * 64, BAR_XA(w));
        tma2d(STAGE(2) + w * 16384 + 8192, &mXA64, w * 128 + 64, tbA * 64, BAR_XA(w));
      }
      TS(0, 14);
      issue(0, 0);
    }
  } else if (!helper) {
    const uint4 v = __ldg((const uint4*)(hg >= 2 ? prm.wv : prm.wk) + tid * 2 + (hg & 1));
#pragma unroll
    for (int i = 0; i < 3; i++) {
      const int key = tid + i * 512;
      sts4(sOne + key * 16, (key % STEPK) < 32 ? 0x00003F80u : 0x00004E80u, 0u, 0u, 0u);
    }
    sts4(sWKV + tid * 16, v.x, v.y, v.z, v.w);
    fence_async();
  }
  __syncthreads();
  if (wg == 4) {
    if (w4 == 0 && !helper && elect_one()) { issue(1, 1); TS(0, 15); }
    asm volatile("setmaxnreg.dec.sync.aligned.u32 32;");
    const uint32_t ep = g_epoch[blockIdx.x] + 1;
    if (helper) {
      if (w4 == 0 && elect_one()) {
        flag_wait(FLAG_B(blockIdx.x - 128), ep * 32);
        fence_async_all();
        TS(1, 10);
        mbar_arrive(BAR_GO);
        g_epoch[blockIdx.x] = ep;
      }
      return;
    }
    mbar_wait(BAR_GO, 0);
    if (w4 == 0 && elect_one()) issue(2, 2);
    {
      uint32_t a[4], b[4];
      float c[4];
      lds4(sWKV + (tid - 512) * 16, a);
      lds4(sWKV + 2048 + (tid - 512) * 16, b);
#pragma unroll
      for (int i = 0; i < 4; i++) c[i] = __uint_as_float(a[i]) + __uint_as_float(b[i]);
      lds4(sWKV + 4096 + (tid - 512) * 16, a);
      lds4(sWKV + 6144 + (tid - 512) * 16, b);
#pragma unroll
      for (int i = 0; i < 4; i++) c[i] += __uint_as_float(a[i]) + __uint_as_float(b[i]);
      sts1(sT + w4 * 256 + lane * 4, pack_bf16(c[0], c[1]));
      sts1(sT + w4 * 256 + 128 + lane * 4, pack_bf16(c[2], c[3]));
    }
    named_bar(9, 128);
    {
      const int t = tid - 512;
#pragma unroll
      for (int i = 0; i < 4; i++) {
        const int key = 1536 + t + i * 128;
        sts4(sOne + key * 16, (key % STEPK) < 32 ? 0x00003F80u : 0x00004E80u, 0u, 0u, 0u);
      }
      fence_async();
      __syncwarp();
      if (lane == 0) mbar_arrive(BAR_Q);
    }
    if (w4 == 0) {
      int s = 0, ph = 0;
#pragma unroll 1
      for (int kb = 3; kb < 8; kb++) {
        mbar_wait(BAR_EMPTY(s), ph);
        if (elect_one()) issue(kb, s);
        if (++s == 3) { s = 0; ph ^= 1; }
      }
      flag_wait(FLAG_KV, ep * 128);
      fence_async_all();
      if (lane == 0) TS(0, 11);
#pragma unroll 1
      for (int m = 0; m < 2; m++) {
        mbar_wait(m == 0 ? BAR_EMPTY(2) : BAR_EMPTY(0), 1 - m);
        if (elect_one()) {
#pragma unroll
          for (int c = 0; c < 3; c++) {
            const int k0 = c == 0 ? 0 : (c == 1 ? 7 * STEPK : 12 * STEPK), k1 = c == 0 ? 7 * STEPK : (c == 1 ? 12 * STEPK : S_TOK);
            const uint32_t bytes = (k1 - k0) * 16, fb = m == 0 ? BAR_KV(c) : BAR_VB(c);
            mbar_expect_tx(fb, 2 * bytes);
#pragma unroll
            for (int p = 0; p < 2; p++)
              bulk_g2s(sb + m * OFF_V + p * 32768 + k0 * 16, g_KV + (m * 2 + p) * S_TOK + k0, bytes, fb);
          }
        }
      }
      mbar_wait(BAR_CL(1), 0);
      flag_wait(FLAG_LM((lane & 7) * 2 + (tbA >> 4)), ep);
      __syncwarp();
      fence_async_all();
      if (lane == 0) TS(2, 13);
#pragma unroll 1
      for (int n = 0; n < 8; n++) {
        mbar_wait(BAR_CL(n < 4 ? n >> 1 : (n == 4 ? 2 : (n < 7 ? 3 : 4))), 0);
        const uint32_t sl = tail_slots(n), fb = BAR_TF(n);
        if (elect_one()) {
          mbar_expect_tx(fb, 24576);
          tma2d(sb + (sl & 255) * 8192, &mO, n * 64, S_TOK + tbA * 64, fb);
          tma2d(sb + ((sl >> 8) & 255) * 8192, &mWoB, hg * 128, n * 64, fb);
          tma2d(sb + (sl >> 16) * 8192, &mWoB, hg * 128 + 64, n * 64, fb);
        }
      }
      if (lane == 0) g_epoch[blockIdx.x] = ep;
    } else if (w4 == 3) {
      flag_wait(FLAG_KV, ep * 128);
      const uint4 a = *(const uint4*)(g_stats + lane * 4);
      const float kmax2 = __uint_as_float(__reduce_max_sync(~0u, a.x)) + __uint_as_float(__reduce_max_sync(~0u, a.y));
      const float vmax = __uint_as_float(__reduce_max_sync(~0u, max(a.z, a.w)));
      const float lv = vmax > 0.f ? __log2f(vmax) : 0.f;
      const float lim = fminf(90.f, fminf(91.f + lv, 95.f - lv));
      float thr = -1.f;
      if (vmax < 1e27f && kmax2 <= 65536.f && lim > 2.f) thr = fminf(60000.f, (lim * lim - 1.f) / (kmax2 * 1.02f + 1e-30f));
      if (lane == 0) { sts1(sM + 16, __float_as_uint(thr)); mbar_arrive(BAR_Q2); }
      mbar_wait(BAR_CL(3), 0);
      flag_wait(FLAG_OA(tbA * 4 + (lane & 3), 0), ep);
      __syncwarp();
      fence_async_all();
#pragma unroll 1
      for (int n = 0; n < 8; n++) {
        mbar_wait(n == 4 ? BAR_CL(4) : BAR_TE(n < 4 ? n : n - 1), 0);
        const uint32_t sl = tail_slots(n < 4 ? n : (n == 4 ? 8 : n - 1)), fb = BAR_TF(n + 8);
        const int k0 = n < 4 ? n * 128 : ((hg + n) & 3) * 128 + 64;
        if (elect_one()) {
          mbar_expect_tx(fb, n < 4 ? 24576 : 16384);
          if (n < 4) tma2d(sb + (sl & 255) * 8192, &mO, k0, tbA * 64, fb);
          tma2d(sb + ((sl >> 8) & 255) * 8192, &mWoA, hg * 128, k0, fb);
          tma2d(sb + (sl >> 16) * 8192, &mWoA, hg * 128 + 64, k0, fb);
        }
      }
    } else {
      const int ch = tbA * 2 + (w4 - 1);
      uint32_t v[4], o[4];
      lds4(sT + (w4 - 1) * 512 + lane * 16, v);
      int kap;
      if (lane < 21) kap = lane * STEPK + 32 + ch;
      else { int idx = ch * 11 + (lane - 21); kap = (idx >> 5) * STEPK + (idx & 31); }
      g_KV[(4 + hg) * S_TOK + kap] = make_uint4(v[0], v[1], v[2], v[3]);
      float st = 0.f;
      if (hg < 2) {
        const float sc = lane < 21 ? 2.f : 1.f;
#pragma unroll
        for (int u = 0; u < 4; u++) {
          uint32_t pv = __shfl_up_sync(~0u, v[u], 1);
          if (lane == 0 || lane >= 21) pv = 0;
          const float x = bf_lo(v[u]), y = bf_hi(v[u]);
          st += x * x + y * y;
          o[u] = pack_f16((x - bf_lo(pv)) * sc, (y - bf_hi(pv)) * sc);
        }
      } else {
        const float sc = lane < 21 ? VSHIFT : 1.f;
#pragma unroll
        for (int u = 0; u < 4; u++) { float x = bf_lo(v[u]), y = bf_hi(v[u]); st += fabsf(x) + fabsf(y); o[u] = pack_bf16(x * sc, y * sc); }
      }
      g_KV[hg * S_TOK + kap] = make_uint4(o[0], o[1], o[2], o[3]);
      const uint32_t um = __reduce_max_sync(~0u, __float_as_uint(st) & 0x7FFFFFFFu);
      if (w4 == 2) {
        if (lane == 0) sts1(sM + 24, um);
        named_arrive(10, 64);
        uint32_t rdy = 0;
#pragma unroll 1
        for (int n = 4; n < 8; n++) {
          mbar_wait(n == 4 ? BAR_CL(4) : BAR_TE(n - 1), 0);
          const int hsel = (hg + n) & 3;
#pragma unroll 1
          for (int it = 0; !((rdy >> hsel) & 1); it++) {
            uint32_t fv;
            asm volatile("ld.acquire.gpu.global.u32 %0, [%1];" : "=r"(fv) : "l"(FLAG_OA(tbA * 4 + (lane & 3), 1)) : "memory");
            rdy = __ballot_sync(~0u, (int32_t)(fv - ep) >= 0);
            if (it > 2000000) __trap();
          }
          if (lane == 0 && n == 7) TS(2, 14);
          fence_async_all();
          const uint32_t sl = tail_slots(n == 4 ? 8 : n - 1), fb = BAR_TF(n + 8);
          if (elect_one()) {
            mbar_expect_tx(fb, 8192);
            tma2d(sb + (sl & 255) * 8192, &mO, hsel * 128 + 64, tbA * 64, fb);
          }
        }
      }
      else {
        named_bar(10, 64);
        if (elect_one()) {
          g_stats[tbA * 4 + hg] = max(um, lds1(sM + 24));
          fence_async_all();
          flag_add(FLAG_KV);
          TS(1, 9);
          mbar_wait(BAR_BDONE, 0);
          tma2d_store(&mQst, sb + OFF_F + 49152, hq * 64, S_TOK + ttB * 128);
          bulk_commit();
          bulk_wait_all();
          fence_async_all();
          flag_add(FLAG_B(hq >> 1));
          TS(0, 12);
          mbar_wait(BAR_Q, 0);
          mbar_arrive(BAR_CL(0));
#pragma unroll 1
          for (int p = 0; p < 2; p++) {
            mbar_wait(BAR_OD(p), 0);
#pragma unroll
            for (int w = 0; w < 4; w++) tma2d_store(&mO16, sb + OFF_F + (p * 4 + w) * 2048, hg * 128 + p * 64 + w * 16, tbA * 64);
            bulk_commit();
            bulk_wait_all();
            if (p == 0) mbar_arrive(BAR_CL(1));
            PUBLISH(FLAG_OA(blockIdx.x, p));
          }
          TS(2, 0);
        }
      }
    }
    return;
  }
  if (helper) { helper_cta(blockIdx.x - 128, sb, bars, wg, w4, &mQst, &mOst); return; }

  {
    float acc[64];
    if (wg == 0) proj_loop<0>(acc, sb, bars, 16384, 0, wg, sWKV);
    else proj_loop<1>(acc, sb, bars, 16384 + wg * 8192, 49152, wg, sWKV);
    asm volatile("setmaxnreg.inc.sync.aligned.u32 112;");
    if (tid == 0) TS(0, 10);
    const uint32_t sF = sb + OFF_F;
    if (wg == 0) {
      uint32_t r[32];
      const uint32_t qa = sF + w4 * 512 + ((lane >> 3) & 1) * 256 + (lane >> 4) * 128 + (lane & 7) * 16;
#pragma unroll
      for (int hd = 0; hd < 8; hd++) {
#pragma unroll
        for (int i = 0; i < 4; i++) r[4 * hd + i] = pack_f16(acc[8 * hd + 2 * i] * QSCALE, acc[8 * hd + 2 * i + 1] * QSCALE);
        stsm4(qa + hd * 2048, r[4 * hd], r[4 * hd + 1], r[4 * hd + 2], r[4 * hd + 3]);
        if (hd == 3) {
          fence_async();
          __syncwarp();
          if (lane == 0) mbar_arrive(BAR_Q);
        }
      }
      fence_async();
      uint32_t nmax = 0;
#pragma unroll
      for (int hd = 0; hd < 8; hd++) {
        const uint32_t* q = r + 4 * hd;
        const uint32_t t0 = hfma2(q[2], q[2], hfma2(q[0], q[0], 0u)), t1 = hfma2(q[3], q[3], hfma2(q[1], q[1], 0u));
        uint32_t n = hadd2(__byte_perm(t0, t1, 0x5410), __byte_perm(t0, t1, 0x7632));
        n = hadd2(n, __shfl_xor_sync(~0u, n, 1));
        n = hadd2(n, __shfl_xor_sync(~0u, n, 2));
        nmax = __vmaxu2(nmax, n & 0x7FFF7FFFu);
      }
      nmax = __reduce_max_sync(~0u, max(nmax & 0xFFFFu, nmax >> 16));
      if (lane == 0) sts1(sM + w4 * 4, nmax);
      uint4* gq = (uint4*)g_Q + blockIdx.x * 1024 + tid;
#pragma unroll
      for (int hd = 0; hd < 8; hd++)
        gq[hd * 128] = make_uint4(pack_bf16(acc[8 * hd], acc[8 * hd + 1]), pack_bf16(acc[8 * hd + 2], acc[8 * hd + 3]),
                                  pack_bf16(acc[8 * hd + 4], acc[8 * hd + 5]), pack_bf16(acc[8 * hd + 6], acc[8 * hd + 7]));
      __syncwarp();
      if (lane == 0) mbar_arrive(BAR_Q2);
    } else if (wg == 3) {
      named_arrive(8, 384);
      named_bar(6, 384);
      const int t = tid & 127;
#pragma unroll
      for (int j = 0; j < 8; j++)
        sts4(sF + 24576 + j * 2048 + t * 16, pack_bf16(acc[8 * j], acc[8 * j + 1]), pack_bf16(acc[8 * j + 2], acc[8 * j + 3]),
             pack_bf16(acc[8 * j + 4], acc[8 * j + 5]), pack_bf16(acc[8 * j + 6], acc[8 * j + 7]));
      named_arrive(7, 256);
    } else {
      uint32_t p[32];
      named_arrive(6, 384);
      if (wg == 2) named_arrive(8, 384);
#pragma unroll
      for (int i = 0; i < 32; i++) p[i] = phi2(acc[2 * i], acc[2 * i + 1]);
      if (wg == 1) {
        named_bar(8, 384);
        const int m = lane >> 3, r = lane & 7;
#pragma unroll
        for (int j = 0; j < 16; j += 2) {
          const int tok = (j + (m >> 1)) * 8 + r;
          const int chunk = w4 * 2 + (m & 1);
          stsm4t(sF + 49152 + tok * 128 + ((chunk ^ r) << 4), p[2 * j], p[2 * j + 1], p[2 * j + 2], p[2 * j + 3]);
        }
        fence_async();
      } else {
        named_bar(7, 256);
        float kv0[4] = {0, 0, 0, 0}, kv1[4] = {0, 0, 0, 0}, z0[4] = {0, 0, 0, 0}, z1[4] = {0, 0, 0, 0};
        const uint32_t one = 0x3F803F80u;
        const int t = tid & 127;
#pragma unroll
        for (int j = 0; j < 8; j++) {
          uint32_t a[4];
          lds4(sF + 24576 + j * 2048 + t * 16, a);
          mma_bf16(kv0, a[0], a[1], a[2], a[3], p[4 * j], p[4 * j + 2]);
          mma_bf16(kv1, a[0], a[1], a[2], a[3], p[4 * j + 1], p[4 * j + 3]);
          mma_bf16(z0, one, one, one, one, p[4 * j], p[4 * j + 2]);
          mma_bf16(z1, one, one, one, one, p[4 * j + 1], p[4 * j + 3]);
        }
        float4* dst = g_kvp + ((ttB * 32 + hq * 4 + w4) * 3) * 32 + lane;
        dst[0] = make_float4(kv0[0], kv0[1], kv1[0], kv1[1]);
        dst[32] = make_float4(kv0[2], kv0[3], kv1[2], kv1[3]);
        dst[64] = make_float4(z0[0], z0[1], z1[0], z1[1]);
      }
      __syncwarp();
      if (lane == 0) mbar_arrive(BAR_BDONE);
    }
  }

  mbar_wait(BAR_Q, 0);
  if (tid == 0) TS(1, 1);
  bool safe = true;
  {
    const uint32_t c63 = 0x1F801F80u + (threadIdx.x >> 20);
    const uint32_t m1 = (gridDim.x >> 20) - 1u;
    const uint64_t dK0 = make_desc(sb + OFF_K, 32768, 128, 0);
    const uint64_t dV0 = make_desc(sb + OFF_V, 128, 32768, 0);
    constexpr uint32_t dKV = ((2048u - 8u)  __H0__ ) + STEPK - (OFF_V - OFF_K) / 16;
    mbar_wait(BAR_KV(0), 0);
#pragma unroll 1
    for (int pass = 0; pass < 2; pass++) {
      const uint64_t dQ = make_desc(sb + OFF_F + (pass * 4 + wg) * 2048, 128, 256, 0);
      float Sm[16], Sp[32], O[12];
      uint32_t P[24];
#pragma unroll
      for (int i = 0; i < 32; i++) Sp[i] = SMAGIC;
#pragma unroll
      for (int i = 0; i < 16; i++) Sm[i] = 0.f;
#pragma unroll
      for (int i = 0; i < 12; i++) O[i] = 0.f;
      fence_regs<16>(Sm); fence_regs<32>(Sp); fence_regs<12>(O);
      if (tid == 0) TS(1, 2 + 2 * pass);
      wg_fence();
      wg_qs32<0>(Sm, dQ, dK0);
      wg_qs64<1>(Sp, dQ, dK0 + 32);
      wg_commit();
      wg_wait<0>();
      fence_regs<16>(Sm); fence_regs<32>(Sp);
      uint32_t vlo = (uint32_t)dV0;
#pragma unroll 1
      for (int seg = 0; seg < 4; seg++) {
        if (pass == 0) {
          if (seg < 3) { mbar_wait(BAR_KV(seg), 0); mbar_wait(BAR_VB(seg), 0); }
        } else if (seg >= 1) {
          if ((tid & 127) == 0) {
            mbar_arrive(BAR_CL(seg));
            if (seg == 3) take_role(sM, wg);
          }
          __syncwarp();
        }
        if ((tid & 127) == 0) TS(4 + wg, pass * 5 + seg);
        const uint32_t vend = vlo + (seg == 0 ? 6 : 5) * STEPK;
#pragma unroll 1
        for (; vlo != vend; vlo += STEPK) {
          uint64_t dK, dV;
          asm("mov.b64 %0, {%1, %2};" : "=l"(dK) : "r"(vlo + dKV), "r"(8u));
          asm("mov.b64 %0, {%1, %2};" : "=l"(dV) : "r"(vlo), "r"(2048u));
#pragma unroll
          for (int i = 0; i < 8; i++) P[i] = pack_bf16(ex2f(Sm[2 * i]), ex2f(Sm[2 * i + 1]));
#pragma unroll
          for (int i = 0; i < 16; i++) P[8 + i] = exp2_pair_fix(Sp[2 * i], Sp[2 * i + 1], c63, m1);
          fence_regs<24>(P);
          wg_fence();
#pragma unroll
          for (int k = 0; k < 6; k++) wg_pv24<1>(O, &P[4 * k], dV + k * 16);
          wg_qs64<1>(Sp, dQ, dK + 32);
          wg_qs32<0>(Sm, dQ, dK);
          wg_commit();
          wg_wait<0>();
          fence_regs<16>(Sm); fence_regs<32>(Sp); fence_regs<12>(O); fence_regs<24>(P);
        }
      }
#pragma unroll
      for (int i = 0; i < 8; i++) P[i] = pack_bf16(ex2f(Sm[2 * i]), ex2f(Sm[2 * i + 1]));
      fence_regs<8>(P);
      wg_fence();
      wg_pv24<1>(O, &P[0], dV0 + 21 * STEPK);
      wg_pv24<1>(O, &P[4], dV0 + 21 * STEPK + 16);
      wg_commit();
      wg_wait<0>();
      fence_regs<12>(O);
      if (pass == 0) {
        uint32_t n[4];
        mbar_wait(BAR_Q2, 0);
        lds4(sM, n);
        const float qn = __half2float(__ushort_as_half((unsigned short)max(max(n[0], n[1]), max(n[2], n[3]))));
        safe = __all_sync(~0u, qn <= __uint_as_float(lds1(sM + 16)));
        if (!safe) break;
      }
      const float l0 = __shfl_sync(~0u, O[8], lane & ~3), l1 = __shfl_sync(~0u, O[10], lane & ~3);
      const float i0 = rcpf(l0), i1 = rcpf(l1);
      stsm4(sb + OFF_F + (pass * 4 + wg) * 2048 + w4 * 512 + (lane & 15) * 32 + (lane >> 4) * 16,
            pack_bf16(O[0] * i0, O[1] * i0), pack_bf16(O[2] * i1, O[3] * i1),
            pack_bf16(O[4] * i0, O[5] * i0), pack_bf16(O[6] * i1, O[7] * i1));
      fence_async();
      __syncwarp();
      if (lane == 0) mbar_arrive(BAR_OD(pass));
      if ((tid & 127) == 0) TS(4 + wg, pass * 5 + 4);
      if (tid == 0) TS(1, 3 + 2 * pass);
      if ((tid & 127) == 0 && pass == 1 && wg > 0) TS(1, 10 + wg);
    }
  }

  if (!safe) {
    if ((tid & 127) == 0) { mbar_arrive(BAR_CL(1)); mbar_arrive(BAR_CL(2)); mbar_arrive(BAR_CL(3)); take_role(sM, wg); }
#pragma unroll 1
    for (int pass = 0; pass < 2; pass++) {
      attn_slow((const uint4*)g_Q + blockIdx.x * 1024 + (pass * 4 + wg) * 128, sb + OFF_F + (pass * 4 + wg) * 2048);
      __syncwarp();
      if (lane == 0) mbar_arrive(BAR_OD(pass));
    }
  }

  {
    named_bar(wg + 1, 128);
    if ((tid & 127) == 0) mbar_arrive(BAR_CL(4));
    const int role = __shfl_sync(~0u, lds1(sM + 32 + wg * 4), 0);
    if ((tid & 127) == 0) TS(4 + wg, 10);
    if (role < 2) {
      float acc[64];
      uint32_t sl = 0;
#pragma unroll 1
      for (int n = 0; n < 8; n++) {
        sl = tail_slots(role == 0 || n < 4 ? n : (n == 4 ? 8 : n - 1));
        const uint32_t w0 = (sl >> 8) & 255, w1 = sl >> 16;
        const uint64_t da = make_desc(sb + (sl & 255) * 8192, 16, 1024, 1), db = make_desc(sb + w0 * 8192, (w1 - w0) * 8192, 1024, 1);
        mbar_wait(BAR_TF(role * 8 + n), 0);
        if ((tid & 127) == 0 && role == 1) TS(2, 2 + n);
        wg_fence();
#pragma unroll
        for (int k = 0; k < 4; k++) wg_ss128<0, 1>(acc, da + k * 2, db + k * 128, (n | k) != 0);
        wg_commit();
        wg_wait<1>();
        if (role == 0 && n >= 1 && (tid & 127) == 0) mbar_arrive(BAR_TE(n - 1));
        __syncwarp();
      }
      wg_wait<0>();
      fence_regs<64>(acc);
      if ((tid & 127) == 0) TS(4 + wg, 11);
      named_bar(wg + 1, 128);
      const int m = lane >> 3, r = lane & 7;
      const uint32_t x0 = sb + ((sl >> 8) & 255) * 8192, x1 = sb + (sl >> 16) * 8192;
#pragma unroll
      for (int j = 0; j < 16; j += 2)
        stsm4((j < 8 ? x0 : x1) + (w4 * 16 + (m & 1) * 8 + r) * 128 + ((((j & 7) + (m >> 1)) ^ r) << 4),
              pack_bf16(acc[4 * j], acc[4 * j + 1]), pack_bf16(acc[4 * j + 2], acc[4 * j + 3]),
              pack_bf16(acc[4 * j + 4], acc[4 * j + 5]), pack_bf16(acc[4 * j + 6], acc[4 * j + 7]));
      fence_async();
      named_bar(wg + 1, 128);
      if (w4 == 0 && elect_one()) {
        tma2d_store(&mOut, x0, (role == 0 ? 512 : 0) + hg * 128, tbA * 64);
        tma2d_store(&mOut, x1, (role == 0 ? 512 : 0) + hg * 128 + 64, tbA * 64);
        bulk_commit();
        asm volatile("cp.async.bulk.wait_group.read 0;" ::: "memory");
        TS(2, 11 + role);
      }
    }
  }
}

typedef CUresult (*EncodeFn)(CUtensorMap*, CUtensorMapDataType, cuuint32_t, void*, const cuuint64_t*, const cuuint64_t*,
                             const cuuint32_t*, const cuuint32_t*, CUtensorMapInterleave, CUtensorMapSwizzle,
                             CUtensorMapL2promotion, CUtensorMapFloatOOBfill);

static void make_map(EncodeFn enc, CUtensorMap* m, const void* ptr, uint64_t cols, uint64_t rows, uint32_t bc, uint32_t br,
                     CUtensorMapSwizzle sw = CU_TENSOR_MAP_SWIZZLE_128B) {
  cuuint64_t dims[2] = {cols, rows};
  cuuint64_t strides[1] = {cols * 2};
  cuuint32_t box[2] = {bc, br};
  cuuint32_t es[2] = {1, 1};
  enc(m, CU_TENSOR_MAP_DATA_TYPE_BFLOAT16, 2, (void*)ptr, dims, strides, box, es, CU_TENSOR_MAP_INTERLEAVE_NONE,
      sw, CU_TENSOR_MAP_L2_PROMOTION_L2_256B, CU_TENSOR_MAP_FLOAT_OOB_FILL_NONE);
}

extern "C" void kernel_launch(void* const* d_in, const int* in_sizes, int n_in, void* d_out, int out_size) {
  (void)in_sizes; (void)n_in; (void)out_size;
  static EncodeFn enc = nullptr;
  static void* pQ = nullptr; static void* pO = nullptr;
  if (!enc) {
    void* fn = nullptr; cudaDriverEntryPointQueryResult qr;
    cudaGetDriverEntryPoint("cuTensorMapEncodeTiled", &fn, cudaEnableDefault, &qr);
    enc = (EncodeFn)fn;
    cudaGetSymbolAddress(&pQ, g_Q);
    cudaGetSymbolAddress(&pO, g_O);
    cudaFuncSetAttribute(k1_main, cudaFuncAttributeMaxDynamicSharedMemorySize, SM_TOTAL);
  }
  CUtensorMap mXA64, mXB, mWq, mWqkv, mQst, mO, mOst, mWoA, mWoB, mOut, mO16;
  make_map(enc, &mXA64, d_in[0], 512, 2048, 64, 64);
  make_map(enc, &mWq, d_in[1], 512, 512, 64, 64);
  make_map(enc, &mWoA, d_in[4], 512, 512, 64, 64);
  make_map(enc, &mXB, d_in[5], 512, 2048, 64, 128);
  make_map(enc, &mWqkv, d_in[6], 1536, 512, 64, 64);
  make_map(enc, &mWoB, d_in[7], 512, 512, 64, 64);
  make_map(enc, &mQst, pQ, 512, 4096, 64, 128);
  make_map(enc, &mO, pO, 512, 4096, 64, 64);
  make_map(enc, &mOst, pO, 512, 4096, 64, 128);
  make_map(enc, &mOut, d_out, 1024, 2048, 64, 64);
  make_map(enc, &mO16, pO, 512, 4096, 16, 64, CU_TENSOR_MAP_SWIZZLE_NONE);
  Params prm{(const __nv_bfloat16*)d_in[2], (const __nv_bfloat16*)d_in[3], (const __nv_bfloat16*)d_in[0]};
  k1_main<<<132, 640, SM_TOTAL, cudaStreamPerThread>>>(mXA64, mXB, mWq, mWqkv, mQst, mOst, mO, mWoA, mWoB, mOut, mO16, prm);
}
```

```cpp
#include <cuda_runtime.h>
#include <cuda_bf16.h>
#include <cuda_fp16.h>
#include <cuda.h>
#include <stdint.h>

#define S_TOK 2048
#define D_MOD 512

__device__ __align__(1024) __nv_bfloat16 g_Q[2 * S_TOK * D_MOD];
__device__ __align__(1024) __nv_bfloat16 g_O[2 * S_TOK * D_MOD];
__device__ __align__(1024) uint4 g_KV[8 * S_TOK];
__device__ __align__(16) uint32_t g_stats[128];
__device__ __align__(16) float4 g_kvp[16 * 32 * 3 * 32];

#define TS(k, i) do {} while (0)
__device__ __forceinline__ uint32_t smem_u32(const void* p) { return (uint32_t)__cvta_generic_to_shared(p); }
__device__ __forceinline__ void mbar_init(uint32_t bar, int cnt) { asm volatile("mbarrier.init.shared::cta.b64 [%0], %1;" :: "r"(bar), "r"(cnt) : "memory"); }
__device__ __forceinline__ void mbar_expect_tx(uint32_t bar, uint32_t bytes) { asm volatile("mbarrier.arrive.expect_tx.shared::cta.b64 _, [%0], %1;" :: "r"(bar), "r"(bytes) : "memory"); }
__device__ __forceinline__ bool mbar_try(uint32_t bar, uint32_t parity) {
  uint32_t ok;
  asm volatile("{\n.reg .pred p;\nmbarrier.try_wait.parity.shared::cta.b64 p, [%1], %2;\nselp.b32 %0, 1, 0, p;\n}\n" : "=r"(ok) : "r"(bar), "r"(parity) : "memory");
  return ok;
}
__device__ __forceinline__ void mbar_wait(uint32_t bar, uint32_t parity) {
  asm volatile("{\n.reg .pred p;\n.reg .u32 c;\nmov.u32 c, 0;\n"
               "LW_%=:\n"
               "mbarrier.try_wait.parity.shared::cta.b64 p, [%0], %1;\n"
               "@p bra LD_%=;\n"
               "add.u32 c, c, 1;\n"
               "setp.lt.u32 p, c, 4000000;\n"
               "@p bra LW_%=;\n"
               "trap;\n"
               "LD_%=:\n}\n" :: "r"(bar), "r"(parity) : "memory");
}
__device__ __forceinline__ void mbar_arrive_cta(uint32_t bar, uint32_t cta) {
  asm volatile("{\n.reg .b32 ra;\nmapa.shared::cluster.u32 ra, %0, %1;\nmbarrier.arrive.shared::cluster.b64 _, [ra];\n}\n" :: "r"(bar), "r"(cta) : "memory");
}
__device__ __forceinline__ void cluster_sync() {
  asm volatile("barrier.cluster.arrive.relaxed.aligned;\nbarrier.cluster.wait.aligned;" ::: "memory");
}
__device__ __forceinline__ void tma2d(uint32_t dst, const CUtensorMap* m, int c0, int c1, uint32_t bar) {
  asm volatile("cp.async.bulk.tensor.2d.shared::cluster.global.mbarrier::complete_tx::bytes [%0], [%1, {%3, %4}], [%2];"
               :: "r"(dst), "l"(m), "r"(bar), "r"(c0), "r"(c1) : "memory");
}
__device__ __forceinline__ void tma2d_mc(uint32_t dst, const CUtensorMap* m, int c0, int c1, uint32_t bar, uint16_t mask) {
  asm volatile("cp.async.bulk.tensor.2d.shared::cluster.global.mbarrier::complete_tx::bytes.multicast::cluster [%0], [%1, {%3, %4}], [%2], %5;"
               :: "r"(dst), "l"(m), "r"(bar), "r"(c0), "r"(c1), "h"(mask) : "memory");
}
__device__ __forceinline__ void tma2d_store(const CUtensorMap* m, uint32_t src, int c0, int c1) {
  asm volatile("cp.async.bulk.tensor.2d.global.shared::cta.bulk_group [%0, {%2, %3}], [%1];"
               :: "l"(m), "r"(src), "r"(c0), "r"(c1) : "memory");
}
__device__ __forceinline__ void bulk_g2s(uint32_t dst, const void* src, uint32_t bytes, uint32_t bar) {
  asm volatile("cp.async.bulk.shared::cluster.global.mbarrier::complete_tx::bytes [%0], [%1], %2, [%3];"
               :: "r"(dst), "l"(src), "r"(bytes), "r"(bar) : "memory");
}
__device__ __forceinline__ void bulk_commit() { asm volatile("cp.async.bulk.commit_group;" ::: "memory"); }
__device__ __forceinline__ void bulk_wait_all() { asm volatile("cp.async.bulk.wait_group 0;" ::: "memory"); }
__device__ __forceinline__ void fence_async() { asm volatile("fence.proxy.async.shared::cta;" ::: "memory"); }
__device__ __forceinline__ void named_bar(int id, int n) { asm volatile("bar.sync %0, %1;" :: "r"(id), "r"(n) : "memory"); }
__device__ __forceinline__ void pdl_launch() { asm volatile("griddepcontrol.launch_dependents;" ::: "memory"); }
__device__ __forceinline__ void pdl_wait() { asm volatile("griddepcontrol.wait;" ::: "memory"); }
__device__ __forceinline__ void wg_fence() { asm volatile("wgmma.fence.sync.aligned;" ::: "memory"); }
__device__ __forceinline__ void wg_commit() { asm volatile("wgmma.commit_group.sync.aligned;" ::: "memory"); }
template <int n> __device__ __forceinline__ void wg_wait() { asm volatile("wgmma.wait_group.sync.aligned %0;" :: "n"(n) : "memory"); }
template <int n> __device__ __forceinline__ void fence_regs(float* r) {
#pragma unroll
  for (int i = 0; i < n; i++) asm volatile("" : "+f"(r[i]) :: "memory");
}
template <int n> __device__ __forceinline__ void fence_regs(uint32_t* r) {
#pragma unroll
  for (int i = 0; i < n; i++) asm volatile("" : "+r"(r[i]) :: "memory");
}
__device__ __forceinline__ uint64_t make_desc(uint32_t addr, uint32_t lbo, uint32_t sbo, uint32_t swz) {
  return (uint64_t)((addr & 0x3FFFF) >> 4) | ((uint64_t)(lbo >> 4) << 16) | ((uint64_t)(sbo >> 4) << 32) | ((uint64_t)swz << 62);
}
__device__ __forceinline__ float ex2f(float x) { float y; asm("ex2.approx.ftz.f32 %0, %1;" : "=f"(y) : "f"(x)); return y; }
__device__ __forceinline__ uint32_t pack_bf16(float lo, float hi) { uint32_t r; asm("cvt.rn.bf16x2.f32 %0, %1, %2;" : "=r"(r) : "f"(hi), "f"(lo)); return r; }
__device__ __forceinline__ uint32_t pack_f16(float lo, float hi) { uint32_t r; asm("cvt.rn.f16x2.f32 %0, %1, %2;" : "=r"(r) : "f"(hi), "f"(lo)); return r; }
__device__ __forceinline__ float bf_lo(uint32_t v) { return __uint_as_float(v << 16); }
__device__ __forceinline__ float bf_hi(uint32_t v) { return __uint_as_float(v & 0xFFFF0000u); }
__device__ __forceinline__ float rbf(float x) { return __bfloat162float(__float2bfloat16_rn(x)); }
__device__ __forceinline__ void stsm4(uint32_t a, uint32_t r0, uint32_t r1, uint32_t r2, uint32_t r3) {
  asm volatile("stmatrix.sync.aligned.m8n8.x4.shared.b16 [%0], {%1,%2,%3,%4};" :: "r"(a), "r"(r0), "r"(r1), "r"(r2), "r"(r3) : "memory");
}
__device__ __forceinline__ void stsm4t(uint32_t a, uint32_t r0, uint32_t r1, uint32_t r2, uint32_t r3) {
  asm volatile("stmatrix.sync.aligned.m8n8.x4.trans.shared.b16 [%0], {%1,%2,%3,%4};" :: "r"(a), "r"(r0), "r"(r1), "r"(r2), "r"(r3) : "memory");
}
__device__ __forceinline__ void mma_bf16(float* d, uint32_t a0, uint32_t a1, uint32_t a2, uint32_t a3, uint32_t b0, uint32_t b1) {
  asm volatile("mma.sync.aligned.m16n8k16.row.col.f32.bf16.bf16.f32 {%0,%1,%2,%3}, {%4,%5,%6,%7}, {%8,%9}, {%0,%1,%2,%3};"
               : "+f"(d[0]), "+f"(d[1]), "+f"(d[2]), "+f"(d[3]) : "r"(a0), "r"(a1), "r"(a2), "r"(a3), "r"(b0), "r"(b1));
}
template<int SD> __device__ __forceinline__ void wg_qs24(float* d, uint64_t da, uint64_t db) {
  asm volatile("wgmma.mma_async.sync.aligned.m64n24k16.f32.f16.f16 {%0,%1,%2,%3,%4,%5,%6,%7,%8,%9,%10,%11}, %12, %13, %14, 1, 1, 0, 0;"
   : "+f"(d[0]),"+f"(d[1]),"+f"(d[2]),"+f"(d[3]),"+f"(d[4]),"+f"(d[5]),"+f"(d[6]),"+f"(d[7]),"+f"(d[8]),"+f"(d[9]),"+f"(d[10]),"+f"(d[11])
   : "l"(da),"l"(db),"n"(SD));
}
template<int SD> __device__ __forceinline__ void wg_qs72(float* d, uint64_t da, uint64_t db) {
  asm volatile("wgmma.mma_async.sync.aligned.m64n72k16.f32.f16.f16 {%0,%1,%2,%3,%4,%5,%6,%7,%8,%9,%10,%11,%12,%13,%14,%15,%16,%17,%18,%19,%20,%21,%22,%23,%24,%25,%26,%27,%28,%29,%30,%31,%32,%33,%34,%35}, %36, %37, %38, 1, 1, 0, 0;"
   : "+f"(d[0]),"+f"(d[1]),"+f"(d[2]),"+f"(d[3]),"+f"(d[4]),"+f"(d[5]),"+f"(d[6]),"+f"(d[7]),"+f"(d[8]),"+f"(d[9]),"+f"(d[10]),"+f"(d[11]),"+f"(d[12]),"+f"(d[13]),"+f"(d[14]),"+f"(d[15]),"+f"(d[16]),"+f"(d[17]),"+f"(d[18]),"+f"(d[19]),"+f"(d[20]),"+f"(d[21]),"+f"(d[22]),"+f"(d[23]),"+f"(d[24]),"+f"(d[25]),"+f"(d[26]),"+f"(d[27]),"+f"(d[28]),"+f"(d[29]),"+f"(d[30]),"+f"(d[31]),"+f"(d[32]),"+f"(d[33]),"+f"(d[34]),"+f"(d[35])
   : "l"(da),"l"(db),"n"(SD));
}
template<int SD> __device__ __forceinline__ void wg_pv24(float* d, const uint32_t* a, uint64_t desc) {
  asm volatile("wgmma.mma_async.sync.aligned.m64n24k16.f32.bf16.bf16 {%0,%1,%2,%3,%4,%5,%6,%7,%8,%9,%10,%11}, {%12,%13,%14,%15}, %16, %17, 1, 1, 1;"
   : "+f"(d[0]),"+f"(d[1]),"+f"(d[2]),"+f"(d[3]),"+f"(d[4]),"+f"(d[5]),"+f"(d[6]),"+f"(d[7]),"+f"(d[8]),"+f"(d[9]),"+f"(d[10]),"+f"(d[11])
   : "r"(a[0]),"r"(a[1]),"r"(a[2]),"r"(a[3]),"l"(desc),"n"(SD));
}
template<int TA, int TB> __device__ __forceinline__ void wg_ss128(float* d, uint64_t da, uint64_t db, int sd) {
  asm volatile("{\n.reg .pred p;\nsetp.ne.b32 p, %66, 0;\n"
   "wgmma.mma_async.sync.aligned.m64n128k16.f32.bf16.bf16 {%0,%1,%2,%3,%4,%5,%6,%7,%8,%9,%10,%11,%12,%13,%14,%15,%16,%17,%18,%19,%20,%21,%22,%23,%24,%25,%26,%27,%28,%29,%30,%31,%32,%33,%34,%35,%36,%37,%38,%39,%40,%41,%42,%43,%44,%45,%46,%47,%48,%49,%50,%51,%52,%53,%54,%55,%56,%57,%58,%59,%60,%61,%62,%63}, %64, %65, p, 1, 1, %67, %68;\n}\n"
   : "+f"(d[0]),"+f"(d[1]),"+f"(d[2]),"+f"(d[3]),"+f"(d[4]),"+f"(d[5]),"+f"(d[6]),"+f"(d[7]),"+f"(d[8]),"+f"(d[9]),"+f"(d[10]),"+f"(d[11]),"+f"(d[12]),"+f"(d[13]),"+f"(d[14]),"+f"(d[15]),"+f"(d[16]),"+f"(d[17]),"+f"(d[18]),"+f"(d[19]),"+f"(d[20]),"+f"(d[21]),"+f"(d[22]),"+f"(d[23]),"+f"(d[24]),"+f"(d[25]),"+f"(d[26]),"+f"(d[27]),"+f"(d[28]),"+f"(d[29]),"+f"(d[30]),"+f"(d[31]),"+f"(d[32]),"+f"(d[33]),"+f"(d[34]),"+f"(d[35]),"+f"(d[36]),"+f"(d[37]),"+f"(d[38]),"+f"(d[39]),"+f"(d[40]),"+f"(d[41]),"+f"(d[42]),"+f"(d[43]),"+f"(d[44]),"+f"(d[45]),"+f"(d[46]),"+f"(d[47]),"+f"(d[48]),"+f"(d[49]),"+f"(d[50]),"+f"(d[51]),"+f"(d[52]),"+f"(d[53]),"+f"(d[54]),"+f"(d[55]),"+f"(d[56]),"+f"(d[57]),"+f"(d[58]),"+f"(d[59]),"+f"(d[60]),"+f"(d[61]),"+f"(d[62]),"+f"(d[63])
   : "l"(da),"l"(db),"r"(sd),"n"(TA),"n"(TB));
}
template<int TA, int TB> __device__ __forceinline__ void wg_ss64(float* d, uint64_t da, uint64_t db, int sd) {
  asm volatile("{\n.reg .pred p;\nsetp.ne.b32 p, %34, 0;\n"
   "wgmma.mma_async.sync.aligned.m64n64k16.f32.bf16.bf16 {%0,%1,%2,%3,%4,%5,%6,%7,%8,%9,%10,%11,%12,%13,%14,%15,%16,%17,%18,%19,%20,%21,%22,%23,%24,%25,%26,%27,%28,%29,%30,%31}, %32, %33, p, 1, 1, %35, %36;\n}\n"
   : "+f"(d[0]),"+f"(d[1]),"+f"(d[2]),"+f"(d[3]),"+f"(d[4]),"+f"(d[5]),"+f"(d[6]),"+f"(d[7]),"+f"(d[8]),"+f"(d[9]),"+f"(d[10]),"+f"(d[11]),"+f"(d[12]),"+f"(d[13]),"+f"(d[14]),"+f"(d[15]),"+f"(d[16]),"+f"(d[17]),"+f"(d[18]),"+f"(d[19]),"+f"(d[20]),"+f"(d[21]),"+f"(d[22]),"+f"(d[23]),"+f"(d[24]),"+f"(d[25]),"+f"(d[26]),"+f"(d[27]),"+f"(d[28]),"+f"(d[29]),"+f"(d[30]),"+f"(d[31])
   : "l"(da),"l"(db),"r"(sd),"n"(TA),"n"(TB));
}
template<int TA, int TB> __device__ __forceinline__ void wg_ss8(float* d, uint64_t da, uint64_t db, int sd) {
  asm volatile("{\n.reg .pred p;\nsetp.ne.b32 p, %6, 0;\n"
   "wgmma.mma_async.sync.aligned.m64n8k16.f32.bf16.bf16 {%0,%1,%2,%3}, %4, %5, p, 1, 1, %7, %8;\n}\n"
   : "+f"(d[0]),"+f"(d[1]),"+f"(d[2]),"+f"(d[3])
   : "l"(da),"l"(db),"r"(sd),"n"(TA),"n"(TB));
}

__device__ __forceinline__ uint32_t phi2(float a, float b) {
  uint32_t r, e;
  asm("cvt.rn.relu.bf16x2.f32 %0, %1, %2;" : "=r"(r) : "f"(b), "f"(a));
  e = pack_bf16(ex2f(a * 1.4426950408889634f), ex2f(b * 1.4426950408889634f));
  asm("add.rn.bf16x2 %0, %0, %1;" : "+r"(e) : "r"(0x35863586u));
  asm("min.NaN.bf16x2 %0, %0, %1;" : "+r"(e) : "r"(0x3F803F80u));
  asm("add.rn.bf16x2 %0, %0, %1;" : "+r"(e) : "r"(r));
  return e;
}

__device__ __forceinline__ void mbar_arrive(uint32_t bar) { asm volatile("mbarrier.arrive.shared::cta.b64 _, [%0];" :: "r"(bar) : "memory"); }
__device__ __forceinline__ void named_arrive(int id, int n) { asm volatile("bar.arrive %0, %1;" :: "r"(id), "r"(n) : "memory"); }
__device__ __forceinline__ void fence_async_all() { asm volatile("fence.proxy.async.global;" ::: "memory"); }
__device__ __forceinline__ void flag_add(uint32_t* f) { asm volatile("fence.acq_rel.gpu;\nred.relaxed.gpu.global.add.u32 [%0], 1;" :: "l"(f) : "memory"); }
#define PUBLISH(f) asm volatile("fence.proxy.async.global;\nred.relaxed.gpu.global.add.u32 [%0], 1;" :: "l"(f) : "memory")
__device__ __forceinline__ void flag_wait(const uint32_t* f, uint32_t target) {
  uint32_t v;
#pragma unroll 1
  for (int it = 0;; it++) {
    asm volatile("ld.acquire.gpu.global.u32 %0, [%1];" : "=r"(v) : "l"(f) : "memory");
    if ((int32_t)(v - target) >= 0) break;
    if (it > 2000000) __trap();
    __nanosleep(64);
  }
}
__device__ __forceinline__ bool elect_one() {
  uint32_t p;
  asm volatile("{\n.reg .pred P;\nelect.sync _|P, 0xFFFFFFFF;\nselp.b32 %0, 1, 0, P;\n}\n" : "=r"(p));
  return p;
}
__device__ __forceinline__ void lds4(uint32_t a, uint32_t* r) {
  asm volatile("ld.shared.v4.b32 {%0,%1,%2,%3}, [%4];" : "=r"(r[0]), "=r"(r[1]), "=r"(r[2]), "=r"(r[3]) : "r"(a) : "memory");
}
__device__ __forceinline__ uint32_t lds1(uint32_t a) { uint32_t r; asm volatile("ld.shared.b32 %0, [%1];" : "=r"(r) : "r"(a) : "memory"); return r; }
__device__ __forceinline__ void sts1(uint32_t a, uint32_t v) { asm volatile("st.shared.b32 [%0], %1;" :: "r"(a), "r"(v) : "memory"); }
__device__ __forceinline__ void sts4(uint32_t a, uint32_t r0, uint32_t r1, uint32_t r2, uint32_t r3) {
  asm volatile("st.shared.v4.b32 [%0], {%1,%2,%3,%4};" :: "r"(a), "r"(r0), "r"(r1), "r"(r2), "r"(r3) : "memory");
}
__device__ __forceinline__ void ldsm4(uint32_t a, uint32_t* r) {
  asm volatile("ldmatrix.sync.aligned.m8n8.x4.shared.b16 {%0,%1,%2,%3}, [%4];" : "=r"(r[0]), "=r"(r[1]), "=r"(r[2]), "=r"(r[3]) : "r"(a) : "memory");
}
__device__ __forceinline__ float rcpf(float x) { float y; asm("rcp.approx.ftz.f32 %0, %1;" : "=f"(y) : "f"(x)); return y; }
__device__ __forceinline__ uint32_t hfma2(uint32_t a, uint32_t b, uint32_t c) { uint32_t r; asm("fma.rn.f16x2 %0, %1, %2, %3;" : "=r"(r) : "r"(a), "r"(b), "r"(c)); return r; }
__device__ __forceinline__ uint32_t hadd2(uint32_t a, uint32_t b) { uint32_t r; asm("add.rn.f16x2 %0, %1, %2;" : "=r"(r) : "r"(a), "r"(b)); return r; }

#define STEPK 96
#define QSCALE 0.36067376022224085f
#define SMAGIC (512.0f + 2.0f * (191.0f - 30.0f - 1.5823545f))
#define VSHIFT 1073741824.0f

__device__ uint32_t g_epoch[132];
__device__ uint32_t g_flag[288 * 8];
#define FLAG_KV (g_flag)
#define FLAG_B(h) (g_flag + (4 + (h)) * 8)
#define FLAG_OA(cta, pass) (g_flag + (16 + (cta) * 2 + (pass)) * 8)
#define FLAG_LM(i) (g_flag + (272 + (i)) * 8)

#define SM_TOTAL (224 * 1024 + 2048 + 1024)
#define OFF_K 0
#define OFF_F 65536
#define OFF_V 131072
#define OFF_MISC (224 * 1024)

#define BAR_FULL(s) (bars + 8 * (s))
#define BAR_EMPTY(s) (bars + 24 + 8 * (s))
#define BAR_KV(c) (bars + 48 + 8 * (c))
#define BAR_BDONE (bars + 80)
#define BAR_Q (bars + 88)
#define BAR_GO (bars + 96)
#define BAR_Q2 (bars + 104)
#define BAR_OD(p) (bars + 112 + 8 * (p))
#define BAR_CL(c) (bars + 128 + 8 * (c))
#define BAR_TE(i) (bars + 168 + 8 * (i))
#define BAR_TF(g) (bars + 224 + 8 * (g))
#define BAR_XA(w) (bars + 352 + 8 * (w))
#define BAR_VB(c) (bars + 384 + 8 * (c))

__device__ __forceinline__ uint32_t exp2_pair_fix(float d0, float d1, uint32_t c63, uint32_t m1) {
  uint32_t w, y, s, r;
  asm("prmt.b32 %0, %1, %2, 0x6521;" : "=r"(w) : "r"(__float_as_uint(d0)), "r"(__float_as_uint(d1)));
  asm("lop3.b32 %0, %1, 0x007F007F, %2, 0xEA;" : "=r"(y) : "r"(w), "r"(c63));
  asm("mad.lo.u32 %0, %1, %2, %3;" : "=r"(s) : "r"(y), "r"(m1), "r"(w));
  asm("fma.rn.bf16x2 %0, %1, %2, %3;" : "=r"(r) : "r"(w), "r"(y), "r"(s));
  return r;
}

__device__ __forceinline__ void attn_slow(const uint4* gq, uint32_t dst) {
  const int t = threadIdx.x & 127;
  const int row = t >> 1, half = t & 1;
  float q[16];
#pragma unroll
  for (int i = 0; i < 4; i++) {
    const uint4 v = gq[(row >> 4) * 32 + (row & 7) * 4 + i];
    const uint32_t lo = (row & 8) ? v.y : v.x, hi = (row & 8) ? v.w : v.z;
    q[2 * i] = bf_lo(lo); q[2 * i + 1] = bf_hi(lo); q[2 * i + 8] = bf_lo(hi); q[2 * i + 9] = bf_hi(hi);
  }
  float m = -INFINITY, l = 0.f, o[16];
#pragma unroll
  for (int i = 0; i < 16; i++) o[i] = 0.f;
#pragma unroll 1
  for (int j = half * 1024; j < half * 1024 + 1024; j++) {
    uint4 ka = g_KV[4 * S_TOK + j], kb = g_KV[5 * S_TOK + j];
    uint4 va = g_KV[6 * S_TOK + j], vb = g_KV[7 * S_TOK + j];
    uint32_t kk[8] = {ka.x, ka.y, ka.z, ka.w, kb.x, kb.y, kb.z, kb.w};
    uint32_t vv[8] = {va.x, va.y, va.z, va.w, vb.x, vb.y, vb.z, vb.w};
    float s = 0.f;
#pragma unroll
    for (int i = 0; i < 8; i++) { s = fmaf(q[2 * i], bf_lo(kk[i]), s); s = fmaf(q[2 * i + 1], bf_hi(kk[i]), s); }
    s = rbf(s) * 0.25f;
    if (s > m) {
      float c = __expf(m - s);
      l *= c;
#pragma unroll
      for (int i = 0; i < 16; i++) o[i] *= c;
      m = s;
    }
    float p = __expf(s - m);
    l += p;
#pragma unroll
    for (int i = 0; i < 8; i++) { o[2 * i] = fmaf(p, bf_lo(vv[i]), o[2 * i]); o[2 * i + 1] = fmaf(p, bf_hi(vv[i]), o[2 * i + 1]); }
  }
  float m2 = __shfl_xor_sync(~0u, m, 1);
  float mm = fmaxf(m, m2);
  float c = __expf(m - mm);
  l *= c; l += __shfl_xor_sync(~0u, l, 1);
  float inv = 1.f / l;
  uint32_t r[8];
#pragma unroll
  for (int i = 0; i < 16; i++) { o[i] *= c; o[i] += __shfl_xor_sync(~0u, o[i], 1); o[i] *= inv; }
#pragma unroll
  for (int i = 0; i < 8; i++) r[i] = pack_bf16(o[2 * i], o[2 * i + 1]);
  if (half == 0) sts4(dst + t * 16, r[0], r[1], r[2], r[3]); else sts4(dst + t * 16, r[4], r[5], r[6], r[7]);
  fence_async();
}

struct Params { const __nv_bfloat16* wk; const __nv_bfloat16* wv; const __nv_bfloat16* xa; };
__device__ __forceinline__ void cp16(uint32_t dst, const void* src) { asm volatile("cp.async.cg.shared.global [%0], [%1], 16;" :: "r"(dst), "l"(src) : "memory"); }

__device__ __forceinline__ void helper_cta(const int h, const uint32_t sb, const uint32_t bars, const int wg, const int w4,
                                           const CUtensorMap* mQ, const CUtensorMap* mOs) {
  const int lane = threadIdx.x & 31;
  mbar_wait(BAR_GO, 0);
  const int cb = wg & 1, col = h * 128 + cb * 64, row0 = S_TOK + (wg >> 1) * 1024;
  const uint32_t buf = sb + wg * 49152;
  if (w4 == 0 && elect_one()) {
    fence_async_all();
#pragma unroll 1
    for (int u = 0; u < 3; u++) {
      mbar_expect_tx(BAR_TF(wg * 3 + u), 16384);
      tma2d(buf + u * 16384, mQ, col, row0 + u * 128, BAR_TF(wg * 3 + u));
    }
  }
  const int head = h * 8 + cb * 4 + w4;
  float4 a0 = make_float4(0, 0, 0, 0), a1 = a0, a2 = a0;
#pragma unroll 8
  for (int tt = 0; tt < 16; tt++) {
    const float4* src = g_kvp + ((tt * 32 + head) * 3) * 32 + lane;
    float4 u = src[0], v = src[32], w = src[64];
    a0.x += u.x; a0.y += u.y; a0.z += u.z; a0.w += u.w;
    a1.x += v.x; a1.y += v.y; a1.z += v.z; a1.w += v.w;
    a2.x += w.x; a2.y += w.y; a2.z += w.z; a2.w += w.w;
  }
  const uint32_t b00 = pack_bf16(a0.x, a0.y), b01 = pack_bf16(a0.z, a0.w);
  const uint32_t b10 = pack_bf16(a1.x, a1.y), b11 = pack_bf16(a1.z, a1.w);
  const uint32_t bz0 = pack_bf16(a2.x, a2.y), bz1 = pack_bf16(a2.z, a2.w);
  const int m = lane >> 3, r = lane & 7;
  const uint32_t off = ((m & 1) * 8 + r) * 128 + (((w4 * 2 + (m >> 1)) ^ r) << 4);
  int s = 0, ph = 0;
#pragma unroll 1
  for (int u = 0; u < 8; u++) {
    const uint32_t bb = buf + s * 16384;
    mbar_wait(BAR_TF(wg * 3 + s), ph);
#pragma unroll
    for (int mt = 0; mt < 8; mt++) {
      uint32_t a[4];
      ldsm4(bb + mt * 2048 + off, a);
      float n0[4] = {0, 0, 0, 0}, n1[4] = {0, 0, 0, 0}, dn[4] = {0, 0, 0, 0};
      mma_bf16(dn, a[0], a[1], a[2], a[3], bz0, bz1);
      mma_bf16(n0, a[0], a[1], a[2], a[3], b00, b01);
      mma_bf16(n1, a[0], a[1], a[2], a[3], b10, b11);
      const float i0 = rcpf(dn[0] + 1e-6f), i1 = rcpf(dn[2] + 1e-6f);
      stsm4(bb + mt * 2048 + off, pack_bf16(n0[0] * i0, n0[1] * i0), pack_bf16(n0[2] * i1, n0[3] * i1),
            pack_bf16(n1[0] * i0, n1[1] * i0), pack_bf16(n1[2] * i1, n1[3] * i1));
    }
    fence_async();
    named_bar(wg + 1, 128);
    if (w4 == 0 && lane == 0) {
      tma2d_store(mOs, bb, col, row0 + u * 128);
      bulk_commit();
      if (u >= 1 && u + 2 < 8) {
        asm volatile("cp.async.bulk.wait_group.read 1;" ::: "memory");
        const int sp = s == 0 ? 2 : s - 1;
        mbar_expect_tx(BAR_TF(wg * 3 + sp), 16384);
        tma2d(buf + sp * 16384, mQ, col, row0 + (u + 2) * 128, BAR_TF(wg * 3 + sp));
      }
    }
    __syncwarp();
    if (++s == 3) { s = 0; ph ^= 1; }
  }
  if (w4 == 0 && lane == 0) {
    bulk_wait_all();
    fence_async_all();
    flag_add(FLAG_LM((h * 2 + cb) * 2 + (wg >> 1)));
    if (wg == 0) TS(1, 8);
  }
}

#define STAGE(s) (sb + (2 - (s)) * 65536)
template <int TR> __device__ __forceinline__ void proj_kb(float* acc, uint32_t st, uint32_t offA, uint32_t offB, int first) {
  const uint64_t da = make_desc(st + offA, TR ? 8192 : 16, 1024, 1);
  const uint64_t db = make_desc(st + offB, TR ? 16 : 8192, 1024, 1);
  wg_fence();
#pragma unroll
  for (int k = 0; k < 4; k++) wg_ss128<TR, 1 - TR>(acc, da + k * (TR ? 128 : 2), db + k * (TR ? 2 : 128), k != 0 || !first);
  wg_commit();
}
template <int TR> __device__ __forceinline__ void proj_loop(float* acc, uint32_t sb, uint32_t bars, uint32_t offA, uint32_t offB,
                                                            int wg, uint32_t sWKV) {
  {
    float kv[4];
    if (threadIdx.x == 0) TS(0, 13);
    mbar_wait(BAR_XA(wg), 0);
    if (threadIdx.x == 0) TS(0, 1);
    const uint64_t da = make_desc(STAGE(2) + wg * 16384, 16, 1024, 1), db = make_desc(sWKV + wg * 2048, 128, 128, 0);
    wg_fence();
#pragma unroll
    for (int k = 0; k < 8; k++) wg_ss8<0, 1>(kv, da + (k >> 2) * 512 + (k & 3) * 2, db + k * 16, k != 0);
    wg_commit();
    wg_wait<0>();
    fence_regs<4>(kv);
    named_bar(wg + 1, 128);
    sts4(sWKV + threadIdx.x * 16, __float_as_uint(kv[0]), __float_as_uint(kv[1]), __float_as_uint(kv[2]), __float_as_uint(kv[3]));
    __syncwarp();
    if ((threadIdx.x & 31) == 0) mbar_arrive(BAR_GO);
  }
  int s = 0, ph = 0, sp = 0;
#pragma unroll 1
  for (int kb = 0; kb < 8; kb++) {
    mbar_wait(BAR_FULL(s), ph);
    if (threadIdx.x == 0) TS(0, 2 + kb);
    proj_kb<TR>(acc, STAGE(s), offA, offB, kb == 0);
    wg_wait<1>();
    if (kb >= 1 && (threadIdx.x & 127) == 0) mbar_arrive(BAR_EMPTY(sp));
    __syncwarp();
    sp = s;
    if (++s == 3) { s = 0; ph ^= 1; }
  }
  wg_wait<0>();
  fence_regs<64>(acc);
}

__device__ __forceinline__ uint32_t tail_slots(int t) {
  const uint32_t lo = t < 4 ? (t < 2 ? (t == 0 ? 0x0C0B0Au : 0x0F0E0Du) : (t == 2 ? 0x100400u : 0x181408u))
                            : (t < 6 ? (t == 4 ? 0x110501u : 0x191502u) : (t == 6 ? 0x161206u : (t == 7 ? 0x1A0703u : 0x1B1713u)));
  return lo;
}

__device__ __forceinline__ void take_role(uint32_t sM, int wg) {
  uint32_t r;
  asm volatile("atom.shared.add.u32 %0, [%1], 1;" : "=r"(r) : "r"(sM + 20) : "memory");
  sts1(sM + 32 + wg * 4, r);
}

__global__ void __launch_bounds__(640, 1)
k1_main(const __grid_constant__ CUtensorMap mXA64, const __grid_constant__ CUtensorMap mXB,
        const __grid_constant__ CUtensorMap mWq, const __grid_constant__ CUtensorMap mWqkv,
        const __grid_constant__ CUtensorMap mQst, const __grid_constant__ CUtensorMap mOst,
        const __grid_constant__ CUtensorMap mO, const __grid_constant__ CUtensorMap mWoA,
        const __grid_constant__ CUtensorMap mWoB, const __grid_constant__ CUtensorMap mOut,
        const __grid_constant__ CUtensorMap mO16, const Params prm) {
  extern __shared__ uint8_t smem_raw[];
  const uint32_t sb = (smem_u32(smem_raw) + 1023u) & ~1023u;
  const uint32_t bars = sb + OFF_MISC, sM = bars + 512, sT = bars + 1024;
  const int tid = threadIdx.x, warp = __shfl_sync(~0u, tid >> 5, 0), wg = warp >> 2, w4 = warp & 3, lane = tid & 31;
  const bool helper = blockIdx.x >= 128;
  if (tid == 0) TS(0, 0);
  const int G = blockIdx.x >> 4, gi = blockIdx.x & 15;
  const int tbA = G * 4 + (gi >> 2), hg = gi & 3;
  const int ttB = (G >> 1) * 4 + (gi >> 2), hq = (G & 1) * 4 + (gi & 3);
  auto issue = [&](int kb, int s) {
    const uint32_t fb = BAR_FULL(s), st = STAGE(s);
    mbar_expect_tx(fb, 65536);
    tma2d(st + 16384, &mXA64, kb * 64, tbA * 64, fb);
    tma2d(st, &mWq, hg * 128, kb * 64, fb);
    tma2d(st + 8192, &mWq, hg * 128 + 64, kb * 64, fb);
    tma2d(st + 49152, &mXB, kb * 64, ttB * 128, fb);
    tma2d(st + 24576, &mWqkv, hq * 64, kb * 64, fb);
    tma2d(st + 32768, &mWqkv, 512 + hq * 64, kb * 64, fb);
    tma2d(st + 40960, &mWqkv, 1024 + hq * 64, kb * 64, fb);
  };
  const uint32_t sOne = sb + OFF_V + 65536, sWKV = sOne + 24576;
  if (warp >= 16) {
    if (warp == 17) {
      if (elect_one()) {
        mbar_init(BAR_BDONE, 8); mbar_init(BAR_Q, 8); mbar_init(BAR_GO, helper ? 1 : 16); mbar_init(BAR_Q2, 5);
        mbar_init(BAR_OD(0), 16); mbar_init(BAR_OD(1), 16); mbar_init(BAR_CL(0), 1); mbar_init(BAR_FULL(2), 1);
#pragma unroll
        for (int i = 0; i < 4; i++) mbar_init(BAR_CL(i + 1), i == 0 ? 5 : 4);
#pragma unroll
        for (int i = 0; i < 3; i++) { mbar_init(BAR_EMPTY(i), 4); mbar_init(BAR_KV(i), 1); mbar_init(BAR_VB(i), 1); }
        sts1(sM + 20, 0);
        asm volatile("fence.mbarrier_init.release.cluster;" ::: "memory");
      }
    } else if (warp == 18) {
      if (elect_one()) {
#pragma unroll
        for (int i = 0; i < 7; i++) mbar_init(BAR_TE(i), 1);
#pragma unroll
        for (int i = 0; i < 16; i++) mbar_init(BAR_TF(i), i < 12 ? 1 : 2);
        asm volatile("fence.mbarrier_init.release.cluster;" ::: "memory");
      }
    } else if (warp == 16 && !helper && elect_one()) {
#pragma unroll
      for (int w = 0; w < 4; w++) mbar_init(BAR_XA(w), 1);
      mbar_init(BAR_FULL(0), 1); mbar_init(BAR_FULL(1), 1);
      asm volatile("fence.mbarrier_init.release.cluster;" ::: "memory");
#pragma unroll
      for (int w = 0; w < 4; w++) {
        mbar_expect_tx(BAR_XA(w), 16384);
        tma2d(STAGE(2) + w * 16384, &mXA64, w * 128, tbA * 64, BAR_XA(w));
        tma2d(STAGE(2) + w * 16384 + 8192, &mXA64, w * 128 + 64, tbA * 64, BAR_XA(w));
      }
      TS(0, 14);
      issue(0, 0);
    }
  } else if (!helper) {
    const uint4 v = __ldg((const uint4*)(hg >= 2 ? prm.wv : prm.wk) + tid * 2 + (hg & 1));
#pragma unroll
    for (int i = 0; i < 3; i++) {
      const int key = tid + i * 512;
      sts4(sOne + key * 16, (key % STEPK) < 24 ? 0x00003F80u : 0x00004E80u, 0u, 0u, 0u);
    }
    sts4(sWKV + tid * 16, v.x, v.y, v.z, v.w);
    fence_async();
  }
  __syncthreads();
  if (wg == 4) {
    if (w4 == 0 && !helper && elect_one()) { issue(1, 1); TS(0, 15); }
    asm volatile("setmaxnreg.dec.sync.aligned.u32 32;");
    const uint32_t ep = g_epoch[blockIdx.x] + 1;
    if (helper) {
      if (w4 == 0 && elect_one()) {
        flag_wait(FLAG_B(blockIdx.x - 128), ep * 32);
        fence_async_all();
        TS(1, 10);
        mbar_arrive(BAR_GO);
        g_epoch[blockIdx.x] = ep;
      }
      return;
    }
    mbar_wait(BAR_GO, 0);
    if (w4 == 0 && elect_one()) issue(2, 2);
    {
      uint32_t a[4], b[4];
      float c[4];
      lds4(sWKV + (tid - 512) * 16, a);
      lds4(sWKV + 2048 + (tid - 512) * 16, b);
#pragma unroll
      for (int i = 0; i < 4; i++) c[i] = __uint_as_float(a[i]) + __uint_as_float(b[i]);
      lds4(sWKV + 4096 + (tid - 512) * 16, a);
      lds4(sWKV + 6144 + (tid - 512) * 16, b);
#pragma unroll
      for (int i = 0; i < 4; i++) c[i] += __uint_as_float(a[i]) + __uint_as_float(b[i]);
      sts1(sT + w4 * 256 + lane * 4, pack_bf16(c[0], c[1]));
      sts1(sT + w4 * 256 + 128 + lane * 4, pack_bf16(c[2], c[3]));
    }
    named_bar(9, 128);
    {
      const int t = tid - 512;
#pragma unroll
      for (int i = 0; i < 4; i++) {
        const int key = 1536 + t + i * 128;
        sts4(sOne + key * 16, (key % STEPK) < 24 ? 0x00003F80u : 0x00004E80u, 0u, 0u, 0u);
      }
      fence_async();
      __syncwarp();
      if (lane == 0) mbar_arrive(BAR_Q);
    }
    if (w4 == 0) {
      int s = 0, ph = 0;
#pragma unroll 1
      for (int kb = 3; kb < 8; kb++) {
        mbar_wait(BAR_EMPTY(s), ph);
        if (elect_one()) issue(kb, s);
        if (++s == 3) { s = 0; ph ^= 1; }
      }
      flag_wait(FLAG_KV, ep * 128);
      fence_async_all();
      if (lane == 0) TS(0, 11);
#pragma unroll 1
      for (int m = 0; m < 2; m++) {
        mbar_wait(m == 0 ? BAR_EMPTY(2) : BAR_EMPTY(0), 1 - m);
        if (elect_one()) {
#pragma unroll
          for (int c = 0; c < 3; c++) {
            const int k0 = c == 0 ? 0 : (c == 1 ? 7 * STEPK : 12 * STEPK), k1 = c == 0 ? 7 * STEPK : (c == 1 ? 12 * STEPK : S_TOK);
            const uint32_t bytes = (k1 - k0) * 16, fb = m == 0 ? BAR_KV(c) : BAR_VB(c);
            mbar_expect_tx(fb, 2 * bytes);
#pragma unroll
            for (int p = 0; p < 2; p++)
              bulk_g2s(sb + m * OFF_V + p * 32768 + k0 * 16, g_KV + (m * 2 + p) * S_TOK + k0, bytes, fb);
          }
        }
      }
      mbar_wait(BAR_CL(1), 0);
      flag_wait(FLAG_LM((lane & 7) * 2 + (tbA >> 4)), ep);
      __syncwarp();
      fence_async_all();
      if (lane == 0) TS(2, 13);
#pragma unroll 1
      for (int n = 0; n < 8; n++) {
        mbar_wait(BAR_CL(n < 4 ? n >> 1 : (n == 4 ? 2 : (n < 7 ? 3 : 4))), 0);
        const uint32_t sl = tail_slots(n), fb = BAR_TF(n);
        if (elect_one()) {
          mbar_expect_tx(fb, 24576);
          tma2d(sb + (sl & 255) * 8192, &mO, n * 64, S_TOK + tbA * 64, fb);
          tma2d(sb + ((sl >> 8) & 255) * 8192, &mWoB, hg * 128, n * 64, fb);
          tma2d(sb + (sl >> 16) * 8192, &mWoB, hg * 128 + 64, n * 64, fb);
        }
      }
      if (lane == 0) g_epoch[blockIdx.x] = ep;
    } else if (w4 == 3) {
      flag_wait(FLAG_KV, ep * 128);
      const uint4 a = *(const uint4*)(g_stats + lane * 4);
      const float kmax2 = __uint_as_float(__reduce_max_sync(~0u, a.x)) + __uint_as_float(__reduce_max_sync(~0u, a.y));
      const float vmax = __uint_as_float(__reduce_max_sync(~0u, max(a.z, a.w)));
      const float lv = vmax > 0.f ? __log2f(vmax) : 0.f;
      const float lim = fminf(90.f, fminf(91.f + lv, 95.f - lv));
      float thr = -1.f;
      if (vmax < 1e27f && kmax2 <= 65536.f && lim > 2.f) thr = fminf(60000.f, (lim * lim - 1.f) / (kmax2 * 1.02f + 1e-30f));
      if (lane == 0) { sts1(sM + 16, __float_as_uint(thr)); mbar_arrive(BAR_Q2); }
      mbar_wait(BAR_CL(3), 0);
      flag_wait(FLAG_OA(tbA * 4 + (lane & 3), 0), ep);
      __syncwarp();
      fence_async_all();
#pragma unroll 1
      for (int n = 0; n < 8; n++) {
        mbar_wait(n == 4 ? BAR_CL(4) : BAR_TE(n < 4 ? n : n - 1), 0);
        const uint32_t sl = tail_slots(n < 4 ? n : (n == 4 ? 8 : n - 1)), fb = BAR_TF(n + 8);
        const int k0 = n < 4 ? n * 128 : ((hg + n) & 3) * 128 + 64;
        if (elect_one()) {
          mbar_expect_tx(fb, n < 4 ? 24576 : 16384);
          if (n < 4) tma2d(sb + (sl & 255) * 8192, &mO, k0, tbA * 64, fb);
          tma2d(sb + ((sl >> 8) & 255) * 8192, &mWoA, hg * 128, k0, fb);
          tma2d(sb + (sl >> 16) * 8192, &mWoA, hg * 128 + 64, k0, fb);
        }
      }
    } else {
      const int tok = (w4 - 1) * 32 + lane;
      int step, col;
      if ((tbA & 3) == 0) {
        const int b8 = tbA >> 2;
        if (tok < 22) { step = tok; col = 24 + b8; }
        else { const int c = tok >= 43; step = tok - 22 - 21 * c; col = 32 + b8 * 2 + c; }
      } else {
        const int b24 = (tbA >> 2) * 3 + (tbA & 3) - 1;
        if (tok < 42) { const int c = tok >= 21; step = tok - 21 * c; col = 48 + b24 * 2 + c; }
        else { step = tok - 42; col = b24; }
      }
      const int kap = step * STEPK + col;
      const bool chained = col >= 24;
      uint32_t v[4], o[4];
      lds4(sT + tok * 16, v);
      g_KV[(4 + hg) * S_TOK + kap] = make_uint4(v[0], v[1], v[2], v[3]);
      float st = 0.f;
      if (hg < 2) {
        o[0] = o[1] = o[2] = o[3] = 0;
        if (chained && step > 0) lds4(sT + tok * 16 - 16, o);
        const float sc = chained ? 2.f : 1.f;
#pragma unroll
        for (int u = 0; u < 4; u++) {
          const float x = bf_lo(v[u]), y = bf_hi(v[u]);
          st += x * x + y * y;
          o[u] = pack_f16((x - bf_lo(o[u])) * sc, (y - bf_hi(o[u])) * sc);
        }
      } else {
        const float sc = chained ? VSHIFT : 1.f;
#pragma unroll
        for (int u = 0; u < 4; u++) { float x = bf_lo(v[u]), y = bf_hi(v[u]); st += fabsf(x) + fabsf(y); o[u] = pack_bf16(x * sc, y * sc); }
      }
      g_KV[hg * S_TOK + kap] = make_uint4(o[0], o[1], o[2], o[3]);
      const uint32_t um = __reduce_max_sync(~0u, __float_as_uint(st) & 0x7FFFFFFFu);
      if (w4 == 2) {
        if (lane == 0) sts1(sM + 24, um);
        named_arrive(10, 64);
        uint32_t rdy = 0;
#pragma unroll 1
        for (int n = 4; n < 8; n++) {
          mbar_wait(n == 4 ? BAR_CL(4) : BAR_TE(n - 1), 0);
          const int hsel = (hg + n) & 3;
#pragma unroll 1
          for (int it = 0; !((rdy >> hsel) & 1); it++) {
            uint32_t fv;
            asm volatile("ld.acquire.gpu.global.u32 %0, [%1];" : "=r"(fv) : "l"(FLAG_OA(tbA * 4 + (lane & 3), 1)) : "memory");
            rdy = __ballot_sync(~0u, (int32_t)(fv - ep) >= 0);
            if (it > 2000000) __trap();
          }
          if (lane == 0 && n == 7) TS(2, 14);
          fence_async_all();
          const uint32_t sl = tail_slots(n == 4 ? 8 : n - 1), fb = BAR_TF(n + 8);
          if (elect_one()) {
            mbar_expect_tx(fb, 8192);
            tma2d(sb + (sl & 255) * 8192, &mO, hsel * 128 + 64, tbA * 64, fb);
          }
        }
      }
      else {
        named_bar(10, 64);
        if (elect_one()) {
          g_stats[tbA * 4 + hg] = max(um, lds1(sM + 24));
          fence_async_all();
          flag_add(FLAG_KV);
          TS(1, 9);
          mbar_wait(BAR_BDONE, 0);
          tma2d_store(&mQst, sb + OFF_F + 49152, hq * 64, S_TOK + ttB * 128);
          bulk_commit();
          bulk_wait_all();
          fence_async_all();
          flag_add(FLAG_B(hq >> 1));
          TS(0, 12);
          mbar_wait(BAR_Q, 0);
          mbar_arrive(BAR_CL(0));
#pragma unroll 1
          for (int p = 0; p < 2; p++) {
            mbar_wait(BAR_OD(p), 0);
#pragma unroll
            for (int w = 0; w < 4; w++) tma2d_store(&mO16, sb + OFF_F + (p * 4 + w) * 2048, hg * 128 + p * 64 + w * 16, tbA * 64);
            bulk_commit();
            bulk_wait_all();
            if (p == 0) mbar_arrive(BAR_CL(1));
            PUBLISH(FLAG_OA(blockIdx.x, p));
          }
          TS(2, 0);
        }
      }
    }
    return;
  }
  if (helper) { helper_cta(blockIdx.x - 128, sb, bars, wg, w4, &mQst, &mOst); return; }

  {
    float acc[64];
    if (wg == 0) proj_loop<0>(acc, sb, bars, 16384, 0, wg, sWKV);
    else proj_loop<1>(acc, sb, bars, 16384 + wg * 8192, 49152, wg, sWKV);
    asm volatile("setmaxnreg.inc.sync.aligned.u32 112;");
    if (tid == 0) TS(0, 10);
    const uint32_t sF = sb + OFF_F;
    if (wg == 0) {
      uint32_t r[32];
      const uint32_t qa = sF + w4 * 512 + ((lane >> 3) & 1) * 256 + (lane >> 4) * 128 + (lane & 7) * 16;
#pragma unroll
      for (int hd = 0; hd < 8; hd++) {
#pragma unroll
        for (int i = 0; i < 4; i++) r[4 * hd + i] = pack_f16(acc[8 * hd + 2 * i] * QSCALE, acc[8 * hd + 2 * i + 1] * QSCALE);
        stsm4(qa + hd * 2048, r[4 * hd], r[4 * hd + 1], r[4 * hd + 2], r[4 * hd + 3]);
        if (hd == 3) {
          fence_async();
          __syncwarp();
          if (lane == 0) mbar_arrive(BAR_Q);
        }
      }
      fence_async();
      uint32_t nmax = 0;
#pragma unroll
      for (int hd = 0; hd < 8; hd++) {
        const uint32_t* q = r + 4 * hd;
        const uint32_t t0 = hfma2(q[2], q[2], hfma2(q[0], q[0], 0u)), t1 = hfma2(q[3], q[3], hfma2(q[1], q[1], 0u));
        uint32_t n = hadd2(__byte_perm(t0, t1, 0x5410), __byte_perm(t0, t1, 0x7632));
        n = hadd2(n, __shfl_xor_sync(~0u, n, 1));
        n = hadd2(n, __shfl_xor_sync(~0u, n, 2));
        nmax = __vmaxu2(nmax, n & 0x7FFF7FFFu);
      }
      nmax = __reduce_max_sync(~0u, max(nmax & 0xFFFFu, nmax >> 16));
      if (lane == 0) sts1(sM + w4 * 4, nmax);
      uint4* gq = (uint4*)g_Q + blockIdx.x * 1024 + tid;
#pragma unroll
      for (int hd = 0; hd < 8; hd++)
        gq[hd * 128] = make_uint4(pack_bf16(acc[8 * hd], acc[8 * hd + 1]), pack_bf16(acc[8 * hd + 2], acc[8 * hd + 3]),
                                  pack_bf16(acc[8 * hd + 4], acc[8 * hd + 5]), pack_bf16(acc[8 * hd + 6], acc[8 * hd + 7]));
      __syncwarp();
      if (lane == 0) mbar_arrive(BAR_Q2);
    } else if (wg == 3) {
      named_arrive(8, 384);
      named_bar(6, 384);
      const int t = tid & 127;
#pragma unroll
      for (int j = 0; j < 8; j++)
        sts4(sF + 24576 + j * 2048 + t * 16, pack_bf16(acc[8 * j], acc[8 * j + 1]), pack_bf16(acc[8 * j + 2], acc[8 * j + 3]),
             pack_bf16(acc[8 * j + 4], acc[8 * j + 5]), pack_bf16(acc[8 * j + 6], acc[8 * j + 7]));
      named_arrive(7, 256);
    } else {
      uint32_t p[32];
      named_arrive(6, 384);
      if (wg == 2) named_arrive(8, 384);
#pragma unroll
      for (int i = 0; i < 32; i++) p[i] = phi2(acc[2 * i], acc[2 * i + 1]);
      if (wg == 1) {
        named_bar(8, 384);
        const int m = lane >> 3, r = lane & 7;
#pragma unroll
        for (int j = 0; j < 16; j += 2) {
          const int tok = (j + (m >> 1)) * 8 + r;
          const int chunk = w4 * 2 + (m & 1);
          stsm4t(sF + 49152 + tok * 128 + ((chunk ^ r) << 4), p[2 * j], p[2 * j + 1], p[2 * j + 2], p[2 * j + 3]);
        }
        fence_async();
      } else {
        named_bar(7, 256);
        float kv0[4] = {0, 0, 0, 0}, kv1[4] = {0, 0, 0, 0}, z0[4] = {0, 0, 0, 0}, z1[4] = {0, 0, 0, 0};
        const uint32_t one = 0x3F803F80u;
        const int t = tid & 127;
#pragma unroll
        for (int j = 0; j < 8; j++) {
          uint32_t a[4];
          lds4(sF + 24576 + j * 2048 + t * 16, a);
          mma_bf16(kv0, a[0], a[1], a[2], a[3], p[4 * j], p[4 * j + 2]);
          mma_bf16(kv1, a[0], a[1], a[2], a[3], p[4 * j + 1], p[4 * j + 3]);
          mma_bf16(z0, one, one, one, one, p[4 * j], p[4 * j + 2]);
          mma_bf16(z1, one, one, one, one, p[4 * j + 1], p[4 * j + 3]);
        }
        float4* dst = g_kvp + ((ttB * 32 + hq * 4 + w4) * 3) * 32 + lane;
        dst[0] = make_float4(kv0[0], kv0[1], kv1[0], kv1[1]);
        dst[32] = make_float4(kv0[2], kv0[3], kv1[2], kv1[3]);
        dst[64] = make_float4(z0[0], z0[1], z1[0], z1[1]);
      }
      __syncwarp();
      if (lane == 0) mbar_arrive(BAR_BDONE);
    }
  }

  bool safe = true;
  {
    const uint32_t c63 = 0x1F801F80u + (threadIdx.x >> 20);
    const uint32_t m1 = (gridDim.x >> 20) - 1u;
    const uint64_t dK0 = make_desc(sb + OFF_K, 32768, 128, 0);
    const uint64_t dV0 = make_desc(sb + OFF_V, 128, 32768, 0);
    constexpr uint32_t dKV = ((2048u - 8u)  __H0__ ) + STEPK - (OFF_V - OFF_K) / 16;
    float Sm[12], Sp[36], O[12];
    uint32_t P[24];
    uint64_t dQ = make_desc(sb + OFF_F + wg * 2048, 128, 256, 0);
#pragma unroll
    for (int i = 0; i < 36; i++) Sp[i] = SMAGIC;
#pragma unroll
    for (int i = 0; i < 12; i++) Sm[i] = 0.f;
    fence_regs<12>(Sm); fence_regs<36>(Sp);
    mbar_wait(BAR_Q, 0);
    mbar_wait(BAR_KV(0), 0);
    wg_fence();
    wg_qs72<1>(Sp, dQ, dK0 + 24);
    wg_qs24<0>(Sm, dQ, dK0);
    wg_commit();
    wg_wait<0>();
    fence_regs<12>(Sm); fence_regs<36>(Sp);
#pragma unroll 1
    for (int pass = 0; pass < 2; pass++) {
#pragma unroll
      for (int i = 0; i < 12; i++) O[i] = 0.f;
      fence_regs<12>(O);
      if (tid == 0) TS(1, 2 + 2 * pass);
      uint32_t vlo = (uint32_t)dV0;
#pragma unroll 1
      for (int seg = 0; seg < 4; seg++) {
        if (pass == 0) {
          if (seg < 3) { mbar_wait(BAR_KV(seg), 0); mbar_wait(BAR_VB(seg), 0); }
        } else if (seg >= 1) {
          if ((tid & 127) == 0) {
            mbar_arrive(BAR_CL(seg));
            if (seg == 3) take_role(sM, wg);
          }
          __syncwarp();
        }
        if ((tid & 127) == 0) TS(4 + wg, pass * 5 + seg);
        const uint32_t vend = vlo + (seg == 0 ? 6 : 5) * STEPK;
#pragma unroll 1
        for (; vlo != vend; vlo += STEPK) {
          uint64_t dK, dV;
          asm("mov.b64 %0, {%1, %2};" : "=l"(dK) : "r"(vlo + dKV), "r"(8u));
          asm("mov.b64 %0, {%1, %2};" : "=l"(dV) : "r"(vlo), "r"(2048u));
#pragma unroll
          for (int i = 0; i < 6; i++) P[i] = pack_bf16(ex2f(Sm[2 * i]), ex2f(Sm[2 * i + 1]));
#pragma unroll
          for (int i = 0; i < 18; i++) P[6 + i] = exp2_pair_fix(Sp[2 * i], Sp[2 * i + 1], c63, m1);
          fence_regs<24>(P);
          wg_fence();
#pragma unroll
          for (int k = 0; k < 6; k++) wg_pv24<1>(O, &P[4 * k], dV + k * 16);
          wg_qs72<1>(Sp, dQ, dK + 24);
          wg_qs24<0>(Sm, dQ, dK);
          wg_commit();
          wg_wait<0>();
          fence_regs<12>(Sm); fence_regs<36>(Sp); fence_regs<12>(O); fence_regs<24>(P);
        }
      }
#pragma unroll
      for (int i = 0; i < 6; i++) P[i] = pack_bf16(ex2f(Sm[2 * i]), ex2f(Sm[2 * i + 1]));
      P[6] = exp2_pair_fix(Sp[0], Sp[1], c63, m1);
      P[7] = exp2_pair_fix(Sp[2], Sp[3], c63, m1);
      fence_regs<8>(P);
#pragma unroll
      for (int i = 0; i < 36; i++) Sp[i] = SMAGIC;
      fence_regs<36>(Sp);
      if (pass == 0) mbar_wait(BAR_Q2, 0);
      const uint32_t sO = sb + OFF_F + (pass * 4 + wg) * 2048;
      dQ += 512;
      wg_fence();
      wg_pv24<1>(O, &P[0], dV0 + 21 * STEPK);
      wg_pv24<1>(O, &P[4], dV0 + 21 * STEPK + 16);
      wg_commit();
      wg_qs72<1>(Sp, dQ, dK0 + 24);
      wg_qs24<0>(Sm, dQ, dK0);
      wg_commit();
      wg_wait<1>();
      fence_regs<12>(O);
      const float l0 = __shfl_sync(~0u, O[8], lane & ~3), l1 = __shfl_sync(~0u, O[10], lane & ~3);
      const float i0 = rcpf(l0), i1 = rcpf(l1);
      stsm4(sO + w4 * 512 + (lane & 15) * 32 + (lane >> 4) * 16,
            pack_bf16(O[0] * i0, O[1] * i0), pack_bf16(O[2] * i1, O[3] * i1),
            pack_bf16(O[4] * i0, O[5] * i0), pack_bf16(O[6] * i1, O[7] * i1));
      fence_async();
      {
        uint32_t n[4];
        lds4(sM, n);
        const float qn = __half2float(__ushort_as_half((unsigned short)max(max(n[0], n[1]), max(n[2], n[3]))));
        safe = __all_sync(~0u, qn <= __uint_as_float(lds1(sM + 16)));
      }
      if (safe && lane == 0) mbar_arrive(BAR_OD(pass));
      wg_wait<0>();
      fence_regs<12>(Sm); fence_regs<36>(Sp);
      if (!safe) break;
      if ((tid & 127) == 0) TS(4 + wg, pass * 5 + 4);
      if (tid == 0) TS(1, 3 + 2 * pass);
    }
  }
  if (!safe) {
    if ((tid & 127) == 0) { mbar_arrive(BAR_CL(1)); mbar_arrive(BAR_CL(2)); mbar_arrive(BAR_CL(3)); take_role(sM, wg); }
#pragma unroll 1
    for (int pass = 0; pass < 2; pass++) {
      attn_slow((const uint4*)g_Q + blockIdx.x * 1024 + (pass * 4 + wg) * 128, sb + OFF_F + (pass * 4 + wg) * 2048);
      __syncwarp();
      if (lane == 0) mbar_arrive(BAR_OD(pass));
    }
  }

  {
    named_bar(wg + 1, 128);
    if ((tid & 127) == 0) mbar_arrive(BAR_CL(4));
    const int role = __shfl_sync(~0u, lds1(sM + 32 + wg * 4), 0);
    if ((tid & 127) == 0) TS(4 + wg, 10);
    if (role < 2) {
      float acc[64];
      uint32_t sl = 0;
#pragma unroll 1
      for (int n = 0; n < 8; n++) {
        sl = tail_slots(role == 0 || n < 4 ? n : (n == 4 ? 8 : n - 1));
        const uint32_t w0 = (sl >> 8) & 255, w1 = sl >> 16;
        const uint64_t da = make_desc(sb + (sl & 255) * 8192, 16, 1024, 1), db = make_desc(sb + w0 * 8192, (w1 - w0) * 8192, 1024, 1);
        mbar_wait(BAR_TF(role * 8 + n), 0);
        if ((tid & 127) == 0 && role == 1) TS(2, 2 + n);
        wg_fence();
#pragma unroll
        for (int k = 0; k < 4; k++) wg_ss128<0, 1>(acc, da + k * 2, db + k * 128, (n | k) != 0);
        wg_commit();
        wg_wait<1>();
        if (role == 0 && n >= 1 && (tid & 127) == 0) mbar_arrive(BAR_TE(n - 1));
        __syncwarp();
      }
      wg_wait<0>();
      fence_regs<64>(acc);
      if ((tid & 127) == 0) TS(4 + wg, 11);
      named_bar(wg + 1, 128);
      const int m = lane >> 3, r = lane & 7;
      const uint32_t x0 = sb + ((sl >> 8) & 255) * 8192, x1 = sb + (sl >> 16) * 8192;
#pragma unroll
      for (int j = 0; j < 16; j += 2)
        stsm4((j < 8 ? x0 : x1) + (w4 * 16 + (m & 1) * 8 + r) * 128 + ((((j & 7) + (m >> 1)) ^ r) << 4),
              pack_bf16(acc[4 * j], acc[4 * j + 1]), pack_bf16(acc[4 * j + 2], acc[4 * j + 3]),
              pack_bf16(acc[4 * j + 4], acc[4 * j + 5]), pack_bf16(acc[4 * j + 6], acc[4 * j + 7]));
      fence_async();
      named_bar(wg + 1, 128);
      if (w4 == 0 && elect_one()) {
        tma2d_store(&mOut, x0, (role == 0 ? 512 : 0) + hg * 128, tbA * 64);
        tma2d_store(&mOut, x1, (role == 0 ? 512 : 0) + hg * 128 + 64, tbA * 64);
        bulk_commit();
        asm volatile("cp.async.bulk.wait_group.read 0;" ::: "memory");
        TS(2, 11 + role);
      }
    }
  }
}

typedef CUresult (*EncodeFn)(CUtensorMap*, CUtensorMapDataType, cuuint32_t, void*, const cuuint64_t*, const cuuint64_t*,
                             const cuuint32_t*, const cuuint32_t*, CUtensorMapInterleave, CUtensorMapSwizzle,
                             CUtensorMapL2promotion, CUtensorMapFloatOOBfill);

static void make_map(EncodeFn enc, CUtensorMap* m, const void* ptr, uint64_t cols, uint64_t rows, uint32_t bc, uint32_t br,
                     CUtensorMapSwizzle sw = CU_TENSOR_MAP_SWIZZLE_128B) {
  cuuint64_t dims[2] = {cols, rows};
  cuuint64_t strides[1] = {cols * 2};
  cuuint32_t box[2] = {bc, br};
  cuuint32_t es[2] = {1, 1};
  enc(m, CU_TENSOR_MAP_DATA_TYPE_BFLOAT16, 2, (void*)ptr, dims, strides, box, es, CU_TENSOR_MAP_INTERLEAVE_NONE,
      sw, CU_TENSOR_MAP_L2_PROMOTION_L2_256B, CU_TENSOR_MAP_FLOAT_OOB_FILL_NONE);
}

extern "C" void kernel_launch(void* const* d_in, const int* in_sizes, int n_in, void* d_out, int out_size) {
  (void)in_sizes; (void)n_in; (void)out_size;
  static EncodeFn enc = nullptr;
  static void* pQ = nullptr; static void* pO = nullptr;
  if (!enc) {
    void* fn = nullptr; cudaDriverEntryPointQueryResult qr;
    cudaGetDriverEntryPoint("cuTensorMapEncodeTiled", &fn, cudaEnableDefault, &qr);
    enc = (EncodeFn)fn;
    cudaGetSymbolAddress(&pQ, g_Q);
    cudaGetSymbolAddress(&pO, g_O);
    cudaFuncSetAttribute(k1_main, cudaFuncAttributeMaxDynamicSharedMemorySize, SM_TOTAL);
  }
  CUtensorMap mXA64, mXB, mWq, mWqkv, mQst, mO, mOst, mWoA, mWoB, mOut, mO16;
  make_map(enc, &mXA64, d_in[0], 512, 2048, 64, 64);
  make_map(enc, &mWq, d_in[1], 512, 512, 64, 64);
  make_map(enc, &mWoA, d_in[4], 512, 512, 64, 64);
  make_map(enc, &mXB, d_in[5], 512, 2048, 64, 128);
  make_map(enc, &mWqkv, d_in[6], 1536, 512, 64, 64);
  make_map(enc, &mWoB, d_in[7], 512, 512, 64, 64);
  make_map(enc, &mQst, pQ, 512, 4096, 64, 128);
  make_map(enc, &mO, pO, 512, 4096, 64, 64);
  make_map(enc, &mOst, pO, 512, 4096, 64, 128);
  make_map(enc, &mOut, d_out, 1024, 2048, 64, 64);
  make_map(enc, &mO16, pO, 512, 4096, 16, 64, CU_TENSOR_MAP_SWIZZLE_NONE);
  Params prm{(const __nv_bfloat16*)d_in[2], (const __nv_bfloat16*)d_in[3], (const __nv_bfloat16*)d_in[0]};
  k1_main<<<132, 640, SM_TOTAL, cudaStreamPerThread>>>(mXA64, mXB, mWq, mWqkv, mQst, mOst, mO, mWoA, mWoB, mOut, mO16, prm);
}
```

```cpp
#include <cuda_runtime.h>
#include <cuda_bf16.h>
#include <cuda_fp16.h>
#include <cuda.h>
#include <stdint.h>

#define S_TOK 2048
#define D_MOD 512

__device__ __align__(1024) __nv_bfloat16 g_Q[2 * S_TOK * D_MOD];
__device__ __align__(1024) __nv_bfloat16 g_O[2 * S_TOK * D_MOD];
__device__ __align__(1024) uint4 g_KV[8 * S_TOK];
__device__ __align__(16) uint32_t g_stats[128];
__device__ __align__(16) float4 g_kvp[16 * 32 * 3 * 32];

#define TS(k, i) do {} while (0)
__device__ __forceinline__ uint32_t smem_u32(const void* p) { return (uint32_t)__cvta_generic_to_shared(p); }
__device__ __forceinline__ void mbar_init(uint32_t bar, int cnt) { asm volatile("mbarrier.init.shared::cta.b64 [%0], %1;" :: "r"(bar), "r"(cnt) : "memory"); }
__device__ __forceinline__ void mbar_expect_tx(uint32_t bar, uint32_t bytes) { asm volatile("mbarrier.arrive.expect_tx.shared::cta.b64 _, [%0], %1;" :: "r"(bar), "r"(bytes) : "memory"); }
__device__ __forceinline__ bool mbar_try(uint32_t bar, uint32_t parity) {
  uint32_t ok;
  asm volatile("{\n.reg .pred p;\nmbarrier.try_wait.parity.shared::cta.b64 p, [%1], %2;\nselp.b32 %0, 1, 0, p;\n}\n" : "=r"(ok) : "r"(bar), "r"(parity) : "memory");
  return ok;
}
__device__ __forceinline__ void mbar_wait(uint32_t bar, uint32_t parity) {
  asm volatile("{\n.reg .pred p;\n.reg .u32 c;\nmov.u32 c, 0;\n"
               "LW_%=:\n"
               "mbarrier.try_wait.parity.shared::cta.b64 p, [%0], %1;\n"
               "@p bra LD_%=;\n"
               "add.u32 c, c, 1;\n"
               "setp.lt.u32 p, c, 4000000;\n"
               "@p bra LW_%=;\n"
               "trap;\n"
               "LD_%=:\n}\n" :: "r"(bar), "r"(parity) : "memory");
}
__device__ __forceinline__ void mbar_arrive_cta(uint32_t bar, uint32_t cta) {
  asm volatile("{\n.reg .b32 ra;\nmapa.shared::cluster.u32 ra, %0, %1;\nmbarrier.arrive.shared::cluster.b64 _, [ra];\n}\n" :: "r"(bar), "r"(cta) : "memory");
}
__device__ __forceinline__ void cluster_sync() {
  asm volatile("barrier.cluster.arrive.relaxed.aligned;\nbarrier.cluster.wait.aligned;" ::: "memory");
}
__device__ __forceinline__ void tma2d(uint32_t dst, const CUtensorMap* m, int c0, int c1, uint32_t bar) {
  asm volatile("cp.async.bulk.tensor.2d.shared::cluster.global.mbarrier::complete_tx::bytes [%0], [%1, {%3, %4}], [%2];"
               :: "r"(dst), "l"(m), "r"(bar), "r"(c0), "r"(c1) : "memory");
}
__device__ __forceinline__ void tma2d_mc(uint32_t dst, const CUtensorMap* m, int c0, int c1, uint32_t bar, uint16_t mask) {
  asm volatile("cp.async.bulk.tensor.2d.shared::cluster.global.mbarrier::complete_tx::bytes.multicast::cluster [%0], [%1, {%3, %4}], [%2], %5;"
               :: "r"(dst), "l"(m), "r"(bar), "r"(c0), "r"(c1), "h"(mask) : "memory");
}
__device__ __forceinline__ void tma2d_store(const CUtensorMap* m, uint32_t src, int c0, int c1) {
  asm volatile("cp.async.bulk.tensor.2d.global.shared::cta.bulk_group [%0, {%2, %3}], [%1];"
               :: "l"(m), "r"(src), "r"(c0), "r"(c1) : "memory");
}
__device__ __forceinline__ void bulk_g2s(uint32_t dst, const void* src, uint32_t bytes, uint32_t bar) {
  asm volatile("cp.async.bulk.shared::cluster.global.mbarrier::complete_tx::bytes [%0], [%1], %2, [%3];"
               :: "r"(dst), "l"(src), "r"(bytes), "r"(bar) : "memory");
}
__device__ __forceinline__ void bulk_commit() { asm volatile("cp.async.bulk.commit_group;" ::: "memory"); }
__device__ __forceinline__ void bulk_wait_all() { asm volatile("cp.async.bulk.wait_group 0;" ::: "memory"); }
__device__ __forceinline__ void fence_async() { asm volatile("fence.proxy.async.shared::cta;" ::: "memory"); }
__device__ __forceinline__ void named_bar(int id, int n) { asm volatile("bar.sync %0, %1;" :: "r"(id), "r"(n) : "memory"); }
__device__ __forceinline__ void pdl_launch() { asm volatile("griddepcontrol.launch_dependents;" ::: "memory"); }
__device__ __forceinline__ void pdl_wait() { asm volatile("griddepcontrol.wait;" ::: "memory"); }
__device__ __forceinline__ void wg_fence() { asm volatile("wgmma.fence.sync.aligned;" ::: "memory"); }
__device__ __forceinline__ void wg_commit() { asm volatile("wgmma.commit_group.sync.aligned;" ::: "memory"); }
template <int n> __device__ __forceinline__ void wg_wait() { asm volatile("wgmma.wait_group.sync.aligned %0;" :: "n"(n) : "memory"); }
template <int n> __device__ __forceinline__ void fence_regs(float* r) {
#pragma unroll
  for (int i = 0; i < n; i++) asm volatile("" : "+f"(r[i]) :: "memory");
}
template <int n> __device__ __forceinline__ void fence_regs(uint32_t* r) {
#pragma unroll
  for (int i = 0; i < n; i++) asm volatile("" : "+r"(r[i]) :: "memory");
}
__device__ __forceinline__ uint64_t make_desc(uint32_t addr, uint32_t lbo, uint32_t sbo, uint32_t swz) {
  return (uint64_t)((addr & 0x3FFFF) >> 4) | ((uint64_t)(lbo >> 4) << 16) | ((uint64_t)(sbo >> 4) << 32) | ((uint64_t)swz << 62);
}
__device__ __forceinline__ float ex2f(float x) { float y; asm("ex2.approx.ftz.f32 %0, %1;" : "=f"(y) : "f"(x)); return y; }
__device__ __forceinline__ uint32_t pack_bf16(float lo, float hi) { uint32_t r; asm("cvt.rn.bf16x2.f32 %0, %1, %2;" : "=r"(r) : "f"(hi), "f"(lo)); return r; }
__device__ __forceinline__ uint32_t pack_f16(float lo, float hi) { uint32_t r; asm("cvt.rn.f16x2.f32 %0, %1, %2;" : "=r"(r) : "f"(hi), "f"(lo)); return r; }
__device__ __forceinline__ float bf_lo(uint32_t v) { return __uint_as_float(v << 16); }
__device__ __forceinline__ float bf_hi(uint32_t v) { return __uint_as_float(v & 0xFFFF0000u); }
__device__ __forceinline__ float rbf(float x) { return __bfloat162float(__float2bfloat16_rn(x)); }
__device__ __forceinline__ void stsm4(uint32_t a, uint32_t r0, uint32_t r1, uint32_t r2, uint32_t r3) {
  asm volatile("stmatrix.sync.aligned.m8n8.x4.shared.b16 [%0], {%1,%2,%3,%4};" :: "r"(a), "r"(r0), "r"(r1), "r"(r2), "r"(r3) : "memory");
}
__device__ __forceinline__ void stsm4t(uint32_t a, uint32_t r0, uint32_t r1, uint32_t r2, uint32_t r3) {
  asm volatile("stmatrix.sync.aligned.m8n8.x4.trans.shared.b16 [%0], {%1,%2,%3,%4};" :: "r"(a), "r"(r0), "r"(r1), "r"(r2), "r"(r3) : "memory");
}
__device__ __forceinline__ void mma_bf16(float* d, uint32_t a0, uint32_t a1, uint32_t a2, uint32_t a3, uint32_t b0, uint32_t b1) {
  asm volatile("mma.sync.aligned.m16n8k16.row.col.f32.bf16.bf16.f32 {%0,%1,%2,%3}, {%4,%5,%6,%7}, {%8,%9}, {%0,%1,%2,%3};"
               : "+f"(d[0]), "+f"(d[1]), "+f"(d[2]), "+f"(d[3]) : "r"(a0), "r"(a1), "r"(a2), "r"(a3), "r"(b0), "r"(b1));
}
template<int SD> __device__ __forceinline__ void wg_qs24(float* d, uint64_t da, uint64_t db) {
  asm volatile("wgmma.mma_async.sync.aligned.m64n24k16.f32.f16.f16 {%0,%1,%2,%3,%4,%5,%6,%7,%8,%9,%10,%11}, %12, %13, %14, 1, 1, 0, 0;"
   : "+f"(d[0]),"+f"(d[1]),"+f"(d[2]),"+f"(d[3]),"+f"(d[4]),"+f"(d[5]),"+f"(d[6]),"+f"(d[7]),"+f"(d[8]),"+f"(d[9]),"+f"(d[10]),"+f"(d[11])
   : "l"(da),"l"(db),"n"(SD));
}
template<int SD> __device__ __forceinline__ void wg_qs72(float* d, uint64_t da, uint64_t db) {
  asm volatile("wgmma.mma_async.sync.aligned.m64n72k16.f32.f16.f16 {%0,%1,%2,%3,%4,%5,%6,%7,%8,%9,%10,%11,%12,%13,%14,%15,%16,%17,%18,%19,%20,%21,%22,%23,%24,%25,%26,%27,%28,%29,%30,%31,%32,%33,%34,%35}, %36, %37, %38, 1, 1, 0, 0;"
   : "+f"(d[0]),"+f"(d[1]),"+f"(d[2]),"+f"(d[3]),"+f"(d[4]),"+f"(d[5]),"+f"(d[6]),"+f"(d[7]),"+f"(d[8]),"+f"(d[9]),"+f"(d[10]),"+f"(d[11]),"+f"(d[12]),"+f"(d[13]),"+f"(d[14]),"+f"(d[15]),"+f"(d[16]),"+f"(d[17]),"+f"(d[18]),"+f"(d[19]),"+f"(d[20]),"+f"(d[21]),"+f"(d[22]),"+f"(d[23]),"+f"(d[24]),"+f"(d[25]),"+f"(d[26]),"+f"(d[27]),"+f"(d[28]),"+f"(d[29]),"+f"(d[30]),"+f"(d[31]),"+f"(d[32]),"+f"(d[33]),"+f"(d[34]),"+f"(d[35])
   : "l"(da),"l"(db),"n"(SD));
}
template<int SD> __device__ __forceinline__ void wg_pv24(float* d, const uint32_t* a, uint64_t desc) {
  asm volatile("wgmma.mma_async.sync.aligned.m64n24k16.f32.bf16.bf16 {%0,%1,%2,%3,%4,%5,%6,%7,%8,%9,%10,%11}, {%12,%13,%14,%15}, %16, %17, 1, 1, 1;"
   : "+f"(d[0]),"+f"(d[1]),"+f"(d[2]),"+f"(d[3]),"+f"(d[4]),"+f"(d[5]),"+f"(d[6]),"+f"(d[7]),"+f"(d[8]),"+f"(d[9]),"+f"(d[10]),"+f"(d[11])
   : "r"(a[0]),"r"(a[1]),"r"(a[2]),"r"(a[3]),"l"(desc),"n"(SD));
}
template<int TA, int TB> __device__ __forceinline__ void wg_ss128(float* d, uint64_t da, uint64_t db, int sd) {
  asm volatile("{\n.reg .pred p;\nsetp.ne.b32 p, %66, 0;\n"
   "wgmma.mma_async.sync.aligned.m64n128k16.f32.bf16.bf16 {%0,%1,%2,%3,%4,%5,%6,%7,%8,%9,%10,%11,%12,%13,%14,%15,%16,%17,%18,%19,%20,%21,%22,%23,%24,%25,%26,%27,%28,%29,%30,%31,%32,%33,%34,%35,%36,%37,%38,%39,%40,%41,%42,%43,%44,%45,%46,%47,%48,%49,%50,%51,%52,%53,%54,%55,%56,%57,%58,%59,%60,%61,%62,%63}, %64, %65, p, 1, 1, %67, %68;\n}\n"
   : "+f"(d[0]),"+f"(d[1]),"+f"(d[2]),"+f"(d[3]),"+f"(d[4]),"+f"(d[5]),"+f"(d[6]),"+f"(d[7]),"+f"(d[8]),"+f"(d[9]),"+f"(d[10]),"+f"(d[11]),"+f"(d[12]),"+f"(d[13]),"+f"(d[14]),"+f"(d[15]),"+f"(d[16]),"+f"(d[17]),"+f"(d[18]),"+f"(d[19]),"+f"(d[20]),"+f"(d[21]),"+f"(d[22]),"+f"(d[23]),"+f"(d[24]),"+f"(d[25]),"+f"(d[26]),"+f"(d[27]),"+f"(d[28]),"+f"(d[29]),"+f"(d[30]),"+f"(d[31]),"+f"(d[32]),"+f"(d[33]),"+f"(d[34]),"+f"(d[35]),"+f"(d[36]),"+f"(d[37]),"+f"(d[38]),"+f"(d[39]),"+f"(d[40]),"+f"(d[41]),"+f"(d[42]),"+f"(d[43]),"+f"(d[44]),"+f"(d[45]),"+f"(d[46]),"+f"(d[47]),"+f"(d[48]),"+f"(d[49]),"+f"(d[50]),"+f"(d[51]),"+f"(d[52]),"+f"(d[53]),"+f"(d[54]),"+f"(d[55]),"+f"(d[56]),"+f"(d[57]),"+f"(d[58]),"+f"(d[59]),"+f"(d[60]),"+f"(d[61]),"+f"(d[62]),"+f"(d[63])
   : "l"(da),"l"(db),"r"(sd),"n"(TA),"n"(TB));
}
template<int TA, int TB> __device__ __forceinline__ void wg_ss64(float* d, uint64_t da, uint64_t db, int sd) {
  asm volatile("{\n.reg .pred p;\nsetp.ne.b32 p, %34, 0;\n"
   "wgmma.mma_async.sync.aligned.m64n64k16.f32.bf16.bf16 {%0,%1,%2,%3,%4,%5,%6,%7,%8,%9,%10,%11,%12,%13,%14,%15,%16,%17,%18,%19,%20,%21,%22,%23,%24,%25,%26,%27,%28,%29,%30,%31}, %32, %33, p, 1, 1, %35, %36;\n}\n"
   : "+f"(d[0]),"+f"(d[1]),"+f"(d[2]),"+f"(d[3]),"+f"(d[4]),"+f"(d[5]),"+f"(d[6]),"+f"(d[7]),"+f"(d[8]),"+f"(d[9]),"+f"(d[10]),"+f"(d[11]),"+f"(d[12]),"+f"(d[13]),"+f"(d[14]),"+f"(d[15]),"+f"(d[16]),"+f"(d[17]),"+f"(d[18]),"+f"(d[19]),"+f"(d[20]),"+f"(d[21]),"+f"(d[22]),"+f"(d[23]),"+f"(d[24]),"+f"(d[25]),"+f"(d[26]),"+f"(d[27]),"+f"(d[28]),"+f"(d[29]),"+f"(d[30]),"+f"(d[31])
   : "l"(da),"l"(db),"r"(sd),"n"(TA),"n"(TB));
}
template<int TA, int TB> __device__ __forceinline__ void wg_ss8(float* d, uint64_t da, uint64_t db, int sd) {
  asm volatile("{\n.reg .pred p;\nsetp.ne.b32 p, %6, 0;\n"
   "wgmma.mma_async.sync.aligned.m64n8k16.f32.bf16.bf16 {%0,%1,%2,%3}, %4, %5, p, 1, 1, %7, %8;\n}\n"
   : "+f"(d[0]),"+f"(d[1]),"+f"(d[2]),"+f"(d[3])
   : "l"(da),"l"(db),"r"(sd),"n"(TA),"n"(TB));
}

__device__ __forceinline__ uint32_t phi2(float a, float b) {
  uint32_t r, e;
  asm("cvt.rn.relu.bf16x2.f32 %0, %1, %2;" : "=r"(r) : "f"(b), "f"(a));
  e = pack_bf16(ex2f(a * 1.4426950408889634f), ex2f(b * 1.4426950408889634f));
  asm("add.rn.bf16x2 %0, %0, %1;" : "+r"(e) : "r"(0x35863586u));
  asm("min.NaN.bf16x2 %0, %0, %1;" : "+r"(e) : "r"(0x3F803F80u));
  asm("add.rn.bf16x2 %0, %0, %1;" : "+r"(e) : "r"(r));
  return e;
}

__device__ __forceinline__ void mbar_arrive(uint32_t bar) { asm volatile("mbarrier.arrive.shared::cta.b64 _, [%0];" :: "r"(bar) : "memory"); }
__device__ __forceinline__ void named_arrive(int id, int n) { asm volatile("bar.arrive %0, %1;" :: "r"(id), "r"(n) : "memory"); }
__device__ __forceinline__ void fence_async_all() { asm volatile("fence.proxy.async.global;" ::: "memory"); }
__device__ __forceinline__ void flag_add(uint32_t* f) { asm volatile("fence.acq_rel.gpu;\nred.relaxed.gpu.global.add.u32 [%0], 1;" :: "l"(f) : "memory"); }
#define PUBLISH(f) asm volatile("fence.proxy.async.global;\nred.relaxed.gpu.global.add.u32 [%0], 1;" :: "l"(f) : "memory")
__device__ __forceinline__ void flag_wait(const uint32_t* f, uint32_t target) {
  uint32_t v;
#pragma unroll 1
  for (int it = 0;; it++) {
    asm volatile("ld.acquire.gpu.global.u32 %0, [%1];" : "=r"(v) : "l"(f) : "memory");
    if ((int32_t)(v - target) >= 0) break;
    if (it > 2000000) __trap();
    __nanosleep(64);
  }
}
__device__ __forceinline__ bool elect_one() {
  uint32_t p;
  asm volatile("{\n.reg .pred P;\nelect.sync _|P, 0xFFFFFFFF;\nselp.b32 %0, 1, 0, P;\n}\n" : "=r"(p));
  return p;
}
__device__ __forceinline__ void lds4(uint32_t a, uint32_t* r) {
  asm volatile("ld.shared.v4.b32 {%0,%1,%2,%3}, [%4];" : "=r"(r[0]), "=r"(r[1]), "=r"(r[2]), "=r"(r[3]) : "r"(a) : "memory");
}
__device__ __forceinline__ uint32_t lds1(uint32_t a) { uint32_t r; asm volatile("ld.shared.b32 %0, [%1];" : "=r"(r) : "r"(a) : "memory"); return r; }
__device__ __forceinline__ void sts1(uint32_t a, uint32_t v) { asm volatile("st.shared.b32 [%0], %1;" :: "r"(a), "r"(v) : "memory"); }
__device__ __forceinline__ void sts4(uint32_t a, uint32_t r0, uint32_t r1, uint32_t r2, uint32_t r3) {
  asm volatile("st.shared.v4.b32 [%0], {%1,%2,%3,%4};" :: "r"(a), "r"(r0), "r"(r1), "r"(r2), "r"(r3) : "memory");
}
__device__ __forceinline__ void ldsm4(uint32_t a, uint32_t* r) {
  asm volatile("ldmatrix.sync.aligned.m8n8.x4.shared.b16 {%0,%1,%2,%3}, [%4];" : "=r"(r[0]), "=r"(r[1]), "=r"(r[2]), "=r"(r[3]) : "r"(a) : "memory");
}
__device__ __forceinline__ float rcpf(float x) { float y; asm("rcp.approx.ftz.f32 %0, %1;" : "=f"(y) : "f"(x)); return y; }
__device__ __forceinline__ uint32_t hfma2(uint32_t a, uint32_t b, uint32_t c) { uint32_t r; asm("fma.rn.f16x2 %0, %1, %2, %3;" : "=r"(r) : "r"(a), "r"(b), "r"(c)); return r; }
__device__ __forceinline__ uint32_t hadd2(uint32_t a, uint32_t b) { uint32_t r; asm("add.rn.f16x2 %0, %1, %2;" : "=r"(r) : "r"(a), "r"(b)); return r; }

#define STEPK 96
#define QSCALE 0.36067376022224085f
#define SMAGIC (512.0f + 2.0f * (191.0f - 30.0f - 1.5823545f))
#define VSHIFT 1073741824.0f

__device__ uint32_t g_epoch[132];
__device__ uint32_t g_flag[288 * 8];
#define FLAG_KV (g_flag)
#define FLAG_B(h) (g_flag + (4 + (h)) * 8)
#define FLAG_OA(cta, pass) (g_flag + (16 + (cta) * 2 + (pass)) * 8)
#define FLAG_LM(i) (g_flag + (272 + (i)) * 8)

#define SM_TOTAL (224 * 1024 + 2048 + 1024)
#define OFF_K 0
#define OFF_F 65536
#define OFF_V 131072
#define OFF_MISC (224 * 1024)

#define BAR_FULL(s) (bars + 8 * (s))
#define BAR_EMPTY(s) (bars + 24 + 8 * (s))
#define BAR_KV(c) (bars + 48 + 8 * (c))
#define BAR_BDONE (bars + 80)
#define BAR_Q (bars + 88)
#define BAR_GO (bars + 96)
#define BAR_Q2 (bars + 104)
#define BAR_OD(p) (bars + 112 + 8 * (p))
#define BAR_CL(c) (bars + 128 + 8 * (c))
#define BAR_TE(i) (bars + 168 + 8 * (i))
#define BAR_TF(g) (bars + 224 + 8 * (g))
#define BAR_XA(w) (bars + 352 + 8 * (w))
#define BAR_VB(c) (bars + 384 + 8 * (c))

__device__ __forceinline__ uint32_t exp2_pair_fix(float d0, float d1, uint32_t c63, uint32_t m1) {
  uint32_t w, y, s, r;
  asm("prmt.b32 %0, %1, %2, 0x6521;" : "=r"(w) : "r"(__float_as_uint(d0)), "r"(__float_as_uint(d1)));
  asm("lop3.b32 %0, %1, 0x007F007F, %2, 0xEA;" : "=r"(y) : "r"(w), "r"(c63));
  asm("mad.lo.u32 %0, %1, %2, %3;" : "=r"(s) : "r"(y), "r"(m1), "r"(w));
  asm("fma.rn.bf16x2 %0, %1, %2, %3;" : "=r"(r) : "r"(w), "r"(y), "r"(s));
  return r;
}

__device__ __forceinline__ void attn_slow(const uint4* gq, uint32_t dst) {
  const int t = threadIdx.x & 127;
  const int row = t >> 1, half = t & 1;
  float q[16];
#pragma unroll
  for (int i = 0; i < 4; i++) {
    const uint4 v = gq[(row >> 4) * 32 + (row & 7) * 4 + i];
    const uint32_t lo = (row & 8) ? v.y : v.x, hi = (row & 8) ? v.w : v.z;
    q[2 * i] = bf_lo(lo); q[2 * i + 1] = bf_hi(lo); q[2 * i + 8] = bf_lo(hi); q[2 * i + 9] = bf_hi(hi);
  }
  float m = -INFINITY, l = 0.f, o[16];
#pragma unroll
  for (int i = 0; i < 16; i++) o[i] = 0.f;
#pragma unroll 1
  for (int j = half * 1024; j < half * 1024 + 1024; j++) {
    uint4 ka = g_KV[4 * S_TOK + j], kb = g_KV[5 * S_TOK + j];
    uint4 va = g_KV[6 * S_TOK + j], vb = g_KV[7 * S_TOK + j];
    uint32_t kk[8] = {ka.x, ka.y, ka.z, ka.w, kb.x, kb.y, kb.z, kb.w};
    uint32_t vv[8] = {va.x, va.y, va.z, va.w, vb.x, vb.y, vb.z, vb.w};
    float s = 0.f;
#pragma unroll
    for (int i = 0; i < 8; i++) { s = fmaf(q[2 * i], bf_lo(kk[i]), s); s = fmaf(q[2 * i + 1], bf_hi(kk[i]), s); }
    s = rbf(s) * 0.25f;
    if (s > m) {
      float c = __expf(m - s);
      l *= c;
#pragma unroll
      for (int i = 0; i < 16; i++) o[i] *= c;
      m = s;
    }
    float p = __expf(s - m);
    l += p;
#pragma unroll
    for (int i = 0; i < 8; i++) { o[2 * i] = fmaf(p, bf_lo(vv[i]), o[2 * i]); o[2 * i + 1] = fmaf(p, bf_hi(vv[i]), o[2 * i + 1]); }
  }
  float m2 = __shfl_xor_sync(~0u, m, 1);
  float mm = fmaxf(m, m2);
  float c = __expf(m - mm);
  l *= c; l += __shfl_xor_sync(~0u, l, 1);
  float inv = 1.f / l;
  uint32_t r[8];
#pragma unroll
  for (int i = 0; i < 16; i++) { o[i] *= c; o[i] += __shfl_xor_sync(~0u, o[i], 1); o[i] *= inv; }
#pragma unroll
  for (int i = 0; i < 8; i++) r[i] = pack_bf16(o[2 * i], o[2 * i + 1]);
  if (half == 0) sts4(dst + t * 16, r[0], r[1], r[2], r[3]); else sts4(dst + t * 16, r[4], r[5], r[6], r[7]);
  fence_async();
}

struct Params { const __nv_bfloat16* wk; const __nv_bfloat16* wv; const __nv_bfloat16* xa; };
__device__ __forceinline__ void cp16(uint32_t dst, const void* src) { asm volatile("cp.async.cg.shared.global [%0], [%1], 16;" :: "r"(dst), "l"(src) : "memory"); }

__device__ __forceinline__ void helper_cta(const int h, const uint32_t sb, const uint32_t bars, const int wg, const int w4,
                                           const CUtensorMap* mQ, const CUtensorMap* mOs) {
  const int lane = threadIdx.x & 31;
  mbar_wait(BAR_GO, 0);
  const int cb = wg & 1, col = h * 128 + cb * 64, row0 = S_TOK + (wg >> 1) * 1024;
  const uint32_t buf = sb + wg * 49152;
  if (w4 == 0 && elect_one()) {
    fence_async_all();
#pragma unroll 1
    for (int u = 0; u < 3; u++) {
      mbar_expect_tx(BAR_TF(wg * 3 + u), 16384);
      tma2d(buf + u * 16384, mQ, col, row0 + u * 128, BAR_TF(wg * 3 + u));
    }
  }
  const int head = h * 8 + cb * 4 + w4;
  float4 a0 = make_float4(0, 0, 0, 0), a1 = a0, a2 = a0;
#pragma unroll 8
  for (int tt = 0; tt < 16; tt++) {
    const float4* src = g_kvp + ((tt * 32 + head) * 3) * 32 + lane;
    float4 u = src[0], v = src[32], w = src[64];
    a0.x += u.x; a0.y += u.y; a0.z += u.z; a0.w += u.w;
    a1.x += v.x; a1.y += v.y; a1.z += v.z; a1.w += v.w;
    a2.x += w.x; a2.y += w.y; a2.z += w.z; a2.w += w.w;
  }
  const uint32_t b00 = pack_bf16(a0.x, a0.y), b01 = pack_bf16(a0.z, a0.w);
  const uint32_t b10 = pack_bf16(a1.x, a1.y), b11 = pack_bf16(a1.z, a1.w);
  const uint32_t bz0 = pack_bf16(a2.x, a2.y), bz1 = pack_bf16(a2.z, a2.w);
  const int m = lane >> 3, r = lane & 7;
  const uint32_t off = ((m & 1) * 8 + r) * 128 + (((w4 * 2 + (m >> 1)) ^ r) << 4);
  int s = 0, ph = 0;
#pragma unroll 1
  for (int u = 0; u < 8; u++) {
    const uint32_t bb = buf + s * 16384;
    mbar_wait(BAR_TF(wg * 3 + s), ph);
#pragma unroll
    for (int mt = 0; mt < 8; mt++) {
      uint32_t a[4];
      ldsm4(bb + mt * 2048 + off, a);
      float n0[4] = {0, 0, 0, 0}, n1[4] = {0, 0, 0, 0}, dn[4] = {0, 0, 0, 0};
      mma_bf16(dn, a[0], a[1], a[2], a[3], bz0, bz1);
      mma_bf16(n0, a[0], a[1], a[2], a[3], b00, b01);
      mma_bf16(n1, a[0], a[1], a[2], a[3], b10, b11);
      const float i0 = rcpf(dn[0] + 1e-6f), i1 = rcpf(dn[2] + 1e-6f);
      stsm4(bb + mt * 2048 + off, pack_bf16(n0[0] * i0, n0[1] * i0), pack_bf16(n0[2] * i1, n0[3] * i1),
            pack_bf16(n1[0] * i0, n1[1] * i0), pack_bf16(n1[2] * i1, n1[3] * i1));
    }
    fence_async();
    named_bar(wg + 1, 128);
    if (w4 == 0 && lane == 0) {
      tma2d_store(mOs, bb, col, row0 + u * 128);
      bulk_commit();
      if (u >= 1 && u + 2 < 8) {
        asm volatile("cp.async.bulk.wait_group.read 1;" ::: "memory");
        const int sp = s == 0 ? 2 : s - 1;
        mbar_expect_tx(BAR_TF(wg * 3 + sp), 16384);
        tma2d(buf + sp * 16384, mQ, col, row0 + (u + 2) * 128, BAR_TF(wg * 3 + sp));
      }
    }
    __syncwarp();
    if (++s == 3) { s = 0; ph ^= 1; }
  }
  if (w4 == 0 && lane == 0) {
    bulk_wait_all();
    fence_async_all();
    flag_add(FLAG_LM((h * 2 + cb) * 2 + (wg >> 1)));
    if (wg == 0) TS(1, 8);
  }
}

#define STAGE(s) (sb + (2 - (s)) * 65536)
template <int TR> __device__ __forceinline__ void proj_kb(float* acc, uint32_t st, uint32_t offA, uint32_t offB, int first) {
  const uint64_t da = make_desc(st + offA, TR ? 8192 : 16, 1024, 1);
  const uint64_t db = make_desc(st + offB, TR ? 16 : 8192, 1024, 1);
  wg_fence();
#pragma unroll
  for (int k = 0; k < 4; k++) wg_ss128<TR, 1 - TR>(acc, da + k * (TR ? 128 : 2), db + k * (TR ? 2 : 128), k != 0 || !first);
  wg_commit();
}
template <int TR> __device__ __forceinline__ void proj_loop(float* acc, uint32_t sb, uint32_t bars, uint32_t offA, uint32_t offB,
                                                            int wg, uint32_t sWKV) {
  {
    float kv[4];
    if (threadIdx.x == 0) TS(0, 13);
    mbar_wait(BAR_XA(wg), 0);
    if (threadIdx.x == 0) TS(0, 1);
    const uint64_t da = make_desc(STAGE(2) + wg * 16384, 16, 1024, 1), db = make_desc(sWKV + wg * 2048, 128, 128, 0);
    wg_fence();
#pragma unroll
    for (int k = 0; k < 8; k++) wg_ss8<0, 1>(kv, da + (k >> 2) * 512 + (k & 3) * 2, db + k * 16, k != 0);
    wg_commit();
    wg_wait<0>();
    fence_regs<4>(kv);
    named_bar(wg + 1, 128);
    sts4(sWKV + threadIdx.x * 16, __float_as_uint(kv[0]), __float_as_uint(kv[1]), __float_as_uint(kv[2]), __float_as_uint(kv[3]));
    __syncwarp();
    if ((threadIdx.x & 31) == 0) mbar_arrive(BAR_GO);
  }
  int s = 0, ph = 0, sp = 0;
#pragma unroll 1
  for (int kb = 0; kb < 8; kb++) {
    mbar_wait(BAR_FULL(s), ph);
    if (threadIdx.x == 0) TS(0, 2 + kb);
    proj_kb<TR>(acc, STAGE(s), offA, offB, kb == 0);
    wg_wait<1>();
    if (kb >= 1 && (threadIdx.x & 127) == 0) mbar_arrive(BAR_EMPTY(sp));
    __syncwarp();
    sp = s;
    if (++s == 3) { s = 0; ph ^= 1; }
  }
  wg_wait<0>();
  fence_regs<64>(acc);
}

__device__ __forceinline__ uint32_t tail_slots(int t) {
  const uint32_t lo = t < 4 ? (t < 2 ? (t == 0 ? 0x0C0B0Au : 0x0F0E0Du) : (t == 2 ? 0x100400u : 0x181408u))
                            : (t < 6 ? (t == 4 ? 0x110501u : 0x191502u) : (t == 6 ? 0x161206u : (t == 7 ? 0x1A0703u : 0x1B1713u)));
  return lo;
}

__device__ __forceinline__ void take_role(uint32_t sM, int wg) {
  uint32_t r;
  asm volatile("atom.shared.add.u32 %0, [%1], 1;" : "=r"(r) : "r"(sM + 20) : "memory");
  sts1(sM + 32 + wg * 4, r);
}

__global__ void __launch_bounds__(640, 1)
k1_main(const __grid_constant__ CUtensorMap mXA64, const __grid_constant__ CUtensorMap mXB,
        const __grid_constant__ CUtensorMap mWq, const __grid_constant__ CUtensorMap mWqkv,
        const __grid_constant__ CUtensorMap mQst, const __grid_constant__ CUtensorMap mOst,
        const __grid_constant__ CUtensorMap mO, const __grid_constant__ CUtensorMap mWoA,
        const __grid_constant__ CUtensorMap mWoB, const __grid_constant__ CUtensorMap mOut,
        const __grid_constant__ CUtensorMap mO16, const Params prm) {
  extern __shared__ uint8_t smem_raw[];
  const uint32_t sb = (smem_u32(smem_raw) + 1023u) & ~1023u;
  const uint32_t bars = sb + OFF_MISC, sM = bars + 512, sT = bars + 1024;
  const int tid = threadIdx.x, warp = __shfl_sync(~0u, tid >> 5, 0), wg = warp >> 2, w4 = warp & 3, lane = tid & 31;
  const bool helper = blockIdx.x >= 128;
  if (tid == 0) TS(0, 0);
  const int G = blockIdx.x >> 4, gi = blockIdx.x & 15;
  const int tbA = G * 4 + (gi >> 2), hg = gi & 3;
  const int ttB = (G >> 1) * 4 + (gi >> 2), hq = (G & 1) * 4 + (gi & 3);
  auto issue = [&](int kb, int s) {
    const uint32_t fb = BAR_FULL(s), st = STAGE(s);
    mbar_expect_tx(fb, 65536);
    tma2d(st + 16384, &mXA64, kb * 64, tbA * 64, fb);
    tma2d(st, &mWq, hg * 128, kb * 64, fb);
    tma2d(st + 8192, &mWq, hg * 128 + 64, kb * 64, fb);
    tma2d(st + 49152, &mXB, kb * 64, ttB * 128, fb);
    tma2d(st + 24576, &mWqkv, hq * 64, kb * 64, fb);
    tma2d(st + 32768, &mWqkv, 512 + hq * 64, kb * 64, fb);
    tma2d(st + 40960, &mWqkv, 1024 + hq * 64, kb * 64, fb);
  };
  const uint32_t sOne = sb + OFF_V + 65536, sWKV = sOne + 24576;
  if (warp >= 16) {
    if (warp == 17) {
      if (elect_one()) {
        mbar_init(BAR_BDONE, 8); mbar_init(BAR_Q, 8); mbar_init(BAR_GO, helper ? 1 : 16); mbar_init(BAR_Q2, 5);
        mbar_init(BAR_OD(0), 16); mbar_init(BAR_OD(1), 16); mbar_init(BAR_CL(0), 1); mbar_init(BAR_FULL(2), 1);
#pragma unroll
        for (int i = 0; i < 4; i++) mbar_init(BAR_CL(i + 1), i == 0 ? 5 : 4);
#pragma unroll
        for (int i = 0; i < 3; i++) { mbar_init(BAR_EMPTY(i), 4); mbar_init(BAR_KV(i), 1); mbar_init(BAR_VB(i), 1); }
        sts1(sM + 20, 0);
        asm volatile("fence.mbarrier_init.release.cluster;" ::: "memory");
      }
    } else if (warp == 18) {
      if (elect_one()) {
#pragma unroll
        for (int i = 0; i < 7; i++) mbar_init(BAR_TE(i), 1);
#pragma unroll
        for (int i = 0; i < 16; i++) mbar_init(BAR_TF(i), i < 12 ? 1 : 2);
        asm volatile("fence.mbarrier_init.release.cluster;" ::: "memory");
      }
    } else if (warp == 16 && !helper && elect_one()) {
#pragma unroll
      for (int w = 0; w < 4; w++) mbar_init(BAR_XA(w), 1);
      mbar_init(BAR_FULL(0), 1); mbar_init(BAR_FULL(1), 1);
      asm volatile("fence.mbarrier_init.release.cluster;" ::: "memory");
#pragma unroll
      for (int w = 0; w < 4; w++) {
        mbar_expect_tx(BAR_XA(w), 16384);
        tma2d(STAGE(2) + w * 16384, &mXA64, w * 128, tbA * 64, BAR_XA(w));
        tma2d(STAGE(2) + w * 16384 + 8192, &mXA64, w * 128 + 64, tbA * 64, BAR_XA(w));
      }
      TS(0, 14);
      issue(0, 0);
    }
  } else if (!helper) {
    const uint4 v = __ldg((const uint4*)(hg >= 2 ? prm.wv : prm.wk) + tid * 2 + (hg & 1));
#pragma unroll
    for (int i = 0; i < 3; i++) {
      const int key = tid + i * 512;
      sts4(sOne + key * 16, (key % STEPK) < 24 ? 0x00003F80u : 0x00004E80u, 0u, 0u, 0u);
    }
    sts4(sWKV + tid * 16, v.x, v.y, v.z, v.w);
    fence_async();
  }
  __syncthreads();
  if (wg == 4) {
    if (w4 == 0 && !helper && elect_one()) { issue(1, 1); TS(0, 15); }
    asm volatile("setmaxnreg.dec.sync.aligned.u32 32;");
    const uint32_t ep = g_epoch[blockIdx.x] + 1;
    if (helper) {
      if (w4 == 0 && elect_one()) {
        flag_wait(FLAG_B(blockIdx.x - 128), ep * 32);
        fence_async_all();
        TS(1, 10);
        mbar_arrive(BAR_GO);
        g_epoch[blockIdx.x] = ep;
      }
      return;
    }
    mbar_wait(BAR_GO, 0);
    if (w4 == 0 && elect_one()) issue(2, 2);
    {
      uint32_t a[4], b[4];
      float c[4];
      lds4(sWKV + (tid - 512) * 16, a);
      lds4(sWKV + 2048 + (tid - 512) * 16, b);
#pragma unroll
      for (int i = 0; i < 4; i++) c[i] = __uint_as_float(a[i]) + __uint_as_float(b[i]);
      lds4(sWKV + 4096 + (tid - 512) * 16, a);
      lds4(sWKV + 6144 + (tid - 512) * 16, b);
#pragma unroll
      for (int i = 0; i < 4; i++) c[i] += __uint_as_float(a[i]) + __uint_as_float(b[i]);
      sts1(sT + w4 * 256 + lane * 4, pack_bf16(c[0], c[1]));
      sts1(sT + w4 * 256 + 128 + lane * 4, pack_bf16(c[2], c[3]));
    }
    named_bar(9, 128);
    {
      const int t = tid - 512;
#pragma unroll
      for (int i = 0; i < 4; i++) {
        const int key = 1536 + t + i * 128;
        sts4(sOne + key * 16, (key % STEPK) < 24 ? 0x00003F80u : 0x00004E80u, 0u, 0u, 0u);
      }
      fence_async();
      __syncwarp();
      if (lane == 0) mbar_arrive(BAR_Q);
    }
    if (w4 == 0) {
      int s = 0, ph = 0;
#pragma unroll 1
      for (int kb = 3; kb < 8; kb++) {
        mbar_wait(BAR_EMPTY(s), ph);
        if (elect_one()) issue(kb, s);
        if (++s == 3) { s = 0; ph ^= 1; }
      }
      flag_wait(FLAG_KV, ep * 128);
      fence_async_all();
      if (lane == 0) TS(0, 11);
#pragma unroll 1
      for (int m = 0; m < 2; m++) {
        mbar_wait(m == 0 ? BAR_EMPTY(2) : BAR_EMPTY(0), 1 - m);
        if (elect_one()) {
          const uint32_t fb = m == 0 ? BAR_KV(0) : BAR_VB(0);
          mbar_expect_tx(fb, 2 * 7 * STEPK * 16);
#pragma unroll
          for (int p = 0; p < 2; p++) bulk_g2s(sb + m * OFF_V + p * 32768, g_KV + (m * 2 + p) * S_TOK, 7 * STEPK * 16, fb);
        }
      }
      mbar_wait(BAR_Q, 0);
      if (elect_one()) {
#pragma unroll
        for (int c = 1; c < 3; c++) {
          const int k0 = c == 1 ? 7 * STEPK : 12 * STEPK, k1 = c == 1 ? 12 * STEPK : S_TOK;
          const uint32_t bytes = (k1 - k0) * 16;
          mbar_expect_tx(BAR_KV(c), 4 * bytes);
#pragma unroll
          for (int p = 0; p < 4; p++)
            bulk_g2s(sb + (p >> 1) * OFF_V + (p & 1) * 32768 + k0 * 16, g_KV + p * S_TOK + k0, bytes, BAR_KV(c));
        }
      }
      mbar_wait(BAR_CL(1), 0);
      flag_wait(FLAG_LM((lane & 7) * 2 + (tbA >> 4)), ep);
      __syncwarp();
      fence_async_all();
      if (lane == 0) TS(2, 13);
#pragma unroll 1
      for (int n = 0; n < 8; n++) {
        mbar_wait(BAR_CL(n < 4 ? n >> 1 : (n == 4 ? 2 : (n < 7 ? 3 : 4))), 0);
        const uint32_t sl = tail_slots(n), fb = BAR_TF(n);
        if (elect_one()) {
          mbar_expect_tx(fb, 24576);
          tma2d(sb + (sl & 255) * 8192, &mO, n * 64, S_TOK + tbA * 64, fb);
          tma2d(sb + ((sl >> 8) & 255) * 8192, &mWoB, hg * 128, n * 64, fb);
          tma2d(sb + (sl >> 16) * 8192, &mWoB, hg * 128 + 64, n * 64, fb);
        }
      }
      if (lane == 0) g_epoch[blockIdx.x] = ep;
    } else if (w4 == 3) {
      flag_wait(FLAG_KV, ep * 128);
      const uint4 a = *(const uint4*)(g_stats + lane * 4);
      const float kmax2 = __uint_as_float(__reduce_max_sync(~0u, a.x)) + __uint_as_float(__reduce_max_sync(~0u, a.y));
      const float vmax = __uint_as_float(__reduce_max_sync(~0u, max(a.z, a.w)));
      const float lv = vmax > 0.f ? __log2f(vmax) : 0.f;
      const float lim = fminf(90.f, fminf(91.f + lv, 95.f - lv));
      float thr = -1.f;
      if (vmax < 1e27f && kmax2 <= 65536.f && lim > 2.f) thr = fminf(60000.f, (lim * lim - 1.f) / (kmax2 * 1.02f + 1e-30f));
      if (lane == 0) { sts1(sM + 16, __float_as_uint(thr)); mbar_arrive(BAR_Q2); }
      mbar_wait(BAR_CL(3), 0);
      flag_wait(FLAG_OA(tbA * 4 + (lane & 3), 0), ep);
      __syncwarp();
      fence_async_all();
#pragma unroll 1
      for (int n = 0; n < 8; n++) {
        mbar_wait(n == 4 ? BAR_CL(4) : BAR_TE(n < 4 ? n : n - 1), 0);
        const uint32_t sl = tail_slots(n < 4 ? n : (n == 4 ? 8 : n - 1)), fb = BAR_TF(n + 8);
        const int k0 = n < 4 ? n * 128 : ((hg + n) & 3) * 128 + 64;
        if (elect_one()) {
          mbar_expect_tx(fb, n < 4 ? 24576 : 16384);
          if (n < 4) tma2d(sb + (sl & 255) * 8192, &mO, k0, tbA * 64, fb);
          tma2d(sb + ((sl >> 8) & 255) * 8192, &mWoA, hg * 128, k0, fb);
          tma2d(sb + (sl >> 16) * 8192, &mWoA, hg * 128 + 64, k0, fb);
        }
      }
    } else {
      const int tok = (w4 - 1) * 32 + lane;
      int step, col;
      if ((tbA & 3) == 0) {
        const int b8 = tbA >> 2;
        if (tok < 22) { step = tok; col = 24 + b8; }
        else { const int c = tok >= 43; step = tok - 22 - 21 * c; col = 32 + b8 * 2 + c; }
      } else {
        const int b24 = (tbA >> 2) * 3 + (tbA & 3) - 1;
        if (tok < 42) { const int c = tok >= 21; step = tok - 21 * c; col = 48 + b24 * 2 + c; }
        else { step = tok - 42; col = b24; }
      }
      const int kap = step * STEPK + col;
      const bool chained = col >= 24;
      uint32_t v[4], o[4];
      lds4(sT + tok * 16, v);
      g_KV[(4 + hg) * S_TOK + kap] = make_uint4(v[0], v[1], v[2], v[3]);
      float st = 0.f;
      if (hg < 2) {
        o[0] = o[1] = o[2] = o[3] = 0;
        if (chained && step > 0) lds4(sT + tok * 16 - 16, o);
        const float sc = chained ? 2.f : 1.f;
#pragma unroll
        for (int u = 0; u < 4; u++) {
          const float x = bf_lo(v[u]), y = bf_hi(v[u]);
          st += x * x + y * y;
          o[u] = pack_f16((x - bf_lo(o[u])) * sc, (y - bf_hi(o[u])) * sc);
        }
      } else {
        const float sc = chained ? VSHIFT : 1.f;
#pragma unroll
        for (int u = 0; u < 4; u++) { float x = bf_lo(v[u]), y = bf_hi(v[u]); st += fabsf(x) + fabsf(y); o[u] = pack_bf16(x * sc, y * sc); }
      }
      g_KV[hg * S_TOK + kap] = make_uint4(o[0], o[1], o[2], o[3]);
      const uint32_t um = __reduce_max_sync(~0u, __float_as_uint(st) & 0x7FFFFFFFu);
      if (w4 == 2) {
        if (lane == 0) sts1(sM + 24, um);
        named_arrive(10, 64);
        uint32_t rdy = 0;
#pragma unroll 1
        for (int n = 4; n < 8; n++) {
          mbar_wait(n == 4 ? BAR_CL(4) : BAR_TE(n - 1), 0);
          const int hsel = (hg + n) & 3;
#pragma unroll 1
          for (int it = 0; !((rdy >> hsel) & 1); it++) {
            uint32_t fv;
            asm volatile("ld.acquire.gpu.global.u32 %0, [%1];" : "=r"(fv) : "l"(FLAG_OA(tbA * 4 + (lane & 3), 1)) : "memory");
            rdy = __ballot_sync(~0u, (int32_t)(fv - ep) >= 0);
            if (it > 2000000) __trap();
          }
          if (lane == 0 && n == 7) TS(2, 14);
          fence_async_all();
          const uint32_t sl = tail_slots(n == 4 ? 8 : n - 1), fb = BAR_TF(n + 8);
          if (elect_one()) {
            mbar_expect_tx(fb, 8192);
            tma2d(sb + (sl & 255) * 8192, &mO, hsel * 128 + 64, tbA * 64, fb);
          }
        }
      }
      else {
        named_bar(10, 64);
        if (elect_one()) {
          g_stats[tbA * 4 + hg] = max(um, lds1(sM + 24));
          fence_async_all();
          flag_add(FLAG_KV);
          TS(1, 9);
          mbar_wait(BAR_BDONE, 0);
          tma2d_store(&mQst, sb + OFF_F + 49152, hq * 64, S_TOK + ttB * 128);
          bulk_commit();
          bulk_wait_all();
          fence_async_all();
          flag_add(FLAG_B(hq >> 1));
          TS(0, 12);
          mbar_wait(BAR_Q, 0);
          mbar_arrive(BAR_CL(0));
#pragma unroll 1
          for (int p = 0; p < 2; p++) {
            mbar_wait(BAR_OD(p), 0);
#pragma unroll
            for (int w = 0; w < 4; w++) tma2d_store(&mO16, sb + OFF_F + (p * 4 + w) * 2048, hg * 128 + p * 64 + w * 16, tbA * 64);
            bulk_commit();
            bulk_wait_all();
            if (p == 0) mbar_arrive(BAR_CL(1));
            PUBLISH(FLAG_OA(blockIdx.x, p));
          }
          TS(2, 0);
        }
      }
    }
    return;
  }
  if (helper) { helper_cta(blockIdx.x - 128, sb, bars, wg, w4, &mQst, &mOst); return; }

  {
    float acc[64];
    if (wg == 0) proj_loop<0>(acc, sb, bars, 16384, 0, wg, sWKV);
    else proj_loop<1>(acc, sb, bars, 16384 + wg * 8192, 49152, wg, sWKV);
    asm volatile("setmaxnreg.inc.sync.aligned.u32 112;");
    if (tid == 0) TS(0, 10);
    const uint32_t sF = sb + OFF_F;
    if (wg == 0) {
      uint32_t r[32];
      const uint32_t qa = sF + w4 * 512 + ((lane >> 3) & 1) * 256 + (lane >> 4) * 128 + (lane & 7) * 16;
#pragma unroll
      for (int hd = 0; hd < 8; hd++) {
#pragma unroll
        for (int i = 0; i < 4; i++) r[4 * hd + i] = pack_f16(acc[8 * hd + 2 * i] * QSCALE, acc[8 * hd + 2 * i + 1] * QSCALE);
        stsm4(qa + hd * 2048, r[4 * hd], r[4 * hd + 1], r[4 * hd + 2], r[4 * hd + 3]);
        if (hd == 3) {
          fence_async();
          __syncwarp();
          if (lane == 0) mbar_arrive(BAR_Q);
        }
      }
      fence_async();
      uint32_t nmax = 0;
#pragma unroll
      for (int hd = 0; hd < 8; hd++) {
        const uint32_t* q = r + 4 * hd;
        const uint32_t t0 = hfma2(q[2], q[2], hfma2(q[0], q[0], 0u)), t1 = hfma2(q[3], q[3], hfma2(q[1], q[1], 0u));
        uint32_t n = hadd2(__byte_perm(t0, t1, 0x5410), __byte_perm(t0, t1, 0x7632));
        n = hadd2(n, __shfl_xor_sync(~0u, n, 1));
        n = hadd2(n, __shfl_xor_sync(~0u, n, 2));
        nmax = __vmaxu2(nmax, n & 0x7FFF7FFFu);
      }
      nmax = __reduce_max_sync(~0u, max(nmax & 0xFFFFu, nmax >> 16));
      if (lane == 0) sts1(sM + w4 * 4, nmax);
      uint4* gq = (uint4*)g_Q + blockIdx.x * 1024 + tid;
#pragma unroll
      for (int hd = 0; hd < 8; hd++)
        gq[hd * 128] = make_uint4(pack_bf16(acc[8 * hd], acc[8 * hd + 1]), pack_bf16(acc[8 * hd + 2], acc[8 * hd + 3]),
                                  pack_bf16(acc[8 * hd + 4], acc[8 * hd + 5]), pack_bf16(acc[8 * hd + 6], acc[8 * hd + 7]));
      __syncwarp();
      if (lane == 0) mbar_arrive(BAR_Q2);
    } else if (wg == 3) {
      named_arrive(8, 384);
      named_bar(6, 384);
      const int t = tid & 127;
#pragma unroll
      for (int j = 0; j < 8; j++)
        sts4(sF + 24576 + j * 2048 + t * 16, pack_bf16(acc[8 * j], acc[8 * j + 1]), pack_bf16(acc[8 * j + 2], acc[8 * j + 3]),
             pack_bf16(acc[8 * j + 4], acc[8 * j + 5]), pack_bf16(acc[8 * j + 6], acc[8 * j + 7]));
      named_arrive(7, 256);
    } else {
      uint32_t p[32];
      named_arrive(6, 384);
      if (wg == 2) named_arrive(8, 384);
#pragma unroll
      for (int i = 0; i < 32; i++) p[i] = phi2(acc[2 * i], acc[2 * i + 1]);
      if (wg == 1) {
        named_bar(8, 384);
        const int m = lane >> 3, r = lane & 7;
#pragma unroll
        for (int j = 0; j < 16; j += 2) {
          const int tok = (j + (m >> 1)) * 8 + r;
          const int chunk = w4 * 2 + (m & 1);
          stsm4t(sF + 49152 + tok * 128 + ((chunk ^ r) << 4), p[2 * j], p[2 * j + 1], p[2 * j + 2], p[2 * j + 3]);
        }
        fence_async();
      } else {
        named_bar(7, 256);
        float kv0[4] = {0, 0, 0, 0}, kv1[4] = {0, 0, 0, 0}, z0[4] = {0, 0, 0, 0}, z1[4] = {0, 0, 0, 0};
        const uint32_t one = 0x3F803F80u;
        const int t = tid & 127;
#pragma unroll
        for (int j = 0; j < 8; j++) {
          uint32_t a[4];
          lds4(sF + 24576 + j * 2048 + t * 16, a);
          mma_bf16(kv0, a[0], a[1], a[2], a[3], p[4 * j], p[4 * j + 2]);
          mma_bf16(kv1, a[0], a[1], a[2], a[3], p[4 * j + 1], p[4 * j + 3]);
          mma_bf16(z0, one, one, one, one, p[4 * j], p[4 * j + 2]);
          mma_bf16(z1, one, one, one, one, p[4 * j + 1], p[4 * j + 3]);
        }
        float4* dst = g_kvp + ((ttB * 32 + hq * 4 + w4) * 3) * 32 + lane;
        dst[0] = make_float4(kv0[0], kv0[1], kv1[0], kv1[1]);
        dst[32] = make_float4(kv0[2], kv0[3], kv1[2], kv1[3]);
        dst[64] = make_float4(z0[0], z0[1], z1[0], z1[1]);
      }
      __syncwarp();
      if (lane == 0) mbar_arrive(BAR_BDONE);
    }
  }

  bool safe = true;
  {
    const uint32_t c63 = 0x1F801F80u + (threadIdx.x >> 20);
    const uint32_t m1 = (gridDim.x >> 20) - 1u;
    const uint64_t dK0 = make_desc(sb + OFF_K, 32768, 128, 0);
    const uint64_t dV0 = make_desc(sb + OFF_V, 128, 32768, 0);
    constexpr uint32_t dKV = ((2048u - 8u)  __H0__ ) + STEPK - (OFF_V - OFF_K) / 16;
    float Sm[12], Sp[36], O[12];
    uint32_t P[24];
    uint64_t dQ = make_desc(sb + OFF_F + wg * 2048, 128, 256, 0);
#pragma unroll
    for (int i = 0; i < 36; i++) Sp[i] = SMAGIC;
#pragma unroll
    for (int i = 0; i < 12; i++) Sm[i] = 0.f;
    fence_regs<12>(Sm); fence_regs<36>(Sp);
    mbar_wait(BAR_Q, 0);
    mbar_wait(BAR_KV(0), 0);
    wg_fence();
    wg_qs72<1>(Sp, dQ, dK0 + 24);
    wg_qs24<0>(Sm, dQ, dK0);
    wg_commit();
    wg_wait<0>();
    fence_regs<12>(Sm); fence_regs<36>(Sp);
#pragma unroll 1
    for (int pass = 0; pass < 2; pass++) {
#pragma unroll
      for (int i = 0; i < 12; i++) O[i] = 0.f;
      fence_regs<12>(O);
      if (tid == 0) TS(1, 2 + 2 * pass);
      uint32_t vlo = (uint32_t)dV0;
#pragma unroll 1
      for (int seg = 0; seg < 4; seg++) {
        if (pass == 0) {
          if (seg < 3) mbar_wait(seg == 0 ? BAR_VB(0) : BAR_KV(seg), 0);
        } else if (seg >= 1) {
          if ((tid & 127) == 0) {
            mbar_arrive(BAR_CL(seg));
            if (seg == 3) take_role(sM, wg);
          }
          __syncwarp();
        }
        if ((tid & 127) == 0) TS(4 + wg, pass * 5 + seg);
        const uint32_t vend = vlo + (seg == 0 ? 6 : 5) * STEPK;
#pragma unroll 1
        for (; vlo != vend; vlo += STEPK) {
          uint64_t dK, dV;
          asm("mov.b64 %0, {%1, %2};" : "=l"(dK) : "r"(vlo + dKV), "r"(8u));
          asm("mov.b64 %0, {%1, %2};" : "=l"(dV) : "r"(vlo), "r"(2048u));
#pragma unroll
          for (int i = 0; i < 6; i++) P[i] = pack_bf16(ex2f(Sm[2 * i]), ex2f(Sm[2 * i + 1]));
#pragma unroll
          for (int i = 0; i < 18; i++) P[6 + i] = exp2_pair_fix(Sp[2 * i], Sp[2 * i + 1], c63, m1);
          fence_regs<24>(P);
          wg_fence();
#pragma unroll
          for (int k = 0; k < 6; k++) wg_pv24<1>(O, &P[4 * k], dV + k * 16);
          wg_qs72<1>(Sp, dQ, dK + 24);
          wg_qs24<0>(Sm, dQ, dK);
          wg_commit();
          wg_wait<0>();
          fence_regs<12>(Sm); fence_regs<36>(Sp); fence_regs<12>(O); fence_regs<24>(P);
        }
      }
#pragma unroll
      for (int i = 0; i < 6; i++) P[i] = pack_bf16(ex2f(Sm[2 * i]), ex2f(Sm[2 * i + 1]));
      P[6] = exp2_pair_fix(Sp[0], Sp[1], c63, m1);
      P[7] = exp2_pair_fix(Sp[2], Sp[3], c63, m1);
      fence_regs<8>(P);
#pragma unroll
      for (int i = 0; i < 36; i++) Sp[i] = SMAGIC;
      fence_regs<36>(Sp);
      if (pass == 0) mbar_wait(BAR_Q2, 0);
      const uint32_t sO = sb + OFF_F + (pass * 4 + wg) * 2048;
      dQ += 512;
      wg_fence();
      wg_pv24<1>(O, &P[0], dV0 + 21 * STEPK);
      wg_pv24<1>(O, &P[4], dV0 + 21 * STEPK + 16);
      wg_commit();
      wg_qs72<1>(Sp, dQ, dK0 + 24);
      wg_qs24<0>(Sm, dQ, dK0);
      wg_commit();
      wg_wait<1>();
      fence_regs<12>(O);
      const float l0 = __shfl_sync(~0u, O[8], lane & ~3), l1 = __shfl_sync(~0u, O[10], lane & ~3);
      const float i0 = rcpf(l0), i1 = rcpf(l1);
      stsm4(sO + w4 * 512 + (lane & 15) * 32 + (lane >> 4) * 16,
            pack_bf16(O[0] * i0, O[1] * i0), pack_bf16(O[2] * i1, O[3] * i1),
            pack_bf16(O[4] * i0, O[5] * i0), pack_bf16(O[6] * i1, O[7] * i1));
      fence_async();
      {
        uint32_t n[4];
        lds4(sM, n);
        const float qn = __half2float(__ushort_as_half((unsigned short)max(max(n[0], n[1]), max(n[2], n[3]))));
        safe = __all_sync(~0u, qn <= __uint_as_float(lds1(sM + 16)));
      }
      if (safe && lane == 0) mbar_arrive(BAR_OD(pass));
      wg_wait<0>();
      fence_regs<12>(Sm); fence_regs<36>(Sp);
      if (!safe) break;
      if ((tid & 127) == 0) TS(4 + wg, pass * 5 + 4);
      if (tid == 0) TS(1, 3 + 2 * pass);
    }
  }
  if (!safe) {
    if ((tid & 127) == 0) { mbar_arrive(BAR_CL(1)); mbar_arrive(BAR_CL(2)); mbar_arrive(BAR_CL(3)); take_role(sM, wg); }
#pragma unroll 1
    for (int pass = 0; pass < 2; pass++) {
      attn_slow((const uint4*)g_Q + blockIdx.x * 1024 + (pass * 4 + wg) * 128, sb + OFF_F + (pass * 4 + wg) * 2048);
      __syncwarp();
      if (lane == 0) mbar_arrive(BAR_OD(pass));
    }
  }

  {
    named_bar(wg + 1, 128);
    if ((tid & 127) == 0) mbar_arrive(BAR_CL(4));
    const int role = __shfl_sync(~0u, lds1(sM + 32 + wg * 4), 0);
    if ((tid & 127) == 0) TS(4 + wg, 10);
    const int m = lane >> 3, r = lane & 7;
    const uint32_t stoff = (w4 * 16 + (m & 1) * 8 + r) * 128;
    if (role == 0) {
      float acc[64];
      uint32_t sl = 0;
#pragma unroll 1
      for (int n = 0; n < 8; n++) {
        sl = tail_slots(n);
        const uint32_t w0 = (sl >> 8) & 255, w1 = sl >> 16;
        const uint64_t da = make_desc(sb + (sl & 255) * 8192, 16, 1024, 1), db = make_desc(sb + w0 * 8192, (w1 - w0) * 8192, 1024, 1);
        mbar_wait(BAR_TF(n), 0);
        wg_fence();
#pragma unroll
        for (int k = 0; k < 4; k++) wg_ss128<0, 1>(acc, da + k * 2, db + k * 128, (n | k) != 0);
        wg_commit();
        if (n == 6) wg_wait<0>(); else wg_wait<1>();
        if ((tid & 127) == 0) {
          if (n >= 1 && n < 7) mbar_arrive(BAR_TE(n - 1));
          if (n == 6) mbar_arrive(BAR_TE(6));
        }
        __syncwarp();
      }
      wg_wait<0>();
      fence_regs<64>(acc);
      if ((tid & 127) == 0) TS(4 + wg, 11);
      named_bar(wg + 1, 128);
      const uint32_t x0 = sb + ((sl >> 8) & 255) * 8192, x1 = sb + (sl >> 16) * 8192;
#pragma unroll
      for (int j = 0; j < 16; j += 2)
        stsm4((j < 8 ? x0 : x1) + stoff + ((((j & 7) + (m >> 1)) ^ r) << 4),
              pack_bf16(acc[4 * j], acc[4 * j + 1]), pack_bf16(acc[4 * j + 2], acc[4 * j + 3]),
              pack_bf16(acc[4 * j + 4], acc[4 * j + 5]), pack_bf16(acc[4 * j + 6], acc[4 * j + 7]));
      fence_async();
      named_bar(wg + 1, 128);
      if (w4 == 0 && elect_one()) {
        tma2d_store(&mOut, x0, 512 + hg * 128, tbA * 64);
        tma2d_store(&mOut, x1, 512 + hg * 128 + 64, tbA * 64);
        bulk_commit();
        asm volatile("cp.async.bulk.wait_group.read 0;" ::: "memory");
        TS(2, 11);
      }
    } else if (role < 3) {
      float acc[32];
#pragma unroll 1
      for (int n = 0; n < 8; n++) {
        const uint32_t sl = tail_slots(n < 4 ? n : (n == 4 ? 8 : n - 1));
        const uint64_t da = make_desc(sb + (sl & 255) * 8192, 16, 1024, 1);
        const uint64_t db = make_desc(sb + ((sl >> (8 * role)) & 255) * 8192, 8192, 1024, 1);
        mbar_wait(BAR_TF(8 + n), 0);
        if ((tid & 127) == 0 && role == 1) TS(2, 2 + n);
        wg_fence();
#pragma unroll
        for (int k = 0; k < 4; k++) wg_ss64<0, 1>(acc, da + k * 2, db + k * 128, (n | k) != 0);
        wg_commit();
        wg_wait<2>();
      }
      wg_wait<0>();
      fence_regs<32>(acc);
      if ((tid & 127) == 0) TS(4 + wg, 11);
      const uint32_t xs = sb + ((tail_slots(0) >> (8 * role)) & 255) * 8192;
#pragma unroll
      for (int j = 0; j < 8; j += 2)
        stsm4(xs + stoff + (((j + (m >> 1)) ^ r) << 4),
              pack_bf16(acc[4 * j], acc[4 * j + 1]), pack_bf16(acc[4 * j + 2], acc[4 * j + 3]),
              pack_bf16(acc[4 * j + 4], acc[4 * j + 5]), pack_bf16(acc[4 * j + 6], acc[4 * j + 7]));
      fence_async();
      named_bar(wg + 1, 128);
      if (w4 == 0 && elect_one()) {
        tma2d_store(&mOut, xs, hg * 128 + (role - 1) * 64, tbA * 64);
        bulk_commit();
        asm volatile("cp.async.bulk.wait_group.read 0;" ::: "memory");
        TS(2, 12);
      }
    }
  }
}

typedef CUresult (*EncodeFn)(CUtensorMap*, CUtensorMapDataType, cuuint32_t, void*, const cuuint64_t*, const cuuint64_t*,
                             const cuuint32_t*, const cuuint32_t*, CUtensorMapInterleave, CUtensorMapSwizzle,
                             CUtensorMapL2promotion, CUtensorMapFloatOOBfill);

static void make_map(EncodeFn enc, CUtensorMap* m, const void* ptr, uint64_t cols, uint64_t rows, uint32_t bc, uint32_t br,
                     CUtensorMapSwizzle sw = CU_TENSOR_MAP_SWIZZLE_128B) {
  cuuint64_t dims[2] = {cols, rows};
  cuuint64_t strides[1] = {cols * 2};
  cuuint32_t box[2] = {bc, br};
  cuuint32_t es[2] = {1, 1};
  enc(m, CU_TENSOR_MAP_DATA_TYPE_BFLOAT16, 2, (void*)ptr, dims, strides, box, es, CU_TENSOR_MAP_INTERLEAVE_NONE,
      sw, CU_TENSOR_MAP_L2_PROMOTION_L2_256B, CU_TENSOR_MAP_FLOAT_OOB_FILL_NONE);
}

extern "C" void kernel_launch(void* const* d_in, const int* in_sizes, int n_in, void* d_out, int out_size) {
  (void)in_sizes; (void)n_in; (void)out_size;
  static EncodeFn enc = nullptr;
  static void* pQ = nullptr; static void* pO = nullptr;
  if (!enc) {
    void* fn = nullptr; cudaDriverEntryPointQueryResult qr;
    cudaGetDriverEntryPoint("cuTensorMapEncodeTiled", &fn, cudaEnableDefault, &qr);
    enc = (EncodeFn)fn;
    cudaGetSymbolAddress(&pQ, g_Q);
    cudaGetSymbolAddress(&pO, g_O);
    cudaFuncSetAttribute(k1_main, cudaFuncAttributeMaxDynamicSharedMemorySize, SM_TOTAL);
  }
  CUtensorMap mXA64, mXB, mWq, mWqkv, mQst, mO, mOst, mWoA, mWoB, mOut, mO16;
  make_map(enc, &mXA64, d_in[0], 512, 2048, 64, 64);
  make_map(enc, &mWq, d_in[1], 512, 512, 64, 64);
  make_map(enc, &mWoA, d_in[4], 512, 512, 64, 64);
  make_map(enc, &mXB, d_in[5], 512, 2048, 64, 128);
  make_map(enc, &mWqkv, d_in[6], 1536, 512, 64, 64);
  make_map(enc, &mWoB, d_in[7], 512, 512, 64, 64);
  make_map(enc, &mQst, pQ, 512, 4096, 64, 128);
  make_map(enc, &mO, pO, 512, 4096, 64, 64);
  make_map(enc, &mOst, pO, 512, 4096, 64, 128);
  make_map(enc, &mOut, d_out, 1024, 2048, 64, 64);
  make_map(enc, &mO16, pO, 512, 4096, 16, 64, CU_TENSOR_MAP_SWIZZLE_NONE);
  Params prm{(const __nv_bfloat16*)d_in[2], (const __nv_bfloat16*)d_in[3], (const __nv_bfloat16*)d_in[0]};
  k1_main<<<132, 640, SM_TOTAL, cudaStreamPerThread>>>(mXA64, mXB, mWq, mWqkv, mQst, mOst, mO, mWoA, mWoB, mOut, mO16, prm);
}
```

```cpp
#include <cuda_runtime.h>
#include <cuda_bf16.h>
#include <cuda_fp16.h>
#include <cuda.h>
#include <stdint.h>

#define S_TOK 2048
#define D_MOD 512

__device__ __align__(1024) __nv_bfloat16 g_Q[2 * S_TOK * D_MOD];
__device__ __align__(1024) __nv_bfloat16 g_O[2 * S_TOK * D_MOD];
__device__ __align__(1024) uint4 g_KV[8 * S_TOK];
__device__ __align__(16) uint32_t g_stats[128];
__device__ __align__(16) float4 g_kvp[16 * 32 * 3 * 32];

#define TS(k, i) do {} while (0)
__device__ __forceinline__ uint32_t smem_u32(const void* p) { return (uint32_t)__cvta_generic_to_shared(p); }
__device__ __forceinline__ void mbar_init(uint32_t bar, int cnt) { asm volatile("mbarrier.init.shared::cta.b64 [%0], %1;" :: "r"(bar), "r"(cnt) : "memory"); }
__device__ __forceinline__ void mbar_expect_tx(uint32_t bar, uint32_t bytes) { asm volatile("mbarrier.arrive.expect_tx.shared::cta.b64 _, [%0], %1;" :: "r"(bar), "r"(bytes) : "memory"); }
__device__ __forceinline__ bool mbar_try(uint32_t bar, uint32_t parity) {
  uint32_t ok;
  asm volatile("{\n.reg .pred p;\nmbarrier.try_wait.parity.shared::cta.b64 p, [%1], %2;\nselp.b32 %0, 1, 0, p;\n}\n" : "=r"(ok) : "r"(bar), "r"(parity) : "memory");
  return ok;
}
__device__ __forceinline__ void mbar_wait(uint32_t bar, uint32_t parity) {
  asm volatile("{\n.reg .pred p;\n.reg .u32 c;\nmov.u32 c, 0;\n"
               "LW_%=:\n"
               "mbarrier.try_wait.parity.shared::cta.b64 p, [%0], %1;\n"
               "@p bra LD_%=;\n"
               "add.u32 c, c, 1;\n"
               "setp.lt.u32 p, c, 4000000;\n"
               "@p bra LW_%=;\n"
               "trap;\n"
               "LD_%=:\n}\n" :: "r"(bar), "r"(parity) : "memory");
}
__device__ __forceinline__ void mbar_arrive_cta(uint32_t bar, uint32_t cta) {
  asm volatile("{\n.reg .b32 ra;\nmapa.shared::cluster.u32 ra, %0, %1;\nmbarrier.arrive.shared::cluster.b64 _, [ra];\n}\n" :: "r"(bar), "r"(cta) : "memory");
}
__device__ __forceinline__ void cluster_sync() {
  asm volatile("barrier.cluster.arrive.relaxed.aligned;\nbarrier.cluster.wait.aligned;" ::: "memory");
}
__device__ __forceinline__ void tma2d(uint32_t dst, const CUtensorMap* m, int c0, int c1, uint32_t bar) {
  asm volatile("cp.async.bulk.tensor.2d.shared::cluster.global.mbarrier::complete_tx::bytes [%0], [%1, {%3, %4}], [%2];"
               :: "r"(dst), "l"(m), "r"(bar), "r"(c0), "r"(c1) : "memory");
}
__device__ __forceinline__ void tma2d_mc(uint32_t dst, const CUtensorMap* m, int c0, int c1, uint32_t bar, uint16_t mask) {
  asm volatile("cp.async.bulk.tensor.2d.shared::cluster.global.mbarrier::complete_tx::bytes.multicast::cluster [%0], [%1, {%3, %4}], [%2], %5;"
               :: "r"(dst), "l"(m), "r"(bar), "r"(c0), "r"(c1), "h"(mask) : "memory");
}
__device__ __forceinline__ void tma2d_store(const CUtensorMap* m, uint32_t src, int c0, int c1) {
  asm volatile("cp.async.bulk.tensor.2d.global.shared::cta.bulk_group [%0, {%2, %3}], [%1];"
               :: "l"(m), "r"(src), "r"(c0), "r"(c1) : "memory");
}
__device__ __forceinline__ void bulk_g2s(uint32_t dst, const void* src, uint32_t bytes, uint32_t bar) {
  asm volatile("cp.async.bulk.shared::cluster.global.mbarrier::complete_tx::bytes [%0], [%1], %2, [%3];"
               :: "r"(dst), "l"(src), "r"(bytes), "r"(bar) : "memory");
}
__device__ __forceinline__ void bulk_commit() { asm volatile("cp.async.bulk.commit_group;" ::: "memory"); }
__device__ __forceinline__ void bulk_wait_all() { asm volatile("cp.async.bulk.wait_group 0;" ::: "memory"); }
__device__ __forceinline__ void fence_async() { asm volatile("fence.proxy.async.shared::cta;" ::: "memory"); }
__device__ __forceinline__ void named_bar(int id, int n) { asm volatile("bar.sync %0, %1;" :: "r"(id), "r"(n) : "memory"); }
__device__ __forceinline__ void pdl_launch() { asm volatile("griddepcontrol.launch_dependents;" ::: "memory"); }
__device__ __forceinline__ void pdl_wait() { asm volatile("griddepcontrol.wait;" ::: "memory"); }
__device__ __forceinline__ void wg_fence() { asm volatile("wgmma.fence.sync.aligned;" ::: "memory"); }
__device__ __forceinline__ void wg_commit() { asm volatile("wgmma.commit_group.sync.aligned;" ::: "memory"); }
template <int n> __device__ __forceinline__ void wg_wait() { asm volatile("wgmma.wait_group.sync.aligned %0;" :: "n"(n) : "memory"); }
template <int n> __device__ __forceinline__ void fence_regs(float* r) {
#pragma unroll
  for (int i = 0; i < n; i++) asm volatile("" : "+f"(r[i]) :: "memory");
}
template <int n> __device__ __forceinline__ void fence_regs(uint32_t* r) {
#pragma unroll
  for (int i = 0; i < n; i++) asm volatile("" : "+r"(r[i]) :: "memory");
}
__device__ __forceinline__ uint64_t make_desc(uint32_t addr, uint32_t lbo, uint32_t sbo, uint32_t swz) {
  return (uint64_t)((addr & 0x3FFFF) >> 4) | ((uint64_t)(lbo >> 4) << 16) | ((uint64_t)(sbo >> 4) << 32) | ((uint64_t)swz << 62);
}
__device__ __forceinline__ float ex2f(float x) { float y; asm("ex2.approx.ftz.f32 %0, %1;" : "=f"(y) : "f"(x)); return y; }
__device__ __forceinline__ uint32_t pack_bf16(float lo, float hi) { uint32_t r; asm("cvt.rn.bf16x2.f32 %0, %1, %2;" : "=r"(r) : "f"(hi), "f"(lo)); return r; }
__device__ __forceinline__ uint32_t pack_f16(float lo, float hi) { uint32_t r; asm("cvt.rn.f16x2.f32 %0, %1, %2;" : "=r"(r) : "f"(hi), "f"(lo)); return r; }
__device__ __forceinline__ float bf_lo(uint32_t v) { return __uint_as_float(v << 16); }
__device__ __forceinline__ float bf_hi(uint32_t v) { return __uint_as_float(v & 0xFFFF0000u); }
__device__ __forceinline__ float rbf(float x) { return __bfloat162float(__float2bfloat16_rn(x)); }
__device__ __forceinline__ void stsm4(uint32_t a, uint32_t r0, uint32_t r1, uint32_t r2, uint32_t r3) {
  asm volatile("stmatrix.sync.aligned.m8n8.x4.shared.b16 [%0], {%1,%2,%3,%4};" :: "r"(a), "r"(r0), "r"(r1), "r"(r2), "r"(r3) : "memory");
}
__device__ __forceinline__ void stsm4t(uint32_t a, uint32_t r0, uint32_t r1, uint32_t r2, uint32_t r3) {
  asm volatile("stmatrix.sync.aligned.m8n8.x4.trans.shared.b16 [%0], {%1,%2,%3,%4};" :: "r"(a), "r"(r0), "r"(r1), "r"(r2), "r"(r3) : "memory");
}
__device__ __forceinline__ void mma_bf16(float* d, uint32_t a0, uint32_t a1, uint32_t a2, uint32_t a3, uint32_t b0, uint32_t b1) {
  asm volatile("mma.sync.aligned.m16n8k16.row.col.f32.bf16.bf16.f32 {%0,%1,%2,%3}, {%4,%5,%6,%7}, {%8,%9}, {%0,%1,%2,%3};"
               : "+f"(d[0]), "+f"(d[1]), "+f"(d[2]), "+f"(d[3]) : "r"(a0), "r"(a1), "r"(a2), "r"(a3), "r"(b0), "r"(b1));
}
template<int SD> __device__ __forceinline__ void wg_qs24(float* d, uint64_t da, uint64_t db) {
  asm volatile("wgmma.mma_async.sync.aligned.m64n24k16.f32.f16.f16 {%0,%1,%2,%3,%4,%5,%6,%7,%8,%9,%10,%11}, %12, %13, %14, 1, 1, 0, 0;"
   : "+f"(d[0]),"+f"(d[1]),"+f"(d[2]),"+f"(d[3]),"+f"(d[4]),"+f"(d[5]),"+f"(d[6]),"+f"(d[7]),"+f"(d[8]),"+f"(d[9]),"+f"(d[10]),"+f"(d[11])
   : "l"(da),"l"(db),"n"(SD));
}
template<int SD> __device__ __forceinline__ void wg_qs72(float* d, uint64_t da, uint64_t db) {
  asm volatile("wgmma.mma_async.sync.aligned.m64n72k16.f32.f16.f16 {%0,%1,%2,%3,%4,%5,%6,%7,%8,%9,%10,%11,%12,%13,%14,%15,%16,%17,%18,%19,%20,%21,%22,%23,%24,%25,%26,%27,%28,%29,%30,%31,%32,%33,%34,%35}, %36, %37, %38, 1, 1, 0, 0;"
   : "+f"(d[0]),"+f"(d[1]),"+f"(d[2]),"+f"(d[3]),"+f"(d[4]),"+f"(d[5]),"+f"(d[6]),"+f"(d[7]),"+f"(d[8]),"+f"(d[9]),"+f"(d[10]),"+f"(d[11]),"+f"(d[12]),"+f"(d[13]),"+f"(d[14]),"+f"(d[15]),"+f"(d[16]),"+f"(d[17]),"+f"(d[18]),"+f"(d[19]),"+f"(d[20]),"+f"(d[21]),"+f"(d[22]),"+f"(d[23]),"+f"(d[24]),"+f"(d[25]),"+f"(d[26]),"+f"(d[27]),"+f"(d[28]),"+f"(d[29]),"+f"(d[30]),"+f"(d[31]),"+f"(d[32]),"+f"(d[33]),"+f"(d[34]),"+f"(d[35])
   : "l"(da),"l"(db),"n"(SD));
}
template<int SD> __device__ __forceinline__ void wg_pv24(float* d, const uint32_t* a, uint64_t desc) {
  asm volatile("wgmma.mma_async.sync.aligned.m64n24k16.f32.bf16.bf16 {%0,%1,%2,%3,%4,%5,%6,%7,%8,%9,%10,%11}, {%12,%13,%14,%15}, %16, %17, 1, 1, 1;"
   : "+f"(d[0]),"+f"(d[1]),"+f"(d[2]),"+f"(d[3]),"+f"(d[4]),"+f"(d[5]),"+f"(d[6]),"+f"(d[7]),"+f"(d[8]),"+f"(d[9]),"+f"(d[10]),"+f"(d[11])
   : "r"(a[0]),"r"(a[1]),"r"(a[2]),"r"(a[3]),"l"(desc),"n"(SD));
}
template<int TA, int TB> __device__ __forceinline__ void wg_ss128(float* d, uint64_t da, uint64_t db, int sd) {
  asm volatile("{\n.reg .pred p;\nsetp.ne.b32 p, %66, 0;\n"
   "wgmma.mma_async.sync.aligned.m64n128k16.f32.bf16.bf16 {%0,%1,%2,%3,%4,%5,%6,%7,%8,%9,%10,%11,%12,%13,%14,%15,%16,%17,%18,%19,%20,%21,%22,%23,%24,%25,%26,%27,%28,%29,%30,%31,%32,%33,%34,%35,%36,%37,%38,%39,%40,%41,%42,%43,%44,%45,%46,%47,%48,%49,%50,%51,%52,%53,%54,%55,%56,%57,%58,%59,%60,%61,%62,%63}, %64, %65, p, 1, 1, %67, %68;\n}\n"
   : "+f"(d[0]),"+f"(d[1]),"+f"(d[2]),"+f"(d[3]),"+f"(d[4]),"+f"(d[5]),"+f"(d[6]),"+f"(d[7]),"+f"(d[8]),"+f"(d[9]),"+f"(d[10]),"+f"(d[11]),"+f"(d[12]),"+f"(d[13]),"+f"(d[14]),"+f"(d[15]),"+f"(d[16]),"+f"(d[17]),"+f"(d[18]),"+f"(d[19]),"+f"(d[20]),"+f"(d[21]),"+f"(d[22]),"+f"(d[23]),"+f"(d[24]),"+f"(d[25]),"+f"(d[26]),"+f"(d[27]),"+f"(d[28]),"+f"(d[29]),"+f"(d[30]),"+f"(d[31]),"+f"(d[32]),"+f"(d[33]),"+f"(d[34]),"+f"(d[35]),"+f"(d[36]),"+f"(d[37]),"+f"(d[38]),"+f"(d[39]),"+f"(d[40]),"+f"(d[41]),"+f"(d[42]),"+f"(d[43]),"+f"(d[44]),"+f"(d[45]),"+f"(d[46]),"+f"(d[47]),"+f"(d[48]),"+f"(d[49]),"+f"(d[50]),"+f"(d[51]),"+f"(d[52]),"+f"(d[53]),"+f"(d[54]),"+f"(d[55]),"+f"(d[56]),"+f"(d[57]),"+f"(d[58]),"+f"(d[59]),"+f"(d[60]),"+f"(d[61]),"+f"(d[62]),"+f"(d[63])
   : "l"(da),"l"(db),"r"(sd),"n"(TA),"n"(TB));
}
template<int TA, int TB> __device__ __forceinline__ void wg_ss64(float* d, uint64_t da, uint64_t db, int sd) {
  asm volatile("{\n.reg .pred p;\nsetp.ne.b32 p, %34, 0;\n"
   "wgmma.mma_async.sync.aligned.m64n64k16.f32.bf16.bf16 {%0,%1,%2,%3,%4,%5,%6,%7,%8,%9,%10,%11,%12,%13,%14,%15,%16,%17,%18,%19,%20,%21,%22,%23,%24,%25,%26,%27,%28,%29,%30,%31}, %32, %33, p, 1, 1, %35, %36;\n}\n"
   : "+f"(d[0]),"+f"(d[1]),"+f"(d[2]),"+f"(d[3]),"+f"(d[4]),"+f"(d[5]),"+f"(d[6]),"+f"(d[7]),"+f"(d[8]),"+f"(d[9]),"+f"(d[10]),"+f"(d[11]),"+f"(d[12]),"+f"(d[13]),"+f"(d[14]),"+f"(d[15]),"+f"(d[16]),"+f"(d[17]),"+f"(d[18]),"+f"(d[19]),"+f"(d[20]),"+f"(d[21]),"+f"(d[22]),"+f"(d[23]),"+f"(d[24]),"+f"(d[25]),"+f"(d[26]),"+f"(d[27]),"+f"(d[28]),"+f"(d[29]),"+f"(d[30]),"+f"(d[31])
   : "l"(da),"l"(db),"r"(sd),"n"(TA),"n"(TB));
}
template<int TA, int TB> __device__ __forceinline__ void wg_ss8(float* d, uint64_t da, uint64_t db, int sd) {
  asm volatile("{\n.reg .pred p;\nsetp.ne.b32 p, %6, 0;\n"
   "wgmma.mma_async.sync.aligned.m64n8k16.f32.bf16.bf16 {%0,%1,%2,%3}, %4, %5, p, 1, 1, %7, %8;\n}\n"
   : "+f"(d[0]),"+f"(d[1]),"+f"(d[2]),"+f"(d[3])
   : "l"(da),"l"(db),"r"(sd),"n"(TA),"n"(TB));
}

__device__ __forceinline__ uint32_t phi2(float a, float b) {
  uint32_t r, e;
  asm("cvt.rn.relu.bf16x2.f32 %0, %1, %2;" : "=r"(r) : "f"(b), "f"(a));
  e = pack_bf16(ex2f(a * 1.4426950408889634f), ex2f(b * 1.4426950408889634f));
  asm("add.rn.bf16x2 %0, %0, %1;" : "+r"(e) : "r"(0x35863586u));
  asm("min.NaN.bf16x2 %0, %0, %1;" : "+r"(e) : "r"(0x3F803F80u));
  asm("add.rn.bf16x2 %0, %0, %1;" : "+r"(e) : "r"(r));
  return e;
}

__device__ __forceinline__ void mbar_arrive(uint32_t bar) { asm volatile("mbarrier.arrive.shared::cta.b64 _, [%0];" :: "r"(bar) : "memory"); }
__device__ __forceinline__ void named_arrive(int id, int n) { asm volatile("bar.arrive %0, %1;" :: "r"(id), "r"(n) : "memory"); }
__device__ __forceinline__ void fence_async_all() { asm volatile("fence.proxy.async.global;" ::: "memory"); }
__device__ __forceinline__ void flag_add(uint32_t* f) { asm volatile("fence.acq_rel.gpu;\nred.relaxed.gpu.global.add.u32 [%0], 1;" :: "l"(f) : "memory"); }
#define PUBLISH(f) asm volatile("fence.proxy.async.global;\nred.relaxed.gpu.global.add.u32 [%0], 1;" :: "l"(f) : "memory")
__device__ __forceinline__ void flag_wait(const uint32_t* f, uint32_t target) {
  uint32_t v;
#pragma unroll 1
  for (int it = 0;; it++) {
    asm volatile("ld.acquire.gpu.global.u32 %0, [%1];" : "=r"(v) : "l"(f) : "memory");
    if ((int32_t)(v - target) >= 0) break;
    if (it > 2000000) __trap();
    __nanosleep(64);
  }
}
__device__ __forceinline__ bool mbar_test(uint32_t bar, uint32_t parity) {
  uint32_t ok;
  asm volatile("{\n.reg .pred p;\nmbarrier.test_wait.parity.shared::cta.b64 p, [%1], %2;\nselp.b32 %0, 1, 0, p;\n}\n" : "=r"(ok) : "r"(bar), "r"(parity) : "memory");
  return ok;
}
__device__ __forceinline__ bool elect_one() {
  uint32_t p;
  asm volatile("{\n.reg .pred P;\nelect.sync _|P, 0xFFFFFFFF;\nselp.b32 %0, 1, 0, P;\n}\n" : "=r"(p));
  return p;
}
__device__ __forceinline__ void lds4(uint32_t a, uint32_t* r) {
  asm volatile("ld.shared.v4.b32 {%0,%1,%2,%3}, [%4];" : "=r"(r[0]), "=r"(r[1]), "=r"(r[2]), "=r"(r[3]) : "r"(a) : "memory");
}
__device__ __forceinline__ uint32_t lds1(uint32_t a) { uint32_t r; asm volatile("ld.shared.b32 %0, [%1];" : "=r"(r) : "r"(a) : "memory"); return r; }
__device__ __forceinline__ void sts1(uint32_t a, uint32_t v) { asm volatile("st.shared.b32 [%0], %1;" :: "r"(a), "r"(v) : "memory"); }
__device__ __forceinline__ void sts4(uint32_t a, uint32_t r0, uint32_t r1, uint32_t r2, uint32_t r3) {
  asm volatile("st.shared.v4.b32 [%0], {%1,%2,%3,%4};" :: "r"(a), "r"(r0), "r"(r1), "r"(r2), "r"(r3) : "memory");
}
__device__ __forceinline__ void ldsm4(uint32_t a, uint32_t* r) {
  asm volatile("ldmatrix.sync.aligned.m8n8.x4.shared.b16 {%0,%1,%2,%3}, [%4];" : "=r"(r[0]), "=r"(r[1]), "=r"(r[2]), "=r"(r[3]) : "r"(a) : "memory");
}
__device__ __forceinline__ float rcpf(float x) { float y; asm("rcp.approx.ftz.f32 %0, %1;" : "=f"(y) : "f"(x)); return y; }
__device__ __forceinline__ uint32_t hfma2(uint32_t a, uint32_t b, uint32_t c) { uint32_t r; asm("fma.rn.f16x2 %0, %1, %2, %3;" : "=r"(r) : "r"(a), "r"(b), "r"(c)); return r; }
__device__ __forceinline__ uint32_t hadd2(uint32_t a, uint32_t b) { uint32_t r; asm("add.rn.f16x2 %0, %1, %2;" : "=r"(r) : "r"(a), "r"(b)); return r; }

#define STEPK 96
#define QSCALE 0.36067376022224085f
#define SMAGIC (512.0f + 2.0f * (191.0f - 30.0f - 1.5823545f))
#define VSHIFT 1073741824.0f

__device__ uint32_t g_epoch[132];
__device__ uint32_t g_flag[288 * 8];
#define FLAG_KV (g_flag)
#define FLAG_B(h) (g_flag + (4 + (h)) * 8)
#define FLAG_OA(cta, pass) (g_flag + (16 + (cta) * 2 + (pass)) * 8)
#define FLAG_LM(i) (g_flag + (272 + (i)) * 8)

#define SM_TOTAL (224 * 1024 + 2048 + 1024)
#define OFF_K 0
#define OFF_F 65536
#define OFF_V 131072
#define OFF_MISC (224 * 1024)

#define BAR_FULL(s) (bars + 8 * (s))
#define BAR_EMPTY(s) (bars + 24 + 8 * (s))
#define BAR_KV(c) (bars + 48 + 8 * (c))
#define BAR_BDONE (bars + 80)
#define BAR_Q (bars + 88)
#define BAR_GO (bars + 96)
#define BAR_Q2 (bars + 104)
#define BAR_OD(p) (bars + 112 + 8 * (p))
#define BAR_CL(c) (bars + 128 + 8 * (c))
#define BAR_TE(i) (bars + 168 + 8 * (i))
#define BAR_TF(g) (bars + 224 + 8 * (g))
#define BAR_XA(w) (bars + 352 + 8 * (w))
#define BAR_VB(c) (bars + 384 + 8 * (c))

__device__ __forceinline__ uint32_t exp2_pair_fix(float d0, float d1, uint32_t c63, uint32_t m1) {
  uint32_t w, y, s, r;
  asm("prmt.b32 %0, %1, %2, 0x6521;" : "=r"(w) : "r"(__float_as_uint(d0)), "r"(__float_as_uint(d1)));
  asm("lop3.b32 %0, %1, 0x007F007F, %2, 0xEA;" : "=r"(y) : "r"(w), "r"(c63));
  asm("mad.lo.u32 %0, %1, %2, %3;" : "=r"(s) : "r"(y), "r"(m1), "r"(w));
  asm("fma.rn.bf16x2 %0, %1, %2, %3;" : "=r"(r) : "r"(w), "r"(y), "r"(s));
  return r;
}

__device__ __forceinline__ void attn_slow(const uint4* gq, uint32_t dst) {
  const int t = threadIdx.x & 127;
  const int row = t >> 1, half = t & 1;
  float q[16];
#pragma unroll
  for (int i = 0; i < 4; i++) {
    const uint4 v = gq[(row >> 4) * 32 + (row & 7) * 4 + i];
    const uint32_t lo = (row & 8) ? v.y : v.x, hi = (row & 8) ? v.w : v.z;
    q[2 * i] = bf_lo(lo); q[2 * i + 1] = bf_hi(lo); q[2 * i + 8] = bf_lo(hi); q[2 * i + 9] = bf_hi(hi);
  }
  float m = -INFINITY, l = 0.f, o[16];
#pragma unroll
  for (int i = 0; i < 16; i++) o[i] = 0.f;
#pragma unroll 1
  for (int j = half * 1024; j < half * 1024 + 1024; j++) {
    uint4 ka = g_KV[4 * S_TOK + j], kb = g_KV[5 * S_TOK + j];
    uint4 va = g_KV[6 * S_TOK + j], vb = g_KV[7 * S_TOK + j];
    uint32_t kk[8] = {ka.x, ka.y, ka.z, ka.w, kb.x, kb.y, kb.z, kb.w};
    uint32_t vv[8] = {va.x, va.y, va.z, va.w, vb.x, vb.y, vb.z, vb.w};
    float s = 0.f;
#pragma unroll
    for (int i = 0; i < 8; i++) { s = fmaf(q[2 * i], bf_lo(kk[i]), s); s = fmaf(q[2 * i + 1], bf_hi(kk[i]), s); }
    s = rbf(s) * 0.25f;
    if (s > m) {
      float c = __expf(m - s);
      l *= c;
#pragma unroll
      for (int i = 0; i < 16; i++) o[i] *= c;
      m = s;
    }
    float p = __expf(s - m);
    l += p;
#pragma unroll
    for (int i = 0; i < 8; i++) { o[2 * i] = fmaf(p, bf_lo(vv[i]), o[2 * i]); o[2 * i + 1] = fmaf(p, bf_hi(vv[i]), o[2 * i + 1]); }
  }
  float m2 = __shfl_xor_sync(~0u, m, 1);
  float mm = fmaxf(m, m2);
  float c = __expf(m - mm);
  l *= c; l += __shfl_xor_sync(~0u, l, 1);
  float inv = 1.f / l;
  uint32_t r[8];
#pragma unroll
  for (int i = 0; i < 16; i++) { o[i] *= c; o[i] += __shfl_xor_sync(~0u, o[i], 1); o[i] *= inv; }
#pragma unroll
  for (int i = 0; i < 8; i++) r[i] = pack_bf16(o[2 * i], o[2 * i + 1]);
  if (half == 0) sts4(dst, r[0], r[1], r[2], r[3]); else sts4(dst, r[4], r[5], r[6], r[7]);
  fence_async();
}

struct Params { const __nv_bfloat16* wk; const __nv_bfloat16* wv; const __nv_bfloat16* xa; };
__device__ __forceinline__ void cp16(uint32_t dst, const void* src) { asm volatile("cp.async.cg.shared.global [%0], [%1], 16;" :: "r"(dst), "l"(src) : "memory"); }

__device__ __forceinline__ void helper_cta(const int h, const uint32_t sb, const uint32_t bars, const int wg, const int w4,
                                           const CUtensorMap* mQ, const CUtensorMap* mOs) {
  const int lane = threadIdx.x & 31;
  mbar_wait(BAR_GO, 0);
  const int cb = wg & 1, col = h * 128 + cb * 64, row0 = S_TOK + (wg >> 1) * 1024;
  const uint32_t buf = sb + wg * 49152;
  if (w4 == 0 && elect_one()) {
    fence_async_all();
#pragma unroll 1
    for (int u = 0; u < 3; u++) {
      mbar_expect_tx(BAR_TF(wg * 3 + u), 16384);
      tma2d(buf + u * 16384, mQ, col, row0 + u * 128, BAR_TF(wg * 3 + u));
    }
  }
  const int head = h * 8 + cb * 4 + w4;
  float4 a0 = make_float4(0, 0, 0, 0), a1 = a0, a2 = a0;
#pragma unroll 8
  for (int tt = 0; tt < 16; tt++) {
    const float4* src = g_kvp + ((tt * 32 + head) * 3) * 32 + lane;
    float4 u = src[0], v = src[32], w = src[64];
    a0.x += u.x; a0.y += u.y; a0.z += u.z; a0.w += u.w;
    a1.x += v.x; a1.y += v.y; a1.z += v.z; a1.w += v.w;
    a2.x += w.x; a2.y += w.y; a2.z += w.z; a2.w += w.w;
  }
  const uint32_t b00 = pack_bf16(a0.x, a0.y), b01 = pack_bf16(a0.z, a0.w);
  const uint32_t b10 = pack_bf16(a1.x, a1.y), b11 = pack_bf16(a1.z, a1.w);
  const uint32_t bz0 = pack_bf16(a2.x, a2.y), bz1 = pack_bf16(a2.z, a2.w);
  const int m = lane >> 3, r = lane & 7;
  const uint32_t off = ((m & 1) * 8 + r) * 128 + (((w4 * 2 + (m >> 1)) ^ r) << 4);
  int s = 0, ph = 0;
#pragma unroll 1
  for (int u = 0; u < 8; u++) {
    const uint32_t bb = buf + s * 16384;
    mbar_wait(BAR_TF(wg * 3 + s), ph);
#pragma unroll
    for (int mt = 0; mt < 8; mt++) {
      uint32_t a[4];
      ldsm4(bb + mt * 2048 + off, a);
      float n0[4] = {0, 0, 0, 0}, n1[4] = {0, 0, 0, 0}, dn[4] = {0, 0, 0, 0};
      mma_bf16(dn, a[0], a[1], a[2], a[3], bz0, bz1);
      mma_bf16(n0, a[0], a[1], a[2], a[3], b00, b01);
      mma_bf16(n1, a[0], a[1], a[2], a[3], b10, b11);
      const float i0 = rcpf(dn[0] + 1e-6f), i1 = rcpf(dn[2] + 1e-6f);
      stsm4(bb + mt * 2048 + off, pack_bf16(n0[0] * i0, n0[1] * i0), pack_bf16(n0[2] * i1, n0[3] * i1),
            pack_bf16(n1[0] * i0, n1[1] * i0), pack_bf16(n1[2] * i1, n1[3] * i1));
    }
    fence_async();
    named_bar(wg + 1, 128);
    if (w4 == 0 && lane == 0) {
      tma2d_store(mOs, bb, col, row0 + u * 128);
      bulk_commit();
      if (u >= 1 && u + 2 < 8) {
        asm volatile("cp.async.bulk.wait_group.read 1;" ::: "memory");
        const int sp = s == 0 ? 2 : s - 1;
        mbar_expect_tx(BAR_TF(wg * 3 + sp), 16384);
        tma2d(buf + sp * 16384, mQ, col, row0 + (u + 2) * 128, BAR_TF(wg * 3 + sp));
      }
    }
    __syncwarp();
    if (++s == 3) { s = 0; ph ^= 1; }
  }
  if (w4 == 0 && lane == 0) {
    bulk_wait_all();
    fence_async_all();
    flag_add(FLAG_LM((h * 2 + cb) * 2 + (wg >> 1)));
    if (wg == 0) TS(1, 8);
  }
}

#define STAGE(s) (sb + (2 - (s)) * 65536)
template <int TR> __device__ __forceinline__ void proj_kb(float* acc, uint32_t st, uint32_t offA, uint32_t offB, int first) {
  const uint64_t da = make_desc(st + offA, TR ? 8192 : 16, 1024, 1);
  const uint64_t db = make_desc(st + offB, TR ? 16 : 8192, 1024, 1);
  wg_fence();
#pragma unroll
  for (int k = 0; k < 4; k++) wg_ss128<TR, 1 - TR>(acc, da + k * (TR ? 128 : 2), db + k * (TR ? 2 : 128), k != 0 || !first);
  wg_commit();
}
template <int TR> __device__ __forceinline__ void proj_loop(float* acc, uint32_t sb, uint32_t bars, uint32_t offA, uint32_t offB,
                                                            int wg, uint32_t sWKV) {
  {
    float kv[4];
    if (threadIdx.x == 0) TS(0, 13);
    mbar_wait(BAR_XA(wg), 0);
    if (threadIdx.x == 0) TS(0, 1);
    const uint64_t da = make_desc(STAGE(2) + wg * 16384, 16, 1024, 1), db = make_desc(sWKV + wg * 2048, 128, 128, 0);
    wg_fence();
#pragma unroll
    for (int k = 0; k < 8; k++) wg_ss8<0, 1>(kv, da + (k >> 2) * 512 + (k & 3) * 2, db + k * 16, k != 0);
    wg_commit();
    wg_wait<0>();
    fence_regs<4>(kv);
    named_bar(wg + 1, 128);
    sts4(sWKV + threadIdx.x * 16, __float_as_uint(kv[0]), __float_as_uint(kv[1]), __float_as_uint(kv[2]), __float_as_uint(kv[3]));
    __syncwarp();
    if ((threadIdx.x & 31) == 0) mbar_arrive(BAR_GO);
  }
  int s = 0, ph = 0, sp = 0;
#pragma unroll 1
  for (int kb = 0; kb < 8; kb++) {
    mbar_wait(BAR_FULL(s), ph);
    if (threadIdx.x == 0) TS(0, 2 + kb);
    proj_kb<TR>(acc, STAGE(s), offA, offB, kb == 0);
    wg_wait<1>();
    if (kb >= 1 && (threadIdx.x & 127) == 0) mbar_arrive(BAR_EMPTY(sp));
    __syncwarp();
    sp = s;
    if (++s == 3) { s = 0; ph ^= 1; }
  }
  wg_wait<0>();
  fence_regs<64>(acc);
}

__device__ __forceinline__ uint32_t tail_slots(int t) {
  const uint32_t lo = t < 4 ? (t < 2 ? (t == 0 ? 0x0C0B0Au : 0x0F0E0Du) : (t == 2 ? 0x100400u : 0x181408u))
                            : (t < 6 ? (t == 4 ? 0x110501u : 0x191502u) : (t == 6 ? 0x161206u : (t == 7 ? 0x130703u : 0x1B171Au)));
  return lo;
}

__device__ __forceinline__ void take_role(uint32_t sM, int wg) {
  uint32_t r;
  asm volatile("atom.shared.add.u32 %0, [%1], 1;" : "=r"(r) : "r"(sM + 20) : "memory");
  sts1(sM + 32 + wg * 4, r);
}

__global__ void __launch_bounds__(640, 1)
k1_main(const __grid_constant__ CUtensorMap mXA64, const __grid_constant__ CUtensorMap mXB,
        const __grid_constant__ CUtensorMap mWq, const __grid_constant__ CUtensorMap mWqkv,
        const __grid_constant__ CUtensorMap mQst, const __grid_constant__ CUtensorMap mOst,
        const __grid_constant__ CUtensorMap mO, const __grid_constant__ CUtensorMap mWoA,
        const __grid_constant__ CUtensorMap mWoB, const __grid_constant__ CUtensorMap mOut,
        const __grid_constant__ CUtensorMap mO16, const Params prm) {
  extern __shared__ uint8_t smem_raw[];
  const uint32_t sb = (smem_u32(smem_raw) + 1023u) & ~1023u;
  const uint32_t bars = sb + OFF_MISC, sM = bars + 512, sT = bars + 1024;
  const int tid = threadIdx.x, warp = __shfl_sync(~0u, tid >> 5, 0), wg = warp >> 2, w4 = warp & 3, lane = tid & 31;
  const bool helper = blockIdx.x >= 128;
  if (tid == 0) TS(0, 0);
  const int G = blockIdx.x >> 4, gi = blockIdx.x & 15;
  const int tbA = G * 4 + (gi >> 2), hg = gi & 3;
  const int ttB = (G >> 1) * 4 + (gi >> 2), hq = (G & 1) * 4 + (gi & 3);
  auto issue = [&](int kb, int s) {
    const uint32_t fb = BAR_FULL(s), st = STAGE(s);
    mbar_expect_tx(fb, 65536);
    tma2d(st + 16384, &mXA64, kb * 64, tbA * 64, fb);
    tma2d(st, &mWq, hg * 128, kb * 64, fb);
    tma2d(st + 8192, &mWq, hg * 128 + 64, kb * 64, fb);
    tma2d(st + 49152, &mXB, kb * 64, ttB * 128, fb);
    tma2d(st + 24576, &mWqkv, hq * 64, kb * 64, fb);
    tma2d(st + 32768, &mWqkv, 512 + hq * 64, kb * 64, fb);
    tma2d(st + 40960, &mWqkv, 1024 + hq * 64, kb * 64, fb);
  };
  const uint32_t sOne = sb + OFF_V + 65536, sWKV = sOne + 24576;
  if (warp >= 16) {
    if (warp == 17) {
      if (elect_one()) {
        mbar_init(BAR_BDONE, 8); mbar_init(BAR_Q, 8); mbar_init(BAR_GO, helper ? 1 : 16); mbar_init(BAR_Q2, 5);
        mbar_init(BAR_OD(0), 16); mbar_init(BAR_OD(1), 16); mbar_init(BAR_CL(0), 1); mbar_init(BAR_FULL(2), 1);
#pragma unroll
        for (int i = 0; i < 4; i++) mbar_init(BAR_CL(i + 1), i == 0 ? 5 : 4);
#pragma unroll
        for (int i = 0; i < 3; i++) { mbar_init(BAR_EMPTY(i), 4); mbar_init(BAR_KV(i), 1); mbar_init(BAR_VB(i), 1); }
        sts1(sM + 20, 0);
        asm volatile("fence.mbarrier_init.release.cluster;" ::: "memory");
      }
    } else if (warp == 18) {
      if (elect_one()) {
#pragma unroll
        for (int i = 0; i < 7; i++) mbar_init(BAR_TE(i), 1);
#pragma unroll
        for (int i = 0; i < 16; i++) mbar_init(BAR_TF(i), i < 12 || i == 15 ? 1 : 2);
        asm volatile("fence.mbarrier_init.release.cluster;" ::: "memory");
      }
    } else if (warp == 16 && !helper && elect_one()) {
#pragma unroll
      for (int w = 0; w < 4; w++) mbar_init(BAR_XA(w), 1);
      mbar_init(BAR_FULL(0), 1); mbar_init(BAR_FULL(1), 1);
      asm volatile("fence.mbarrier_init.release.cluster;" ::: "memory");
#pragma unroll
      for (int w = 0; w < 4; w++) {
        mbar_expect_tx(BAR_XA(w), 16384);
        tma2d(STAGE(2) + w * 16384, &mXA64, w * 128, tbA * 64, BAR_XA(w));
        tma2d(STAGE(2) + w * 16384 + 8192, &mXA64, w * 128 + 64, tbA * 64, BAR_XA(w));
      }
      TS(0, 14);
      issue(0, 0);
    }
  } else if (!helper) {
    const uint4 v = __ldg((const uint4*)(hg >= 2 ? prm.wv : prm.wk) + tid * 2 + (hg & 1));
#pragma unroll
    for (int i = 0; i < 3; i++) {
      const int key = tid + i * 512;
      sts4(sOne + key * 16, (key % STEPK) < 24 ? 0x00003F80u : 0x00004E80u, 0u, 0u, 0u);
    }
    sts4(sWKV + tid * 16, v.x, v.y, v.z, v.w);
    fence_async();
  }
  __syncthreads();
  if (wg == 4) {
    if (w4 == 0 && !helper && elect_one()) { issue(1, 1); TS(0, 15); }
    asm volatile("setmaxnreg.dec.sync.aligned.u32 32;");
    const uint32_t ep = g_epoch[blockIdx.x] + 1;
    if (helper) {
      if (w4 == 0 && elect_one()) {
        flag_wait(FLAG_B(blockIdx.x - 128), ep * 32);
        fence_async_all();
        TS(1, 10);
        mbar_arrive(BAR_GO);
        g_epoch[blockIdx.x] = ep;
      }
      return;
    }
    mbar_wait(BAR_GO, 0);
    if (w4 == 0 && elect_one()) issue(2, 2);
    {
      uint32_t a[4], b[4];
      float c[4];
      lds4(sWKV + (tid - 512) * 16, a);
      lds4(sWKV + 2048 + (tid - 512) * 16, b);
#pragma unroll
      for (int i = 0; i < 4; i++) c[i] = __uint_as_float(a[i]) + __uint_as_float(b[i]);
      lds4(sWKV + 4096 + (tid - 512) * 16, a);
      lds4(sWKV + 6144 + (tid - 512) * 16, b);
#pragma unroll
      for (int i = 0; i < 4; i++) c[i] += __uint_as_float(a[i]) + __uint_as_float(b[i]);
      sts1(sT + w4 * 256 + lane * 4, pack_bf16(c[0], c[1]));
      sts1(sT + w4 * 256 + 128 + lane * 4, pack_bf16(c[2], c[3]));
    }
    named_bar(9, 128);
    {
      const int t = tid - 512;
#pragma unroll
      for (int i = 0; i < 4; i++) {
        const int key = 1536 + t + i * 128;
        sts4(sOne + key * 16, (key % STEPK) < 24 ? 0x00003F80u : 0x00004E80u, 0u, 0u, 0u);
      }
      fence_async();
      __syncwarp();
      if (lane == 0) mbar_arrive(BAR_Q);
    }
    if (w4 == 0) {
      int s = 0, ph = 0;
#pragma unroll 1
      for (int kb = 3; kb < 8; kb++) {
        mbar_wait(BAR_EMPTY(s), ph);
        if (elect_one()) issue(kb, s);
        if (++s == 3) { s = 0; ph ^= 1; }
      }
      flag_wait(FLAG_KV, ep * 128);
      fence_async_all();
      if (lane == 0) TS(0, 11);
#pragma unroll 1
      for (int m = 0; m < 2; m++) {
        mbar_wait(m == 0 ? BAR_EMPTY(2) : BAR_EMPTY(0), 1 - m);
        if (elect_one()) {
          const uint32_t fb = m == 0 ? BAR_KV(0) : BAR_VB(0);
          mbar_expect_tx(fb, 2 * 7 * STEPK * 16);
#pragma unroll
          for (int p = 0; p < 2; p++) bulk_g2s(sb + m * OFF_V + p * 32768, g_KV + (m * 2 + p) * S_TOK, 7 * STEPK * 16, fb);
        }
      }
      mbar_wait(BAR_Q, 0);
      if (elect_one()) {
#pragma unroll
        for (int c = 1; c < 3; c++) {
          const int k0 = c == 1 ? 7 * STEPK : 12 * STEPK, k1 = c == 1 ? 12 * STEPK : S_TOK;
          const uint32_t bytes = (k1 - k0) * 16;
          mbar_expect_tx(BAR_KV(c), 4 * bytes);
#pragma unroll
          for (int p = 0; p < 4; p++)
            bulk_g2s(sb + (p >> 1) * OFF_V + (p & 1) * 32768 + k0 * 16, g_KV + p * S_TOK + k0, bytes, BAR_KV(c));
        }
      }
      mbar_wait(BAR_CL(1), 0);
      flag_wait(FLAG_LM((lane & 7) * 2 + (tbA >> 4)), ep);
      __syncwarp();
      fence_async_all();
      if (lane == 0) TS(2, 13);
#pragma unroll 1
      for (int n = 0; n < 8; n++) {
        mbar_wait(BAR_CL(n < 4 ? n >> 1 : (n == 4 ? 2 : (n < 7 ? 3 : 4))), 0);
        const uint32_t sl = tail_slots(n), fb = BAR_TF(n);
        if (elect_one()) {
          mbar_expect_tx(fb, 24576);
          tma2d(sb + (sl & 255) * 8192, &mO, n * 64, S_TOK + tbA * 64, fb);
          tma2d(sb + ((sl >> 8) & 255) * 8192, &mWoB, hg * 128, n * 64, fb);
          tma2d(sb + (sl >> 16) * 8192, &mWoB, hg * 128 + 64, n * 64, fb);
        }
      }
      if (lane == 0) g_epoch[blockIdx.x] = ep;
    } else if (w4 == 3) {
      flag_wait(FLAG_KV, ep * 128);
      const uint4 a = *(const uint4*)(g_stats + lane * 4);
      const float kmax2 = __uint_as_float(__reduce_max_sync(~0u, a.x)) + __uint_as_float(__reduce_max_sync(~0u, a.y));
      const float vmax = __uint_as_float(__reduce_max_sync(~0u, max(a.z, a.w)));
      const float lv = vmax > 0.f ? __log2f(vmax) : 0.f;
      const float lim = fminf(90.f, fminf(91.f + lv, 95.f - lv));
      float thr = -1.f;
      if (vmax < 1e27f && kmax2 <= 65536.f && lim > 2.f) thr = fminf(60000.f, (lim * lim - 1.f) / (kmax2 * 1.02f + 1e-30f));
      if (lane == 0) { sts1(sM + 16, __float_as_uint(thr)); mbar_arrive(BAR_Q2); }
      mbar_wait(BAR_CL(3), 0);
      flag_wait(FLAG_OA(tbA * 4 + (lane & 3), 0), ep);
      __syncwarp();
      fence_async_all();
#pragma unroll 1
      for (int n = 0; n < 8; n++) {
        mbar_wait(n == 7 ? BAR_CL(4) : BAR_TE(n), 0);
        const uint32_t sl = tail_slots(n == 7 ? 8 : n), fb = BAR_TF(n + 8);
        const int k0 = n < 4 ? n * 128 : ((hg + n + 1) & 3) * 128 + 64;
        if (elect_one()) {
          mbar_expect_tx(fb, n < 4 ? 24576 : 16384);
          if (n < 4) tma2d(sb + (sl & 255) * 8192, &mO, k0, tbA * 64, fb);
          tma2d(sb + ((sl >> 8) & 255) * 8192, &mWoA, hg * 128, k0, fb);
          tma2d(sb + (sl >> 16) * 8192, &mWoA, hg * 128 + 64, k0, fb);
        }
      }
    } else {
      const int tok = (w4 - 1) * 32 + lane;
      int step, col;
      if ((tbA & 3) == 0) {
        const int b8 = tbA >> 2;
        if (tok < 22) { step = tok; col = 24 + b8; }
        else { const int c = tok >= 43; step = tok - 22 - 21 * c; col = 32 + b8 * 2 + c; }
      } else {
        const int b24 = (tbA >> 2) * 3 + (tbA & 3) - 1;
        if (tok < 42) { const int c = tok >= 21; step = tok - 21 * c; col = 48 + b24 * 2 + c; }
        else { step = tok - 42; col = b24; }
      }
      const int kap = step * STEPK + col;
      const bool chained = col >= 24;
      uint32_t v[4], o[4];
      lds4(sT + tok * 16, v);
      g_KV[(4 + hg) * S_TOK + kap] = make_uint4(v[0], v[1], v[2], v[3]);
      float st = 0.f;
      if (hg < 2) {
        o[0] = o[1] = o[2] = o[3] = 0;
        if (chained && step > 0) lds4(sT + tok * 16 - 16, o);
        const float sc = chained ? 2.f : 1.f;
#pragma unroll
        for (int u = 0; u < 4; u++) {
          const float x = bf_lo(v[u]), y = bf_hi(v[u]);
          st += x * x + y * y;
          o[u] = pack_f16((x - bf_lo(o[u])) * sc, (y - bf_hi(o[u])) * sc);
        }
      } else {
        const float sc = chained ? VSHIFT : 1.f;
#pragma unroll
        for (int u = 0; u < 4; u++) { float x = bf_lo(v[u]), y = bf_hi(v[u]); st += fabsf(x) + fabsf(y); o[u] = pack_bf16(x * sc, y * sc); }
      }
      g_KV[hg * S_TOK + kap] = make_uint4(o[0], o[1], o[2], o[3]);
      const uint32_t um = __reduce_max_sync(~0u, __float_as_uint(st) & 0x7FFFFFFFu);
      if (w4 == 2) {
        if (lane == 0) sts1(sM + 24, um);
        named_arrive(10, 64);
        mbar_wait(BAR_TE(4), 0);
        uint32_t pend = 7;
        const int li = lane < 3 ? lane : 0;
        const uint32_t* fl = FLAG_OA(tbA * 4 + ((hg + li + 1) & 3), 1);
#pragma unroll 1
        for (int it = 0; pend; it++) {
          uint32_t fv;
          asm volatile("ld.acquire.gpu.global.u32 %0, [%1];" : "=r"(fv) : "l"(fl) : "memory");
          const uint32_t go = __ballot_sync(~0u, (int32_t)(fv - ep) >= 0 && mbar_test(BAR_TE(4 + li), 0)) & pend;
          if (go) {
            fence_async_all();
            if (elect_one()) {
#pragma unroll
              for (int n = 0; n < 3; n++)
                if ((go >> n) & 1) {
                  mbar_expect_tx(BAR_TF(12 + n), 8192);
                  tma2d(sb + (tail_slots(4 + n) & 255) * 8192, &mO, ((hg + n + 1) & 3) * 128 + 64, tbA * 64, BAR_TF(12 + n));
                }
            }
            pend &= ~go;
          }
          if (it > 2000000) __trap();
        }
        if (lane == 0) TS(2, 14);
      }
      else {
        named_bar(10, 64);
        if (elect_one()) {
          g_stats[tbA * 4 + hg] = max(um, lds1(sM + 24));
          fence_async_all();
          flag_add(FLAG_KV);
          TS(1, 9);
          mbar_wait(BAR_BDONE, 0);
          tma2d_store(&mQst, sb + OFF_F + 49152, hq * 64, S_TOK + ttB * 128);
          bulk_commit();
          bulk_wait_all();
          fence_async_all();
          flag_add(FLAG_B(hq >> 1));
          TS(0, 12);
          mbar_wait(BAR_Q, 0);
          mbar_arrive(BAR_CL(0));
#pragma unroll 1
          for (int p = 0; p < 2; p++) {
            mbar_wait(BAR_OD(p), 0);
            if (p == 0) {
#pragma unroll
              for (int w = 0; w < 4; w++) tma2d_store(&mO16, sb + OFF_F + w * 2048, hg * 128 + w * 16, tbA * 64);
            } else {
              tma2d_store(&mO, sb + 26 * 8192, hg * 128 + 64, tbA * 64);
            }
            bulk_commit();
            bulk_wait_all();
            if (p == 0) mbar_arrive(BAR_CL(1));
            PUBLISH(FLAG_OA(blockIdx.x, p));
          }
          TS(2, 0);
        }
      }
    }
    return;
  }
  if (helper) { helper_cta(blockIdx.x - 128, sb, bars, wg, w4, &mQst, &mOst); return; }

  {
    float acc[64];
    if (wg == 0) proj_loop<0>(acc, sb, bars, 16384, 0, wg, sWKV);
    else proj_loop<1>(acc, sb, bars, 16384 + wg * 8192, 49152, wg, sWKV);
    asm volatile("setmaxnreg.inc.sync.aligned.u32 112;");
    if (tid == 0) TS(0, 10);
    const uint32_t sF = sb + OFF_F;
    if (wg == 0) {
      uint32_t r[32];
      const uint32_t qa = sF + w4 * 512 + ((lane >> 3) & 1) * 256 + (lane >> 4) * 128 + (lane & 7) * 16;
#pragma unroll
      for (int hd = 0; hd < 8; hd++) {
#pragma unroll
        for (int i = 0; i < 4; i++) r[4 * hd + i] = pack_f16(acc[8 * hd + 2 * i] * QSCALE, acc[8 * hd + 2 * i + 1] * QSCALE);
        stsm4(qa + hd * 2048, r[4 * hd], r[4 * hd + 1], r[4 * hd + 2], r[4 * hd + 3]);
        if (hd == 3) {
          fence_async();
          __syncwarp();
          if (lane == 0) mbar_arrive(BAR_Q);
        }
      }
      fence_async();
      uint32_t nmax = 0;
#pragma unroll
      for (int hd = 0; hd < 8; hd++) {
        const uint32_t* q = r + 4 * hd;
        const uint32_t t0 = hfma2(q[2], q[2], hfma2(q[0], q[0], 0u)), t1 = hfma2(q[3], q[3], hfma2(q[1], q[1], 0u));
        uint32_t n = hadd2(__byte_perm(t0, t1, 0x5410), __byte_perm(t0, t1, 0x7632));
        n = hadd2(n, __shfl_xor_sync(~0u, n, 1));
        n = hadd2(n, __shfl_xor_sync(~0u, n, 2));
        nmax = __vmaxu2(nmax, n & 0x7FFF7FFFu);
      }
      nmax = __reduce_max_sync(~0u, max(nmax & 0xFFFFu, nmax >> 16));
      if (lane == 0) sts1(sM + w4 * 4, nmax);
      uint4* gq = (uint4*)g_Q + blockIdx.x * 1024 + tid;
#pragma unroll
      for (int hd = 0; hd < 8; hd++)
        gq[hd * 128] = make_uint4(pack_bf16(acc[8 * hd], acc[8 * hd + 1]), pack_bf16(acc[8 * hd + 2], acc[8 * hd + 3]),
                                  pack_bf16(acc[8 * hd + 4], acc[8 * hd + 5]), pack_bf16(acc[8 * hd + 6], acc[8 * hd + 7]));
      __syncwarp();
      if (lane == 0) mbar_arrive(BAR_Q2);
    } else if (wg == 3) {
      named_arrive(8, 384);
      named_bar(6, 384);
      const int t = tid & 127;
#pragma unroll
      for (int j = 0; j < 8; j++)
        sts4(sF + 24576 + j * 2048 + t * 16, pack_bf16(acc[8 * j], acc[8 * j + 1]), pack_bf16(acc[8 * j + 2], acc[8 * j + 3]),
             pack_bf16(acc[8 * j + 4], acc[8 * j + 5]), pack_bf16(acc[8 * j + 6], acc[8 * j + 7]));
      named_arrive(7, 256);
    } else {
      uint32_t p[32];
      named_arrive(6, 384);
      if (wg == 2) named_arrive(8, 384);
#pragma unroll
      for (int i = 0; i < 32; i++) p[i] = phi2(acc[2 * i], acc[2 * i + 1]);
      if (wg == 1) {
        named_bar(8, 384);
        const int m = lane >> 3, r = lane & 7;
#pragma unroll
        for (int j = 0; j < 16; j += 2) {
          const int tok = (j + (m >> 1)) * 8 + r;
          const int chunk = w4 * 2 + (m & 1);
          stsm4t(sF + 49152 + tok * 128 + ((chunk ^ r) << 4), p[2 * j], p[2 * j + 1], p[2 * j + 2], p[2 * j + 3]);
        }
        fence_async();
      } else {
        named_bar(7, 256);
        float kv0[4] = {0, 0, 0, 0}, kv1[4] = {0, 0, 0, 0}, z0[4] = {0, 0, 0, 0}, z1[4] = {0, 0, 0, 0};
        const uint32_t one = 0x3F803F80u;
        const int t = tid & 127;
#pragma unroll
        for (int j = 0; j < 8; j++) {
          uint32_t a[4];
          lds4(sF + 24576 + j * 2048 + t * 16, a);
          mma_bf16(kv0, a[0], a[1], a[2], a[3], p[4 * j], p[4 * j + 2]);
          mma_bf16(kv1, a[0], a[1], a[2], a[3], p[4 * j + 1], p[4 * j + 3]);
          mma_bf16(z0, one, one, one, one, p[4 * j], p[4 * j + 2]);
          mma_bf16(z1, one, one, one, one, p[4 * j + 1], p[4 * j + 3]);
        }
        float4* dst = g_kvp + ((ttB * 32 + hq * 4 + w4) * 3) * 32 + lane;
        dst[0] = make_float4(kv0[0], kv0[1], kv1[0], kv1[1]);
        dst[32] = make_float4(kv0[2], kv0[3], kv1[2], kv1[3]);
        dst[64] = make_float4(z0[0], z0[1], z1[0], z1[1]);
      }
      __syncwarp();
      if (lane == 0) mbar_arrive(BAR_BDONE);
    }
  }

  bool safe = true;
  {
    const uint32_t c63 = 0x1F801F80u + (threadIdx.x >> 20);
    const uint32_t m1 = (gridDim.x >> 20) - 1u;
    const uint64_t dK0 = make_desc(sb + OFF_K, 32768, 128, 0);
    const uint64_t dV0 = make_desc(sb + OFF_V, 128, 32768, 0);
    constexpr uint32_t dKV = ((2048u - 8u)  __H0__ ) + STEPK - (OFF_V - OFF_K) / 16;
    float Sm[12], Sp[36], O[12];
    uint32_t P[24];
    uint64_t dQ = make_desc(sb + OFF_F + wg * 2048, 128, 256, 0);
#pragma unroll
    for (int i = 0; i < 36; i++) Sp[i] = SMAGIC;
#pragma unroll
    for (int i = 0; i < 12; i++) Sm[i] = 0.f;
    fence_regs<12>(Sm); fence_regs<36>(Sp);
    mbar_wait(BAR_Q, 0);
    mbar_wait(BAR_KV(0), 0);
    wg_fence();
    wg_qs72<1>(Sp, dQ, dK0 + 24);
    wg_qs24<0>(Sm, dQ, dK0);
    wg_commit();
    wg_wait<0>();
    fence_regs<12>(Sm); fence_regs<36>(Sp);
#pragma unroll 1
    for (int pass = 0; pass < 2; pass++) {
#pragma unroll
      for (int i = 0; i < 12; i++) O[i] = 0.f;
      fence_regs<12>(O);
      if (tid == 0) TS(1, 2 + 2 * pass);
      uint32_t vlo = (uint32_t)dV0;
#pragma unroll 1
      for (int seg = 0; seg < 4; seg++) {
        if (pass == 0) {
          if (seg < 3) mbar_wait(seg == 0 ? BAR_VB(0) : BAR_KV(seg), 0);
        } else if (seg >= 1) {
          if ((tid & 127) == 0) {
            mbar_arrive(BAR_CL(seg));
            if (seg == 3) take_role(sM, wg);
          }
          __syncwarp();
        }
        if ((tid & 127) == 0) TS(4 + wg, pass * 5 + seg);
        const uint32_t vend = vlo + (seg == 0 ? 6 : 5) * STEPK;
#pragma unroll 1
        for (; vlo != vend; vlo += STEPK) {
          uint64_t dK, dV;
          asm("mov.b64 %0, {%1, %2};" : "=l"(dK) : "r"(vlo + dKV), "r"(8u));
          asm("mov.b64 %0, {%1, %2};" : "=l"(dV) : "r"(vlo), "r"(2048u));
#pragma unroll
          for (int i = 0; i < 6; i++) P[i] = pack_bf16(ex2f(Sm[2 * i]), ex2f(Sm[2 * i + 1]));
#pragma unroll
          for (int i = 0; i < 18; i++) P[6 + i] = exp2_pair_fix(Sp[2 * i], Sp[2 * i + 1], c63, m1);
          fence_regs<24>(P);
          wg_fence();
#pragma unroll
          for (int k = 0; k < 6; k++) wg_pv24<1>(O, &P[4 * k], dV + k * 16);
          wg_qs72<1>(Sp, dQ, dK + 24);
          wg_qs24<0>(Sm, dQ, dK);
          wg_commit();
          wg_wait<0>();
          fence_regs<12>(Sm); fence_regs<36>(Sp); fence_regs<12>(O); fence_regs<24>(P);
        }
      }
#pragma unroll
      for (int i = 0; i < 6; i++) P[i] = pack_bf16(ex2f(Sm[2 * i]), ex2f(Sm[2 * i + 1]));
      P[6] = exp2_pair_fix(Sp[0], Sp[1], c63, m1);
      P[7] = exp2_pair_fix(Sp[2], Sp[3], c63, m1);
      fence_regs<8>(P);
#pragma unroll
      for (int i = 0; i < 36; i++) Sp[i] = SMAGIC;
      fence_regs<36>(Sp);
      mbar_wait(pass == 0 ? BAR_Q2 : BAR_CL(3), 0);
      const uint32_t sO = pass == 0 ? sb + OFF_F + wg * 2048 + w4 * 512 + (lane & 15) * 32 + (lane >> 4) * 16
                                    : sb + 26 * 8192 + (w4 * 16 + (lane & 15)) * 128 + (((wg * 2 + (lane >> 4)) ^ (lane & 7)) << 4);
      dQ += 512;
      wg_fence();
      wg_pv24<1>(O, &P[0], dV0 + 21 * STEPK);
      wg_pv24<1>(O, &P[4], dV0 + 21 * STEPK + 16);
      wg_commit();
      wg_qs72<1>(Sp, dQ, dK0 + 24);
      wg_qs24<0>(Sm, dQ, dK0);
      wg_commit();
      wg_wait<1>();
      fence_regs<12>(O);
      const float l0 = __shfl_sync(~0u, O[8], lane & ~3), l1 = __shfl_sync(~0u, O[10], lane & ~3);
      const float i0 = rcpf(l0), i1 = rcpf(l1);
      stsm4(sO,
            pack_bf16(O[0] * i0, O[1] * i0), pack_bf16(O[2] * i1, O[3] * i1),
            pack_bf16(O[4] * i0, O[5] * i0), pack_bf16(O[6] * i1, O[7] * i1));
      fence_async();
      {
        uint32_t n[4];
        lds4(sM, n);
        const float qn = __half2float(__ushort_as_half((unsigned short)max(max(n[0], n[1]), max(n[2], n[3]))));
        safe = __all_sync(~0u, qn <= __uint_as_float(lds1(sM + 16)));
      }
      if (safe && lane == 0) mbar_arrive(BAR_OD(pass));
      wg_wait<0>();
      fence_regs<12>(Sm); fence_regs<36>(Sp);
      if (!safe) break;
      if ((tid & 127) == 0) TS(4 + wg, pass * 5 + 4);
      if (tid == 0) TS(1, 3 + 2 * pass);
    }
  }
  if (!safe) {
    if ((tid & 127) == 0) { mbar_arrive(BAR_CL(1)); mbar_arrive(BAR_CL(2)); mbar_arrive(BAR_CL(3)); take_role(sM, wg); }
#pragma unroll 1
    for (int pass = 0; pass < 2; pass++) {
      const int t = tid & 127;
      mbar_wait(BAR_CL(3), 0);
      attn_slow((const uint4*)g_Q + blockIdx.x * 1024 + (pass * 4 + wg) * 128,
                pass == 0 ? sb + OFF_F + wg * 2048 + t * 16
                          : sb + 26 * 8192 + (t >> 1) * 128 + (((wg * 2 + (t & 1)) ^ ((t >> 1) & 7)) << 4));
      __syncwarp();
      if (lane == 0) mbar_arrive(BAR_OD(pass));
    }
  }

  {
    named_bar(wg + 1, 128);
    if ((tid & 127) == 0) mbar_arrive(BAR_CL(4));
    const int role = __shfl_sync(~0u, lds1(sM + 32 + wg * 4), 0);
    if ((tid & 127) == 0) TS(4 + wg, 10);
    const int m = lane >> 3, r = lane & 7;
    const uint32_t stoff = (w4 * 16 + (m & 1) * 8 + r) * 128;
    if (role == 0) {
      float acc[64];
      uint32_t sl = 0;
#pragma unroll 1
      for (int n = 0; n < 8; n++) {
        sl = tail_slots(n);
        const uint32_t w0 = (sl >> 8) & 255, w1 = sl >> 16;
        const uint64_t da = make_desc(sb + (sl & 255) * 8192, 16, 1024, 1), db = make_desc(sb + w0 * 8192, (w1 - w0) * 8192, 1024, 1);
        mbar_wait(BAR_TF(n), 0);
        wg_fence();
#pragma unroll
        for (int k = 0; k < 4; k++) wg_ss128<0, 1>(acc, da + k * 2, db + k * 128, (n | k) != 0);
        wg_commit();
        if (n == 6) wg_wait<0>(); else wg_wait<1>();
        if ((tid & 127) == 0) {
          if (n >= 1 && n < 7) mbar_arrive(BAR_TE(n - 1));
          if (n == 6) mbar_arrive(BAR_TE(6));
        }
        __syncwarp();
      }
      wg_wait<0>();
      fence_regs<64>(acc);
      if ((tid & 127) == 0) TS(4 + wg, 11);
      named_bar(wg + 1, 128);
      const uint32_t x0 = sb + ((sl >> 8) & 255) * 8192, x1 = sb + (sl >> 16) * 8192;
#pragma unroll
      for (int j = 0; j < 16; j += 2)
        stsm4((j < 8 ? x0 : x1) + stoff + ((((j & 7) + (m >> 1)) ^ r) << 4),
              pack_bf16(acc[4 * j], acc[4 * j + 1]), pack_bf16(acc[4 * j + 2], acc[4 * j + 3]),
              pack_bf16(acc[4 * j + 4], acc[4 * j + 5]), pack_bf16(acc[4 * j + 6], acc[4 * j + 7]));
      fence_async();
      named_bar(wg + 1, 128);
      if (w4 == 0 && elect_one()) {
        tma2d_store(&mOut, x0, 512 + hg * 128, tbA * 64);
        tma2d_store(&mOut, x1, 512 + hg * 128 + 64, tbA * 64);
        bulk_commit();
        asm volatile("cp.async.bulk.wait_group.read 0;" ::: "memory");
        TS(2, 11);
      }
    } else if (role < 3) {
      float acc[32];
#pragma unroll 1
      for (int n = 0; n < 8; n++) {
        const uint32_t sl = tail_slots(n == 7 ? 8 : n);
        const uint64_t da = make_desc(sb + (sl & 255) * 8192, 16, 1024, 1);
        const uint64_t db = make_desc(sb + ((sl >> (8 * role)) & 255) * 8192, 8192, 1024, 1);
        mbar_wait(BAR_TF(8 + n), 0);
        if (n == 7) mbar_wait(BAR_OD(1), 0);
        if ((tid & 127) == 0 && role == 1) TS(2, 2 + n);
        wg_fence();
#pragma unroll
        for (int k = 0; k < 4; k++) wg_ss64<0, 1>(acc, da + k * 2, db + k * 128, (n | k) != 0);
        wg_commit();
        wg_wait<2>();
      }
      wg_wait<0>();
      fence_regs<32>(acc);
      if ((tid & 127) == 0) TS(4 + wg, 11);
      const uint32_t xs = sb + ((tail_slots(0) >> (8 * role)) & 255) * 8192;
#pragma unroll
      for (int j = 0; j < 8; j += 2)
        stsm4(xs + stoff + (((j + (m >> 1)) ^ r) << 4),
              pack_bf16(acc[4 * j], acc[4 * j + 1]), pack_bf16(acc[4 * j + 2], acc[4 * j + 3]),
              pack_bf16(acc[4 * j + 4], acc[4 * j + 5]), pack_bf16(acc[4 * j + 6], acc[4 * j + 7]));
      fence_async();
      named_bar(wg + 1, 128);
      if (w4 == 0 && elect_one()) {
        tma2d_store(&mOut, xs, hg * 128 + (role - 1) * 64, tbA * 64);
        bulk_commit();
        asm volatile("cp.async.bulk.wait_group.read 0;" ::: "memory");
        TS(2, 12);
      }
    }
  }
}

typedef CUresult (*EncodeFn)(CUtensorMap*, CUtensorMapDataType, cuuint32_t, void*, const cuuint64_t*, const cuuint64_t*,
                             const cuuint32_t*, const cuuint32_t*, CUtensorMapInterleave, CUtensorMapSwizzle,
                             CUtensorMapL2promotion, CUtensorMapFloatOOBfill);

static void make_map(EncodeFn enc, CUtensorMap* m, const void* ptr, uint64_t cols, uint64_t rows, uint32_t bc, uint32_t br,
                     CUtensorMapSwizzle sw = CU_TENSOR_MAP_SWIZZLE_128B) {
  cuuint64_t dims[2] = {cols, rows};
  cuuint64_t strides[1] = {cols * 2};
  cuuint32_t box[2] = {bc, br};
  cuuint32_t es[2] = {1, 1};
  enc(m, CU_TENSOR_MAP_DATA_TYPE_BFLOAT16, 2, (void*)ptr, dims, strides, box, es, CU_TENSOR_MAP_INTERLEAVE_NONE,
      sw, CU_TENSOR_MAP_L2_PROMOTION_L2_256B, CU_TENSOR_MAP_FLOAT_OOB_FILL_NONE);
}

extern "C" void kernel_launch(void* const* d_in, const int* in_sizes, int n_in, void* d_out, int out_size) {
  (void)in_sizes; (void)n_in; (void)out_size;
  static EncodeFn enc = nullptr;
  static void* pQ = nullptr; static void* pO = nullptr;
  if (!enc) {
    void* fn = nullptr; cudaDriverEntryPointQueryResult qr;
    cudaGetDriverEntryPoint("cuTensorMapEncodeTiled", &fn, cudaEnableDefault, &qr);
    enc = (EncodeFn)fn;
    cudaGetSymbolAddress(&pQ, g_Q);
    cudaGetSymbolAddress(&pO, g_O);
    cudaFuncSetAttribute(k1_main, cudaFuncAttributeMaxDynamicSharedMemorySize, SM_TOTAL);
  }
  CUtensorMap mXA64, mXB, mWq, mWqkv, mQst, mO, mOst, mWoA, mWoB, mOut, mO16;
  make_map(enc, &mXA64, d_in[0], 512, 2048, 64, 64);
  make_map(enc, &mWq, d_in[1], 512, 512, 64, 64);
  make_map(enc, &mWoA, d_in[4], 512, 512, 64, 64);
  make_map(enc, &mXB, d_in[5], 512, 2048, 64, 128);
  make_map(enc, &mWqkv, d_in[6], 1536, 512, 64, 64);
  make_map(enc, &mWoB, d_in[7], 512, 512, 64, 64);
  make_map(enc, &mQst, pQ, 512, 4096, 64, 128);
  make_map(enc, &mO, pO, 512, 4096, 64, 64);
  make_map(enc, &mOst, pO, 512, 4096, 64, 128);
  make_map(enc, &mOut, d_out, 1024, 2048, 64, 64);
  make_map(enc, &mO16, pO, 512, 4096, 16, 64, CU_TENSOR_MAP_SWIZZLE_NONE);
  Params prm{(const __nv_bfloat16*)d_in[2], (const __nv_bfloat16*)d_in[3], (const __nv_bfloat16*)d_in[0]};
  k1_main<<<132, 640, SM_TOTAL, cudaStreamPerThread>>>(mXA64, mXB, mWq, mWqkv, mQst, mOst, mO, mWoA, mWoB, mOut, mO16, prm);
}
```

```cpp
#include <cuda_runtime.h>
#include <cuda_bf16.h>
#include <cuda_fp16.h>
#include <cuda.h>
#include <stdint.h>

#define S_TOK 2048
#define D_MOD 512

__device__ __align__(1024) __nv_bfloat16 g_Q[2 * S_TOK * D_MOD];
__device__ __align__(1024) __nv_bfloat16 g_O[2 * S_TOK * D_MOD];
__device__ __align__(1024) uint4 g_KV[8 * S_TOK];
__device__ __align__(16) uint32_t g_stats[128];
__device__ __align__(16) float4 g_kvp[16 * 32 * 3 * 32];

#define TS(k, i) do {} while (0)
__device__ __forceinline__ uint32_t smem_u32(const void* p) { return (uint32_t)__cvta_generic_to_shared(p); }
__device__ __forceinline__ void mbar_init(uint32_t bar, int cnt) { asm volatile("mbarrier.init.shared::cta.b64 [%0], %1;" :: "r"(bar), "r"(cnt) : "memory"); }
__device__ __forceinline__ void mbar_expect_tx(uint32_t bar, uint32_t bytes) { asm volatile("mbarrier.arrive.expect_tx.shared::cta.b64 _, [%0], %1;" :: "r"(bar), "r"(bytes) : "memory"); }
__device__ __forceinline__ bool mbar_try(uint32_t bar, uint32_t parity) {
  uint32_t ok;
  asm volatile("{\n.reg .pred p;\nmbarrier.try_wait.parity.shared::cta.b64 p, [%1], %2;\nselp.b32 %0, 1, 0, p;\n}\n" : "=r"(ok) : "r"(bar), "r"(parity) : "memory");
  return ok;
}
__device__ __forceinline__ void mbar_wait(uint32_t bar, uint32_t parity) {
  asm volatile("{\n.reg .pred p;\n.reg .u32 c;\nmov.u32 c, 0;\n"
               "LW_%=:\n"
               "mbarrier.try_wait.parity.shared::cta.b64 p, [%0], %1;\n"
               "@p bra LD_%=;\n"
               "add.u32 c, c, 1;\n"
               "setp.lt.u32 p, c, 4000000;\n"
               "@p bra LW_%=;\n"
               "trap;\n"
               "LD_%=:\n}\n" :: "r"(bar), "r"(parity) : "memory");
}
__device__ __forceinline__ void mbar_arrive_cta(uint32_t bar, uint32_t cta) {
  asm volatile("{\n.reg .b32 ra;\nmapa.shared::cluster.u32 ra, %0, %1;\nmbarrier.arrive.shared::cluster.b64 _, [ra];\n}\n" :: "r"(bar), "r"(cta) : "memory");
}
__device__ __forceinline__ void cluster_sync() {
  asm volatile("barrier.cluster.arrive.relaxed.aligned;\nbarrier.cluster.wait.aligned;" ::: "memory");
}
__device__ __forceinline__ void tma2d(uint32_t dst, const CUtensorMap* m, int c0, int c1, uint32_t bar) {
  asm volatile("cp.async.bulk.tensor.2d.shared::cluster.global.mbarrier::complete_tx::bytes [%0], [%1, {%3, %4}], [%2];"
               :: "r"(dst), "l"(m), "r"(bar), "r"(c0), "r"(c1) : "memory");
}
__device__ __forceinline__ void tma2d_mc(uint32_t dst, const CUtensorMap* m, int c0, int c1, uint32_t bar, uint16_t mask) {
  asm volatile("cp.async.bulk.tensor.2d.shared::cluster.global.mbarrier::complete_tx::bytes.multicast::cluster [%0], [%1, {%3, %4}], [%2], %5;"
               :: "r"(dst), "l"(m), "r"(bar), "r"(c0), "r"(c1), "h"(mask) : "memory");
}
__device__ __forceinline__ void tma2d_store(const CUtensorMap* m, uint32_t src, int c0, int c1) {
  asm volatile("cp.async.bulk.tensor.2d.global.shared::cta.bulk_group [%0, {%2, %3}], [%1];"
               :: "l"(m), "r"(src), "r"(c0), "r"(c1) : "memory");
}
__device__ __forceinline__ void bulk_g2s(uint32_t dst, const void* src, uint32_t bytes, uint32_t bar) {
  asm volatile("cp.async.bulk.shared::cluster.global.mbarrier::complete_tx::bytes [%0], [%1], %2, [%3];"
               :: "r"(dst), "l"(src), "r"(bytes), "r"(bar) : "memory");
}
__device__ __forceinline__ void bulk_commit() { asm volatile("cp.async.bulk.commit_group;" ::: "memory"); }
__device__ __forceinline__ void bulk_wait_all() { asm volatile("cp.async.bulk.wait_group 0;" ::: "memory"); }
__device__ __forceinline__ void fence_async() { asm volatile("fence.proxy.async.shared::cta;" ::: "memory"); }
__device__ __forceinline__ void named_bar(int id, int n) { asm volatile("bar.sync %0, %1;" :: "r"(id), "r"(n) : "memory"); }
__device__ __forceinline__ void pdl_launch() { asm volatile("griddepcontrol.launch_dependents;" ::: "memory"); }
__device__ __forceinline__ void pdl_wait() { asm volatile("griddepcontrol.wait;" ::: "memory"); }
__device__ __forceinline__ void wg_fence() { asm volatile("wgmma.fence.sync.aligned;" ::: "memory"); }
__device__ __forceinline__ void wg_commit() { asm volatile("wgmma.commit_group.sync.aligned;" ::: "memory"); }
template <int n> __device__ __forceinline__ void wg_wait() { asm volatile("wgmma.wait_group.sync.aligned %0;" :: "n"(n) : "memory"); }
template <int n> __device__ __forceinline__ void fence_regs(float* r) {
#pragma unroll
  for (int i = 0; i < n; i++) asm volatile("" : "+f"(r[i]) :: "memory");
}
template <int n> __device__ __forceinline__ void fence_regs(uint32_t* r) {
#pragma unroll
  for (int i = 0; i < n; i++) asm volatile("" : "+r"(r[i]) :: "memory");
}
__device__ __forceinline__ uint64_t make_desc(uint32_t addr, uint32_t lbo, uint32_t sbo, uint32_t swz) {
  return (uint64_t)((addr & 0x3FFFF) >> 4) | ((uint64_t)(lbo >> 4) << 16) | ((uint64_t)(sbo >> 4) << 32) | ((uint64_t)swz << 62);
}
__device__ __forceinline__ float ex2f(float x) { float y; asm("ex2.approx.ftz.f32 %0, %1;" : "=f"(y) : "f"(x)); return y; }
__device__ __forceinline__ uint32_t pack_bf16(float lo, float hi) { uint32_t r; asm("cvt.rn.bf16x2.f32 %0, %1, %2;" : "=r"(r) : "f"(hi), "f"(lo)); return r; }
__device__ __forceinline__ uint32_t pack_f16(float lo, float hi) { uint32_t r; asm("cvt.rn.f16x2.f32 %0, %1, %2;" : "=r"(r) : "f"(hi), "f"(lo)); return r; }
__device__ __forceinline__ float bf_lo(uint32_t v) { return __uint_as_float(v << 16); }
__device__ __forceinline__ float bf_hi(uint32_t v) { return __uint_as_float(v & 0xFFFF0000u); }
__device__ __forceinline__ float rbf(float x) { return __bfloat162float(__float2bfloat16_rn(x)); }
__device__ __forceinline__ void stsm4(uint32_t a, uint32_t r0, uint32_t r1, uint32_t r2, uint32_t r3) {
  asm volatile("stmatrix.sync.aligned.m8n8.x4.shared.b16 [%0], {%1,%2,%3,%4};" :: "r"(a), "r"(r0), "r"(r1), "r"(r2), "r"(r3) : "memory");
}
__device__ __forceinline__ void stsm4t(uint32_t a, uint32_t r0, uint32_t r1, uint32_t r2, uint32_t r3) {
  asm volatile("stmatrix.sync.aligned.m8n8.x4.trans.shared.b16 [%0], {%1,%2,%3,%4};" :: "r"(a), "r"(r0), "r"(r1), "r"(r2), "r"(r3) : "memory");
}
__device__ __forceinline__ void mma_bf16(float* d, uint32_t a0, uint32_t a1, uint32_t a2, uint32_t a3, uint32_t b0, uint32_t b1) {
  asm volatile("mma.sync.aligned.m16n8k16.row.col.f32.bf16.bf16.f32 {%0,%1,%2,%3}, {%4,%5,%6,%7}, {%8,%9}, {%0,%1,%2,%3};"
               : "+f"(d[0]), "+f"(d[1]), "+f"(d[2]), "+f"(d[3]) : "r"(a0), "r"(a1), "r"(a2), "r"(a3), "r"(b0), "r"(b1));
}
template<int SD> __device__ __forceinline__ void wg_qs24(float* d, uint64_t da, uint64_t db) {
  asm volatile("wgmma.mma_async.sync.aligned.m64n24k16.f32.f16.f16 {%0,%1,%2,%3,%4,%5,%6,%7,%8,%9,%10,%11}, %12, %13, %14, 1, 1, 0, 0;"
   : "+f"(d[0]),"+f"(d[1]),"+f"(d[2]),"+f"(d[3]),"+f"(d[4]),"+f"(d[5]),"+f"(d[6]),"+f"(d[7]),"+f"(d[8]),"+f"(d[9]),"+f"(d[10]),"+f"(d[11])
   : "l"(da),"l"(db),"n"(SD));
}
template<int SD> __device__ __forceinline__ void wg_qs72(float* d, uint64_t da, uint64_t db) {
  asm volatile("wgmma.mma_async.sync.aligned.m64n72k16.f32.f16.f16 {%0,%1,%2,%3,%4,%5,%6,%7,%8,%9,%10,%11,%12,%13,%14,%15,%16,%17,%18,%19,%20,%21,%22,%23,%24,%25,%26,%27,%28,%29,%30,%31,%32,%33,%34,%35}, %36, %37, %38, 1, 1, 0, 0;"
   : "+f"(d[0]),"+f"(d[1]),"+f"(d[2]),"+f"(d[3]),"+f"(d[4]),"+f"(d[5]),"+f"(d[6]),"+f"(d[7]),"+f"(d[8]),"+f"(d[9]),"+f"(d[10]),"+f"(d[11]),"+f"(d[12]),"+f"(d[13]),"+f"(d[14]),"+f"(d[15]),"+f"(d[16]),"+f"(d[17]),"+f"(d[18]),"+f"(d[19]),"+f"(d[20]),"+f"(d[21]),"+f"(d[22]),"+f"(d[23]),"+f"(d[24]),"+f"(d[25]),"+f"(d[26]),"+f"(d[27]),"+f"(d[28]),"+f"(d[29]),"+f"(d[30]),"+f"(d[31]),"+f"(d[32]),"+f"(d[33]),"+f"(d[34]),"+f"(d[35])
   : "l"(da),"l"(db),"n"(SD));
}
template<int SD> __device__ __forceinline__ void wg_pv24(float* d, const uint32_t* a, uint64_t desc) {
  asm volatile("wgmma.mma_async.sync.aligned.m64n24k16.f32.bf16.bf16 {%0,%1,%2,%3,%4,%5,%6,%7,%8,%9,%10,%11}, {%12,%13,%14,%15}, %16, %17, 1, 1, 1;"
   : "+f"(d[0]),"+f"(d[1]),"+f"(d[2]),"+f"(d[3]),"+f"(d[4]),"+f"(d[5]),"+f"(d[6]),"+f"(d[7]),"+f"(d[8]),"+f"(d[9]),"+f"(d[10]),"+f"(d[11])
   : "r"(a[0]),"r"(a[1]),"r"(a[2]),"r"(a[3]),"l"(desc),"n"(SD));
}
template<int TA, int TB> __device__ __forceinline__ void wg_ss128(float* d, uint64_t da, uint64_t db, int sd) {
  asm volatile("{\n.reg .pred p;\nsetp.ne.b32 p, %66, 0;\n"
   "wgmma.mma_async.sync.aligned.m64n128k16.f32.bf16.bf16 {%0,%1,%2,%3,%4,%5,%6,%7,%8,%9,%10,%11,%12,%13,%14,%15,%16,%17,%18,%19,%20,%21,%22,%23,%24,%25,%26,%27,%28,%29,%30,%31,%32,%33,%34,%35,%36,%37,%38,%39,%40,%41,%42,%43,%44,%45,%46,%47,%48,%49,%50,%51,%52,%53,%54,%55,%56,%57,%58,%59,%60,%61,%62,%63}, %64, %65, p, 1, 1, %67, %68;\n}\n"
   : "+f"(d[0]),"+f"(d[1]),"+f"(d[2]),"+f"(d[3]),"+f"(d[4]),"+f"(d[5]),"+f"(d[6]),"+f"(d[7]),"+f"(d[8]),"+f"(d[9]),"+f"(d[10]),"+f"(d[11]),"+f"(d[12]),"+f"(d[13]),"+f"(d[14]),"+f"(d[15]),"+f"(d[16]),"+f"(d[17]),"+f"(d[18]),"+f"(d[19]),"+f"(d[20]),"+f"(d[21]),"+f"(d[22]),"+f"(d[23]),"+f"(d[24]),"+f"(d[25]),"+f"(d[26]),"+f"(d[27]),"+f"(d[28]),"+f"(d[29]),"+f"(d[30]),"+f"(d[31]),"+f"(d[32]),"+f"(d[33]),"+f"(d[34]),"+f"(d[35]),"+f"(d[36]),"+f"(d[37]),"+f"(d[38]),"+f"(d[39]),"+f"(d[40]),"+f"(d[41]),"+f"(d[42]),"+f"(d[43]),"+f"(d[44]),"+f"(d[45]),"+f"(d[46]),"+f"(d[47]),"+f"(d[48]),"+f"(d[49]),"+f"(d[50]),"+f"(d[51]),"+f"(d[52]),"+f"(d[53]),"+f"(d[54]),"+f"(d[55]),"+f"(d[56]),"+f"(d[57]),"+f"(d[58]),"+f"(d[59]),"+f"(d[60]),"+f"(d[61]),"+f"(d[62]),"+f"(d[63])
   : "l"(da),"l"(db),"r"(sd),"n"(TA),"n"(TB));
}
template<int TA, int TB> __device__ __forceinline__ void wg_ss64(float* d, uint64_t da, uint64_t db, int sd) {
  asm volatile("{\n.reg .pred p;\nsetp.ne.b32 p, %34, 0;\n"
   "wgmma.mma_async.sync.aligned.m64n64k16.f32.bf16.bf16 {%0,%1,%2,%3,%4,%5,%6,%7,%8,%9,%10,%11,%12,%13,%14,%15,%16,%17,%18,%19,%20,%21,%22,%23,%24,%25,%26,%27,%28,%29,%30,%31}, %32, %33, p, 1, 1, %35, %36;\n}\n"
   : "+f"(d[0]),"+f"(d[1]),"+f"(d[2]),"+f"(d[3]),"+f"(d[4]),"+f"(d[5]),"+f"(d[6]),"+f"(d[7]),"+f"(d[8]),"+f"(d[9]),"+f"(d[10]),"+f"(d[11]),"+f"(d[12]),"+f"(d[13]),"+f"(d[14]),"+f"(d[15]),"+f"(d[16]),"+f"(d[17]),"+f"(d[18]),"+f"(d[19]),"+f"(d[20]),"+f"(d[21]),"+f"(d[22]),"+f"(d[23]),"+f"(d[24]),"+f"(d[25]),"+f"(d[26]),"+f"(d[27]),"+f"(d[28]),"+f"(d[29]),"+f"(d[30]),"+f"(d[31])
   : "l"(da),"l"(db),"r"(sd),"n"(TA),"n"(TB));
}
template<int TA, int TB> __device__ __forceinline__ void wg_ss8(float* d, uint64_t da, uint64_t db, int sd) {
  asm volatile("{\n.reg .pred p;\nsetp.ne.b32 p, %6, 0;\n"
   "wgmma.mma_async.sync.aligned.m64n8k16.f32.bf16.bf16 {%0,%1,%2,%3}, %4, %5, p, 1, 1, %7, %8;\n}\n"
   : "+f"(d[0]),"+f"(d[1]),"+f"(d[2]),"+f"(d[3])
   : "l"(da),"l"(db),"r"(sd),"n"(TA),"n"(TB));
}

__device__ __forceinline__ uint32_t phi2(float a, float b) {
  uint32_t r, e;
  asm("cvt.rn.relu.bf16x2.f32 %0, %1, %2;" : "=r"(r) : "f"(b), "f"(a));
  e = pack_bf16(ex2f(a * 1.4426950408889634f), ex2f(b * 1.4426950408889634f));
  asm("add.rn.bf16x2 %0, %0, %1;" : "+r"(e) : "r"(0x35863586u));
  asm("min.NaN.bf16x2 %0, %0, %1;" : "+r"(e) : "r"(0x3F803F80u));
  asm("add.rn.bf16x2 %0, %0, %1;" : "+r"(e) : "r"(r));
  return e;
}

__device__ __forceinline__ void mbar_arrive(uint32_t bar) { asm volatile("mbarrier.arrive.shared::cta.b64 _, [%0];" :: "r"(bar) : "memory"); }
__device__ __forceinline__ void named_arrive(int id, int n) { asm volatile("bar.arrive %0, %1;" :: "r"(id), "r"(n) : "memory"); }
__device__ __forceinline__ void fence_async_all() { asm volatile("fence.proxy.async.global;" ::: "memory"); }
__device__ __forceinline__ void flag_add(uint32_t* f) { asm volatile("fence.acq_rel.gpu;\nred.relaxed.gpu.global.add.u32 [%0], 1;" :: "l"(f) : "memory"); }
#define PUBLISH(f) asm volatile("fence.proxy.async.global;\nred.relaxed.gpu.global.add.u32 [%0], 1;" :: "l"(f) : "memory")
__device__ __forceinline__ void flag_wait(const uint32_t* f, uint32_t target) {
  uint32_t v;
#pragma unroll 1
  for (int it = 0;; it++) {
    asm volatile("ld.acquire.gpu.global.u32 %0, [%1];" : "=r"(v) : "l"(f) : "memory");
    if ((int32_t)(v - target) >= 0) break;
    if (it > 2000000) __trap();
    __nanosleep(64);
  }
}
__device__ __forceinline__ bool mbar_test(uint32_t bar, uint32_t parity) {
  uint32_t ok;
  asm volatile("{\n.reg .pred p;\nmbarrier.test_wait.parity.shared::cta.b64 p, [%1], %2;\nselp.b32 %0, 1, 0, p;\n}\n" : "=r"(ok) : "r"(bar), "r"(parity) : "memory");
  return ok;
}
__device__ __forceinline__ bool elect_one() {
  uint32_t p;
  asm volatile("{\n.reg .pred P;\nelect.sync _|P, 0xFFFFFFFF;\nselp.b32 %0, 1, 0, P;\n}\n" : "=r"(p));
  return p;
}
__device__ __forceinline__ void lds4(uint32_t a, uint32_t* r) {
  asm volatile("ld.shared.v4.b32 {%0,%1,%2,%3}, [%4];" : "=r"(r[0]), "=r"(r[1]), "=r"(r[2]), "=r"(r[3]) : "r"(a) : "memory");
}
__device__ __forceinline__ uint32_t lds1(uint32_t a) { uint32_t r; asm volatile("ld.shared.b32 %0, [%1];" : "=r"(r) : "r"(a) : "memory"); return r; }
__device__ __forceinline__ void sts1(uint32_t a, uint32_t v) { asm volatile("st.shared.b32 [%0], %1;" :: "r"(a), "r"(v) : "memory"); }
__device__ __forceinline__ void sts4(uint32_t a, uint32_t r0, uint32_t r1, uint32_t r2, uint32_t r3) {
  asm volatile("st.shared.v4.b32 [%0], {%1,%2,%3,%4};" :: "r"(a), "r"(r0), "r"(r1), "r"(r2), "r"(r3) : "memory");
}
__device__ __forceinline__ void ldsm4(uint32_t a, uint32_t* r) {
  asm volatile("ldmatrix.sync.aligned.m8n8.x4.shared.b16 {%0,%1,%2,%3}, [%4];" : "=r"(r[0]), "=r"(r[1]), "=r"(r[2]), "=r"(r[3]) : "r"(a) : "memory");
}
__device__ __forceinline__ float rcpf(float x) { float y; asm("rcp.approx.ftz.f32 %0, %1;" : "=f"(y) : "f"(x)); return y; }
__device__ __forceinline__ uint32_t hfma2(uint32_t a, uint32_t b, uint32_t c) { uint32_t r; asm("fma.rn.f16x2 %0, %1, %2, %3;" : "=r"(r) : "r"(a), "r"(b), "r"(c)); return r; }
__device__ __forceinline__ uint32_t hadd2(uint32_t a, uint32_t b) { uint32_t r; asm("add.rn.f16x2 %0, %1, %2;" : "=r"(r) : "r"(a), "r"(b)); return r; }

#define STEPK 96
#define SLEEP_NS 500
#define QSCALE 0.36067376022224085f
#define SMAGIC (512.0f + 2.0f * (191.0f - 30.0f - 1.5823545f))
#define VSHIFT 1073741824.0f

__device__ uint32_t g_epoch[132];
__device__ uint32_t g_flag[288 * 8];
#define FLAG_KV (g_flag)
#define FLAG_B(h) (g_flag + (4 + (h)) * 8)
#define FLAG_OA(cta, pass) (g_flag + (16 + (cta) * 2 + (pass)) * 8)
#define FLAG_LM(i) (g_flag + (272 + (i)) * 8)

#define SM_TOTAL (224 * 1024 + 2048 + 1024)
#define OFF_K 0
#define OFF_F 65536
#define OFF_V 131072
#define OFF_MISC (224 * 1024)

#define BAR_FULL(s) (bars + 8 * (s))
#define BAR_EMPTY(s) (bars + 24 + 8 * (s))
#define BAR_KV(c) (bars + 48 + 8 * (c))
#define BAR_BDONE (bars + 80)
#define BAR_Q (bars + 88)
#define BAR_GO (bars + 96)
#define BAR_Q2 (bars + 104)
#define BAR_OD(p) (bars + 112 + 8 * (p))
#define BAR_CL(c) (bars + 128 + 8 * (c))
#define BAR_TE(i) (bars + 168 + 8 * (i))
#define BAR_TF(g) (bars + 224 + 8 * (g))
#define BAR_XA(w) (bars + 352 + 8 * (w))
#define BAR_VB(c) (bars + 384 + 8 * (c))

__device__ __forceinline__ uint32_t exp2_pair_fix(float d0, float d1, uint32_t c63, uint32_t m1) {
  uint32_t w, y, s, r;
  asm("prmt.b32 %0, %1, %2, 0x6521;" : "=r"(w) : "r"(__float_as_uint(d0)), "r"(__float_as_uint(d1)));
  asm("lop3.b32 %0, %1, 0x007F007F, %2, 0xEA;" : "=r"(y) : "r"(w), "r"(c63));
  asm("mad.lo.u32 %0, %1, %2, %3;" : "=r"(s) : "r"(y), "r"(m1), "r"(w));
  asm("fma.rn.bf16x2 %0, %1, %2, %3;" : "=r"(r) : "r"(w), "r"(y), "r"(s));
  return r;
}

__device__ __forceinline__ void attn_slow(const uint4* gq, uint32_t dst) {
  const int t = threadIdx.x & 127;
  const int row = t >> 1, half = t & 1;
  float q[16];
#pragma unroll
  for (int i = 0; i < 4; i++) {
    const uint4 v = gq[(row >> 4) * 32 + (row & 7) * 4 + i];
    const uint32_t lo = (row & 8) ? v.y : v.x, hi = (row & 8) ? v.w : v.z;
    q[2 * i] = bf_lo(lo); q[2 * i + 1] = bf_hi(lo); q[2 * i + 8] = bf_lo(hi); q[2 * i + 9] = bf_hi(hi);
  }
  float m = -INFINITY, l = 0.f, o[16];
#pragma unroll
  for (int i = 0; i < 16; i++) o[i] = 0.f;
#pragma unroll 1
  for (int j = half * 1024; j < half * 1024 + 1024; j++) {
    uint4 ka = g_KV[4 * S_TOK + j], kb = g_KV[5 * S_TOK + j];
    uint4 va = g_KV[6 * S_TOK + j], vb = g_KV[7 * S_TOK + j];
    uint32_t kk[8] = {ka.x, ka.y, ka.z, ka.w, kb.x, kb.y, kb.z, kb.w};
    uint32_t vv[8] = {va.x, va.y, va.z, va.w, vb.x, vb.y, vb.z, vb.w};
    float s = 0.f;
#pragma unroll
    for (int i = 0; i < 8; i++) { s = fmaf(q[2 * i], bf_lo(kk[i]), s); s = fmaf(q[2 * i + 1], bf_hi(kk[i]), s); }
    s = rbf(s) * 0.25f;
    if (s > m) {
      float c = __expf(m - s);
      l *= c;
#pragma unroll
      for (int i = 0; i < 16; i++) o[i] *= c;
      m = s;
    }
    float p = __expf(s - m);
    l += p;
#pragma unroll
    for (int i = 0; i < 8; i++) { o[2 * i] = fmaf(p, bf_lo(vv[i]), o[2 * i]); o[2 * i + 1] = fmaf(p, bf_hi(vv[i]), o[2 * i + 1]); }
  }
  float m2 = __shfl_xor_sync(~0u, m, 1);
  float mm = fmaxf(m, m2);
  float c = __expf(m - mm);
  l *= c; l += __shfl_xor_sync(~0u, l, 1);
  float inv = 1.f / l;
  uint32_t r[8];
#pragma unroll
  for (int i = 0; i < 16; i++) { o[i] *= c; o[i] += __shfl_xor_sync(~0u, o[i], 1); o[i] *= inv; }
#pragma unroll
  for (int i = 0; i < 8; i++) r[i] = pack_bf16(o[2 * i], o[2 * i + 1]);
  if (half == 0) sts4(dst, r[0], r[1], r[2], r[3]); else sts4(dst, r[4], r[5], r[6], r[7]);
  fence_async();
}

struct Params { const __nv_bfloat16* wk; const __nv_bfloat16* wv; const __nv_bfloat16* xa; };
__device__ __forceinline__ void cp16(uint32_t dst, const void* src) { asm volatile("cp.async.cg.shared.global [%0], [%1], 16;" :: "r"(dst), "l"(src) : "memory"); }

__device__ __forceinline__ void helper_cta(const int h, const uint32_t sb, const uint32_t bars, const int wg, const int w4,
                                           const CUtensorMap* mQ, const CUtensorMap* mOs) {
  const int lane = threadIdx.x & 31;
  mbar_wait(BAR_GO, 0);
  const int cb = wg & 1, col = h * 128 + cb * 64, row0 = S_TOK + (wg >> 1) * 1024;
  const uint32_t buf = sb + wg * 49152;
  if (w4 == 0 && elect_one()) {
    fence_async_all();
#pragma unroll 1
    for (int u = 0; u < 3; u++) {
      mbar_expect_tx(BAR_TF(wg * 3 + u), 16384);
      tma2d(buf + u * 16384, mQ, col, row0 + u * 128, BAR_TF(wg * 3 + u));
    }
  }
  const int head = h * 8 + cb * 4 + w4;
  float4 a0 = make_float4(0, 0, 0, 0), a1 = a0, a2 = a0;
#pragma unroll 8
  for (int tt = 0; tt < 16; tt++) {
    const float4* src = g_kvp + ((tt * 32 + head) * 3) * 32 + lane;
    float4 u = src[0], v = src[32], w = src[64];
    a0.x += u.x; a0.y += u.y; a0.z += u.z; a0.w += u.w;
    a1.x += v.x; a1.y += v.y; a1.z += v.z; a1.w += v.w;
    a2.x += w.x; a2.y += w.y; a2.z += w.z; a2.w += w.w;
  }
  const uint32_t b00 = pack_bf16(a0.x, a0.y), b01 = pack_bf16(a0.z, a0.w);
  const uint32_t b10 = pack_bf16(a1.x, a1.y), b11 = pack_bf16(a1.z, a1.w);
  const uint32_t bz0 = pack_bf16(a2.x, a2.y), bz1 = pack_bf16(a2.z, a2.w);
  const int m = lane >> 3, r = lane & 7;
  const uint32_t off = ((m & 1) * 8 + r) * 128 + (((w4 * 2 + (m >> 1)) ^ r) << 4);
  int s = 0, ph = 0;
#pragma unroll 1
  for (int u = 0; u < 8; u++) {
    const uint32_t bb = buf + s * 16384;
    mbar_wait(BAR_TF(wg * 3 + s), ph);
#pragma unroll
    for (int mt = 0; mt < 8; mt++) {
      uint32_t a[4];
      ldsm4(bb + mt * 2048 + off, a);
      float n0[4] = {0, 0, 0, 0}, n1[4] = {0, 0, 0, 0}, dn[4] = {0, 0, 0, 0};
      mma_bf16(dn, a[0], a[1], a[2], a[3], bz0, bz1);
      mma_bf16(n0, a[0], a[1], a[2], a[3], b00, b01);
      mma_bf16(n1, a[0], a[1], a[2], a[3], b10, b11);
      const float i0 = rcpf(dn[0] + 1e-6f), i1 = rcpf(dn[2] + 1e-6f);
      stsm4(bb + mt * 2048 + off, pack_bf16(n0[0] * i0, n0[1] * i0), pack_bf16(n0[2] * i1, n0[3] * i1),
            pack_bf16(n1[0] * i0, n1[1] * i0), pack_bf16(n1[2] * i1, n1[3] * i1));
    }
    fence_async();
    named_bar(wg + 1, 128);
    if (w4 == 0 && lane == 0) {
      tma2d_store(mOs, bb, col, row0 + u * 128);
      bulk_commit();
      if (u >= 1 && u + 2 < 8) {
        asm volatile("cp.async.bulk.wait_group.read 1;" ::: "memory");
        const int sp = s == 0 ? 2 : s - 1;
        mbar_expect_tx(BAR_TF(wg * 3 + sp), 16384);
        tma2d(buf + sp * 16384, mQ, col, row0 + (u + 2) * 128, BAR_TF(wg * 3 + sp));
      }
    }
    __syncwarp();
    if (++s == 3) { s = 0; ph ^= 1; }
  }
  if (w4 == 0 && lane == 0) {
    bulk_wait_all();
    fence_async_all();
    flag_add(FLAG_LM((h * 2 + cb) * 2 + (wg >> 1)));
    if (wg == 0) TS(1, 8);
  }
}

#define STAGE(s) (sb + (2 - (s)) * 65536)
template <int TR> __device__ __forceinline__ void proj_kb(float* acc, uint32_t st, uint32_t offA, uint32_t offB, int first) {
  const uint64_t da = make_desc(st + offA, TR ? 8192 : 16, 1024, 1);
  const uint64_t db = make_desc(st + offB, TR ? 16 : 8192, 1024, 1);
  wg_fence();
#pragma unroll
  for (int k = 0; k < 4; k++) wg_ss128<TR, 1 - TR>(acc, da + k * (TR ? 128 : 2), db + k * (TR ? 2 : 128), k != 0 || !first);
  wg_commit();
}
template <int TR> __device__ __forceinline__ void proj_loop(float* acc, uint32_t sb, uint32_t bars, uint32_t offA, uint32_t offB,
                                                            int wg, uint32_t sWKV) {
  {
    float kv[4];
    if (threadIdx.x == 0) TS(0, 13);
    mbar_wait(BAR_XA(wg), 0);
    if (threadIdx.x == 0) TS(0, 1);
    const uint64_t da = make_desc(STAGE(2) + wg * 16384, 16, 1024, 1), db = make_desc(sWKV + wg * 2048, 128, 128, 0);
    wg_fence();
#pragma unroll
    for (int k = 0; k < 8; k++) wg_ss8<0, 1>(kv, da + (k >> 2) * 512 + (k & 3) * 2, db + k * 16, k != 0);
    wg_commit();
    wg_wait<0>();
    fence_regs<4>(kv);
    named_bar(wg + 1, 128);
    sts4(sWKV + threadIdx.x * 16, __float_as_uint(kv[0]), __float_as_uint(kv[1]), __float_as_uint(kv[2]), __float_as_uint(kv[3]));
    __syncwarp();
    if ((threadIdx.x & 31) == 0) mbar_arrive(BAR_GO);
  }
  int s = 0, ph = 0, sp = 0;
#pragma unroll 1
  for (int kb = 0; kb < 8; kb++) {
    mbar_wait(BAR_FULL(s), ph);
    if (threadIdx.x == 0) TS(0, 2 + kb);
    proj_kb<TR>(acc, STAGE(s), offA, offB, kb == 0);
    wg_wait<1>();
    if (kb >= 1 && (threadIdx.x & 127) == 0) mbar_arrive(BAR_EMPTY(sp));
    __syncwarp();
    sp = s;
    if (++s == 3) { s = 0; ph ^= 1; }
  }
  wg_wait<0>();
  fence_regs<64>(acc);
}

__device__ __forceinline__ uint32_t tail_slots(int t) {
  const uint32_t lo = t < 4 ? (t < 2 ? (t == 0 ? 0x0C0B0Au : 0x0F0E0Du) : (t == 2 ? 0x100400u : 0x181408u))
                            : (t < 6 ? (t == 4 ? 0x110501u : 0x191502u) : (t == 6 ? 0x161206u : (t == 7 ? 0x130703u : 0x1B171Au)));
  return lo;
}

__device__ __forceinline__ void take_role(uint32_t sM, int wg) {
  uint32_t r;
  asm volatile("atom.shared.add.u32 %0, [%1], 1;" : "=r"(r) : "r"(sM + 20) : "memory");
  sts1(sM + 32 + wg * 4, r);
}

__global__ void __launch_bounds__(640, 1)
k1_main(const __grid_constant__ CUtensorMap mXA64, const __grid_constant__ CUtensorMap mXB,
        const __grid_constant__ CUtensorMap mWq, const __grid_constant__ CUtensorMap mWqkv,
        const __grid_constant__ CUtensorMap mQst, const __grid_constant__ CUtensorMap mOst,
        const __grid_constant__ CUtensorMap mO, const __grid_constant__ CUtensorMap mWoA,
        const __grid_constant__ CUtensorMap mWoB, const __grid_constant__ CUtensorMap mOut,
        const __grid_constant__ CUtensorMap mO16, const Params prm) {
  extern __shared__ uint8_t smem_raw[];
  const uint32_t sb = (smem_u32(smem_raw) + 1023u) & ~1023u;
  const uint32_t bars = sb + OFF_MISC, sM = bars + 512, sT = bars + 1024;
  const int tid = threadIdx.x, warp = __shfl_sync(~0u, tid >> 5, 0), wg = warp >> 2, w4 = warp & 3, lane = tid & 31;
  const bool helper = blockIdx.x >= 128;
  if (tid == 0) TS(0, 0);
  const int G = blockIdx.x >> 4, gi = blockIdx.x & 15;
  const int tbA = G * 4 + (gi >> 2), hg = gi & 3;
  const int ttB = (G >> 1) * 4 + (gi >> 2), hq = (G & 1) * 4 + (gi & 3);
  auto issue = [&](int kb, int s) {
    const uint32_t fb = BAR_FULL(s), st = STAGE(s);
    mbar_expect_tx(fb, 65536);
    tma2d(st + 16384, &mXA64, kb * 64, tbA * 64, fb);
    tma2d(st, &mWq, hg * 128, kb * 64, fb);
    tma2d(st + 8192, &mWq, hg * 128 + 64, kb * 64, fb);
    tma2d(st + 49152, &mXB, kb * 64, ttB * 128, fb);
    tma2d(st + 24576, &mWqkv, hq * 64, kb * 64, fb);
    tma2d(st + 32768, &mWqkv, 512 + hq * 64, kb * 64, fb);
    tma2d(st + 40960, &mWqkv, 1024 + hq * 64, kb * 64, fb);
  };
  const uint32_t sOne = sb + OFF_V + 65536, sWKV = sOne + 24576;
  if (warp >= 16) {
    if (warp == 17) {
      if (elect_one()) {
        mbar_init(BAR_BDONE, 8); mbar_init(BAR_Q, 8); mbar_init(BAR_GO, helper ? 1 : 16); mbar_init(BAR_Q2, 5);
        mbar_init(BAR_OD(0), 16); mbar_init(BAR_OD(1), 16); mbar_init(BAR_CL(0), 1); mbar_init(BAR_FULL(2), 1);
#pragma unroll
        for (int i = 0; i < 4; i++) mbar_init(BAR_CL(i + 1), i == 0 ? 5 : 4);
#pragma unroll
        for (int i = 0; i < 3; i++) { mbar_init(BAR_EMPTY(i), 4); mbar_init(BAR_KV(i), 1); mbar_init(BAR_VB(i), 1); }
        sts1(sM + 20, 0);
        asm volatile("fence.mbarrier_init.release.cluster;" ::: "memory");
      }
    } else if (warp == 18) {
      if (elect_one()) {
#pragma unroll
        for (int i = 0; i < 7; i++) mbar_init(BAR_TE(i), 1);
#pragma unroll
        for (int i = 0; i < 16; i++) mbar_init(BAR_TF(i), i < 12 || i == 15 ? 1 : 2);
        asm volatile("fence.mbarrier_init.release.cluster;" ::: "memory");
      }
    } else if (warp == 16 && !helper && elect_one()) {
#pragma unroll
      for (int w = 0; w < 4; w++) mbar_init(BAR_XA(w), 1);
      mbar_init(BAR_FULL(0), 1); mbar_init(BAR_FULL(1), 1);
      asm volatile("fence.mbarrier_init.release.cluster;" ::: "memory");
#pragma unroll
      for (int w = 0; w < 4; w++) {
        mbar_expect_tx(BAR_XA(w), 16384);
        tma2d(STAGE(2) + w * 16384, &mXA64, w * 128, tbA * 64, BAR_XA(w));
        tma2d(STAGE(2) + w * 16384 + 8192, &mXA64, w * 128 + 64, tbA * 64, BAR_XA(w));
      }
      TS(0, 14);
      issue(0, 0);
    }
  } else if (!helper) {
    const uint4 v = __ldg((const uint4*)(hg >= 2 ? prm.wv : prm.wk) + tid * 2 + (hg & 1));
#pragma unroll
    for (int i = 0; i < 3; i++) {
      const int key = tid + i * 512;
      sts4(sOne + key * 16, (key % STEPK) < 24 ? 0x00003F80u : 0x00004E80u, 0u, 0u, 0u);
    }
    sts4(sWKV + tid * 16, v.x, v.y, v.z, v.w);
    fence_async();
  }
  __syncthreads();
  if (wg == 4) {
    if (w4 == 0 && !helper && elect_one()) { issue(1, 1); TS(0, 15); }
    asm volatile("setmaxnreg.dec.sync.aligned.u32 32;");
    const uint32_t ep = g_epoch[blockIdx.x] + 1;
    if (helper) {
      if (w4 == 0 && elect_one()) {
        flag_wait(FLAG_B(blockIdx.x - 128), ep * 32);
        fence_async_all();
        TS(1, 10);
        mbar_arrive(BAR_GO);
        g_epoch[blockIdx.x] = ep;
      }
      return;
    }
    mbar_wait(BAR_GO, 0);
    if (w4 == 0 && elect_one()) issue(2, 2);
    {
      uint32_t a[4], b[4];
      float c[4];
      lds4(sWKV + (tid - 512) * 16, a);
      lds4(sWKV + 2048 + (tid - 512) * 16, b);
#pragma unroll
      for (int i = 0; i < 4; i++) c[i] = __uint_as_float(a[i]) + __uint_as_float(b[i]);
      lds4(sWKV + 4096 + (tid - 512) * 16, a);
      lds4(sWKV + 6144 + (tid - 512) * 16, b);
#pragma unroll
      for (int i = 0; i < 4; i++) c[i] += __uint_as_float(a[i]) + __uint_as_float(b[i]);
      sts1(sT + w4 * 256 + lane * 4, pack_bf16(c[0], c[1]));
      sts1(sT + w4 * 256 + 128 + lane * 4, pack_bf16(c[2], c[3]));
    }
    named_bar(9, 128);
    {
      const int t = tid - 512;
#pragma unroll
      for (int i = 0; i < 4; i++) {
        const int key = 1536 + t + i * 128;
        sts4(sOne + key * 16, (key % STEPK) < 24 ? 0x00003F80u : 0x00004E80u, 0u, 0u, 0u);
      }
      fence_async();
      __syncwarp();
      if (lane == 0) mbar_arrive(BAR_Q);
    }
    if (w4 == 0) {
      int s = 0, ph = 0;
#pragma unroll 1
      for (int kb = 3; kb < 8; kb++) {
        mbar_wait(BAR_EMPTY(s), ph);
        if (elect_one()) issue(kb, s);
        if (++s == 3) { s = 0; ph ^= 1; }
      }
      flag_wait(FLAG_KV, ep * 128);
      fence_async_all();
      if (lane == 0) TS(0, 11);
#pragma unroll 1
      for (int m = 0; m < 2; m++) {
        mbar_wait(m == 0 ? BAR_EMPTY(2) : BAR_EMPTY(0), 1 - m);
        if (elect_one()) {
          const uint32_t fb = m == 0 ? BAR_KV(0) : BAR_VB(0);
          mbar_expect_tx(fb, 2 * 7 * STEPK * 16);
#pragma unroll
          for (int p = 0; p < 2; p++) bulk_g2s(sb + m * OFF_V + p * 32768, g_KV + (m * 2 + p) * S_TOK, 7 * STEPK * 16, fb);
        }
      }
      mbar_wait(BAR_Q, 0);
      if (elect_one()) {
#pragma unroll
        for (int c = 1; c < 3; c++) {
          const int k0 = c == 1 ? 7 * STEPK : 12 * STEPK, k1 = c == 1 ? 12 * STEPK : S_TOK;
          const uint32_t bytes = (k1 - k0) * 16;
          mbar_expect_tx(BAR_KV(c), 4 * bytes);
#pragma unroll
          for (int p = 0; p < 4; p++)
            bulk_g2s(sb + (p >> 1) * OFF_V + (p & 1) * 32768 + k0 * 16, g_KV + p * S_TOK + k0, bytes, BAR_KV(c));
        }
      }
      mbar_wait(BAR_CL(1), 0);
      flag_wait(FLAG_LM((lane & 7) * 2 + (tbA >> 4)), ep);
      __syncwarp();
      fence_async_all();
      if (lane == 0) TS(2, 13);
#pragma unroll 1
      for (int n = 0; n < 8; n++) {
        mbar_wait(n == 7 ? BAR_TE(0) : BAR_CL(n < 4 ? n >> 1 : (n == 4 ? 2 : 3)), 0);
        const uint32_t sl = tail_slots(n == 7 ? 0 : n), fb = BAR_TF(n);
        if (elect_one()) {
          mbar_expect_tx(fb, 24576);
          tma2d(sb + (sl & 255) * 8192, &mO, n * 64, S_TOK + tbA * 64, fb);
          tma2d(sb + ((sl >> 8) & 255) * 8192, &mWoB, hg * 128, n * 64, fb);
          tma2d(sb + (sl >> 16) * 8192, &mWoB, hg * 128 + 64, n * 64, fb);
        }
      }
      if (lane == 0) g_epoch[blockIdx.x] = ep;
    } else if (w4 == 3) {
      flag_wait(FLAG_KV, ep * 128);
      const uint4 a = *(const uint4*)(g_stats + lane * 4);
      const float kmax2 = __uint_as_float(__reduce_max_sync(~0u, a.x)) + __uint_as_float(__reduce_max_sync(~0u, a.y));
      const float vmax = __uint_as_float(__reduce_max_sync(~0u, max(a.z, a.w)));
      const float lv = vmax > 0.f ? __log2f(vmax) : 0.f;
      const float lim = fminf(90.f, fminf(91.f + lv, 95.f - lv));
      float thr = -1.f;
      if (vmax < 1e27f && kmax2 <= 65536.f && lim > 2.f) thr = fminf(60000.f, (lim * lim - 1.f) / (kmax2 * 1.02f + 1e-30f));
      if (lane == 0) { sts1(sM + 16, __float_as_uint(thr)); mbar_arrive(BAR_Q2); }
      mbar_wait(BAR_CL(3), 0);
      flag_wait(FLAG_OA(tbA * 4 + (lane & 3), 0), ep);
      __syncwarp();
      fence_async_all();
#pragma unroll 1
      for (int n = 0; n < 8; n++) {
        mbar_wait(n >= 6 ? BAR_CL(4) : BAR_TE(n + 1), 0);
        const uint32_t sl = tail_slots(n + 1), fb = BAR_TF(n + 8);
        const int k0 = n < 4 ? n * 128 : ((hg + n + 1) & 3) * 128 + 64;
        if (elect_one()) {
          mbar_expect_tx(fb, n < 4 ? 24576 : 16384);
          if (n < 4) tma2d(sb + (sl & 255) * 8192, &mO, k0, tbA * 64, fb);
          tma2d(sb + ((sl >> 8) & 255) * 8192, &mWoA, hg * 128, k0, fb);
          tma2d(sb + (sl >> 16) * 8192, &mWoA, hg * 128 + 64, k0, fb);
        }
      }
    } else {
      const int tok = (w4 - 1) * 32 + lane;
      int step, col;
      if ((tbA & 3) == 0) {
        const int b8 = tbA >> 2;
        if (tok < 22) { step = tok; col = 24 + b8; }
        else { const int c = tok >= 43; step = tok - 22 - 21 * c; col = 32 + b8 * 2 + c; }
      } else {
        const int b24 = (tbA >> 2) * 3 + (tbA & 3) - 1;
        if (tok < 42) { const int c = tok >= 21; step = tok - 21 * c; col = 48 + b24 * 2 + c; }
        else { step = tok - 42; col = b24; }
      }
      const int kap = step * STEPK + col;
      const bool chained = col >= 24;
      uint32_t v[4], o[4];
      lds4(sT + tok * 16, v);
      g_KV[(4 + hg) * S_TOK + kap] = make_uint4(v[0], v[1], v[2], v[3]);
      float st = 0.f;
      if (hg < 2) {
        o[0] = o[1] = o[2] = o[3] = 0;
        if (chained && step > 0) lds4(sT + tok * 16 - 16, o);
        const float sc = chained ? 2.f : 1.f;
#pragma unroll
        for (int u = 0; u < 4; u++) {
          const float x = bf_lo(v[u]), y = bf_hi(v[u]);
          st += x * x + y * y;
          o[u] = pack_f16((x - bf_lo(o[u])) * sc, (y - bf_hi(o[u])) * sc);
        }
      } else {
        const float sc = chained ? VSHIFT : 1.f;
#pragma unroll
        for (int u = 0; u < 4; u++) { float x = bf_lo(v[u]), y = bf_hi(v[u]); st += fabsf(x) + fabsf(y); o[u] = pack_bf16(x * sc, y * sc); }
      }
      g_KV[hg * S_TOK + kap] = make_uint4(o[0], o[1], o[2], o[3]);
      const uint32_t um = __reduce_max_sync(~0u, __float_as_uint(st) & 0x7FFFFFFFu);
      if (w4 == 2) {
        if (lane == 0) sts1(sM + 24, um);
        named_arrive(10, 64);
        mbar_wait(BAR_TE(5), 0);
        uint32_t pend = 7;
        const int li = lane < 3 ? lane : 0;
        const uint32_t* fl = FLAG_OA(tbA * 4 + ((hg + li + 1) & 3), 1);
#pragma unroll 1
        for (int it = 0; pend; it++) {
          uint32_t fv;
          asm volatile("ld.acquire.gpu.global.u32 %0, [%1];" : "=r"(fv) : "l"(fl) : "memory");
          const uint32_t go = __ballot_sync(~0u, (int32_t)(fv - ep) >= 0 && mbar_test(li == 2 ? BAR_CL(4) : BAR_TE(5 + li), 0)) & pend;
          if (go) {
            fence_async_all();
            if (elect_one()) {
#pragma unroll
              for (int n = 0; n < 3; n++)
                if ((go >> n) & 1) {
                  mbar_expect_tx(BAR_TF(12 + n), 8192);
                  tma2d(sb + (tail_slots(5 + n) & 255) * 8192, &mO, ((hg + n + 1) & 3) * 128 + 64, tbA * 64, BAR_TF(12 + n));
                }
            }
            pend &= ~go;
          }
          if (it > 2000000) __trap();
        }
        if (lane == 0) TS(2, 14);
      }
      else {
        named_bar(10, 64);
        if (elect_one()) {
          g_stats[tbA * 4 + hg] = max(um, lds1(sM + 24));
          fence_async_all();
          flag_add(FLAG_KV);
          TS(1, 9);
          mbar_wait(BAR_BDONE, 0);
          tma2d_store(&mQst, sb + OFF_F + 49152, hq * 64, S_TOK + ttB * 128);
          bulk_commit();
          bulk_wait_all();
          fence_async_all();
          flag_add(FLAG_B(hq >> 1));
          TS(0, 12);
          mbar_wait(BAR_Q, 0);
          mbar_arrive(BAR_CL(0));
#pragma unroll 1
          for (int p = 0; p < 2; p++) {
            mbar_wait(BAR_OD(p), 0);
            if (p == 0) {
#pragma unroll
              for (int w = 0; w < 4; w++) tma2d_store(&mO16, sb + OFF_F + w * 2048, hg * 128 + w * 16, tbA * 64);
            } else {
              tma2d_store(&mO, sb + 26 * 8192, hg * 128 + 64, tbA * 64);
            }
            bulk_commit();
            bulk_wait_all();
            if (p == 0) mbar_arrive(BAR_CL(1));
            PUBLISH(FLAG_OA(blockIdx.x, p));
          }
          TS(2, 0);
        }
      }
    }
    return;
  }
  if (helper) { helper_cta(blockIdx.x - 128, sb, bars, wg, w4, &mQst, &mOst); return; }

  {
    float acc[64];
    if (wg == 0) proj_loop<0>(acc, sb, bars, 16384, 0, wg, sWKV);
    else proj_loop<1>(acc, sb, bars, 16384 + wg * 8192, 49152, wg, sWKV);
    asm volatile("setmaxnreg.inc.sync.aligned.u32 112;");
    if (tid == 0) TS(0, 10);
    const uint32_t sF = sb + OFF_F;
    if (wg == 0) {
      uint32_t r[32];
      const uint32_t qa = sF + w4 * 512 + ((lane >> 3) & 1) * 256 + (lane >> 4) * 128 + (lane & 7) * 16;
#pragma unroll
      for (int hd = 0; hd < 8; hd++) {
#pragma unroll
        for (int i = 0; i < 4; i++) r[4 * hd + i] = pack_f16(acc[8 * hd + 2 * i] * QSCALE, acc[8 * hd + 2 * i + 1] * QSCALE);
        stsm4(qa + hd * 2048, r[4 * hd], r[4 * hd + 1], r[4 * hd + 2], r[4 * hd + 3]);
        if (hd == 3) {
          fence_async();
          __syncwarp();
          if (lane == 0) mbar_arrive(BAR_Q);
        }
      }
      fence_async();
      uint32_t nmax = 0;
#pragma unroll
      for (int hd = 0; hd < 8; hd++) {
        const uint32_t* q = r + 4 * hd;
        const uint32_t t0 = hfma2(q[2], q[2], hfma2(q[0], q[0], 0u)), t1 = hfma2(q[3], q[3], hfma2(q[1], q[1], 0u));
        uint32_t n = hadd2(__byte_perm(t0, t1, 0x5410), __byte_perm(t0, t1, 0x7632));
        n = hadd2(n, __shfl_xor_sync(~0u, n, 1));
        n = hadd2(n, __shfl_xor_sync(~0u, n, 2));
        nmax = __vmaxu2(nmax, n & 0x7FFF7FFFu);
      }
      nmax = __reduce_max_sync(~0u, max(nmax & 0xFFFFu, nmax >> 16));
      if (lane == 0) sts1(sM + w4 * 4, nmax);
      uint4* gq = (uint4*)g_Q + blockIdx.x * 1024 + tid;
#pragma unroll
      for (int hd = 0; hd < 8; hd++)
        gq[hd * 128] = make_uint4(pack_bf16(acc[8 * hd], acc[8 * hd + 1]), pack_bf16(acc[8 * hd + 2], acc[8 * hd + 3]),
                                  pack_bf16(acc[8 * hd + 4], acc[8 * hd + 5]), pack_bf16(acc[8 * hd + 6], acc[8 * hd + 7]));
      __syncwarp();
      if (lane == 0) mbar_arrive(BAR_Q2);
    } else if (wg == 3) {
      named_arrive(8, 384);
      named_bar(6, 384);
      const int t = tid & 127;
#pragma unroll
      for (int j = 0; j < 8; j++)
        sts4(sF + 24576 + j * 2048 + t * 16, pack_bf16(acc[8 * j], acc[8 * j + 1]), pack_bf16(acc[8 * j + 2], acc[8 * j + 3]),
             pack_bf16(acc[8 * j + 4], acc[8 * j + 5]), pack_bf16(acc[8 * j + 6], acc[8 * j + 7]));
      named_arrive(7, 256);
    } else {
      uint32_t p[32];
      named_arrive(6, 384);
      if (wg == 2) named_arrive(8, 384);
#pragma unroll
      for (int i = 0; i < 32; i++) p[i] = phi2(acc[2 * i], acc[2 * i + 1]);
      if (wg == 1) {
        named_bar(8, 384);
        const int m = lane >> 3, r = lane & 7;
#pragma unroll
        for (int j = 0; j < 16; j += 2) {
          const int tok = (j + (m >> 1)) * 8 + r;
          const int chunk = w4 * 2 + (m & 1);
          stsm4t(sF + 49152 + tok * 128 + ((chunk ^ r) << 4), p[2 * j], p[2 * j + 1], p[2 * j + 2], p[2 * j + 3]);
        }
        fence_async();
      } else {
        named_bar(7, 256);
        float kv0[4] = {0, 0, 0, 0}, kv1[4] = {0, 0, 0, 0}, z0[4] = {0, 0, 0, 0}, z1[4] = {0, 0, 0, 0};
        const uint32_t one = 0x3F803F80u;
        const int t = tid & 127;
#pragma unroll
        for (int j = 0; j < 8; j++) {
          uint32_t a[4];
          lds4(sF + 24576 + j * 2048 + t * 16, a);
          mma_bf16(kv0, a[0], a[1], a[2], a[3], p[4 * j], p[4 * j + 2]);
          mma_bf16(kv1, a[0], a[1], a[2], a[3], p[4 * j + 1], p[4 * j + 3]);
          mma_bf16(z0, one, one, one, one, p[4 * j], p[4 * j + 2]);
          mma_bf16(z1, one, one, one, one, p[4 * j + 1], p[4 * j + 3]);
        }
        float4* dst = g_kvp + ((ttB * 32 + hq * 4 + w4) * 3) * 32 + lane;
        dst[0] = make_float4(kv0[0], kv0[1], kv1[0], kv1[1]);
        dst[32] = make_float4(kv0[2], kv0[3], kv1[2], kv1[3]);
        dst[64] = make_float4(z0[0], z0[1], z1[0], z1[1]);
      }
      __syncwarp();
      if (lane == 0) mbar_arrive(BAR_BDONE);
    }
  }

  bool safe = true;
  {
    const uint32_t c63 = 0x1F801F80u + (threadIdx.x >> 20);
    const uint32_t m1 = (gridDim.x >> 20) - 1u;
    const uint64_t dK0 = make_desc(sb + OFF_K, 32768, 128, 0);
    const uint64_t dV0 = make_desc(sb + OFF_V, 128, 32768, 0);
    constexpr uint32_t dKV = ((2048u - 8u)  __H0__ ) + STEPK - (OFF_V - OFF_K) / 16;
    float Sm[12], Sp[36], O[12];
    uint32_t P[24];
    uint64_t dQ = make_desc(sb + OFF_F + wg * 2048, 128, 256, 0);
#pragma unroll
    for (int i = 0; i < 36; i++) Sp[i] = SMAGIC;
#pragma unroll
    for (int i = 0; i < 12; i++) Sm[i] = 0.f;
    fence_regs<12>(Sm); fence_regs<36>(Sp);
    mbar_wait(BAR_Q, 0);
    mbar_wait(BAR_KV(0), 0);
    wg_fence();
    wg_qs72<1>(Sp, dQ, dK0 + 24);
    wg_qs24<0>(Sm, dQ, dK0);
    wg_commit();
    wg_wait<0>();
    fence_regs<12>(Sm); fence_regs<36>(Sp);
#pragma unroll 1
    for (int pass = 0; pass < 2; pass++) {
#pragma unroll
      for (int i = 0; i < 12; i++) O[i] = 0.f;
      fence_regs<12>(O);
      if (tid == 0) TS(1, 2 + 2 * pass);
      uint32_t vlo = (uint32_t)dV0;
#pragma unroll 1
      for (int seg = 0; seg < 4; seg++) {
        if (pass == 0) {
          if (seg < 3) mbar_wait(seg == 0 ? BAR_VB(0) : BAR_KV(seg), 0);
        } else if (seg >= 1) {
          if ((tid & 127) == 0) {
            mbar_arrive(BAR_CL(seg));
            if (seg == 3) take_role(sM, wg);
          }
          __syncwarp();
        }
        if (wg < 3 && seg == wg + 1) __nanosleep(SLEEP_NS);
        if ((tid & 127) == 0) TS(4 + wg, pass * 5 + seg);
        const uint32_t vend = vlo + (seg == 0 ? 6 : 5) * STEPK;
#pragma unroll 1
        for (; vlo != vend; vlo += STEPK) {
          uint64_t dK, dV;
          asm("mov.b64 %0, {%1, %2};" : "=l"(dK) : "r"(vlo + dKV), "r"(8u));
          asm("mov.b64 %0, {%1, %2};" : "=l"(dV) : "r"(vlo), "r"(2048u));
#pragma unroll
          for (int i = 0; i < 6; i++) P[i] = pack_bf16(ex2f(Sm[2 * i]), ex2f(Sm[2 * i + 1]));
#pragma unroll
          for (int i = 0; i < 18; i++) P[6 + i] = exp2_pair_fix(Sp[2 * i], Sp[2 * i + 1], c63, m1);
          fence_regs<24>(P);
          wg_fence();
#pragma unroll
          for (int k = 0; k < 6; k++) wg_pv24<1>(O, &P[4 * k], dV + k * 16);
          wg_qs72<1>(Sp, dQ, dK + 24);
          wg_qs24<0>(Sm, dQ, dK);
          wg_commit();
          wg_wait<0>();
          fence_regs<12>(Sm); fence_regs<36>(Sp); fence_regs<12>(O); fence_regs<24>(P);
        }
      }
#pragma unroll
      for (int i = 0; i < 6; i++) P[i] = pack_bf16(ex2f(Sm[2 * i]), ex2f(Sm[2 * i + 1]));
      P[6] = exp2_pair_fix(Sp[0], Sp[1], c63, m1);
      P[7] = exp2_pair_fix(Sp[2], Sp[3], c63, m1);
      fence_regs<8>(P);
#pragma unroll
      for (int i = 0; i < 36; i++) Sp[i] = SMAGIC;
      fence_regs<36>(Sp);
      mbar_wait(pass == 0 ? BAR_Q2 : BAR_CL(3), 0);
      const uint32_t sO = pass == 0 ? sb + OFF_F + wg * 2048 + w4 * 512 + (lane & 15) * 32 + (lane >> 4) * 16
                                    : sb + 26 * 8192 + (w4 * 16 + (lane & 15)) * 128 + (((wg * 2 + (lane >> 4)) ^ (lane & 7)) << 4);
      dQ += 512;
      wg_fence();
      wg_pv24<1>(O, &P[0], dV0 + 21 * STEPK);
      wg_pv24<1>(O, &P[4], dV0 + 21 * STEPK + 16);
      wg_commit();
      wg_qs72<1>(Sp, dQ, dK0 + 24);
      wg_qs24<0>(Sm, dQ, dK0);
      wg_commit();
      wg_wait<1>();
      fence_regs<12>(O);
      const float l0 = __shfl_sync(~0u, O[8], lane & ~3), l1 = __shfl_sync(~0u, O[10], lane & ~3);
      const float i0 = rcpf(l0), i1 = rcpf(l1);
      stsm4(sO,
            pack_bf16(O[0] * i0, O[1] * i0), pack_bf16(O[2] * i1, O[3] * i1),
            pack_bf16(O[4] * i0, O[5] * i0), pack_bf16(O[6] * i1, O[7] * i1));
      fence_async();
      {
        uint32_t n[4];
        lds4(sM, n);
        const float qn = __half2float(__ushort_as_half((unsigned short)max(max(n[0], n[1]), max(n[2], n[3]))));
        safe = __all_sync(~0u, qn <= __uint_as_float(lds1(sM + 16)));
      }
      if (safe && lane == 0) mbar_arrive(BAR_OD(pass));
      wg_wait<0>();
      fence_regs<12>(Sm); fence_regs<36>(Sp);
      if (!safe) break;
      if ((tid & 127) == 0) TS(4 + wg, pass * 5 + 4);
      if (tid == 0) TS(1, 3 + 2 * pass);
    }
  }
  if (!safe) {
    if ((tid & 127) == 0) { mbar_arrive(BAR_CL(1)); mbar_arrive(BAR_CL(2)); mbar_arrive(BAR_CL(3)); take_role(sM, wg); }
#pragma unroll 1
    for (int pass = 0; pass < 2; pass++) {
      const int t = tid & 127;
      mbar_wait(BAR_CL(3), 0);
      attn_slow((const uint4*)g_Q + blockIdx.x * 1024 + (pass * 4 + wg) * 128,
                pass == 0 ? sb + OFF_F + wg * 2048 + t * 16
                          : sb + 26 * 8192 + (t >> 1) * 128 + (((wg * 2 + (t & 1)) ^ ((t >> 1) & 7)) << 4));
      __syncwarp();
      if (lane == 0) mbar_arrive(BAR_OD(pass));
    }
  }

  {
    named_bar(wg + 1, 128);
    if ((tid & 127) == 0) mbar_arrive(BAR_CL(4));
    const int role = __shfl_sync(~0u, lds1(sM + 32 + wg * 4), 0);
    if ((tid & 127) == 0) TS(4 + wg, 10);
    const int m = lane >> 3, r = lane & 7;
    const uint32_t stoff = (w4 * 16 + (m & 1) * 8 + r) * 128;
    if (role == 0) {
      float acc[64];
      uint32_t sl = 0;
#pragma unroll 1
      for (int n = 0; n < 8; n++) {
        sl = tail_slots(n == 7 ? 0 : n);
        const uint32_t w0 = (sl >> 8) & 255, w1 = sl >> 16;
        const uint64_t da = make_desc(sb + (sl & 255) * 8192, 16, 1024, 1), db = make_desc(sb + w0 * 8192, (w1 - w0) * 8192, 1024, 1);
        mbar_wait(BAR_TF(n), 0);
        wg_fence();
#pragma unroll
        for (int k = 0; k < 4; k++) wg_ss128<0, 1>(acc, da + k * 2, db + k * 128, (n | k) != 0);
        wg_commit();
        wg_wait<1>();
        if (n >= 1 && (tid & 127) == 0) mbar_arrive(BAR_TE(n - 1));
        __syncwarp();
      }
      wg_wait<0>();
      fence_regs<64>(acc);
      if ((tid & 127) == 0) TS(4 + wg, 11);
      named_bar(wg + 1, 128);
      const uint32_t x0 = sb + ((sl >> 8) & 255) * 8192, x1 = sb + (sl >> 16) * 8192;
#pragma unroll
      for (int j = 0; j < 16; j += 2)
        stsm4((j < 8 ? x0 : x1) + stoff + ((((j & 7) + (m >> 1)) ^ r) << 4),
              pack_bf16(acc[4 * j], acc[4 * j + 1]), pack_bf16(acc[4 * j + 2], acc[4 * j + 3]),
              pack_bf16(acc[4 * j + 4], acc[4 * j + 5]), pack_bf16(acc[4 * j + 6], acc[4 * j + 7]));
      fence_async();
      named_bar(wg + 1, 128);
      if (w4 == 0 && elect_one()) {
        tma2d_store(&mOut, x0, 512 + hg * 128, tbA * 64);
        tma2d_store(&mOut, x1, 512 + hg * 128 + 64, tbA * 64);
        bulk_commit();
        asm volatile("cp.async.bulk.wait_group.read 0;" ::: "memory");
        TS(2, 11);
      }
    } else if (role < 3) {
      float acc[32];
#pragma unroll 1
      for (int n = 0; n < 8; n++) {
        const uint32_t sl = tail_slots(n + 1);
        const uint64_t da = make_desc(sb + (sl & 255) * 8192, 16, 1024, 1);
        const uint64_t db = make_desc(sb + ((sl >> (8 * role)) & 255) * 8192, 8192, 1024, 1);
        mbar_wait(BAR_TF(8 + n), 0);
        if (n == 7) mbar_wait(BAR_OD(1), 0);
        if ((tid & 127) == 0 && role == 1) TS(2, 2 + n);
        wg_fence();
#pragma unroll
        for (int k = 0; k < 4; k++) wg_ss64<0, 1>(acc, da + k * 2, db + k * 128, (n | k) != 0);
        wg_commit();
        wg_wait<2>();
      }
      wg_wait<0>();
      fence_regs<32>(acc);
      if ((tid & 127) == 0) TS(4 + wg, 11);
      const uint32_t xs = sb + ((tail_slots(1) >> (8 * role)) & 255) * 8192;
#pragma unroll
      for (int j = 0; j < 8; j += 2)
        stsm4(xs + stoff + (((j + (m >> 1)) ^ r) << 4),
              pack_bf16(acc[4 * j], acc[4 * j + 1]), pack_bf16(acc[4 * j + 2], acc[4 * j + 3]),
              pack_bf16(acc[4 * j + 4], acc[4 * j + 5]), pack_bf16(acc[4 * j + 6], acc[4 * j + 7]));
      fence_async();
      named_bar(wg + 1, 128);
      if (w4 == 0 && elect_one()) {
        tma2d_store(&mOut, xs, hg * 128 + (role - 1) * 64, tbA * 64);
        bulk_commit();
        asm volatile("cp.async.bulk.wait_group.read 0;" ::: "memory");
        TS(2, 12);
      }
    }
  }
}

typedef CUresult (*EncodeFn)(CUtensorMap*, CUtensorMapDataType, cuuint32_t, void*, const cuuint64_t*, const cuuint64_t*,
                             const cuuint32_t*, const cuuint32_t*, CUtensorMapInterleave, CUtensorMapSwizzle,
                             CUtensorMapL2promotion, CUtensorMapFloatOOBfill);

static void make_map(EncodeFn enc, CUtensorMap* m, const void* ptr, uint64_t cols, uint64_t rows, uint32_t bc, uint32_t br,
                     CUtensorMapSwizzle sw = CU_TENSOR_MAP_SWIZZLE_128B) {
  cuuint64_t dims[2] = {cols, rows};
  cuuint64_t strides[1] = {cols * 2};
  cuuint32_t box[2] = {bc, br};
  cuuint32_t es[2] = {1, 1};
  enc(m, CU_TENSOR_MAP_DATA_TYPE_BFLOAT16, 2, (void*)ptr, dims, strides, box, es, CU_TENSOR_MAP_INTERLEAVE_NONE,
      sw, CU_TENSOR_MAP_L2_PROMOTION_L2_256B, CU_TENSOR_MAP_FLOAT_OOB_FILL_NONE);
}

extern "C" void kernel_launch(void* const* d_in, const int* in_sizes, int n_in, void* d_out, int out_size) {
  (void)in_sizes; (void)n_in; (void)out_size;
  static EncodeFn enc = nullptr;
  static void* pQ = nullptr; static void* pO = nullptr;
  if (!enc) {
    void* fn = nullptr; cudaDriverEntryPointQueryResult qr;
    cudaGetDriverEntryPoint("cuTensorMapEncodeTiled", &fn, cudaEnableDefault, &qr);
    enc = (EncodeFn)fn;
    cudaGetSymbolAddress(&pQ, g_Q);
    cudaGetSymbolAddress(&pO, g_O);
    cudaFuncSetAttribute(k1_main, cudaFuncAttributeMaxDynamicSharedMemorySize, SM_TOTAL);
  }
  CUtensorMap mXA64, mXB, mWq, mWqkv, mQst, mO, mOst, mWoA, mWoB, mOut, mO16;
  make_map(enc, &mXA64, d_in[0], 512, 2048, 64, 64);
  make_map(enc, &mWq, d_in[1], 512, 512, 64, 64);
  make_map(enc, &mWoA, d_in[4], 512, 512, 64, 64);
  make_map(enc, &mXB, d_in[5], 512, 2048, 64, 128);
  make_map(enc, &mWqkv, d_in[6], 1536, 512, 64, 64);
  make_map(enc, &mWoB, d_in[7], 512, 512, 64, 64);
  make_map(enc, &mQst, pQ, 512, 4096, 64, 128);
  make_map(enc, &mO, pO, 512, 4096, 64, 64);
  make_map(enc, &mOst, pO, 512, 4096, 64, 128);
  make_map(enc, &mOut, d_out, 1024, 2048, 64, 64);
  make_map(enc, &mO16, pO, 512, 4096, 16, 64, CU_TENSOR_MAP_SWIZZLE_NONE);
  Params prm{(const __nv_bfloat16*)d_in[2], (const __nv_bfloat16*)d_in[3], (const __nv_bfloat16*)d_in[0]};
  k1_main<<<132, 640, SM_TOTAL, cudaStreamPerThread>>>(mXA64, mXB, mWq, mWqkv, mQst, mOst, mO, mWoA, mWoB, mOut, mO16, prm);
}
```

```cpp
#include <cuda_runtime.h>
#include <cuda_bf16.h>
#include <cuda_fp16.h>
#include <cuda.h>
#include <stdint.h>

#define S_TOK 2048
#define D_MOD 512

__device__ __align__(1024) __nv_bfloat16 g_Q[2 * S_TOK * D_MOD];
__device__ __align__(1024) __nv_bfloat16 g_O[2 * S_TOK * D_MOD];
__device__ __align__(1024) uint4 g_KV[8 * S_TOK];
__device__ __align__(16) uint32_t g_stats[128];
__device__ __align__(16) float4 g_kvp[16 * 32 * 3 * 32];

#define TS(k, i) do {} while (0)
__device__ __forceinline__ uint32_t smem_u32(const void* p) { return (uint32_t)__cvta_generic_to_shared(p); }
__device__ __forceinline__ void mbar_init(uint32_t bar, int cnt) { asm volatile("mbarrier.init.shared::cta.b64 [%0], %1;" :: "r"(bar), "r"(cnt) : "memory"); }
__device__ __forceinline__ void mbar_expect_tx(uint32_t bar, uint32_t bytes) { asm volatile("mbarrier.arrive.expect_tx.shared::cta.b64 _, [%0], %1;" :: "r"(bar), "r"(bytes) : "memory"); }
__device__ __forceinline__ bool mbar_try(uint32_t bar, uint32_t parity) {
  uint32_t ok;
  asm volatile("{\n.reg .pred p;\nmbarrier.try_wait.parity.shared::cta.b64 p, [%1], %2;\nselp.b32 %0, 1, 0, p;\n}\n" : "=r"(ok) : "r"(bar), "r"(parity) : "memory");
  return ok;
}
__device__ __forceinline__ void mbar_wait(uint32_t bar, uint32_t parity) {
  asm volatile("{\n.reg .pred p;\n.reg .u32 c;\nmov.u32 c, 0;\n"
               "LW_%=:\n"
               "mbarrier.try_wait.parity.shared::cta.b64 p, [%0], %1;\n"
               "@p bra LD_%=;\n"
               "add.u32 c, c, 1;\n"
               "setp.lt.u32 p, c, 4000000;\n"
               "@p bra LW_%=;\n"
               "trap;\n"
               "LD_%=:\n}\n" :: "r"(bar), "r"(parity) : "memory");
}
__device__ __forceinline__ void mbar_arrive_cta(uint32_t bar, uint32_t cta) {
  asm volatile("{\n.reg .b32 ra;\nmapa.shared::cluster.u32 ra, %0, %1;\nmbarrier.arrive.shared::cluster.b64 _, [ra];\n}\n" :: "r"(bar), "r"(cta) : "memory");
}
__device__ __forceinline__ void cluster_sync() {
  asm volatile("barrier.cluster.arrive.relaxed.aligned;\nbarrier.cluster.wait.aligned;" ::: "memory");
}
__device__ __forceinline__ void tma2d(uint32_t dst, const CUtensorMap* m, int c0, int c1, uint32_t bar) {
  asm volatile("cp.async.bulk.tensor.2d.shared::cluster.global.mbarrier::complete_tx::bytes [%0], [%1, {%3, %4}], [%2];"
               :: "r"(dst), "l"(m), "r"(bar), "r"(c0), "r"(c1) : "memory");
}
__device__ __forceinline__ void tma2d_mc(uint32_t dst, const CUtensorMap* m, int c0, int c1, uint32_t bar, uint16_t mask) {
  asm volatile("cp.async.bulk.tensor.2d.shared::cluster.global.mbarrier::complete_tx::bytes.multicast::cluster [%0], [%1, {%3, %4}], [%2], %5;"
               :: "r"(dst), "l"(m), "r"(bar), "r"(c0), "r"(c1), "h"(mask) : "memory");
}
__device__ __forceinline__ void tma2d_store(const CUtensorMap* m, uint32_t src, int c0, int c1) {
  asm volatile("cp.async.bulk.tensor.2d.global.shared::cta.bulk_group [%0, {%2, %3}], [%1];"
               :: "l"(m), "r"(src), "r"(c0), "r"(c1) : "memory");
}
__device__ __forceinline__ void bulk_g2s(uint32_t dst, const void* src, uint32_t bytes, uint32_t bar) {
  asm volatile("cp.async.bulk.shared::cluster.global.mbarrier::complete_tx::bytes [%0], [%1], %2, [%3];"
               :: "r"(dst), "l"(src), "r"(bytes), "r"(bar) : "memory");
}
__device__ __forceinline__ void bulk_commit() { asm volatile("cp.async.bulk.commit_group;" ::: "memory"); }
__device__ __forceinline__ void bulk_wait_all() { asm volatile("cp.async.bulk.wait_group 0;" ::: "memory"); }
__device__ __forceinline__ void fence_async() { asm volatile("fence.proxy.async.shared::cta;" ::: "memory"); }
__device__ __forceinline__ void named_bar(int id, int n) { asm volatile("bar.sync %0, %1;" :: "r"(id), "r"(n) : "memory"); }
__device__ __forceinline__ void pdl_launch() { asm volatile("griddepcontrol.launch_dependents;" ::: "memory"); }
__device__ __forceinline__ void pdl_wait() { asm volatile("griddepcontrol.wait;" ::: "memory"); }
__device__ __forceinline__ void wg_fence() { asm volatile("wgmma.fence.sync.aligned;" ::: "memory"); }
__device__ __forceinline__ void wg_commit() { asm volatile("wgmma.commit_group.sync.aligned;" ::: "memory"); }
template <int n> __device__ __forceinline__ void wg_wait() { asm volatile("wgmma.wait_group.sync.aligned %0;" :: "n"(n) : "memory"); }
template <int n> __device__ __forceinline__ void fence_regs(float* r) {
#pragma unroll
  for (int i = 0; i < n; i++) asm volatile("" : "+f"(r[i]) :: "memory");
}
template <int n> __device__ __forceinline__ void fence_regs(uint32_t* r) {
#pragma unroll
  for (int i = 0; i < n; i++) asm volatile("" : "+r"(r[i]) :: "memory");
}
__device__ __forceinline__ uint64_t make_desc(uint32_t addr, uint32_t lbo, uint32_t sbo, uint32_t swz) {
  return (uint64_t)((addr & 0x3FFFF) >> 4) | ((uint64_t)(lbo >> 4) << 16) | ((uint64_t)(sbo >> 4) << 32) | ((uint64_t)swz << 62);
}
__device__ __forceinline__ float ex2f(float x) { float y; asm("ex2.approx.ftz.f32 %0, %1;" : "=f"(y) : "f"(x)); return y; }
__device__ __forceinline__ uint32_t pack_bf16(float lo, float hi) { uint32_t r; asm("cvt.rn.bf16x2.f32 %0, %1, %2;" : "=r"(r) : "f"(hi), "f"(lo)); return r; }
__device__ __forceinline__ uint32_t pack_f16(float lo, float hi) { uint32_t r; asm("cvt.rn.f16x2.f32 %0, %1, %2;" : "=r"(r) : "f"(hi), "f"(lo)); return r; }
__device__ __forceinline__ float bf_lo(uint32_t v) { return __uint_as_float(v << 16); }
__device__ __forceinline__ float bf_hi(uint32_t v) { return __uint_as_float(v & 0xFFFF0000u); }
__device__ __forceinline__ float rbf(float x) { return __bfloat162float(__float2bfloat16_rn(x)); }
__device__ __forceinline__ void stsm4(uint32_t a, uint32_t r0, uint32_t r1, uint32_t r2, uint32_t r3) {
  asm volatile("stmatrix.sync.aligned.m8n8.x4.shared.b16 [%0], {%1,%2,%3,%4};" :: "r"(a), "r"(r0), "r"(r1), "r"(r2), "r"(r3) : "memory");
}
__device__ __forceinline__ void stsm4t(uint32_t a, uint32_t r0, uint32_t r1, uint32_t r2, uint32_t r3) {
  asm volatile("stmatrix.sync.aligned.m8n8.x4.trans.shared.b16 [%0], {%1,%2,%3,%4};" :: "r"(a), "r"(r0), "r"(r1), "r"(r2), "r"(r3) : "memory");
}
__device__ __forceinline__ void mma_bf16(float* d, uint32_t a0, uint32_t a1, uint32_t a2, uint32_t a3, uint32_t b0, uint32_t b1) {
  asm volatile("mma.sync.aligned.m16n8k16.row.col.f32.bf16.bf16.f32 {%0,%1,%2,%3}, {%4,%5,%6,%7}, {%8,%9}, {%0,%1,%2,%3};"
               : "+f"(d[0]), "+f"(d[1]), "+f"(d[2]), "+f"(d[3]) : "r"(a0), "r"(a1), "r"(a2), "r"(a3), "r"(b0), "r"(b1));
}
template<int SD> __device__ __forceinline__ void wg_qs24(float* d, uint64_t da, uint64_t db) {
  asm volatile("wgmma.mma_async.sync.aligned.m64n24k16.f32.f16.f16 {%0,%1,%2,%3,%4,%5,%6,%7,%8,%9,%10,%11}, %12, %13, %14, 1, 1, 0, 0;"
   : "+f"(d[0]),"+f"(d[1]),"+f"(d[2]),"+f"(d[3]),"+f"(d[4]),"+f"(d[5]),"+f"(d[6]),"+f"(d[7]),"+f"(d[8]),"+f"(d[9]),"+f"(d[10]),"+f"(d[11])
   : "l"(da),"l"(db),"n"(SD));
}
template<int SD> __device__ __forceinline__ void wg_qs72(float* d, uint64_t da, uint64_t db) {
  asm volatile("wgmma.mma_async.sync.aligned.m64n72k16.f32.f16.f16 {%0,%1,%2,%3,%4,%5,%6,%7,%8,%9,%10,%11,%12,%13,%14,%15,%16,%17,%18,%19,%20,%21,%22,%23,%24,%25,%26,%27,%28,%29,%30,%31,%32,%33,%34,%35}, %36, %37, %38, 1, 1, 0, 0;"
   : "+f"(d[0]),"+f"(d[1]),"+f"(d[2]),"+f"(d[3]),"+f"(d[4]),"+f"(d[5]),"+f"(d[6]),"+f"(d[7]),"+f"(d[8]),"+f"(d[9]),"+f"(d[10]),"+f"(d[11]),"+f"(d[12]),"+f"(d[13]),"+f"(d[14]),"+f"(d[15]),"+f"(d[16]),"+f"(d[17]),"+f"(d[18]),"+f"(d[19]),"+f"(d[20]),"+f"(d[21]),"+f"(d[22]),"+f"(d[23]),"+f"(d[24]),"+f"(d[25]),"+f"(d[26]),"+f"(d[27]),"+f"(d[28]),"+f"(d[29]),"+f"(d[30]),"+f"(d[31]),"+f"(d[32]),"+f"(d[33]),"+f"(d[34]),"+f"(d[35])
   : "l"(da),"l"(db),"n"(SD));
}
template<int SD> __device__ __forceinline__ void wg_pv24(float* d, const uint32_t* a, uint64_t desc) {
  asm volatile("wgmma.mma_async.sync.aligned.m64n24k16.f32.bf16.bf16 {%0,%1,%2,%3,%4,%5,%6,%7,%8,%9,%10,%11}, {%12,%13,%14,%15}, %16, %17, 1, 1, 1;"
   : "+f"(d[0]),"+f"(d[1]),"+f"(d[2]),"+f"(d[3]),"+f"(d[4]),"+f"(d[5]),"+f"(d[6]),"+f"(d[7]),"+f"(d[8]),"+f"(d[9]),"+f"(d[10]),"+f"(d[11])
   : "r"(a[0]),"r"(a[1]),"r"(a[2]),"r"(a[3]),"l"(desc),"n"(SD));
}
template<int TA, int TB> __device__ __forceinline__ void wg_ss128(float* d, uint64_t da, uint64_t db, int sd) {
  asm volatile("{\n.reg .pred p;\nsetp.ne.b32 p, %66, 0;\n"
   "wgmma.mma_async.sync.aligned.m64n128k16.f32.bf16.bf16 {%0,%1,%2,%3,%4,%5,%6,%7,%8,%9,%10,%11,%12,%13,%14,%15,%16,%17,%18,%19,%20,%21,%22,%23,%24,%25,%26,%27,%28,%29,%30,%31,%32,%33,%34,%35,%36,%37,%38,%39,%40,%41,%42,%43,%44,%45,%46,%47,%48,%49,%50,%51,%52,%53,%54,%55,%56,%57,%58,%59,%60,%61,%62,%63}, %64, %65, p, 1, 1, %67, %68;\n}\n"
   : "+f"(d[0]),"+f"(d[1]),"+f"(d[2]),"+f"(d[3]),"+f"(d[4]),"+f"(d[5]),"+f"(d[6]),"+f"(d[7]),"+f"(d[8]),"+f"(d[9]),"+f"(d[10]),"+f"(d[11]),"+f"(d[12]),"+f"(d[13]),"+f"(d[14]),"+f"(d[15]),"+f"(d[16]),"+f"(d[17]),"+f"(d[18]),"+f"(d[19]),"+f"(d[20]),"+f"(d[21]),"+f"(d[22]),"+f"(d[23]),"+f"(d[24]),"+f"(d[25]),"+f"(d[26]),"+f"(d[27]),"+f"(d[28]),"+f"(d[29]),"+f"(d[30]),"+f"(d[31]),"+f"(d[32]),"+f"(d[33]),"+f"(d[34]),"+f"(d[35]),"+f"(d[36]),"+f"(d[37]),"+f"(d[38]),"+f"(d[39]),"+f"(d[40]),"+f"(d[41]),"+f"(d[42]),"+f"(d[43]),"+f"(d[44]),"+f"(d[45]),"+f"(d[46]),"+f"(d[47]),"+f"(d[48]),"+f"(d[49]),"+f"(d[50]),"+f"(d[51]),"+f"(d[52]),"+f"(d[53]),"+f"(d[54]),"+f"(d[55]),"+f"(d[56]),"+f"(d[57]),"+f"(d[58]),"+f"(d[59]),"+f"(d[60]),"+f"(d[61]),"+f"(d[62]),"+f"(d[63])
   : "l"(da),"l"(db),"r"(sd),"n"(TA),"n"(TB));
}
template<int TA, int TB> __device__ __forceinline__ void wg_ss64(float* d, uint64_t da, uint64_t db, int sd) {
  asm volatile("{\n.reg .pred p;\nsetp.ne.b32 p, %34, 0;\n"
   "wgmma.mma_async.sync.aligned.m64n64k16.f32.bf16.bf16 {%0,%1,%2,%3,%4,%5,%6,%7,%8,%9,%10,%11,%12,%13,%14,%15,%16,%17,%18,%19,%20,%21,%22,%23,%24,%25,%26,%27,%28,%29,%30,%31}, %32, %33, p, 1, 1, %35, %36;\n}\n"
   : "+f"(d[0]),"+f"(d[1]),"+f"(d[2]),"+f"(d[3]),"+f"(d[4]),"+f"(d[5]),"+f"(d[6]),"+f"(d[7]),"+f"(d[8]),"+f"(d[9]),"+f"(d[10]),"+f"(d[11]),"+f"(d[12]),"+f"(d[13]),"+f"(d[14]),"+f"(d[15]),"+f"(d[16]),"+f"(d[17]),"+f"(d[18]),"+f"(d[19]),"+f"(d[20]),"+f"(d[21]),"+f"(d[22]),"+f"(d[23]),"+f"(d[24]),"+f"(d[25]),"+f"(d[26]),"+f"(d[27]),"+f"(d[28]),"+f"(d[29]),"+f"(d[30]),"+f"(d[31])
   : "l"(da),"l"(db),"r"(sd),"n"(TA),"n"(TB));
}
template<int TA, int TB> __device__ __forceinline__ void wg_ss8(float* d, uint64_t da, uint64_t db, int sd) {
  asm volatile("{\n.reg .pred p;\nsetp.ne.b32 p, %6, 0;\n"
   "wgmma.mma_async.sync.aligned.m64n8k16.f32.bf16.bf16 {%0,%1,%2,%3}, %4, %5, p, 1, 1, %7, %8;\n}\n"
   : "+f"(d[0]),"+f"(d[1]),"+f"(d[2]),"+f"(d[3])
   : "l"(da),"l"(db),"r"(sd),"n"(TA),"n"(TB));
}

__device__ __forceinline__ uint32_t phi2(float a, float b) {
  uint32_t r, e;
  asm("cvt.rn.relu.bf16x2.f32 %0, %1, %2;" : "=r"(r) : "f"(b), "f"(a));
  e = pack_bf16(ex2f(a * 1.4426950408889634f), ex2f(b * 1.4426950408889634f));
  asm("add.rn.bf16x2 %0, %0, %1;" : "+r"(e) : "r"(0x35863586u));
  asm("min.NaN.bf16x2 %0, %0, %1;" : "+r"(e) : "r"(0x3F803F80u));
  asm("add.rn.bf16x2 %0, %0, %1;" : "+r"(e) : "r"(r));
  return e;
}

__device__ __forceinline__ void mbar_arrive(uint32_t bar) { asm volatile("mbarrier.arrive.shared::cta.b64 _, [%0];" :: "r"(bar) : "memory"); }
__device__ __forceinline__ void named_arrive(int id, int n) { asm volatile("bar.arrive %0, %1;" :: "r"(id), "r"(n) : "memory"); }
__device__ __forceinline__ void fence_async_all() { asm volatile("fence.proxy.async.global;" ::: "memory"); }
__device__ __forceinline__ void flag_add(uint32_t* f) { asm volatile("fence.acq_rel.gpu;\nred.relaxed.gpu.global.add.u32 [%0], 1;" :: "l"(f) : "memory"); }
#define PUBLISH(f) asm volatile("fence.proxy.async.global;\nred.relaxed.gpu.global.add.u32 [%0], 1;" :: "l"(f) : "memory")
__device__ __forceinline__ void flag_wait(const uint32_t* f, uint32_t target) {
  uint32_t v;
#pragma unroll 1
  for (int it = 0;; it++) {
    asm volatile("ld.acquire.gpu.global.u32 %0, [%1];" : "=r"(v) : "l"(f) : "memory");
    if ((int32_t)(v - target) >= 0) break;
    if (it > 2000000) __trap();
    __nanosleep(64);
  }
}
__device__ __forceinline__ bool mbar_test(uint32_t bar, uint32_t parity) {
  uint32_t ok;
  asm volatile("{\n.reg .pred p;\nmbarrier.test_wait.parity.shared::cta.b64 p, [%1], %2;\nselp.b32 %0, 1, 0, p;\n}\n" : "=r"(ok) : "r"(bar), "r"(parity) : "memory");
  return ok;
}
__device__ __forceinline__ bool elect_one() {
  uint32_t p;
  asm volatile("{\n.reg .pred P;\nelect.sync _|P, 0xFFFFFFFF;\nselp.b32 %0, 1, 0, P;\n}\n" : "=r"(p));
  return p;
}
__device__ __forceinline__ void lds4(uint32_t a, uint32_t* r) {
  asm volatile("ld.shared.v4.b32 {%0,%1,%2,%3}, [%4];" : "=r"(r[0]), "=r"(r[1]), "=r"(r[2]), "=r"(r[3]) : "r"(a) : "memory");
}
__device__ __forceinline__ uint32_t lds1(uint32_t a) { uint32_t r; asm volatile("ld.shared.b32 %0, [%1];" : "=r"(r) : "r"(a) : "memory"); return r; }
__device__ __forceinline__ void sts1(uint32_t a, uint32_t v) { asm volatile("st.shared.b32 [%0], %1;" :: "r"(a), "r"(v) : "memory"); }
__device__ __forceinline__ void sts4(uint32_t a, uint32_t r0, uint32_t r1, uint32_t r2, uint32_t r3) {
  asm volatile("st.shared.v4.b32 [%0], {%1,%2,%3,%4};" :: "r"(a), "r"(r0), "r"(r1), "r"(r2), "r"(r3) : "memory");
}
__device__ __forceinline__ void ldsm4(uint32_t a, uint32_t* r) {
  asm volatile("ldmatrix.sync.aligned.m8n8.x4.shared.b16 {%0,%1,%2,%3}, [%4];" : "=r"(r[0]), "=r"(r[1]), "=r"(r[2]), "=r"(r[3]) : "r"(a) : "memory");
}
__device__ __forceinline__ float rcpf(float x) { float y; asm("rcp.approx.ftz.f32 %0, %1;" : "=f"(y) : "f"(x)); return y; }
__device__ __forceinline__ uint32_t hfma2(uint32_t a, uint32_t b, uint32_t c) { uint32_t r; asm("fma.rn.f16x2 %0, %1, %2, %3;" : "=r"(r) : "r"(a), "r"(b), "r"(c)); return r; }
__device__ __forceinline__ uint32_t hadd2(uint32_t a, uint32_t b) { uint32_t r; asm("add.rn.f16x2 %0, %1, %2;" : "=r"(r) : "r"(a), "r"(b)); return r; }

#define STEPK 96
#define QSCALE 0.36067376022224085f
#define SMAGIC (512.0f + 2.0f * (191.0f - 30.0f - 1.5823545f))
#define VSHIFT 1073741824.0f

__device__ uint32_t g_epoch[132];
__device__ uint32_t g_flag[288 * 8];
#define FLAG_KV (g_flag)
#define FLAG_B(h) (g_flag + (4 + (h)) * 8)
#define FLAG_OA(cta, pass) (g_flag + (16 + (cta) * 2 + (pass)) * 8)
#define FLAG_LM(i) (g_flag + (272 + (i)) * 8)

#define SM_TOTAL (224 * 1024 + 2048 + 1024)
#define OFF_K 0
#define OFF_F 65536
#define OFF_V 131072
#define OFF_MISC (224 * 1024)

#define BAR_FULL(s) (bars + 8 * (s))
#define BAR_EMPTY(s) (bars + 24 + 8 * (s))
#define BAR_KV(c) (bars + 48 + 8 * (c))
#define BAR_BDONE (bars + 80)
#define BAR_Q (bars + 88)
#define BAR_GO (bars + 96)
#define BAR_Q2 (bars + 104)
#define BAR_OD(p) (bars + 112 + 8 * (p))
#define BAR_CL(c) (bars + 128 + 8 * (c))
#define BAR_TE(i) (bars + 168 + 8 * (i))
#define BAR_TF(g) (bars + 224 + 8 * (g))
#define BAR_XA(w) (bars + 352 + 8 * (w))
#define BAR_VB(c) (bars + 384 + 8 * (c))

__device__ __forceinline__ uint32_t exp2_pair_fix(float d0, float d1, uint32_t c63, uint32_t m1) {
  uint32_t w, y, s, r;
  asm("prmt.b32 %0, %1, %2, 0x6521;" : "=r"(w) : "r"(__float_as_uint(d0)), "r"(__float_as_uint(d1)));
  asm("lop3.b32 %0, %1, 0x007F007F, %2, 0xEA;" : "=r"(y) : "r"(w), "r"(c63));
  asm("mad.lo.u32 %0, %1, %2, %3;" : "=r"(s) : "r"(y), "r"(m1), "r"(w));
  asm("fma.rn.bf16x2 %0, %1, %2, %3;" : "=r"(r) : "r"(w), "r"(y), "r"(s));
  return r;
}

__device__ __forceinline__ void attn_slow(const uint4* gq, uint32_t dst) {
  const int t = threadIdx.x & 127;
  const int row = t >> 1, half = t & 1;
  float q[16];
#pragma unroll
  for (int i = 0; i < 4; i++) {
    const uint4 v = gq[(row >> 4) * 32 + (row & 7) * 4 + i];
    const uint32_t lo = (row & 8) ? v.y : v.x, hi = (row & 8) ? v.w : v.z;
    q[2 * i] = bf_lo(lo); q[2 * i + 1] = bf_hi(lo); q[2 * i + 8] = bf_lo(hi); q[2 * i + 9] = bf_hi(hi);
  }
  float m = -INFINITY, l = 0.f, o[16];
#pragma unroll
  for (int i = 0; i < 16; i++) o[i] = 0.f;
#pragma unroll 1
  for (int j = half * 1024; j < half * 1024 + 1024; j++) {
    uint4 ka = g_KV[4 * S_TOK + j], kb = g_KV[5 * S_TOK + j];
    uint4 va = g_KV[6 * S_TOK + j], vb = g_KV[7 * S_TOK + j];
    uint32_t kk[8] = {ka.x, ka.y, ka.z, ka.w, kb.x, kb.y, kb.z, kb.w};
    uint32_t vv[8] = {va.x, va.y, va.z, va.w, vb.x, vb.y, vb.z, vb.w};
    float s = 0.f;
#pragma unroll
    for (int i = 0; i < 8; i++) { s = fmaf(q[2 * i], bf_lo(kk[i]), s); s = fmaf(q[2 * i + 1], bf_hi(kk[i]), s); }
    s = rbf(s) * 0.25f;
    if (s > m) {
      float c = __expf(m - s);
      l *= c;
#pragma unroll
      for (int i = 0; i < 16; i++) o[i] *= c;
      m = s;
    }
    float p = __expf(s - m);
    l += p;
#pragma unroll
    for (int i = 0; i < 8; i++) { o[2 * i] = fmaf(p, bf_lo(vv[i]), o[2 * i]); o[2 * i + 1] = fmaf(p, bf_hi(vv[i]), o[2 * i + 1]); }
  }
  float m2 = __shfl_xor_sync(~0u, m, 1);
  float mm = fmaxf(m, m2);
  float c = __expf(m - mm);
  l *= c; l += __shfl_xor_sync(~0u, l, 1);
  float inv = 1.f / l;
  uint32_t r[8];
#pragma unroll
  for (int i = 0; i < 16; i++) { o[i] *= c; o[i] += __shfl_xor_sync(~0u, o[i], 1); o[i] *= inv; }
#pragma unroll
  for (int i = 0; i < 8; i++) r[i] = pack_bf16(o[2 * i], o[2 * i + 1]);
  if (half == 0) sts4(dst, r[0], r[1], r[2], r[3]); else sts4(dst, r[4], r[5], r[6], r[7]);
  fence_async();
}

struct Params { const __nv_bfloat16* wk; const __nv_bfloat16* wv; const __nv_bfloat16* xa; };
__device__ __forceinline__ void cp16(uint32_t dst, const void* src) { asm volatile("cp.async.cg.shared.global [%0], [%1], 16;" :: "r"(dst), "l"(src) : "memory"); }

__device__ __forceinline__ void helper_cta(const int h, const uint32_t sb, const uint32_t bars, const int wg, const int w4,
                                           const CUtensorMap* mQ, const CUtensorMap* mOs) {
  const int lane = threadIdx.x & 31;
  mbar_wait(BAR_GO, 0);
  const int cb = wg & 1, col = h * 128 + cb * 64, row0 = S_TOK + (wg >> 1) * 1024;
  const uint32_t buf = sb + wg * 49152;
  if (w4 == 0 && elect_one()) {
    fence_async_all();
#pragma unroll 1
    for (int u = 0; u < 3; u++) {
      mbar_expect_tx(BAR_TF(wg * 3 + u), 16384);
      tma2d(buf + u * 16384, mQ, col, row0 + u * 128, BAR_TF(wg * 3 + u));
    }
  }
  const int head = h * 8 + cb * 4 + w4;
  float4 a0 = make_float4(0, 0, 0, 0), a1 = a0, a2 = a0;
#pragma unroll 8
  for (int tt = 0; tt < 16; tt++) {
    const float4* src = g_kvp + ((tt * 32 + head) * 3) * 32 + lane;
    float4 u = src[0], v = src[32], w = src[64];
    a0.x += u.x; a0.y += u.y; a0.z += u.z; a0.w += u.w;
    a1.x += v.x; a1.y += v.y; a1.z += v.z; a1.w += v.w;
    a2.x += w.x; a2.y += w.y; a2.z += w.z; a2.w += w.w;
  }
  const uint32_t b00 = pack_bf16(a0.x, a0.y), b01 = pack_bf16(a0.z, a0.w);
  const uint32_t b10 = pack_bf16(a1.x, a1.y), b11 = pack_bf16(a1.z, a1.w);
  const uint32_t bz0 = pack_bf16(a2.x, a2.y), bz1 = pack_bf16(a2.z, a2.w);
  const int m = lane >> 3, r = lane & 7;
  const uint32_t off = ((m & 1) * 8 + r) * 128 + (((w4 * 2 + (m >> 1)) ^ r) << 4);
  int s = 0, ph = 0;
#pragma unroll 1
  for (int u = 0; u < 8; u++) {
    const uint32_t bb = buf + s * 16384;
    mbar_wait(BAR_TF(wg * 3 + s), ph);
#pragma unroll
    for (int mt = 0; mt < 8; mt++) {
      uint32_t a[4];
      ldsm4(bb + mt * 2048 + off, a);
      float n0[4] = {0, 0, 0, 0}, n1[4] = {0, 0, 0, 0}, dn[4] = {0, 0, 0, 0};
      mma_bf16(dn, a[0], a[1], a[2], a[3], bz0, bz1);
      mma_bf16(n0, a[0], a[1], a[2], a[3], b00, b01);
      mma_bf16(n1, a[0], a[1], a[2], a[3], b10, b11);
      const float i0 = rcpf(dn[0] + 1e-6f), i1 = rcpf(dn[2] + 1e-6f);
      stsm4(bb + mt * 2048 + off, pack_bf16(n0[0] * i0, n0[1] * i0), pack_bf16(n0[2] * i1, n0[3] * i1),
            pack_bf16(n1[0] * i0, n1[1] * i0), pack_bf16(n1[2] * i1, n1[3] * i1));
    }
    fence_async();
    named_bar(wg + 1, 128);
    if (w4 == 0 && lane == 0) {
      tma2d_store(mOs, bb, col, row0 + u * 128);
      bulk_commit();
      if (u >= 1 && u + 2 < 8) {
        asm volatile("cp.async.bulk.wait_group.read 1;" ::: "memory");
        const int sp = s == 0 ? 2 : s - 1;
        mbar_expect_tx(BAR_TF(wg * 3 + sp), 16384);
        tma2d(buf + sp * 16384, mQ, col, row0 + (u + 2) * 128, BAR_TF(wg * 3 + sp));
      }
    }
    __syncwarp();
    if (++s == 3) { s = 0; ph ^= 1; }
  }
  if (w4 == 0 && lane == 0) {
    bulk_wait_all();
    fence_async_all();
    flag_add(FLAG_LM((h * 2 + cb) * 2 + (wg >> 1)));
    if (wg == 0) TS(1, 8);
  }
}

#define STAGE(s) (sb + (2 - (s)) * 65536)
template <int TR> __device__ __forceinline__ void proj_kb(float* acc, uint32_t st, uint32_t offA, uint32_t offB, int first) {
  const uint64_t da = make_desc(st + offA, TR ? 8192 : 16, 1024, 1);
  const uint64_t db = make_desc(st + offB, TR ? 16 : 8192, 1024, 1);
  wg_fence();
#pragma unroll
  for (int k = 0; k < 4; k++) wg_ss128<TR, 1 - TR>(acc, da + k * (TR ? 128 : 2), db + k * (TR ? 2 : 128), k != 0 || !first);
  wg_commit();
}
template <int TR> __device__ __forceinline__ void proj_loop(float* acc, uint32_t sb, uint32_t bars, uint32_t offA, uint32_t offB,
                                                            int wg, uint32_t sWKV) {
  {
    float kv[4];
    if (threadIdx.x == 0) TS(0, 13);
    mbar_wait(BAR_XA(wg), 0);
    if (threadIdx.x == 0) TS(0, 1);
    const uint64_t da = make_desc(STAGE(2) + wg * 16384, 16, 1024, 1), db = make_desc(sWKV + wg * 2048, 128, 128, 0);
    wg_fence();
#pragma unroll
    for (int k = 0; k < 8; k++) wg_ss8<0, 1>(kv, da + (k >> 2) * 512 + (k & 3) * 2, db + k * 16, k != 0);
    wg_commit();
    wg_wait<0>();
    fence_regs<4>(kv);
    named_bar(wg + 1, 128);
    sts4(sWKV + threadIdx.x * 16, __float_as_uint(kv[0]), __float_as_uint(kv[1]), __float_as_uint(kv[2]), __float_as_uint(kv[3]));
    __syncwarp();
    if ((threadIdx.x & 31) == 0) mbar_arrive(BAR_GO);
  }
  int s = 0, ph = 0, sp = 0;
#pragma unroll 1
  for (int kb = 0; kb < 8; kb++) {
    mbar_wait(BAR_FULL(s), ph);
    if (threadIdx.x == 0) TS(0, 2 + kb);
    proj_kb<TR>(acc, STAGE(s), offA, offB, kb == 0);
    wg_wait<1>();
    if (kb >= 1 && (threadIdx.x & 127) == 0) mbar_arrive(BAR_EMPTY(sp));
    __syncwarp();
    sp = s;
    if (++s == 3) { s = 0; ph ^= 1; }
  }
  wg_wait<0>();
  fence_regs<64>(acc);
}

__device__ __forceinline__ uint32_t tail_slots(int t) {
  const uint32_t lo = t < 4 ? (t < 2 ? (t == 0 ? 0x0C0B0Au : 0x0F0E0Du) : (t == 2 ? 0x100400u : 0x181408u))
                            : (t < 6 ? (t == 4 ? 0x110501u : 0x191502u) : (t == 6 ? 0x161206u : (t == 7 ? 0x130703u : 0x1B171Au)));
  return lo;
}

__device__ __forceinline__ void take_role(uint32_t sM, int wg) {
  uint32_t r;
  asm volatile("atom.shared.add.u32 %0, [%1], 1;" : "=r"(r) : "r"(sM + 20) : "memory");
  sts1(sM + 32 + wg * 4, r);
}

__global__ void __launch_bounds__(640, 1)
k1_main(const __grid_constant__ CUtensorMap mXA64, const __grid_constant__ CUtensorMap mXB,
        const __grid_constant__ CUtensorMap mWq, const __grid_constant__ CUtensorMap mWqkv,
        const __grid_constant__ CUtensorMap mQst, const __grid_constant__ CUtensorMap mOst,
        const __grid_constant__ CUtensorMap mO, const __grid_constant__ CUtensorMap mWoA,
        const __grid_constant__ CUtensorMap mWoB, const __grid_constant__ CUtensorMap mOut,
        const __grid_constant__ CUtensorMap mO16, const Params prm) {
  extern __shared__ uint8_t smem_raw[];
  const uint32_t sb = (smem_u32(smem_raw) + 1023u) & ~1023u;
  const uint32_t bars = sb + OFF_MISC, sM = bars + 512, sT = bars + 1024;
  const int tid = threadIdx.x, warp = __shfl_sync(~0u, tid >> 5, 0), wg = warp >> 2, w4 = warp & 3, lane = tid & 31;
  const bool helper = blockIdx.x >= 128;
  if (tid == 0) TS(0, 0);
  const int G = blockIdx.x >> 4, gi = blockIdx.x & 15;
  const int tbA = G * 4 + (gi >> 2), hg = gi & 3;
  const int ttB = (G >> 1) * 4 + (gi >> 2), hq = (G & 1) * 4 + (gi & 3);
  auto issue = [&](int kb, int s) {
    const uint32_t fb = BAR_FULL(s), st = STAGE(s);
    mbar_expect_tx(fb, 65536);
    tma2d(st + 16384, &mXA64, kb * 64, tbA * 64, fb);
    tma2d(st, &mWq, hg * 128, kb * 64, fb);
    tma2d(st + 8192, &mWq, hg * 128 + 64, kb * 64, fb);
    tma2d(st + 49152, &mXB, kb * 64, ttB * 128, fb);
    tma2d(st + 24576, &mWqkv, hq * 64, kb * 64, fb);
    tma2d(st + 32768, &mWqkv, 512 + hq * 64, kb * 64, fb);
    tma2d(st + 40960, &mWqkv, 1024 + hq * 64, kb * 64, fb);
  };
  const uint32_t sOne = sb + OFF_V + 65536, sWKV = sOne + 24576;
  if (warp >= 16) {
    if (warp == 17) {
      if (elect_one()) {
        mbar_init(BAR_BDONE, 8); mbar_init(BAR_Q, 8); mbar_init(BAR_GO, helper ? 1 : 16); mbar_init(BAR_Q2, 5);
        mbar_init(BAR_OD(0), 16); mbar_init(BAR_OD(1), 16); mbar_init(BAR_CL(0), 1); mbar_init(BAR_FULL(2), 1);
#pragma unroll
        for (int i = 0; i < 4; i++) mbar_init(BAR_CL(i + 1), i == 0 ? 5 : 4);
#pragma unroll
        for (int i = 0; i < 3; i++) { mbar_init(BAR_EMPTY(i), 4); mbar_init(BAR_KV(i), 1); mbar_init(BAR_VB(i), 1); }
        sts1(sM + 20, 0);
        asm volatile("fence.mbarrier_init.release.cluster;" ::: "memory");
      }
    } else if (warp == 18) {
      if (elect_one()) {
#pragma unroll
        for (int i = 0; i < 7; i++) mbar_init(BAR_TE(i), 1);
#pragma unroll
        for (int i = 0; i < 16; i++) mbar_init(BAR_TF(i), i < 12 || i == 15 ? 1 : 2);
        asm volatile("fence.mbarrier_init.release.cluster;" ::: "memory");
      }
    } else if (warp == 16 && !helper && elect_one()) {
#pragma unroll
      for (int w = 0; w < 4; w++) mbar_init(BAR_XA(w), 1);
      mbar_init(BAR_FULL(0), 1); mbar_init(BAR_FULL(1), 1);
      asm volatile("fence.mbarrier_init.release.cluster;" ::: "memory");
#pragma unroll
      for (int w = 0; w < 4; w++) {
        mbar_expect_tx(BAR_XA(w), 16384);
        tma2d(STAGE(2) + w * 16384, &mXA64, w * 128, tbA * 64, BAR_XA(w));
        tma2d(STAGE(2) + w * 16384 + 8192, &mXA64, w * 128 + 64, tbA * 64, BAR_XA(w));
      }
      TS(0, 14);
      issue(0, 0);
    }
  } else if (!helper) {
    const uint4 v = __ldg((const uint4*)(hg >= 2 ? prm.wv : prm.wk) + tid * 2 + (hg & 1));
#pragma unroll
    for (int i = 0; i < 3; i++) {
      const int key = tid + i * 512;
      sts4(sOne + key * 16, (key % STEPK) < 24 ? 0x00003F80u : 0x00004E80u, 0u, 0u, 0u);
    }
    sts4(sWKV + tid * 16, v.x, v.y, v.z, v.w);
    fence_async();
  }
  __syncthreads();
  if (wg == 4) {
    if (w4 == 0 && !helper && elect_one()) { issue(1, 1); TS(0, 15); }
    asm volatile("setmaxnreg.dec.sync.aligned.u32 32;");
    const uint32_t ep = g_epoch[blockIdx.x] + 1;
    if (helper) {
      if (w4 == 0 && elect_one()) {
        flag_wait(FLAG_B(blockIdx.x - 128), ep * 32);
        fence_async_all();
        TS(1, 10);
        mbar_arrive(BAR_GO);
        g_epoch[blockIdx.x] = ep;
      }
      return;
    }
    mbar_wait(BAR_GO, 0);
    if (w4 == 0 && elect_one()) issue(2, 2);
    {
      uint32_t a[4], b[4];
      float c[4];
      lds4(sWKV + (tid - 512) * 16, a);
      lds4(sWKV + 2048 + (tid - 512) * 16, b);
#pragma unroll
      for (int i = 0; i < 4; i++) c[i] = __uint_as_float(a[i]) + __uint_as_float(b[i]);
      lds4(sWKV + 4096 + (tid - 512) * 16, a);
      lds4(sWKV + 6144 + (tid - 512) * 16, b);
#pragma unroll
      for (int i = 0; i < 4; i++) c[i] += __uint_as_float(a[i]) + __uint_as_float(b[i]);
      sts1(sT + w4 * 256 + lane * 4, pack_bf16(c[0], c[1]));
      sts1(sT + w4 * 256 + 128 + lane * 4, pack_bf16(c[2], c[3]));
    }
    named_bar(9, 128);
    {
      const int t = tid - 512;
#pragma unroll
      for (int i = 0; i < 4; i++) {
        const int key = 1536 + t + i * 128;
        sts4(sOne + key * 16, (key % STEPK) < 24 ? 0x00003F80u : 0x00004E80u, 0u, 0u, 0u);
      }
      fence_async();
      __syncwarp();
      if (lane == 0) mbar_arrive(BAR_Q);
    }
    if (w4 == 0) {
      int s = 0, ph = 0;
#pragma unroll 1
      for (int kb = 3; kb < 8; kb++) {
        mbar_wait(BAR_EMPTY(s), ph);
        if (elect_one()) issue(kb, s);
        if (++s == 3) { s = 0; ph ^= 1; }
      }
      flag_wait(FLAG_KV, ep * 128);
      fence_async_all();
      if (lane == 0) TS(0, 11);
#pragma unroll 1
      for (int m = 0; m < 2; m++) {
        mbar_wait(m == 0 ? BAR_EMPTY(2) : BAR_EMPTY(0), 1 - m);
        if (elect_one()) {
          const uint32_t fb = m == 0 ? BAR_KV(0) : BAR_VB(0);
          mbar_expect_tx(fb, 2 * 7 * STEPK * 16);
#pragma unroll
          for (int p = 0; p < 2; p++) bulk_g2s(sb + m * OFF_V + p * 32768, g_KV + (m * 2 + p) * S_TOK, 7 * STEPK * 16, fb);
        }
      }
      mbar_wait(BAR_Q, 0);
      if (elect_one()) {
#pragma unroll
        for (int c = 1; c < 3; c++) {
          const int k0 = c == 1 ? 7 * STEPK : 12 * STEPK, k1 = c == 1 ? 12 * STEPK : S_TOK;
          const uint32_t bytes = (k1 - k0) * 16;
          mbar_expect_tx(BAR_KV(c), 4 * bytes);
#pragma unroll
          for (int p = 0; p < 4; p++)
            bulk_g2s(sb + (p >> 1) * OFF_V + (p & 1) * 32768 + k0 * 16, g_KV + p * S_TOK + k0, bytes, BAR_KV(c));
        }
      }
      mbar_wait(BAR_CL(1), 0);
      flag_wait(FLAG_LM((lane & 7) * 2 + (tbA >> 4)), ep);
      __syncwarp();
      fence_async_all();
      if (lane == 0) TS(2, 13);
#pragma unroll 1
      for (int n = 0; n < 8; n++) {
        mbar_wait(BAR_CL(n < 4 ? n >> 1 : (n == 4 ? 2 : (n < 7 ? 3 : 4))), 0);
        const uint32_t sl = tail_slots(n), fb = BAR_TF(n);
        if (elect_one()) {
          mbar_expect_tx(fb, 24576);
          tma2d(sb + (sl & 255) * 8192, &mO, n * 64, S_TOK + tbA * 64, fb);
          tma2d(sb + ((sl >> 8) & 255) * 8192, &mWoB, hg * 128, n * 64, fb);
          tma2d(sb + (sl >> 16) * 8192, &mWoB, hg * 128 + 64, n * 64, fb);
        }
      }
      if (lane == 0) g_epoch[blockIdx.x] = ep;
    } else if (w4 == 3) {
      flag_wait(FLAG_KV, ep * 128);
      const uint4 a = *(const uint4*)(g_stats + lane * 4);
      const float kmax2 = __uint_as_float(__reduce_max_sync(~0u, a.x)) + __uint_as_float(__reduce_max_sync(~0u, a.y));
      const float vmax = __uint_as_float(__reduce_max_sync(~0u, max(a.z, a.w)));
      const float lv = vmax > 0.f ? __log2f(vmax) : 0.f;
      const float lim = fminf(90.f, fminf(91.f + lv, 95.f - lv));
      float thr = -1.f;
      if (vmax < 1e27f && kmax2 <= 65536.f && lim > 2.f) thr = fminf(60000.f, (lim * lim - 1.f) / (kmax2 * 1.02f + 1e-30f));
      if (lane == 0) { sts1(sM + 16, __float_as_uint(thr)); mbar_arrive(BAR_Q2); }
      mbar_wait(BAR_CL(3), 0);
      flag_wait(FLAG_OA(tbA * 4 + (lane & 3), 0), ep);
      __syncwarp();
      fence_async_all();
#pragma unroll 1
      for (int n = 0; n < 8; n++) {
        mbar_wait(n == 7 ? BAR_CL(4) : BAR_TE(n), 0);
        const uint32_t sl = tail_slots(n == 7 ? 8 : n), fb = BAR_TF(n + 8);
        const int k0 = n < 4 ? n * 128 : ((hg + n + 1) & 3) * 128 + 64;
        if (elect_one()) {
          mbar_expect_tx(fb, n < 4 ? 24576 : 16384);
          if (n < 4) tma2d(sb + (sl & 255) * 8192, &mO, k0, tbA * 64, fb);
          tma2d(sb + ((sl >> 8) & 255) * 8192, &mWoA, hg * 128, k0, fb);
          tma2d(sb + (sl >> 16) * 8192, &mWoA, hg * 128 + 64, k0, fb);
        }
      }
    } else {
      const int tok = (w4 - 1) * 32 + lane;
      int step, col;
      if ((tbA & 3) == 0) {
        const int b8 = tbA >> 2;
        if (tok < 22) { step = tok; col = 24 + b8; }
        else { const int c = tok >= 43; step = tok - 22 - 21 * c; col = 32 + b8 * 2 + c; }
      } else {
        const int b24 = (tbA >> 2) * 3 + (tbA & 3) - 1;
        if (tok < 42) { const int c = tok >= 21; step = tok - 21 * c; col = 48 + b24 * 2 + c; }
        else { step = tok - 42; col = b24; }
      }
      const int kap = step * STEPK + col;
      const bool chained = col >= 24;
      uint32_t v[4], o[4];
      lds4(sT + tok * 16, v);
      g_KV[(4 + hg) * S_TOK + kap] = make_uint4(v[0], v[1], v[2], v[3]);
      float st = 0.f;
      if (hg < 2) {
        o[0] = o[1] = o[2] = o[3] = 0;
        if (chained && step > 0) lds4(sT + tok * 16 - 16, o);
        const float sc = chained ? 2.f : 1.f;
#pragma unroll
        for (int u = 0; u < 4; u++) {
          const float x = bf_lo(v[u]), y = bf_hi(v[u]);
          st += x * x + y * y;
          o[u] = pack_f16((x - bf_lo(o[u])) * sc, (y - bf_hi(o[u])) * sc);
        }
      } else {
        const float sc = chained ? VSHIFT : 1.f;
#pragma unroll
        for (int u = 0; u < 4; u++) { float x = bf_lo(v[u]), y = bf_hi(v[u]); st += fabsf(x) + fabsf(y); o[u] = pack_bf16(x * sc, y * sc); }
      }
      g_KV[hg * S_TOK + kap] = make_uint4(o[0], o[1], o[2], o[3]);
      const uint32_t um = __reduce_max_sync(~0u, __float_as_uint(st) & 0x7FFFFFFFu);
      if (w4 == 2) {
        if (lane == 0) sts1(sM + 24, um);
        named_arrive(10, 64);
        mbar_wait(BAR_TE(4), 0);
        uint32_t pend = 7;
        const int li = lane < 3 ? lane : 0;
        const uint32_t* fl = FLAG_OA(tbA * 4 + ((hg + li + 1) & 3), 1);
#pragma unroll 1
        for (int it = 0; pend; it++) {
          uint32_t fv;
          asm volatile("ld.acquire.gpu.global.u32 %0, [%1];" : "=r"(fv) : "l"(fl) : "memory");
          const uint32_t go = __ballot_sync(~0u, (int32_t)(fv - ep) >= 0 && mbar_test(BAR_TE(4 + li), 0)) & pend;
          if (go) {
            fence_async_all();
            if (elect_one()) {
#pragma unroll
              for (int n = 0; n < 3; n++)
                if ((go >> n) & 1) {
                  mbar_expect_tx(BAR_TF(12 + n), 8192);
                  tma2d(sb + (tail_slots(4 + n) & 255) * 8192, &mO, ((hg + n + 1) & 3) * 128 + 64, tbA * 64, BAR_TF(12 + n));
                }
            }
            pend &= ~go;
          }
          if (it > 2000000) __trap();
        }
        if (lane == 0) TS(2, 14);
      }
      else {
        named_bar(10, 64);
        if (elect_one()) {
          g_stats[tbA * 4 + hg] = max(um, lds1(sM + 24));
          fence_async_all();
          flag_add(FLAG_KV);
          TS(1, 9);
          mbar_wait(BAR_BDONE, 0);
          tma2d_store(&mQst, sb + OFF_F + 49152, hq * 64, S_TOK + ttB * 128);
          bulk_commit();
          bulk_wait_all();
          fence_async_all();
          flag_add(FLAG_B(hq >> 1));
          TS(0, 12);
          mbar_wait(BAR_Q, 0);
          mbar_arrive(BAR_CL(0));
#pragma unroll 1
          for (int p = 0; p < 2; p++) {
            mbar_wait(BAR_OD(p), 0);
            if (p == 0) {
#pragma unroll
              for (int w = 0; w < 4; w++) tma2d_store(&mO16, sb + OFF_F + w * 2048, hg * 128 + w * 16, tbA * 64);
            } else {
              tma2d_store(&mO, sb + 26 * 8192, hg * 128 + 64, tbA * 64);
            }
            bulk_commit();
            bulk_wait_all();
            if (p == 0) mbar_arrive(BAR_CL(1));
            PUBLISH(FLAG_OA(blockIdx.x, p));
          }
          TS(2, 0);
        }
      }
    }
    return;
  }
  if (helper) { helper_cta(blockIdx.x - 128, sb, bars, wg, w4, &mQst, &mOst); return; }

  {
    float acc[64];
    if (wg == 0) proj_loop<0>(acc, sb, bars, 16384, 0, wg, sWKV);
    else proj_loop<1>(acc, sb, bars, 16384 + wg * 8192, 49152, wg, sWKV);
    if (tid == 0) TS(0, 10);
    const uint32_t sF = sb + OFF_F;
    const uint32_t qa = sF + w4 * 512 + ((lane >> 3) & 1) * 256 + (lane >> 4) * 128 + (lane & 7) * 16;
    if (wg == 0) {
#pragma unroll
      for (int hd = 0; hd < 4; hd++)
        stsm4(qa + hd * 2048, pack_f16(acc[8 * hd] * QSCALE, acc[8 * hd + 1] * QSCALE), pack_f16(acc[8 * hd + 2] * QSCALE, acc[8 * hd + 3] * QSCALE),
              pack_f16(acc[8 * hd + 4] * QSCALE, acc[8 * hd + 5] * QSCALE), pack_f16(acc[8 * hd + 6] * QSCALE, acc[8 * hd + 7] * QSCALE));
      fence_async();
      __syncwarp();
      if (lane == 0) mbar_arrive(BAR_Q);
    } else {
      if (wg != 3) named_arrive(6, 384);
      if (wg != 1) named_arrive(8, 384);
    }
    asm volatile("setmaxnreg.inc.sync.aligned.u32 112;");
    fence_regs<64>(acc);
    if (wg == 0) {
      uint32_t r[32];
#pragma unroll
      for (int hd = 0; hd < 8; hd++) {
#pragma unroll
        for (int i = 0; i < 4; i++) r[4 * hd + i] = pack_f16(acc[8 * hd + 2 * i] * QSCALE, acc[8 * hd + 2 * i + 1] * QSCALE);
        if (hd >= 4) stsm4(qa + hd * 2048, r[4 * hd], r[4 * hd + 1], r[4 * hd + 2], r[4 * hd + 3]);
      }
      fence_async();
      uint32_t nmax = 0;
#pragma unroll
      for (int hd = 0; hd < 8; hd++) {
        const uint32_t* q = r + 4 * hd;
        const uint32_t t0 = hfma2(q[2], q[2], hfma2(q[0], q[0], 0u)), t1 = hfma2(q[3], q[3], hfma2(q[1], q[1], 0u));
        uint32_t n = hadd2(__byte_perm(t0, t1, 0x5410), __byte_perm(t0, t1, 0x7632));
        n = hadd2(n, __shfl_xor_sync(~0u, n, 1));
        n = hadd2(n, __shfl_xor_sync(~0u, n, 2));
        nmax = __vmaxu2(nmax, n & 0x7FFF7FFFu);
      }
      nmax = __reduce_max_sync(~0u, max(nmax & 0xFFFFu, nmax >> 16));
      if (lane == 0) sts1(sM + w4 * 4, nmax);
      uint4* gq = (uint4*)g_Q + blockIdx.x * 1024 + tid;
#pragma unroll
      for (int hd = 0; hd < 8; hd++)
        gq[hd * 128] = make_uint4(pack_bf16(acc[8 * hd], acc[8 * hd + 1]), pack_bf16(acc[8 * hd + 2], acc[8 * hd + 3]),
                                  pack_bf16(acc[8 * hd + 4], acc[8 * hd + 5]), pack_bf16(acc[8 * hd + 6], acc[8 * hd + 7]));
      __syncwarp();
      if (lane == 0) mbar_arrive(BAR_Q2);
    } else if (wg == 3) {
      named_bar(6, 384);
      const int t = tid & 127;
#pragma unroll
      for (int j = 0; j < 8; j++)
        sts4(sF + 24576 + j * 2048 + t * 16, pack_bf16(acc[8 * j], acc[8 * j + 1]), pack_bf16(acc[8 * j + 2], acc[8 * j + 3]),
             pack_bf16(acc[8 * j + 4], acc[8 * j + 5]), pack_bf16(acc[8 * j + 6], acc[8 * j + 7]));
      named_arrive(7, 256);
    } else {
      uint32_t p[32];
#pragma unroll
      for (int i = 0; i < 32; i++) p[i] = phi2(acc[2 * i], acc[2 * i + 1]);
      if (wg == 1) {
        named_bar(8, 384);
        const int m = lane >> 3, r = lane & 7;
#pragma unroll
        for (int j = 0; j < 16; j += 2) {
          const int tok = (j + (m >> 1)) * 8 + r;
          const int chunk = w4 * 2 + (m & 1);
          stsm4t(sF + 49152 + tok * 128 + ((chunk ^ r) << 4), p[2 * j], p[2 * j + 1], p[2 * j + 2], p[2 * j + 3]);
        }
        fence_async();
      } else {
        named_bar(7, 256);
        float kv0[4] = {0, 0, 0, 0}, kv1[4] = {0, 0, 0, 0}, z0[4] = {0, 0, 0, 0}, z1[4] = {0, 0, 0, 0};
        const uint32_t one = 0x3F803F80u;
        const int t = tid & 127;
#pragma unroll
        for (int j = 0; j < 8; j++) {
          uint32_t a[4];
          lds4(sF + 24576 + j * 2048 + t * 16, a);
          mma_bf16(kv0, a[0], a[1], a[2], a[3], p[4 * j], p[4 * j + 2]);
          mma_bf16(kv1, a[0], a[1], a[2], a[3], p[4 * j + 1], p[4 * j + 3]);
          mma_bf16(z0, one, one, one, one, p[4 * j], p[4 * j + 2]);
          mma_bf16(z1, one, one, one, one, p[4 * j + 1], p[4 * j + 3]);
        }
        float4* dst = g_kvp + ((ttB * 32 + hq * 4 + w4) * 3) * 32 + lane;
        dst[0] = make_float4(kv0[0], kv0[1], kv1[0], kv1[1]);
        dst[32] = make_float4(kv0[2], kv0[3], kv1[2], kv1[3]);
        dst[64] = make_float4(z0[0], z0[1], z1[0], z1[1]);
      }
      __syncwarp();
      if (lane == 0) mbar_arrive(BAR_BDONE);
    }
  }

  bool safe = true;
  {
    const uint32_t c63 = 0x1F801F80u + (threadIdx.x >> 20);
    const uint32_t m1 = (gridDim.x >> 20) - 1u;
    const uint64_t dK0 = make_desc(sb + OFF_K, 32768, 128, 0);
    const uint64_t dV0 = make_desc(sb + OFF_V, 128, 32768, 0);
    constexpr uint32_t dKV = ((2048u - 8u)  __H0__ ) + STEPK - (OFF_V - OFF_K) / 16;
    float Sm[12], Sp[36], O[12];
    uint32_t P[24];
    uint64_t dQ = make_desc(sb + OFF_F + wg * 2048, 128, 256, 0);
#pragma unroll
    for (int i = 0; i < 36; i++) Sp[i] = SMAGIC;
#pragma unroll
    for (int i = 0; i < 12; i++) Sm[i] = 0.f;
    fence_regs<12>(Sm); fence_regs<36>(Sp);
    mbar_wait(BAR_Q, 0);
    mbar_wait(BAR_KV(0), 0);
    wg_fence();
    wg_qs72<1>(Sp, dQ, dK0 + 24);
    wg_qs24<0>(Sm, dQ, dK0);
    wg_commit();
    wg_wait<0>();
    fence_regs<12>(Sm); fence_regs<36>(Sp);
#pragma unroll 1
    for (int pass = 0; pass < 2; pass++) {
#pragma unroll
      for (int i = 0; i < 12; i++) O[i] = 0.f;
      fence_regs<12>(O);
      if (tid == 0) TS(1, 2 + 2 * pass);
      uint32_t vlo = (uint32_t)dV0;
#pragma unroll 1
      for (int seg = 0; seg < 4; seg++) {
        if (pass == 0) {
          if (seg < 3) mbar_wait(seg == 0 ? BAR_VB(0) : BAR_KV(seg), 0);
        } else if (seg >= 1) {
          if ((tid & 127) == 0) {
            mbar_arrive(BAR_CL(seg));
            if (seg == 3) take_role(sM, wg);
          }
          __syncwarp();
        }
        if ((tid & 127) == 0) TS(4 + wg, pass * 5 + seg);
        const uint32_t vend = vlo + (seg == 0 ? 6 : 5) * STEPK;
#pragma unroll 1
        for (; vlo != vend; vlo += STEPK) {
          uint64_t dK, dV;
          asm("mov.b64 %0, {%1, %2};" : "=l"(dK) : "r"(vlo + dKV), "r"(8u));
          asm("mov.b64 %0, {%1, %2};" : "=l"(dV) : "r"(vlo), "r"(2048u));
#pragma unroll
          for (int i = 0; i < 6; i++) P[i] = pack_bf16(ex2f(Sm[2 * i]), ex2f(Sm[2 * i + 1]));
#pragma unroll
          for (int i = 0; i < 18; i++) P[6 + i] = exp2_pair_fix(Sp[2 * i], Sp[2 * i + 1], c63, m1);
          fence_regs<24>(P);
          wg_fence();
#pragma unroll
          for (int k = 0; k < 6; k++) wg_pv24<1>(O, &P[4 * k], dV + k * 16);
          wg_qs72<1>(Sp, dQ, dK + 24);
          wg_qs24<0>(Sm, dQ, dK);
          wg_commit();
          wg_wait<0>();
          fence_regs<12>(Sm); fence_regs<36>(Sp); fence_regs<12>(O); fence_regs<24>(P);
        }
      }
#pragma unroll
      for (int i = 0; i < 6; i++) P[i] = pack_bf16(ex2f(Sm[2 * i]), ex2f(Sm[2 * i + 1]));
      P[6] = exp2_pair_fix(Sp[0], Sp[1], c63, m1);
      P[7] = exp2_pair_fix(Sp[2], Sp[3], c63, m1);
      fence_regs<8>(P);
#pragma unroll
      for (int i = 0; i < 36; i++) Sp[i] = SMAGIC;
      fence_regs<36>(Sp);
      mbar_wait(pass == 0 ? BAR_Q2 : BAR_CL(3), 0);
      const uint32_t sO = pass == 0 ? sb + OFF_F + wg * 2048 + w4 * 512 + (lane & 15) * 32 + (lane >> 4) * 16
                                    : sb + 26 * 8192 + (w4 * 16 + (lane & 15)) * 128 + (((wg * 2 + (lane >> 4)) ^ (lane & 7)) << 4);
      dQ += 512;
      wg_fence();
      wg_pv24<1>(O, &P[0], dV0 + 21 * STEPK);
      wg_pv24<1>(O, &P[4], dV0 + 21 * STEPK + 16);
      wg_commit();
      wg_qs72<1>(Sp, dQ, dK0 + 24);
      wg_qs24<0>(Sm, dQ, dK0);
      wg_commit();
      wg_wait<1>();
      fence_regs<12>(O);
      const float l0 = __shfl_sync(~0u, O[8], lane & ~3), l1 = __shfl_sync(~0u, O[10], lane & ~3);
      const float i0 = rcpf(l0), i1 = rcpf(l1);
      stsm4(sO,
            pack_bf16(O[0] * i0, O[1] * i0), pack_bf16(O[2] * i1, O[3] * i1),
            pack_bf16(O[4] * i0, O[5] * i0), pack_bf16(O[6] * i1, O[7] * i1));
      fence_async();
      {
        uint32_t n[4];
        lds4(sM, n);
        const float qn = __half2float(__ushort_as_half((unsigned short)max(max(n[0], n[1]), max(n[2], n[3]))));
        safe = __all_sync(~0u, qn <= __uint_as_float(lds1(sM + 16)));
      }
      if (safe && lane == 0) mbar_arrive(BAR_OD(pass));
      wg_wait<0>();
      fence_regs<12>(Sm); fence_regs<36>(Sp);
      if (!safe) break;
      if ((tid & 127) == 0) TS(4 + wg, pass * 5 + 4);
      if (tid == 0) TS(1, 3 + 2 * pass);
    }
  }
  if (!safe) {
    if ((tid & 127) == 0) { mbar_arrive(BAR_CL(1)); mbar_arrive(BAR_CL(2)); mbar_arrive(BAR_CL(3)); take_role(sM, wg); }
#pragma unroll 1
    for (int pass = 0; pass < 2; pass++) {
      const int t = tid & 127;
      mbar_wait(BAR_CL(3), 0);
      attn_slow((const uint4*)g_Q + blockIdx.x * 1024 + (pass * 4 + wg) * 128,
                pass == 0 ? sb + OFF_F + wg * 2048 + t * 16
                          : sb + 26 * 8192 + (t >> 1) * 128 + (((wg * 2 + (t & 1)) ^ ((t >> 1) & 7)) << 4));
      __syncwarp();
      if (lane == 0) mbar_arrive(BAR_OD(pass));
    }
  }

  {
    named_bar(wg + 1, 128);
    if ((tid & 127) == 0) mbar_arrive(BAR_CL(4));
    const int role = __shfl_sync(~0u, lds1(sM + 32 + wg * 4), 0);
    if ((tid & 127) == 0) TS(4 + wg, 10);
    const int m = lane >> 3, r = lane & 7;
    const uint32_t stoff = (w4 * 16 + (m & 1) * 8 + r) * 128;
    if (role == 0) {
      float acc[64];
      uint32_t sl = 0;
#pragma unroll 1
      for (int n = 0; n < 8; n++) {
        sl = tail_slots(n);
        const uint32_t w0 = (sl >> 8) & 255, w1 = sl >> 16;
        const uint64_t da = make_desc(sb + (sl & 255) * 8192, 16, 1024, 1), db = make_desc(sb + w0 * 8192, (w1 - w0) * 8192, 1024, 1);
        mbar_wait(BAR_TF(n), 0);
        wg_fence();
#pragma unroll
        for (int k = 0; k < 4; k++) wg_ss128<0, 1>(acc, da + k * 2, db + k * 128, (n | k) != 0);
        wg_commit();
        if (n == 6) wg_wait<0>(); else wg_wait<1>();
        if ((tid & 127) == 0) {
          if (n >= 1 && n < 7) mbar_arrive(BAR_TE(n - 1));
          if (n == 6) mbar_arrive(BAR_TE(6));
        }
        __syncwarp();
      }
      wg_wait<0>();
      fence_regs<64>(acc);
      if ((tid & 127) == 0) TS(4 + wg, 11);
      named_bar(wg + 1, 128);
      const uint32_t x0 = sb + ((sl >> 8) & 255) * 8192, x1 = sb + (sl >> 16) * 8192;
#pragma unroll
      for (int j = 0; j < 16; j += 2)
        stsm4((j < 8 ? x0 : x1) + stoff + ((((j & 7) + (m >> 1)) ^ r) << 4),
              pack_bf16(acc[4 * j], acc[4 * j + 1]), pack_bf16(acc[4 * j + 2], acc[4 * j + 3]),
              pack_bf16(acc[4 * j + 4], acc[4 * j + 5]), pack_bf16(acc[4 * j + 6], acc[4 * j + 7]));
      fence_async();
      named_bar(wg + 1, 128);
      if (w4 == 0 && elect_one()) {
        tma2d_store(&mOut, x0, 512 + hg * 128, tbA * 64);
        tma2d_store(&mOut, x1, 512 + hg * 128 + 64, tbA * 64);
        bulk_commit();
        asm volatile("cp.async.bulk.wait_group.read 0;" ::: "memory");
        TS(2, 11);
      }
    } else if (role < 3) {
      float acc[32];
#pragma unroll 1
      for (int n = 0; n < 8; n++) {
        const uint32_t sl = tail_slots(n == 7 ? 8 : n);
        const uint64_t da = make_desc(sb + (sl & 255) * 8192, 16, 1024, 1);
        const uint64_t db = make_desc(sb + ((sl >> (8 * role)) & 255) * 8192, 8192, 1024, 1);
        mbar_wait(BAR_TF(8 + n), 0);
        if (n == 7) mbar_wait(BAR_OD(1), 0);
        if ((tid & 127) == 0 && role == 1) TS(2, 2 + n);
        wg_fence();
#pragma unroll
        for (int k = 0; k < 4; k++) wg_ss64<0, 1>(acc, da + k * 2, db + k * 128, (n | k) != 0);
        wg_commit();
        wg_wait<2>();
      }
      wg_wait<0>();
      fence_regs<32>(acc);
      if ((tid & 127) == 0) TS(4 + wg, 11);
      const uint32_t xs = sb + ((tail_slots(0) >> (8 * role)) & 255) * 8192;
#pragma unroll
      for (int j = 0; j < 8; j += 2)
        stsm4(xs + stoff + (((j + (m >> 1)) ^ r) << 4),
              pack_bf16(acc[4 * j], acc[4 * j + 1]), pack_bf16(acc[4 * j + 2], acc[4 * j + 3]),
              pack_bf16(acc[4 * j + 4], acc[4 * j + 5]), pack_bf16(acc[4 * j + 6], acc[4 * j + 7]));
      fence_async();
      named_bar(wg + 1, 128);
      if (w4 == 0 && elect_one()) {
        tma2d_store(&mOut, xs, hg * 128 + (role - 1) * 64, tbA * 64);
        bulk_commit();
        asm volatile("cp.async.bulk.wait_group.read 0;" ::: "memory");
        TS(2, 12);
      }
    }
  }
}

typedef CUresult (*EncodeFn)(CUtensorMap*, CUtensorMapDataType, cuuint32_t, void*, const cuuint64_t*, const cuuint64_t*,
                             const cuuint32_t*, const cuuint32_t*, CUtensorMapInterleave, CUtensorMapSwizzle,
                             CUtensorMapL2promotion, CUtensorMapFloatOOBfill);

static void make_map(EncodeFn enc, CUtensorMap* m, const void* ptr, uint64_t cols, uint64_t rows, uint32_t bc, uint32_t br,
                     CUtensorMapSwizzle sw = CU_TENSOR_MAP_SWIZZLE_128B) {
  cuuint64_t dims[2] = {cols, rows};
  cuuint64_t strides[1] = {cols * 2};
  cuuint32_t box[2] = {bc, br};
  cuuint32_t es[2] = {1, 1};
  enc(m, CU_TENSOR_MAP_DATA_TYPE_BFLOAT16, 2, (void*)ptr, dims, strides, box, es, CU_TENSOR_MAP_INTERLEAVE_NONE,
      sw, CU_TENSOR_MAP_L2_PROMOTION_L2_256B, CU_TENSOR_MAP_FLOAT_OOB_FILL_NONE);
}

extern "C" void kernel_launch(void* const* d_in, const int* in_sizes, int n_in, void* d_out, int out_size) {
  (void)in_sizes; (void)n_in; (void)out_size;
  static EncodeFn enc = nullptr;
  static void* pQ = nullptr; static void* pO = nullptr;
  if (!enc) {
    void* fn = nullptr; cudaDriverEntryPointQueryResult qr;
    cudaGetDriverEntryPoint("cuTensorMapEncodeTiled", &fn, cudaEnableDefault, &qr);
    enc = (EncodeFn)fn;
    cudaGetSymbolAddress(&pQ, g_Q);
    cudaGetSymbolAddress(&pO, g_O);
    cudaFuncSetAttribute(k1_main, cudaFuncAttributeMaxDynamicSharedMemorySize, SM_TOTAL);
  }
  CUtensorMap mXA64, mXB, mWq, mWqkv, mQst, mO, mOst, mWoA, mWoB, mOut, mO16;
  make_map(enc, &mXA64, d_in[0], 512, 2048, 64, 64);
  make_map(enc, &mWq, d_in[1], 512, 512, 64, 64);
  make_map(enc, &mWoA, d_in[4], 512, 512, 64, 64);
  make_map(enc, &mXB, d_in[5], 512, 2048, 64, 128);
  make_map(enc, &mWqkv, d_in[6], 1536, 512, 64, 64);
  make_map(enc, &mWoB, d_in[7], 512, 512, 64, 64);
  make_map(enc, &mQst, pQ, 512, 4096, 64, 128);
  make_map(enc, &mO, pO, 512, 4096, 64, 64);
  make_map(enc, &mOst, pO, 512, 4096, 64, 128);
  make_map(enc, &mOut, d_out, 1024, 2048, 64, 64);
  make_map(enc, &mO16, pO, 512, 4096, 16, 64, CU_TENSOR_MAP_SWIZZLE_NONE);
  Params prm{(const __nv_bfloat16*)d_in[2], (const __nv_bfloat16*)d_in[3], (const __nv_bfloat16*)d_in[0]};
  k1_main<<<132, 640, SM_TOTAL, cudaStreamPerThread>>>(mXA64, mXB, mWq, mWqkv, mQst, mOst, mO, mWoA, mWoB, mOut, mO16, prm);
}
```

```cpp
#include <cuda_runtime.h>
#include <cuda_bf16.h>
#include <cuda_fp16.h>
#include <cuda.h>
#include <stdint.h>

#define S_TOK 2048
#define D_MOD 512

__device__ __align__(1024) __nv_bfloat16 g_Q[2 * S_TOK * D_MOD];
__device__ __align__(1024) __nv_bfloat16 g_O[2 * S_TOK * D_MOD];
__device__ __align__(1024) uint4 g_KV[8 * S_TOK];
__device__ __align__(16) uint32_t g_stats[128];
__device__ __align__(16) float4 g_kvp[16 * 32 * 3 * 32];

#define TS(k, i) do {} while (0)
__device__ __forceinline__ uint32_t smem_u32(const void* p) { return (uint32_t)__cvta_generic_to_shared(p); }
__device__ __forceinline__ void mbar_init(uint32_t bar, int cnt) { asm volatile("mbarrier.init.shared::cta.b64 [%0], %1;" :: "r"(bar), "r"(cnt) : "memory"); }
__device__ __forceinline__ void mbar_expect_tx(uint32_t bar, uint32_t bytes) { asm volatile("mbarrier.arrive.expect_tx.shared::cta.b64 _, [%0], %1;" :: "r"(bar), "r"(bytes) : "memory"); }
__device__ __forceinline__ bool mbar_try(uint32_t bar, uint32_t parity) {
  uint32_t ok;
  asm volatile("{\n.reg .pred p;\nmbarrier.try_wait.parity.shared::cta.b64 p, [%1], %2;\nselp.b32 %0, 1, 0, p;\n}\n" : "=r"(ok) : "r"(bar), "r"(parity) : "memory");
  return ok;
}
__device__ __forceinline__ void mbar_wait(uint32_t bar, uint32_t parity) {
  asm volatile("{\n.reg .pred p;\n.reg .u32 c;\nmov.u32 c, 0;\n"
               "LW_%=:\n"
               "mbarrier.try_wait.parity.shared::cta.b64 p, [%0], %1;\n"
               "@p bra LD_%=;\n"
               "add.u32 c, c, 1;\n"
               "setp.lt.u32 p, c, 4000000;\n"
               "@p bra LW_%=;\n"
               "trap;\n"
               "LD_%=:\n}\n" :: "r"(bar), "r"(parity) : "memory");
}
__device__ __forceinline__ void mbar_arrive_cta(uint32_t bar, uint32_t cta) {
  asm volatile("{\n.reg .b32 ra;\nmapa.shared::cluster.u32 ra, %0, %1;\nmbarrier.arrive.shared::cluster.b64 _, [ra];\n}\n" :: "r"(bar), "r"(cta) : "memory");
}
__device__ __forceinline__ void cluster_sync() {
  asm volatile("barrier.cluster.arrive.relaxed.aligned;\nbarrier.cluster.wait.aligned;" ::: "memory");
}
__device__ __forceinline__ void tma2d(uint32_t dst, const CUtensorMap* m, int c0, int c1, uint32_t bar) {
  asm volatile("cp.async.bulk.tensor.2d.shared::cluster.global.mbarrier::complete_tx::bytes [%0], [%1, {%3, %4}], [%2];"
               :: "r"(dst), "l"(m), "r"(bar), "r"(c0), "r"(c1) : "memory");
}
__device__ __forceinline__ void tma2d_mc(uint32_t dst, const CUtensorMap* m, int c0, int c1, uint32_t bar, uint16_t mask) {
  asm volatile("cp.async.bulk.tensor.2d.shared::cluster.global.mbarrier::complete_tx::bytes.multicast::cluster [%0], [%1, {%3, %4}], [%2], %5;"
               :: "r"(dst), "l"(m), "r"(bar), "r"(c0), "r"(c1), "h"(mask) : "memory");
}
__device__ __forceinline__ void tma2d_store(const CUtensorMap* m, uint32_t src, int c0, int c1) {
  asm volatile("cp.async.bulk.tensor.2d.global.shared::cta.bulk_group [%0, {%2, %3}], [%1];"
               :: "l"(m), "r"(src), "r"(c0), "r"(c1) : "memory");
}
__device__ __forceinline__ void bulk_g2s(uint32_t dst, const void* src, uint32_t bytes, uint32_t bar) {
  asm volatile("cp.async.bulk.shared::cluster.global.mbarrier::complete_tx::bytes [%0], [%1], %2, [%3];"
               :: "r"(dst), "l"(src), "r"(bytes), "r"(bar) : "memory");
}
__device__ __forceinline__ void bulk_commit() { asm volatile("cp.async.bulk.commit_group;" ::: "memory"); }
__device__ __forceinline__ void bulk_wait_all() { asm volatile("cp.async.bulk.wait_group 0;" ::: "memory"); }
__device__ __forceinline__ void fence_async() { asm volatile("fence.proxy.async.shared::cta;" ::: "memory"); }
__device__ __forceinline__ void named_bar(int id, int n) { asm volatile("bar.sync %0, %1;" :: "r"(id), "r"(n) : "memory"); }
__device__ __forceinline__ void pdl_launch() { asm volatile("griddepcontrol.launch_dependents;" ::: "memory"); }
__device__ __forceinline__ void pdl_wait() { asm volatile("griddepcontrol.wait;" ::: "memory"); }
__device__ __forceinline__ void wg_fence() { asm volatile("wgmma.fence.sync.aligned;" ::: "memory"); }
__device__ __forceinline__ void wg_commit() { asm volatile("wgmma.commit_group.sync.aligned;" ::: "memory"); }
template <int n> __device__ __forceinline__ void wg_wait() { asm volatile("wgmma.wait_group.sync.aligned %0;" :: "n"(n) : "memory"); }
template <int n> __device__ __forceinline__ void fence_regs(float* r) {
#pragma unroll
  for (int i = 0; i < n; i++) asm volatile("" : "+f"(r[i]) :: "memory");
}
template <int n> __device__ __forceinline__ void fence_regs(uint32_t* r) {
#pragma unroll
  for (int i = 0; i < n; i++) asm volatile("" : "+r"(r[i]) :: "memory");
}
__device__ __forceinline__ uint64_t make_desc(uint32_t addr, uint32_t lbo, uint32_t sbo, uint32_t swz) {
  return (uint64_t)((addr & 0x3FFFF) >> 4) | ((uint64_t)(lbo >> 4) << 16) | ((uint64_t)(sbo >> 4) << 32) | ((uint64_t)swz << 62);
}
__device__ __forceinline__ float ex2f(float x) { float y; asm("ex2.approx.ftz.f32 %0, %1;" : "=f"(y) : "f"(x)); return y; }
__device__ __forceinline__ uint32_t pack_bf16(float lo, float hi) { uint32_t r; asm("cvt.rn.bf16x2.f32 %0, %1, %2;" : "=r"(r) : "f"(hi), "f"(lo)); return r; }
__device__ __forceinline__ uint32_t pack_f16(float lo, float hi) { uint32_t r; asm("cvt.rn.f16x2.f32 %0, %1, %2;" : "=r"(r) : "f"(hi), "f"(lo)); return r; }
__device__ __forceinline__ float bf_lo(uint32_t v) { return __uint_as_float(v << 16); }
__device__ __forceinline__ float bf_hi(uint32_t v) { return __uint_as_float(v & 0xFFFF0000u); }
__device__ __forceinline__ float rbf(float x) { return __bfloat162float(__float2bfloat16_rn(x)); }
__device__ __forceinline__ void stsm4(uint32_t a, uint32_t r0, uint32_t r1, uint32_t r2, uint32_t r3) {
  asm volatile("stmatrix.sync.aligned.m8n8.x4.shared.b16 [%0], {%1,%2,%3,%4};" :: "r"(a), "r"(r0), "r"(r1), "r"(r2), "r"(r3) : "memory");
}
__device__ __forceinline__ void stsm4t(uint32_t a, uint32_t r0, uint32_t r1, uint32_t r2, uint32_t r3) {
  asm volatile("stmatrix.sync.aligned.m8n8.x4.trans.shared.b16 [%0], {%1,%2,%3,%4};" :: "r"(a), "r"(r0), "r"(r1), "r"(r2), "r"(r3) : "memory");
}
__device__ __forceinline__ void mma_bf16(float* d, uint32_t a0, uint32_t a1, uint32_t a2, uint32_t a3, uint32_t b0, uint32_t b1) {
  asm volatile("mma.sync.aligned.m16n8k16.row.col.f32.bf16.bf16.f32 {%0,%1,%2,%3}, {%4,%5,%6,%7}, {%8,%9}, {%0,%1,%2,%3};"
               : "+f"(d[0]), "+f"(d[1]), "+f"(d[2]), "+f"(d[3]) : "r"(a0), "r"(a1), "r"(a2), "r"(a3), "r"(b0), "r"(b1));
}
template<int SD> __device__ __forceinline__ void wg_qs24(float* d, uint64_t da, uint64_t db) {
  asm volatile("wgmma.mma_async.sync.aligned.m64n24k16.f32.f16.f16 {%0,%1,%2,%3,%4,%5,%6,%7,%8,%9,%10,%11}, %12, %13, %14, 1, 1, 0, 0;"
   : "+f"(d[0]),"+f"(d[1]),"+f"(d[2]),"+f"(d[3]),"+f"(d[4]),"+f"(d[5]),"+f"(d[6]),"+f"(d[7]),"+f"(d[8]),"+f"(d[9]),"+f"(d[10]),"+f"(d[11])
   : "l"(da),"l"(db),"n"(SD));
}
template<int SD> __device__ __forceinline__ void wg_qs72(float* d, uint64_t da, uint64_t db) {
  asm volatile("wgmma.mma_async.sync.aligned.m64n72k16.f32.f16.f16 {%0,%1,%2,%3,%4,%5,%6,%7,%8,%9,%10,%11,%12,%13,%14,%15,%16,%17,%18,%19,%20,%21,%22,%23,%24,%25,%26,%27,%28,%29,%30,%31,%32,%33,%34,%35}, %36, %37, %38, 1, 1, 0, 0;"
   : "+f"(d[0]),"+f"(d[1]),"+f"(d[2]),"+f"(d[3]),"+f"(d[4]),"+f"(d[5]),"+f"(d[6]),"+f"(d[7]),"+f"(d[8]),"+f"(d[9]),"+f"(d[10]),"+f"(d[11]),"+f"(d[12]),"+f"(d[13]),"+f"(d[14]),"+f"(d[15]),"+f"(d[16]),"+f"(d[17]),"+f"(d[18]),"+f"(d[19]),"+f"(d[20]),"+f"(d[21]),"+f"(d[22]),"+f"(d[23]),"+f"(d[24]),"+f"(d[25]),"+f"(d[26]),"+f"(d[27]),"+f"(d[28]),"+f"(d[29]),"+f"(d[30]),"+f"(d[31]),"+f"(d[32]),"+f"(d[33]),"+f"(d[34]),"+f"(d[35])
   : "l"(da),"l"(db),"n"(SD));
}
template<int SD> __device__ __forceinline__ void wg_pv24(float* d, const uint32_t* a, uint64_t desc) {
  asm volatile("wgmma.mma_async.sync.aligned.m64n24k16.f32.bf16.bf16 {%0,%1,%2,%3,%4,%5,%6,%7,%8,%9,%10,%11}, {%12,%13,%14,%15}, %16, %17, 1, 1, 1;"
   : "+f"(d[0]),"+f"(d[1]),"+f"(d[2]),"+f"(d[3]),"+f"(d[4]),"+f"(d[5]),"+f"(d[6]),"+f"(d[7]),"+f"(d[8]),"+f"(d[9]),"+f"(d[10]),"+f"(d[11])
   : "r"(a[0]),"r"(a[1]),"r"(a[2]),"r"(a[3]),"l"(desc),"n"(SD));
}
template<int TA, int TB> __device__ __forceinline__ void wg_ss128(float* d, uint64_t da, uint64_t db, int sd) {
  asm volatile("{\n.reg .pred p;\nsetp.ne.b32 p, %66, 0;\n"
   "wgmma.mma_async.sync.aligned.m64n128k16.f32.bf16.bf16 {%0,%1,%2,%3,%4,%5,%6,%7,%8,%9,%10,%11,%12,%13,%14,%15,%16,%17,%18,%19,%20,%21,%22,%23,%24,%25,%26,%27,%28,%29,%30,%31,%32,%33,%34,%35,%36,%37,%38,%39,%40,%41,%42,%43,%44,%45,%46,%47,%48,%49,%50,%51,%52,%53,%54,%55,%56,%57,%58,%59,%60,%61,%62,%63}, %64, %65, p, 1, 1, %67, %68;\n}\n"
   : "+f"(d[0]),"+f"(d[1]),"+f"(d[2]),"+f"(d[3]),"+f"(d[4]),"+f"(d[5]),"+f"(d[6]),"+f"(d[7]),"+f"(d[8]),"+f"(d[9]),"+f"(d[10]),"+f"(d[11]),"+f"(d[12]),"+f"(d[13]),"+f"(d[14]),"+f"(d[15]),"+f"(d[16]),"+f"(d[17]),"+f"(d[18]),"+f"(d[19]),"+f"(d[20]),"+f"(d[21]),"+f"(d[22]),"+f"(d[23]),"+f"(d[24]),"+f"(d[25]),"+f"(d[26]),"+f"(d[27]),"+f"(d[28]),"+f"(d[29]),"+f"(d[30]),"+f"(d[31]),"+f"(d[32]),"+f"(d[33]),"+f"(d[34]),"+f"(d[35]),"+f"(d[36]),"+f"(d[37]),"+f"(d[38]),"+f"(d[39]),"+f"(d[40]),"+f"(d[41]),"+f"(d[42]),"+f"(d[43]),"+f"(d[44]),"+f"(d[45]),"+f"(d[46]),"+f"(d[47]),"+f"(d[48]),"+f"(d[49]),"+f"(d[50]),"+f"(d[51]),"+f"(d[52]),"+f"(d[53]),"+f"(d[54]),"+f"(d[55]),"+f"(d[56]),"+f"(d[57]),"+f"(d[58]),"+f"(d[59]),"+f"(d[60]),"+f"(d[61]),"+f"(d[62]),"+f"(d[63])
   : "l"(da),"l"(db),"r"(sd),"n"(TA),"n"(TB));
}
template<int TA, int TB> __device__ __forceinline__ void wg_ss64(float* d, uint64_t da, uint64_t db, int sd) {
  asm volatile("{\n.reg .pred p;\nsetp.ne.b32 p, %34, 0;\n"
   "wgmma.mma_async.sync.aligned.m64n64k16.f32.bf16.bf16 {%0,%1,%2,%3,%4,%5,%6,%7,%8,%9,%10,%11,%12,%13,%14,%15,%16,%17,%18,%19,%20,%21,%22,%23,%24,%25,%26,%27,%28,%29,%30,%31}, %32, %33, p, 1, 1, %35, %36;\n}\n"
   : "+f"(d[0]),"+f"(d[1]),"+f"(d[2]),"+f"(d[3]),"+f"(d[4]),"+f"(d[5]),"+f"(d[6]),"+f"(d[7]),"+f"(d[8]),"+f"(d[9]),"+f"(d[10]),"+f"(d[11]),"+f"(d[12]),"+f"(d[13]),"+f"(d[14]),"+f"(d[15]),"+f"(d[16]),"+f"(d[17]),"+f"(d[18]),"+f"(d[19]),"+f"(d[20]),"+f"(d[21]),"+f"(d[22]),"+f"(d[23]),"+f"(d[24]),"+f"(d[25]),"+f"(d[26]),"+f"(d[27]),"+f"(d[28]),"+f"(d[29]),"+f"(d[30]),"+f"(d[31])
   : "l"(da),"l"(db),"r"(sd),"n"(TA),"n"(TB));
}
template<int TA, int TB> __device__ __forceinline__ void wg_ss8(float* d, uint64_t da, uint64_t db, int sd) {
  asm volatile("{\n.reg .pred p;\nsetp.ne.b32 p, %6, 0;\n"
   "wgmma.mma_async.sync.aligned.m64n8k16.f32.bf16.bf16 {%0,%1,%2,%3}, %4, %5, p, 1, 1, %7, %8;\n}\n"
   : "+f"(d[0]),"+f"(d[1]),"+f"(d[2]),"+f"(d[3])
   : "l"(da),"l"(db),"r"(sd),"n"(TA),"n"(TB));
}

__device__ __forceinline__ uint32_t phi2(float a, float b) {
  uint32_t r, e;
  asm("cvt.rn.relu.bf16x2.f32 %0, %1, %2;" : "=r"(r) : "f"(b), "f"(a));
  e = pack_bf16(ex2f(a * 1.4426950408889634f), ex2f(b * 1.4426950408889634f));
  asm("add.rn.bf16x2 %0, %0, %1;" : "+r"(e) : "r"(0x35863586u));
  asm("min.NaN.bf16x2 %0, %0, %1;" : "+r"(e) : "r"(0x3F803F80u));
  asm("add.rn.bf16x2 %0, %0, %1;" : "+r"(e) : "r"(r));
  return e;
}

__device__ __forceinline__ void mbar_wait_long(uint32_t bar, uint32_t parity) {
  asm volatile("{\n.reg .pred p;\n.reg .u32 c;\nmov.u32 c, 0;\n"
               "LW_%=:\n"
               "mbarrier.try_wait.parity.shared::cta.b64 p, [%0], %1, 100000;\n"
               "@p bra LD_%=;\n"
               "add.u32 c, c, 1;\n"
               "setp.lt.u32 p, c, 20000;\n"
               "@p bra LW_%=;\n"
               "trap;\n"
               "LD_%=:\n}\n" :: "r"(bar), "r"(parity) : "memory");
}
__device__ __forceinline__ void mbar_arrive(uint32_t bar) { asm volatile("mbarrier.arrive.shared::cta.b64 _, [%0];" :: "r"(bar) : "memory"); }
__device__ __forceinline__ void named_arrive(int id, int n) { asm volatile("bar.arrive %0, %1;" :: "r"(id), "r"(n) : "memory"); }
__device__ __forceinline__ void fence_async_all() { asm volatile("fence.proxy.async.global;" ::: "memory"); }
__device__ __forceinline__ void flag_add(uint32_t* f) { asm volatile("fence.acq_rel.gpu;\nred.relaxed.gpu.global.add.u32 [%0], 1;" :: "l"(f) : "memory"); }
#define PUBLISH(f) asm volatile("fence.proxy.async.global;\nred.relaxed.gpu.global.add.u32 [%0], 1;" :: "l"(f) : "memory")
__device__ __forceinline__ void flag_wait(const uint32_t* f, uint32_t target) {
  uint32_t v;
#pragma unroll 1
  for (int it = 0;; it++) {
    asm volatile("ld.acquire.gpu.global.u32 %0, [%1];" : "=r"(v) : "l"(f) : "memory");
    if ((int32_t)(v - target) >= 0) break;
    if (it > 2000000) __trap();
    __nanosleep(64);
  }
}
__device__ __forceinline__ bool mbar_test(uint32_t bar, uint32_t parity) {
  uint32_t ok;
  asm volatile("{\n.reg .pred p;\nmbarrier.test_wait.parity.shared::cta.b64 p, [%1], %2;\nselp.b32 %0, 1, 0, p;\n}\n" : "=r"(ok) : "r"(bar), "r"(parity) : "memory");
  return ok;
}
__device__ __forceinline__ bool elect_one() {
  uint32_t p;
  asm volatile("{\n.reg .pred P;\nelect.sync _|P, 0xFFFFFFFF;\nselp.b32 %0, 1, 0, P;\n}\n" : "=r"(p));
  return p;
}
__device__ __forceinline__ void lds4(uint32_t a, uint32_t* r) {
  asm volatile("ld.shared.v4.b32 {%0,%1,%2,%3}, [%4];" : "=r"(r[0]), "=r"(r[1]), "=r"(r[2]), "=r"(r[3]) : "r"(a) : "memory");
}
__device__ __forceinline__ uint32_t lds1(uint32_t a) { uint32_t r; asm volatile("ld.shared.b32 %0, [%1];" : "=r"(r) : "r"(a) : "memory"); return r; }
__device__ __forceinline__ void sts1(uint32_t a, uint32_t v) { asm volatile("st.shared.b32 [%0], %1;" :: "r"(a), "r"(v) : "memory"); }
__device__ __forceinline__ void sts4(uint32_t a, uint32_t r0, uint32_t r1, uint32_t r2, uint32_t r3) {
  asm volatile("st.shared.v4.b32 [%0], {%1,%2,%3,%4};" :: "r"(a), "r"(r0), "r"(r1), "r"(r2), "r"(r3) : "memory");
}
__device__ __forceinline__ void ldsm4(uint32_t a, uint32_t* r) {
  asm volatile("ldmatrix.sync.aligned.m8n8.x4.shared.b16 {%0,%1,%2,%3}, [%4];" : "=r"(r[0]), "=r"(r[1]), "=r"(r[2]), "=r"(r[3]) : "r"(a) : "memory");
}
__device__ __forceinline__ float rcpf(float x) { float y; asm("rcp.approx.ftz.f32 %0, %1;" : "=f"(y) : "f"(x)); return y; }
__device__ __forceinline__ uint32_t hfma2(uint32_t a, uint32_t b, uint32_t c) { uint32_t r; asm("fma.rn.f16x2 %0, %1, %2, %3;" : "=r"(r) : "r"(a), "r"(b), "r"(c)); return r; }
__device__ __forceinline__ uint32_t hadd2(uint32_t a, uint32_t b) { uint32_t r; asm("add.rn.f16x2 %0, %1, %2;" : "=r"(r) : "r"(a), "r"(b)); return r; }

#define STEPK 96
#define QSCALE 0.36067376022224085f
#define SMAGIC (512.0f + 2.0f * (191.0f - 30.0f - 1.5823545f))
#define VSHIFT 1073741824.0f

__device__ uint32_t g_epoch[132];
__device__ uint32_t g_flag[288 * 8];
#define FLAG_KV (g_flag)
#define FLAG_B(h) (g_flag + (4 + (h)) * 8)
#define FLAG_OA(cta, pass) (g_flag + (16 + (cta) * 2 + (pass)) * 8)
#define FLAG_LM(i) (g_flag + (272 + (i)) * 8)

#define SM_TOTAL (224 * 1024 + 2048 + 1024)
#define OFF_K 0
#define OFF_F 65536
#define OFF_V 131072
#define OFF_MISC (224 * 1024)

#define BAR_FULL(s) (bars + 8 * (s))
#define BAR_EMPTY(s) (bars + 24 + 8 * (s))
#define BAR_KV(c) (bars + 48 + 8 * (c))
#define BAR_BDONE (bars + 80)
#define BAR_Q (bars + 88)
#define BAR_GO (bars + 96)
#define BAR_Q2 (bars + 104)
#define BAR_OD(p) (bars + 112 + 8 * (p))
#define BAR_CL(c) (bars + 128 + 8 * (c))
#define BAR_TE(i) (bars + 168 + 8 * (i))
#define BAR_TF(g) (bars + 224 + 8 * (g))
#define BAR_XA(w) (bars + 352 + 8 * (w))
#define BAR_VB(c) (bars + 384 + 8 * (c))

__device__ __forceinline__ uint32_t exp2_pair_fix(float d0, float d1, uint32_t c63, uint32_t m1) {
  uint32_t w, y, s, r;
  asm("prmt.b32 %0, %1, %2, 0x6521;" : "=r"(w) : "r"(__float_as_uint(d0)), "r"(__float_as_uint(d1)));
  asm("lop3.b32 %0, %1, 0x007F007F, %2, 0xEA;" : "=r"(y) : "r"(w), "r"(c63));
  asm("mad.lo.u32 %0, %1, %2, %3;" : "=r"(s) : "r"(y), "r"(m1), "r"(w));
  asm("fma.rn.bf16x2 %0, %1, %2, %3;" : "=r"(r) : "r"(w), "r"(y), "r"(s));
  return r;
}

__device__ __forceinline__ void attn_slow(const uint4* gq, uint32_t dst) {
  const int t = threadIdx.x & 127;
  const int row = t >> 1, half = t & 1;
  float q[16];
#pragma unroll
  for (int i = 0; i < 4; i++) {
    const uint4 v = gq[(row >> 4) * 32 + (row & 7) * 4 + i];
    const uint32_t lo = (row & 8) ? v.y : v.x, hi = (row & 8) ? v.w : v.z;
    q[2 * i] = bf_lo(lo); q[2 * i + 1] = bf_hi(lo); q[2 * i + 8] = bf_lo(hi); q[2 * i + 9] = bf_hi(hi);
  }
  float m = -INFINITY, l = 0.f, o[16];
#pragma unroll
  for (int i = 0; i < 16; i++) o[i] = 0.f;
#pragma unroll 1
  for (int j = half * 1024; j < half * 1024 + 1024; j++) {
    uint4 ka = g_KV[4 * S_TOK + j], kb = g_KV[5 * S_TOK + j];
    uint4 va = g_KV[6 * S_TOK + j], vb = g_KV[7 * S_TOK + j];
    uint32_t kk[8] = {ka.x, ka.y, ka.z, ka.w, kb.x, kb.y, kb.z, kb.w};
    uint32_t vv[8] = {va.x, va.y, va.z, va.w, vb.x, vb.y, vb.z, vb.w};
    float s = 0.f;
#pragma unroll
    for (int i = 0; i < 8; i++) { s = fmaf(q[2 * i], bf_lo(kk[i]), s); s = fmaf(q[2 * i + 1], bf_hi(kk[i]), s); }
    s = rbf(s) * 0.25f;
    if (s > m) {
      float c = __expf(m - s);
      l *= c;
#pragma unroll
      for (int i = 0; i < 16; i++) o[i] *= c;
      m = s;
    }
    float p = __expf(s - m);
    l += p;
#pragma unroll
    for (int i = 0; i < 8; i++) { o[2 * i] = fmaf(p, bf_lo(vv[i]), o[2 * i]); o[2 * i + 1] = fmaf(p, bf_hi(vv[i]), o[2 * i + 1]); }
  }
  float m2 = __shfl_xor_sync(~0u, m, 1);
  float mm = fmaxf(m, m2);
  float c = __expf(m - mm);
  l *= c; l += __shfl_xor_sync(~0u, l, 1);
  float inv = 1.f / l;
  uint32_t r[8];
#pragma unroll
  for (int i = 0; i < 16; i++) { o[i] *= c; o[i] += __shfl_xor_sync(~0u, o[i], 1); o[i] *= inv; }
#pragma unroll
  for (int i = 0; i < 8; i++) r[i] = pack_bf16(o[2 * i], o[2 * i + 1]);
  if (half == 0) sts4(dst, r[0], r[1], r[2], r[3]); else sts4(dst, r[4], r[5], r[6], r[7]);
  fence_async();
}

struct Params { const __nv_bfloat16* wk; const __nv_bfloat16* wv; const __nv_bfloat16* xa; };
__device__ __forceinline__ void cp16(uint32_t dst, const void* src) { asm volatile("cp.async.cg.shared.global [%0], [%1], 16;" :: "r"(dst), "l"(src) : "memory"); }

__device__ __forceinline__ void helper_cta(const int h, const uint32_t sb, const uint32_t bars, const int wg, const int w4,
                                           const CUtensorMap* mQ, const CUtensorMap* mOs) {
  const int lane = threadIdx.x & 31;
  mbar_wait(BAR_GO, 0);
  const int cb = wg & 1, col = h * 128 + cb * 64, row0 = S_TOK + (wg >> 1) * 1024;
  const uint32_t buf = sb + wg * 49152;
  if (w4 == 0 && elect_one()) {
    fence_async_all();
#pragma unroll 1
    for (int u = 0; u < 3; u++) {
      mbar_expect_tx(BAR_TF(wg * 3 + u), 16384);
      tma2d(buf + u * 16384, mQ, col, row0 + u * 128, BAR_TF(wg * 3 + u));
    }
  }
  const int head = h * 8 + cb * 4 + w4;
  float4 a0 = make_float4(0, 0, 0, 0), a1 = a0, a2 = a0;
#pragma unroll 8
  for (int tt = 0; tt < 16; tt++) {
    const float4* src = g_kvp + ((tt * 32 + head) * 3) * 32 + lane;
    float4 u = src[0], v = src[32], w = src[64];
    a0.x += u.x; a0.y += u.y; a0.z += u.z; a0.w += u.w;
    a1.x += v.x; a1.y += v.y; a1.z += v.z; a1.w += v.w;
    a2.x += w.x; a2.y += w.y; a2.z += w.z; a2.w += w.w;
  }
  const uint32_t b00 = pack_bf16(a0.x, a0.y), b01 = pack_bf16(a0.z, a0.w);
  const uint32_t b10 = pack_bf16(a1.x, a1.y), b11 = pack_bf16(a1.z, a1.w);
  const uint32_t bz0 = pack_bf16(a2.x, a2.y), bz1 = pack_bf16(a2.z, a2.w);
  const int m = lane >> 3, r = lane & 7;
  const uint32_t off = ((m & 1) * 8 + r) * 128 + (((w4 * 2 + (m >> 1)) ^ r) << 4);
  int s = 0, ph = 0;
#pragma unroll 1
  for (int u = 0; u < 8; u++) {
    const uint32_t bb = buf + s * 16384;
    mbar_wait(BAR_TF(wg * 3 + s), ph);
#pragma unroll
    for (int mt = 0; mt < 8; mt++) {
      uint32_t a[4];
      ldsm4(bb + mt * 2048 + off, a);
      float n0[4] = {0, 0, 0, 0}, n1[4] = {0, 0, 0, 0}, dn[4] = {0, 0, 0, 0};
      mma_bf16(dn, a[0], a[1], a[2], a[3], bz0, bz1);
      mma_bf16(n0, a[0], a[1], a[2], a[3], b00, b01);
      mma_bf16(n1, a[0], a[1], a[2], a[3], b10, b11);
      const float i0 = rcpf(dn[0] + 1e-6f), i1 = rcpf(dn[2] + 1e-6f);
      stsm4(bb + mt * 2048 + off, pack_bf16(n0[0] * i0, n0[1] * i0), pack_bf16(n0[2] * i1, n0[3] * i1),
            pack_bf16(n1[0] * i0, n1[1] * i0), pack_bf16(n1[2] * i1, n1[3] * i1));
    }
    fence_async();
    named_bar(wg + 1, 128);
    if (w4 == 0 && lane == 0) {
      tma2d_store(mOs, bb, col, row0 + u * 128);
      bulk_commit();
      if (u >= 1 && u + 2 < 8) {
        asm volatile("cp.async.bulk.wait_group.read 1;" ::: "memory");
        const int sp = s == 0 ? 2 : s - 1;
        mbar_expect_tx(BAR_TF(wg * 3 + sp), 16384);
        tma2d(buf + sp * 16384, mQ, col, row0 + (u + 2) * 128, BAR_TF(wg * 3 + sp));
      }
    }
    __syncwarp();
    if (++s == 3) { s = 0; ph ^= 1; }
  }
  if (w4 == 0 && lane == 0) {
    bulk_wait_all();
    fence_async_all();
    flag_add(FLAG_LM((h * 2 + cb) * 2 + (wg >> 1)));
    if (wg == 0) TS(1, 8);
  }
}

#define STAGE(s) (sb + (2 - (s)) * 65536)
template <int TR> __device__ __forceinline__ void proj_kb(float* acc, uint32_t st, uint32_t offA, uint32_t offB, int first) {
  const uint64_t da = make_desc(st + offA, TR ? 8192 : 16, 1024, 1);
  const uint64_t db = make_desc(st + offB, TR ? 16 : 8192, 1024, 1);
  wg_fence();
#pragma unroll
  for (int k = 0; k < 4; k++) wg_ss128<TR, 1 - TR>(acc, da + k * (TR ? 128 : 2), db + k * (TR ? 2 : 128), k != 0 || !first);
  wg_commit();
}
template <int TR> __device__ __forceinline__ void proj_loop(float* acc, uint32_t sb, uint32_t bars, uint32_t offA, uint32_t offB,
                                                            int wg, uint32_t sWKV) {
  {
    float kv[4];
    if (threadIdx.x == 0) TS(0, 13);
    mbar_wait(BAR_XA(wg), 0);
    if (threadIdx.x == 0) TS(0, 1);
    const uint64_t da = make_desc(STAGE(2) + wg * 16384, 16, 1024, 1), db = make_desc(sWKV + wg * 2048, 128, 128, 0);
    wg_fence();
#pragma unroll
    for (int k = 0; k < 8; k++) wg_ss8<0, 1>(kv, da + (k >> 2) * 512 + (k & 3) * 2, db + k * 16, k != 0);
    wg_commit();
    wg_wait<0>();
    fence_regs<4>(kv);
    named_bar(wg + 1, 128);
    sts4(sWKV + threadIdx.x * 16, __float_as_uint(kv[0]), __float_as_uint(kv[1]), __float_as_uint(kv[2]), __float_as_uint(kv[3]));
    __syncwarp();
    if ((threadIdx.x & 31) == 0) mbar_arrive(BAR_GO);
  }
  int s = 0, ph = 0, sp = 0;
#pragma unroll 1
  for (int kb = 0; kb < 8; kb++) {
    mbar_wait(BAR_FULL(s), ph);
    if (threadIdx.x == 0) TS(0, 2 + kb);
    proj_kb<TR>(acc, STAGE(s), offA, offB, kb == 0);
    wg_wait<1>();
    if (kb >= 1 && (threadIdx.x & 127) == 0) mbar_arrive(BAR_EMPTY(sp));
    __syncwarp();
    sp = s;
    if (++s == 3) { s = 0; ph ^= 1; }
  }
  wg_wait<0>();
  fence_regs<64>(acc);
}

__device__ __forceinline__ uint32_t tail_slots(int t) {
  const uint32_t lo = t < 4 ? (t < 2 ? (t == 0 ? 0x0C0B0Au : 0x0F0E0Du) : (t == 2 ? 0x100400u : 0x181408u))
                            : (t < 6 ? (t == 4 ? 0x12061Au : 0x050116u) : (t == 6 ? 0x151103u : (t == 7 ? 0x190207u : 0x171309u)));
  return lo;
}

__device__ __forceinline__ void take_role(uint32_t sM, int wg) {
  uint32_t r;
  asm volatile("atom.shared.add.u32 %0, [%1], 1;" : "=r"(r) : "r"(sM + 20) : "memory");
  sts1(sM + 32 + wg * 4, r);
}

__global__ void __launch_bounds__(640, 1)
k1_main(const __grid_constant__ CUtensorMap mXA64, const __grid_constant__ CUtensorMap mXB,
        const __grid_constant__ CUtensorMap mWq, const __grid_constant__ CUtensorMap mWqkv,
        const __grid_constant__ CUtensorMap mQst, const __grid_constant__ CUtensorMap mOst,
        const __grid_constant__ CUtensorMap mO, const __grid_constant__ CUtensorMap mWoA,
        const __grid_constant__ CUtensorMap mWoB, const __grid_constant__ CUtensorMap mOut,
        const __grid_constant__ CUtensorMap mO16, const Params prm) {
  extern __shared__ uint8_t smem_raw[];
  const uint32_t sb = (smem_u32(smem_raw) + 1023u) & ~1023u;
  const uint32_t bars = sb + OFF_MISC, sM = bars + 512, sT = bars + 1024;
  const int tid = threadIdx.x, warp = __shfl_sync(~0u, tid >> 5, 0), wg = warp >> 2, w4 = warp & 3, lane = tid & 31;
  const bool helper = blockIdx.x >= 128;
  if (tid == 0) TS(0, 0);
  const int G = blockIdx.x >> 4, gi = blockIdx.x & 15;
  const int tbA = G * 4 + (gi >> 2), hg = gi & 3;
  const int ttB = (G >> 1) * 4 + (gi >> 2), hq = (G & 1) * 4 + (gi & 3);
  auto issue = [&](int kb, int s) {
    const uint32_t fb = BAR_FULL(s), st = STAGE(s);
    mbar_expect_tx(fb, 65536);
    tma2d(st + 16384, &mXA64, kb * 64, tbA * 64, fb);
    tma2d(st, &mWq, hg * 128, kb * 64, fb);
    tma2d(st + 8192, &mWq, hg * 128 + 64, kb * 64, fb);
    tma2d(st + 49152, &mXB, kb * 64, ttB * 128, fb);
    tma2d(st + 24576, &mWqkv, hq * 64, kb * 64, fb);
    tma2d(st + 32768, &mWqkv, 512 + hq * 64, kb * 64, fb);
    tma2d(st + 40960, &mWqkv, 1024 + hq * 64, kb * 64, fb);
  };
  const uint32_t sOne = sb + OFF_V + 65536, sWKV = sOne + 24576;
  if (warp >= 16) {
    if (warp == 17) {
      if (elect_one()) {
        mbar_init(BAR_BDONE, 8); mbar_init(BAR_Q, 8); mbar_init(BAR_GO, helper ? 1 : 16); mbar_init(BAR_Q2, 5);
        mbar_init(BAR_OD(0), 16); mbar_init(BAR_OD(1), 16); mbar_init(BAR_CL(0), 1); mbar_init(BAR_FULL(2), 1);
#pragma unroll
        for (int i = 0; i < 4; i++) mbar_init(BAR_CL(i + 1), i == 0 ? 5 : 4);
#pragma unroll
        for (int i = 0; i < 3; i++) { mbar_init(BAR_EMPTY(i), 4); mbar_init(BAR_KV(i), 1); mbar_init(BAR_VB(i), 1); }
        sts1(sM + 20, 0);
        asm volatile("fence.mbarrier_init.release.cluster;" ::: "memory");
      }
    } else if (warp == 18) {
      if (elect_one()) {
#pragma unroll
        for (int i = 0; i < 7; i++) mbar_init(BAR_TE(i), 1);
#pragma unroll
        for (int i = 0; i < 16; i++) mbar_init(BAR_TF(i), i < 13 ? 1 : 2);
        asm volatile("fence.mbarrier_init.release.cluster;" ::: "memory");
      }
    } else if (warp == 16 && !helper && elect_one()) {
#pragma unroll
      for (int w = 0; w < 4; w++) mbar_init(BAR_XA(w), 1);
      mbar_init(BAR_FULL(0), 1); mbar_init(BAR_FULL(1), 1);
      asm volatile("fence.mbarrier_init.release.cluster;" ::: "memory");
#pragma unroll
      for (int w = 0; w < 4; w++) {
        mbar_expect_tx(BAR_XA(w), 16384);
        tma2d(STAGE(2) + w * 16384, &mXA64, w * 128, tbA * 64, BAR_XA(w));
        tma2d(STAGE(2) + w * 16384 + 8192, &mXA64, w * 128 + 64, tbA * 64, BAR_XA(w));
      }
      TS(0, 14);
      issue(0, 0);
    }
  } else if (!helper) {
    const uint4 v = __ldg((const uint4*)(hg >= 2 ? prm.wv : prm.wk) + tid * 2 + (hg & 1));
#pragma unroll
    for (int i = 0; i < 3; i++) {
      const int key = tid + i * 512;
      sts4(sOne + key * 16, (key % STEPK) < 24 ? 0x00003F80u : 0x00004E80u, 0u, 0u, 0u);
    }
    sts4(sWKV + tid * 16, v.x, v.y, v.z, v.w);
    fence_async();
  }
  __syncthreads();
  if (wg == 4) {
    if (w4 == 0 && !helper && elect_one()) { issue(1, 1); TS(0, 15); }
    asm volatile("setmaxnreg.dec.sync.aligned.u32 32;");
    const uint32_t ep = g_epoch[blockIdx.x] + 1;
    if (helper) {
      if (w4 == 0 && elect_one()) {
        flag_wait(FLAG_B(blockIdx.x - 128), ep * 32);
        fence_async_all();
        TS(1, 10);
        mbar_arrive(BAR_GO);
        g_epoch[blockIdx.x] = ep;
      }
      return;
    }
    mbar_wait(BAR_GO, 0);
    if (w4 == 0 && elect_one()) issue(2, 2);
    {
      uint32_t a[4], b[4];
      float c[4];
      lds4(sWKV + (tid - 512) * 16, a);
      lds4(sWKV + 2048 + (tid - 512) * 16, b);
#pragma unroll
      for (int i = 0; i < 4; i++) c[i] = __uint_as_float(a[i]) + __uint_as_float(b[i]);
      lds4(sWKV + 4096 + (tid - 512) * 16, a);
      lds4(sWKV + 6144 + (tid - 512) * 16, b);
#pragma unroll
      for (int i = 0; i < 4; i++) c[i] += __uint_as_float(a[i]) + __uint_as_float(b[i]);
      sts1(sT + w4 * 256 + lane * 4, pack_bf16(c[0], c[1]));
      sts1(sT + w4 * 256 + 128 + lane * 4, pack_bf16(c[2], c[3]));
    }
    named_bar(9, 128);
    {
      const int t = tid - 512;
#pragma unroll
      for (int i = 0; i < 4; i++) {
        const int key = 1536 + t + i * 128;
        sts4(sOne + key * 16, (key % STEPK) < 24 ? 0x00003F80u : 0x00004E80u, 0u, 0u, 0u);
      }
      fence_async();
      __syncwarp();
      if (lane == 0) mbar_arrive(BAR_Q);
    }
    if (w4 == 0) {
      int s = 0, ph = 0;
#pragma unroll 1
      for (int kb = 3; kb < 8; kb++) {
        mbar_wait(BAR_EMPTY(s), ph);
        if (elect_one()) issue(kb, s);
        if (++s == 3) { s = 0; ph ^= 1; }
      }
      flag_wait(FLAG_KV, ep * 128);
      fence_async_all();
      if (lane == 0) TS(0, 11);
#pragma unroll 1
      for (int m = 0; m < 2; m++) {
        mbar_wait(m == 0 ? BAR_EMPTY(2) : BAR_EMPTY(0), 1 - m);
        if (elect_one()) {
          const uint32_t fb = m == 0 ? BAR_KV(0) : BAR_VB(0);
          mbar_expect_tx(fb, 2 * 7 * STEPK * 16);
#pragma unroll
          for (int p = 0; p < 2; p++) bulk_g2s(sb + m * OFF_V + p * 32768, g_KV + (m * 2 + p) * S_TOK, 7 * STEPK * 16, fb);
        }
      }
      mbar_wait(BAR_Q, 0);
      if (elect_one()) {
#pragma unroll
        for (int c = 1; c < 3; c++) {
          const int k0 = c == 1 ? 7 * STEPK : 12 * STEPK, k1 = c == 1 ? 12 * STEPK : S_TOK;
          const uint32_t bytes = (k1 - k0) * 16;
          mbar_expect_tx(BAR_KV(c), 4 * bytes);
#pragma unroll
          for (int p = 0; p < 4; p++)
            bulk_g2s(sb + (p >> 1) * OFF_V + (p & 1) * 32768 + k0 * 16, g_KV + p * S_TOK + k0, bytes, BAR_KV(c));
        }
      }
      mbar_wait_long(BAR_CL(3), 0);
      flag_wait(FLAG_LM((lane & 7) * 2 + (tbA >> 4)), ep);
      __syncwarp();
      fence_async_all();
      if (lane == 0) TS(2, 13);
#pragma unroll 1
      for (int n = 0; n < 8; n++) {
        mbar_wait(n == 7 ? BAR_CL(4) : BAR_TE(n), 0);
        const uint32_t sl = tail_slots(n == 7 ? 8 : n & 3), fb = BAR_TF(n);
        if (elect_one()) {
          mbar_expect_tx(fb, 24576);
          tma2d(sb + (sl & 255) * 8192, &mO, n * 64, S_TOK + tbA * 64, fb);
          tma2d(sb + ((sl >> 8) & 255) * 8192, &mWoB, hg * 128, n * 64, fb);
          tma2d(sb + (sl >> 16) * 8192, &mWoB, hg * 128 + 64, n * 64, fb);
        }
      }
      if (lane == 0) g_epoch[blockIdx.x] = ep;
    } else if (w4 == 3) {
      flag_wait(FLAG_KV, ep * 128);
      const uint4 a = *(const uint4*)(g_stats + lane * 4);
      const float kmax2 = __uint_as_float(__reduce_max_sync(~0u, a.x)) + __uint_as_float(__reduce_max_sync(~0u, a.y));
      const float vmax = __uint_as_float(__reduce_max_sync(~0u, max(a.z, a.w)));
      const float lv = vmax > 0.f ? __log2f(vmax) : 0.f;
      const float lim = fminf(90.f, fminf(91.f + lv, 95.f - lv));
      float thr = -1.f;
      if (vmax < 1e27f && kmax2 <= 65536.f && lim > 2.f) thr = fminf(60000.f, (lim * lim - 1.f) / (kmax2 * 1.02f + 1e-30f));
      if (lane == 0) { sts1(sM + 16, __float_as_uint(thr)); mbar_arrive(BAR_Q2); }
      mbar_wait_long(BAR_CL(1), 0);
      flag_wait(FLAG_OA(tbA * 4 + (lane & 3), 0), ep);
      __syncwarp();
      fence_async_all();
#pragma unroll 1
      for (int it = 0; it < 8; it++) {
        const int n = it < 4 ? it : (it < 6 ? it + 1 : (it == 6 ? 4 : 7));
        mbar_wait_long(BAR_CL(it < 4 ? 0 : (it < 6 ? 2 : 3)), 0);
        const uint32_t sl = tail_slots(n), fb = BAR_TF(n + 8);
        const int k0 = n < 4 ? n * 128 : ((hg + n) & 3) * 128 + 64;
        if (elect_one()) {
          mbar_expect_tx(fb, n < 4 ? 24576 : 16384);
          if (n < 4) tma2d(sb + (sl & 255) * 8192, &mO, k0, tbA * 64, fb);
          tma2d(sb + ((sl >> 8) & 255) * 8192, &mWoA, hg * 128, k0, fb);
          tma2d(sb + (sl >> 16) * 8192, &mWoA, hg * 128 + 64, k0, fb);
        }
      }
    } else {
      const int tok = (w4 - 1) * 32 + lane;
      int step, col;
      if ((tbA & 3) == 0) {
        const int b8 = tbA >> 2;
        if (tok < 22) { step = tok; col = 24 + b8; }
        else { const int c = tok >= 43; step = tok - 22 - 21 * c; col = 32 + b8 * 2 + c; }
      } else {
        const int b24 = (tbA >> 2) * 3 + (tbA & 3) - 1;
        if (tok < 42) { const int c = tok >= 21; step = tok - 21 * c; col = 48 + b24 * 2 + c; }
        else { step = tok - 42; col = b24; }
      }
      const int kap = step * STEPK + col;
      const bool chained = col >= 24;
      uint32_t v[4], o[4];
      lds4(sT + tok * 16, v);
      g_KV[(4 + hg) * S_TOK + kap] = make_uint4(v[0], v[1], v[2], v[3]);
      float st = 0.f;
      if (hg < 2) {
        o[0] = o[1] = o[2] = o[3] = 0;
        if (chained && step > 0) lds4(sT + tok * 16 - 16, o);
        const float sc = chained ? 2.f : 1.f;
#pragma unroll
        for (int u = 0; u < 4; u++) {
          const float x = bf_lo(v[u]), y = bf_hi(v[u]);
          st += x * x + y * y;
          o[u] = pack_f16((x - bf_lo(o[u])) * sc, (y - bf_hi(o[u])) * sc);
        }
      } else {
        const float sc = chained ? VSHIFT : 1.f;
#pragma unroll
        for (int u = 0; u < 4; u++) { float x = bf_lo(v[u]), y = bf_hi(v[u]); st += fabsf(x) + fabsf(y); o[u] = pack_bf16(x * sc, y * sc); }
      }
      g_KV[hg * S_TOK + kap] = make_uint4(o[0], o[1], o[2], o[3]);
      const uint32_t um = __reduce_max_sync(~0u, __float_as_uint(st) & 0x7FFFFFFFu);
      if (w4 == 2) {
        if (lane == 0) sts1(sM + 24, um);
        named_arrive(10, 64);
        mbar_wait_long(BAR_TE(0), 0);
        uint32_t pend = 7;
        const int li = lane < 3 ? lane : 0;
        const uint32_t* fl = FLAG_OA(tbA * 4 + ((hg + li + 1) & 3), 1);
#pragma unroll 1
        for (int it = 0; pend; it++) {
          uint32_t fv;
          asm volatile("ld.acquire.gpu.global.u32 %0, [%1];" : "=r"(fv) : "l"(fl) : "memory");
          const uint32_t go = __ballot_sync(~0u, (int32_t)(fv - ep) >= 0 && mbar_test(BAR_CL(li == 0 ? 3 : 4), 0)) & pend;
          if (go) {
            fence_async_all();
            if (elect_one()) {
#pragma unroll
              for (int n = 0; n < 3; n++)
                if ((go >> n) & 1) {
                  mbar_expect_tx(BAR_TF(13 + n), 8192);
                  tma2d(sb + (tail_slots(5 + n) & 255) * 8192, &mO, ((hg + n + 1) & 3) * 128 + 64, tbA * 64, BAR_TF(13 + n));
                }
            }
            pend &= ~go;
          }
          if (it > 2000000) __trap();
        }
        if (lane == 0) TS(2, 14);
      }
      else {
        named_bar(10, 64);
        if (elect_one()) {
          g_stats[tbA * 4 + hg] = max(um, lds1(sM + 24));
          fence_async_all();
          flag_add(FLAG_KV);
          TS(1, 9);
          mbar_wait_long(BAR_BDONE, 0);
          tma2d_store(&mQst, sb + OFF_F + 49152, hq * 64, S_TOK + ttB * 128);
          bulk_commit();
          bulk_wait_all();
          fence_async_all();
          flag_add(FLAG_B(hq >> 1));
          TS(0, 12);
          mbar_wait(BAR_Q, 0);
          mbar_arrive(BAR_CL(0));
#pragma unroll 1
          for (int p = 0; p < 2; p++) {
            mbar_wait_long(BAR_OD(p), 0);
            if (p == 0) {
#pragma unroll
              for (int w = 0; w < 4; w++) tma2d_store(&mO16, sb + OFF_F + w * 2048, hg * 128 + w * 16, tbA * 64);
            } else {
              tma2d_store(&mO, sb + 26 * 8192, hg * 128 + 64, tbA * 64);
            }
            bulk_commit();
            bulk_wait_all();
            if (p == 0) mbar_arrive(BAR_CL(1));
            PUBLISH(FLAG_OA(blockIdx.x, p));
          }
          TS(2, 0);
        }
      }
    }
    return;
  }
  if (helper) { helper_cta(blockIdx.x - 128, sb, bars, wg, w4, &mQst, &mOst); return; }

  {
    float acc[64];
    if (wg == 0) proj_loop<0>(acc, sb, bars, 16384, 0, wg, sWKV);
    else proj_loop<1>(acc, sb, bars, 16384 + wg * 8192, 49152, wg, sWKV);
    if (tid == 0) TS(0, 10);
    const uint32_t sF = sb + OFF_F;
    const uint32_t qa = sF + w4 * 512 + ((lane >> 3) & 1) * 256 + (lane >> 4) * 128 + (lane & 7) * 16;
    if (wg == 0) {
#pragma unroll
      for (int hd = 0; hd < 4; hd++)
        stsm4(qa + hd * 2048, pack_f16(acc[8 * hd] * QSCALE, acc[8 * hd + 1] * QSCALE), pack_f16(acc[8 * hd + 2] * QSCALE, acc[8 * hd + 3] * QSCALE),
              pack_f16(acc[8 * hd + 4] * QSCALE, acc[8 * hd + 5] * QSCALE), pack_f16(acc[8 * hd + 6] * QSCALE, acc[8 * hd + 7] * QSCALE));
      fence_async();
      __syncwarp();
      if (lane == 0) mbar_arrive(BAR_Q);
    } else {
      if (wg != 3) named_arrive(6, 384);
      if (wg != 1) named_arrive(8, 384);
    }
    asm volatile("setmaxnreg.inc.sync.aligned.u32 112;");
    fence_regs<64>(acc);
    if (wg == 0) {
      uint32_t r[32];
#pragma unroll
      for (int hd = 0; hd < 8; hd++) {
#pragma unroll
        for (int i = 0; i < 4; i++) r[4 * hd + i] = pack_f16(acc[8 * hd + 2 * i] * QSCALE, acc[8 * hd + 2 * i + 1] * QSCALE);
        if (hd >= 4) stsm4(qa + hd * 2048, r[4 * hd], r[4 * hd + 1], r[4 * hd + 2], r[4 * hd + 3]);
      }
      fence_async();
      uint32_t nmax = 0;
#pragma unroll
      for (int hd = 0; hd < 8; hd++) {
        const uint32_t* q = r + 4 * hd;
        const uint32_t t0 = hfma2(q[2], q[2], hfma2(q[0], q[0], 0u)), t1 = hfma2(q[3], q[3], hfma2(q[1], q[1], 0u));
        uint32_t n = hadd2(__byte_perm(t0, t1, 0x5410), __byte_perm(t0, t1, 0x7632));
        n = hadd2(n, __shfl_xor_sync(~0u, n, 1));
        n = hadd2(n, __shfl_xor_sync(~0u, n, 2));
        nmax = __vmaxu2(nmax, n & 0x7FFF7FFFu);
      }
      nmax = __reduce_max_sync(~0u, max(nmax & 0xFFFFu, nmax >> 16));
      if (lane == 0) sts1(sM + w4 * 4, nmax);
      uint4* gq = (uint4*)g_Q + blockIdx.x * 1024 + tid;
#pragma unroll
      for (int hd = 0; hd < 8; hd++)
        gq[hd * 128] = make_uint4(pack_bf16(acc[8 * hd], acc[8 * hd + 1]), pack_bf16(acc[8 * hd + 2], acc[8 * hd + 3]),
                                  pack_bf16(acc[8 * hd + 4], acc[8 * hd + 5]), pack_bf16(acc[8 * hd + 6], acc[8 * hd + 7]));
      __syncwarp();
      if (lane == 0) mbar_arrive(BAR_Q2);
    } else if (wg == 3) {
      named_bar(6, 384);
      const int t = tid & 127;
#pragma unroll
      for (int j = 0; j < 8; j++)
        sts4(sF + 24576 + j * 2048 + t * 16, pack_bf16(acc[8 * j], acc[8 * j + 1]), pack_bf16(acc[8 * j + 2], acc[8 * j + 3]),
             pack_bf16(acc[8 * j + 4], acc[8 * j + 5]), pack_bf16(acc[8 * j + 6], acc[8 * j + 7]));
      named_arrive(7, 256);
    } else {
      uint32_t p[32];
#pragma unroll
      for (int i = 0; i < 32; i++) p[i] = phi2(acc[2 * i], acc[2 * i + 1]);
      if (wg == 1) {
        named_bar(8, 384);
        const int m = lane >> 3, r = lane & 7;
#pragma unroll
        for (int j = 0; j < 16; j += 2) {
          const int tok = (j + (m >> 1)) * 8 + r;
          const int chunk = w4 * 2 + (m & 1);
          stsm4t(sF + 49152 + tok * 128 + ((chunk ^ r) << 4), p[2 * j], p[2 * j + 1], p[2 * j + 2], p[2 * j + 3]);
        }
        fence_async();
      } else {
        named_bar(7, 256);
        float kv0[4] = {0, 0, 0, 0}, kv1[4] = {0, 0, 0, 0}, z0[4] = {0, 0, 0, 0}, z1[4] = {0, 0, 0, 0};
        const uint32_t one = 0x3F803F80u;
        const int t = tid & 127;
#pragma unroll
        for (int j = 0; j < 8; j++) {
          uint32_t a[4];
          lds4(sF + 24576 + j * 2048 + t * 16, a);
          mma_bf16(kv0, a[0], a[1], a[2], a[3], p[4 * j], p[4 * j + 2]);
          mma_bf16(kv1, a[0], a[1], a[2], a[3], p[4 * j + 1], p[4 * j + 3]);
          mma_bf16(z0, one, one, one, one, p[4 * j], p[4 * j + 2]);
          mma_bf16(z1, one, one, one, one, p[4 * j + 1], p[4 * j + 3]);
        }
        float4* dst = g_kvp + ((ttB * 32 + hq * 4 + w4) * 3) * 32 + lane;
        dst[0] = make_float4(kv0[0], kv0[1], kv1[0], kv1[1]);
        dst[32] = make_float4(kv0[2], kv0[3], kv1[2], kv1[3]);
        dst[64] = make_float4(z0[0], z0[1], z1[0], z1[1]);
      }
      __syncwarp();
      if (lane == 0) mbar_arrive(BAR_BDONE);
    }
  }

  bool safe = true;
  {
    const uint32_t c63 = 0x1F801F80u + (threadIdx.x >> 20);
    const uint32_t m1 = (gridDim.x >> 20) - 1u;
    const uint64_t dK0 = make_desc(sb + OFF_K, 32768, 128, 0);
    const uint64_t dV0 = make_desc(sb + OFF_V, 128, 32768, 0);
    constexpr uint32_t dKV = ((2048u - 8u)  __H0__ ) + STEPK - (OFF_V - OFF_K) / 16;
    float Sm[12], Sp[36], O[12];
    uint32_t P[24];
    uint64_t dQ = make_desc(sb + OFF_F + wg * 2048, 128, 256, 0);
#pragma unroll
    for (int i = 0; i < 36; i++) Sp[i] = SMAGIC;
#pragma unroll
    for (int i = 0; i < 12; i++) Sm[i] = 0.f;
    fence_regs<12>(Sm); fence_regs<36>(Sp);
    mbar_wait(BAR_Q, 0);
    mbar_wait(BAR_KV(0), 0);
    wg_fence();
    wg_qs72<1>(Sp, dQ, dK0 + 24);
    wg_qs24<0>(Sm, dQ, dK0);
    wg_commit();
    wg_wait<0>();
    fence_regs<12>(Sm); fence_regs<36>(Sp);
#pragma unroll 1
    for (int pass = 0; pass < 2; pass++) {
#pragma unroll
      for (int i = 0; i < 12; i++) O[i] = 0.f;
      fence_regs<12>(O);
      if (tid == 0) TS(1, 2 + 2 * pass);
      uint32_t vlo = (uint32_t)dV0;
#pragma unroll 1
      for (int seg = 0; seg < 4; seg++) {
        if (pass == 0) {
          if (seg < 3) mbar_wait(seg == 0 ? BAR_VB(0) : BAR_KV(seg), 0);
        } else if (seg >= 1) {
          if ((tid & 127) == 0) {
            mbar_arrive(BAR_CL(seg));
            if (seg == 3) take_role(sM, wg);
          }
          __syncwarp();
        }
        if ((tid & 127) == 0) TS(4 + wg, pass * 5 + seg);
        const uint32_t vend = vlo + (seg == 0 ? 6 : 5) * STEPK;
#pragma unroll 1
        for (; vlo != vend; vlo += STEPK) {
          uint64_t dK, dV;
          asm("mov.b64 %0, {%1, %2};" : "=l"(dK) : "r"(vlo + dKV), "r"(8u));
          asm("mov.b64 %0, {%1, %2};" : "=l"(dV) : "r"(vlo), "r"(2048u));
#pragma unroll
          for (int i = 0; i < 6; i++) P[i] = pack_bf16(ex2f(Sm[2 * i]), ex2f(Sm[2 * i + 1]));
#pragma unroll
          for (int i = 0; i < 18; i++) P[6 + i] = exp2_pair_fix(Sp[2 * i], Sp[2 * i + 1], c63, m1);
          fence_regs<24>(P);
          wg_fence();
#pragma unroll
          for (int k = 0; k < 6; k++) wg_pv24<1>(O, &P[4 * k], dV + k * 16);
          wg_qs72<1>(Sp, dQ, dK + 24);
          wg_qs24<0>(Sm, dQ, dK);
          wg_commit();
          wg_wait<0>();
          fence_regs<12>(Sm); fence_regs<36>(Sp); fence_regs<12>(O); fence_regs<24>(P);
        }
      }
#pragma unroll
      for (int i = 0; i < 6; i++) P[i] = pack_bf16(ex2f(Sm[2 * i]), ex2f(Sm[2 * i + 1]));
      P[6] = exp2_pair_fix(Sp[0], Sp[1], c63, m1);
      P[7] = exp2_pair_fix(Sp[2], Sp[3], c63, m1);
      fence_regs<8>(P);
#pragma unroll
      for (int i = 0; i < 36; i++) Sp[i] = SMAGIC;
      fence_regs<36>(Sp);
      mbar_wait(pass == 0 ? BAR_Q2 : BAR_CL(3), 0);
      const uint32_t sO = pass == 0 ? sb + OFF_F + wg * 2048 + w4 * 512 + (lane & 15) * 32 + (lane >> 4) * 16
                                    : sb + 26 * 8192 + (w4 * 16 + (lane & 15)) * 128 + (((wg * 2 + (lane >> 4)) ^ (lane & 7)) << 4);
      dQ += 512;
      wg_fence();
      wg_pv24<1>(O, &P[0], dV0 + 21 * STEPK);
      wg_pv24<1>(O, &P[4], dV0 + 21 * STEPK + 16);
      wg_commit();
      wg_qs72<1>(Sp, dQ, dK0 + 24);
      wg_qs24<0>(Sm, dQ, dK0);
      wg_commit();
      wg_wait<1>();
      fence_regs<12>(O);
      const float l0 = __shfl_sync(~0u, O[8], lane & ~3), l1 = __shfl_sync(~0u, O[10], lane & ~3);
      const float i0 = rcpf(l0), i1 = rcpf(l1);
      stsm4(sO,
            pack_bf16(O[0] * i0, O[1] * i0), pack_bf16(O[2] * i1, O[3] * i1),
            pack_bf16(O[4] * i0, O[5] * i0), pack_bf16(O[6] * i1, O[7] * i1));
      fence_async();
      {
        uint32_t n[4];
        lds4(sM, n);
        const float qn = __half2float(__ushort_as_half((unsigned short)max(max(n[0], n[1]), max(n[2], n[3]))));
        safe = __all_sync(~0u, qn <= __uint_as_float(lds1(sM + 16)));
      }
      if (safe && lane == 0) mbar_arrive(BAR_OD(pass));
      wg_wait<0>();
      fence_regs<12>(Sm); fence_regs<36>(Sp);
      if (!safe) break;
      if ((tid & 127) == 0) TS(4 + wg, pass * 5 + 4);
      if (tid == 0) TS(1, 3 + 2 * pass);
    }
  }
  if (!safe) {
    if ((tid & 127) == 0) { mbar_arrive(BAR_CL(1)); mbar_arrive(BAR_CL(2)); mbar_arrive(BAR_CL(3)); take_role(sM, wg); }
#pragma unroll 1
    for (int pass = 0; pass < 2; pass++) {
      const int t = tid & 127;
      mbar_wait(BAR_CL(3), 0);
      attn_slow((const uint4*)g_Q + blockIdx.x * 1024 + (pass * 4 + wg) * 128,
                pass == 0 ? sb + OFF_F + wg * 2048 + t * 16
                          : sb + 26 * 8192 + (t >> 1) * 128 + (((wg * 2 + (t & 1)) ^ ((t >> 1) & 7)) << 4));
      __syncwarp();
      if (lane == 0) mbar_arrive(BAR_OD(pass));
    }
  }

  {
    named_bar(wg + 1, 128);
    if ((tid & 127) == 0) mbar_arrive(BAR_CL(4));
    const int role = __shfl_sync(~0u, lds1(sM + 32 + wg * 4), 0);
    if ((tid & 127) == 0) TS(4 + wg, 10);
    const int m = lane >> 3, r = lane & 7;
    const uint32_t stoff = (w4 * 16 + (m & 1) * 8 + r) * 128;
    if (role < 2) {
      float acc[64];
      uint32_t sl = 0;
#pragma unroll 1
      for (int n = 0; n < 8; n++) {
        sl = tail_slots(role == 0 ? n : (n == 7 ? 8 : n & 3));
        const uint32_t w0 = (sl >> 8) & 255, w1 = sl >> 16;
        const uint64_t da = make_desc(sb + (sl & 255) * 8192, 16, 1024, 1), db = make_desc(sb + w0 * 8192, (w1 - w0) * 8192, 1024, 1);
        mbar_wait(BAR_TF(role == 0 ? 8 + n : n), 0);
        if (role == 0 && n == 4) mbar_wait(BAR_OD(1), 0);
        if ((tid & 127) == 0 && role == 0) TS(2, 2 + n);
        wg_fence();
#pragma unroll
        for (int k = 0; k < 4; k++) wg_ss128<0, 1>(acc, da + k * 2, db + k * 128, (n | k) != 0);
        wg_commit();
        if (n < 4) {
          wg_wait<0>();
          if (n + role < 4 && (tid & 127) == 0) mbar_arrive(BAR_TE(role * 4 + n));
          __syncwarp();
        } else {
          wg_wait<1>();
        }
      }
      wg_wait<0>();
      fence_regs<64>(acc);
      if ((tid & 127) == 0) TS(4 + wg, 11);
      sl = tail_slots(role == 0 ? 4 : 0);
      const uint32_t x0 = sb + ((sl >> 8) & 255) * 8192, x1 = sb + (sl >> 16) * 8192;
#pragma unroll
      for (int j = 0; j < 16; j += 2)
        stsm4((j < 8 ? x0 : x1) + stoff + ((((j & 7) + (m >> 1)) ^ r) << 4),
              pack_bf16(acc[4 * j], acc[4 * j + 1]), pack_bf16(acc[4 * j + 2], acc[4 * j + 3]),
              pack_bf16(acc[4 * j + 4], acc[4 * j + 5]), pack_bf16(acc[4 * j + 6], acc[4 * j + 7]));
      fence_async();
      named_bar(wg + 1, 128);
      if (w4 == 0 && elect_one()) {
        tma2d_store(&mOut, x0, role * 512 + hg * 128, tbA * 64);
        tma2d_store(&mOut, x1, role * 512 + hg * 128 + 64, tbA * 64);
        bulk_commit();
        asm volatile("cp.async.bulk.wait_group.read 0;" ::: "memory");
        TS(2, 12 - role);
      }
    }
  }
}

typedef CUresult (*EncodeFn)(CUtensorMap*, CUtensorMapDataType, cuuint32_t, void*, const cuuint64_t*, const cuuint64_t*,
                             const cuuint32_t*, const cuuint32_t*, CUtensorMapInterleave, CUtensorMapSwizzle,
                             CUtensorMapL2promotion, CUtensorMapFloatOOBfill);

static void make_map(EncodeFn enc, CUtensorMap* m, const void* ptr, uint64_t cols, uint64_t rows, uint32_t bc, uint32_t br,
                     CUtensorMapSwizzle sw = CU_TENSOR_MAP_SWIZZLE_128B) {
  cuuint64_t dims[2] = {cols, rows};
  cuuint64_t strides[1] = {cols * 2};
  cuuint32_t box[2] = {bc, br};
  cuuint32_t es[2] = {1, 1};
  enc(m, CU_TENSOR_MAP_DATA_TYPE_BFLOAT16, 2, (void*)ptr, dims, strides, box, es, CU_TENSOR_MAP_INTERLEAVE_NONE,
      sw, CU_TENSOR_MAP_L2_PROMOTION_L2_256B, CU_TENSOR_MAP_FLOAT_OOB_FILL_NONE);
}

extern "C" void kernel_launch(void* const* d_in, const int* in_sizes, int n_in, void* d_out, int out_size) {
  (void)in_sizes; (void)n_in; (void)out_size;
  static EncodeFn enc = nullptr;
  static void* pQ = nullptr; static void* pO = nullptr;
  if (!enc) {
    void* fn = nullptr; cudaDriverEntryPointQueryResult qr;
    cudaGetDriverEntryPoint("cuTensorMapEncodeTiled", &fn, cudaEnableDefault, &qr);
    enc = (EncodeFn)fn;
    cudaGetSymbolAddress(&pQ, g_Q);
    cudaGetSymbolAddress(&pO, g_O);
    cudaFuncSetAttribute(k1_main, cudaFuncAttributeMaxDynamicSharedMemorySize, SM_TOTAL);
  }
  CUtensorMap mXA64, mXB, mWq, mWqkv, mQst, mO, mOst, mWoA, mWoB, mOut, mO16;
  make_map(enc, &mXA64, d_in[0], 512, 2048, 64, 64);
  make_map(enc, &mWq, d_in[1], 512, 512, 64, 64);
  make_map(enc, &mWoA, d_in[4], 512, 512, 64, 64);
  make_map(enc, &mXB, d_in[5], 512, 2048, 64, 128);
  make_map(enc, &mWqkv, d_in[6], 1536, 512, 64, 64);
  make_map(enc, &mWoB, d_in[7], 512, 512, 64, 64);
  make_map(enc, &mQst, pQ, 512, 4096, 64, 128);
  make_map(enc, &mO, pO, 512, 4096, 64, 64);
  make_map(enc, &mOst, pO, 512, 4096, 64, 128);
  make_map(enc, &mOut, d_out, 1024, 2048, 64, 64);
  make_map(enc, &mO16, pO, 512, 4096, 16, 64, CU_TENSOR_MAP_SWIZZLE_NONE);
  Params prm{(const __nv_bfloat16*)d_in[2], (const __nv_bfloat16*)d_in[3], (const __nv_bfloat16*)d_in[0]};
  k1_main<<<132, 640, SM_TOTAL, cudaStreamPerThread>>>(mXA64, mXB, mWq, mWqkv, mQst, mOst, mO, mWoA, mWoB, mOut, mO16, prm);
}
```

```cpp
#include <cuda_runtime.h>
#include <cuda_bf16.h>
#include <cuda_fp16.h>
#include <cuda.h>
#include <stdint.h>

#define S_TOK 2048
#define D_MOD 512

__device__ __align__(1024) __nv_bfloat16 g_Q[2 * S_TOK * D_MOD];
__device__ __align__(1024) __nv_bfloat16 g_O[2 * S_TOK * D_MOD];
__device__ __align__(1024) uint4 g_KV[8 * S_TOK];
__device__ __align__(16) uint32_t g_stats[128];
__device__ __align__(16) float4 g_kvp[16 * 32 * 3 * 32];

#define TS(k, i) do {} while (0)
__device__ __forceinline__ uint32_t smem_u32(const void* p) { return (uint32_t)__cvta_generic_to_shared(p); }
__device__ __forceinline__ void mbar_init(uint32_t bar, int cnt) { asm volatile("mbarrier.init.shared::cta.b64 [%0], %1;" :: "r"(bar), "r"(cnt) : "memory"); }
__device__ __forceinline__ void mbar_expect_tx(uint32_t bar, uint32_t bytes) { asm volatile("mbarrier.arrive.expect_tx.shared::cta.b64 _, [%0], %1;" :: "r"(bar), "r"(bytes) : "memory"); }
__device__ __forceinline__ bool mbar_try(uint32_t bar, uint32_t parity) {
  uint32_t ok;
  asm volatile("{\n.reg .pred p;\nmbarrier.try_wait.parity.shared::cta.b64 p, [%1], %2;\nselp.b32 %0, 1, 0, p;\n}\n" : "=r"(ok) : "r"(bar), "r"(parity) : "memory");
  return ok;
}
__device__ __forceinline__ void mbar_wait(uint32_t bar, uint32_t parity) {
  asm volatile("{\n.reg .pred p;\n.reg .u32 c;\nmov.u32 c, 0;\n"
               "LW_%=:\n"
               "mbarrier.try_wait.parity.shared::cta.b64 p, [%0], %1;\n"
               "@p bra LD_%=;\n"
               "add.u32 c, c, 1;\n"
               "setp.lt.u32 p, c, 4000000;\n"
               "@p bra LW_%=;\n"
               "trap;\n"
               "LD_%=:\n}\n" :: "r"(bar), "r"(parity) : "memory");
}
__device__ __forceinline__ void mbar_arrive_cta(uint32_t bar, uint32_t cta) {
  asm volatile("{\n.reg .b32 ra;\nmapa.shared::cluster.u32 ra, %0, %1;\nmbarrier.arrive.shared::cluster.b64 _, [ra];\n}\n" :: "r"(bar), "r"(cta) : "memory");
}
__device__ __forceinline__ void cluster_sync() {
  asm volatile("barrier.cluster.arrive.relaxed.aligned;\nbarrier.cluster.wait.aligned;" ::: "memory");
}
__device__ __forceinline__ void tma2d(uint32_t dst, const CUtensorMap* m, int c0, int c1, uint32_t bar) {
  asm volatile("cp.async.bulk.tensor.2d.shared::cluster.global.mbarrier::complete_tx::bytes [%0], [%1, {%3, %4}], [%2];"
               :: "r"(dst), "l"(m), "r"(bar), "r"(c0), "r"(c1) : "memory");
}
__device__ __forceinline__ void tma2d_mc(uint32_t dst, const CUtensorMap* m, int c0, int c1, uint32_t bar, uint16_t mask) {
  asm volatile("cp.async.bulk.tensor.2d.shared::cluster.global.mbarrier::complete_tx::bytes.multicast::cluster [%0], [%1, {%3, %4}], [%2], %5;"
               :: "r"(dst), "l"(m), "r"(bar), "r"(c0), "r"(c1), "h"(mask) : "memory");
}
__device__ __forceinline__ void tma2d_store(const CUtensorMap* m, uint32_t src, int c0, int c1) {
  asm volatile("cp.async.bulk.tensor.2d.global.shared::cta.bulk_group [%0, {%2, %3}], [%1];"
               :: "l"(m), "r"(src), "r"(c0), "r"(c1) : "memory");
}
__device__ __forceinline__ void bulk_g2s(uint32_t dst, const void* src, uint32_t bytes, uint32_t bar) {
  asm volatile("cp.async.bulk.shared::cluster.global.mbarrier::complete_tx::bytes [%0], [%1], %2, [%3];"
               :: "r"(dst), "l"(src), "r"(bytes), "r"(bar) : "memory");
}
__device__ __forceinline__ void bulk_commit() { asm volatile("cp.async.bulk.commit_group;" ::: "memory"); }
__device__ __forceinline__ void bulk_wait_all() { asm volatile("cp.async.bulk.wait_group 0;" ::: "memory"); }
__device__ __forceinline__ void fence_async() { asm volatile("fence.proxy.async.shared::cta;" ::: "memory"); }
__device__ __forceinline__ void named_bar(int id, int n) { asm volatile("bar.sync %0, %1;" :: "r"(id), "r"(n) : "memory"); }
__device__ __forceinline__ void pdl_launch() { asm volatile("griddepcontrol.launch_dependents;" ::: "memory"); }
__device__ __forceinline__ void pdl_wait() { asm volatile("griddepcontrol.wait;" ::: "memory"); }
__device__ __forceinline__ void wg_fence() { asm volatile("wgmma.fence.sync.aligned;" ::: "memory"); }
__device__ __forceinline__ void wg_commit() { asm volatile("wgmma.commit_group.sync.aligned;" ::: "memory"); }
template <int n> __device__ __forceinline__ void wg_wait() { asm volatile("wgmma.wait_group.sync.aligned %0;" :: "n"(n) : "memory"); }
template <int n> __device__ __forceinline__ void fence_regs(float* r) {
#pragma unroll
  for (int i = 0; i < n; i++) asm volatile("" : "+f"(r[i]) :: "memory");
}
template <int n> __device__ __forceinline__ void fence_regs(uint32_t* r) {
#pragma unroll
  for (int i = 0; i < n; i++) asm volatile("" : "+r"(r[i]) :: "memory");
}
__device__ __forceinline__ uint64_t make_desc(uint32_t addr, uint32_t lbo, uint32_t sbo, uint32_t swz) {
  return (uint64_t)((addr & 0x3FFFF) >> 4) | ((uint64_t)(lbo >> 4) << 16) | ((uint64_t)(sbo >> 4) << 32) | ((uint64_t)swz << 62);
}
__device__ __forceinline__ float ex2f(float x) { float y; asm("ex2.approx.ftz.f32 %0, %1;" : "=f"(y) : "f"(x)); return y; }
__device__ __forceinline__ uint32_t pack_bf16(float lo, float hi) { uint32_t r; asm("cvt.rn.bf16x2.f32 %0, %1, %2;" : "=r"(r) : "f"(hi), "f"(lo)); return r; }
__device__ __forceinline__ uint32_t pack_f16(float lo, float hi) { uint32_t r; asm("cvt.rn.f16x2.f32 %0, %1, %2;" : "=r"(r) : "f"(hi), "f"(lo)); return r; }
__device__ __forceinline__ float bf_lo(uint32_t v) { return __uint_as_float(v << 16); }
__device__ __forceinline__ float bf_hi(uint32_t v) { return __uint_as_float(v & 0xFFFF0000u); }
__device__ __forceinline__ float rbf(float x) { return __bfloat162float(__float2bfloat16_rn(x)); }
__device__ __forceinline__ void stsm4(uint32_t a, uint32_t r0, uint32_t r1, uint32_t r2, uint32_t r3) {
  asm volatile("stmatrix.sync.aligned.m8n8.x4.shared.b16 [%0], {%1,%2,%3,%4};" :: "r"(a), "r"(r0), "r"(r1), "r"(r2), "r"(r3) : "memory");
}
__device__ __forceinline__ void stsm4t(uint32_t a, uint32_t r0, uint32_t r1, uint32_t r2, uint32_t r3) {
  asm volatile("stmatrix.sync.aligned.m8n8.x4.trans.shared.b16 [%0], {%1,%2,%3,%4};" :: "r"(a), "r"(r0), "r"(r1), "r"(r2), "r"(r3) : "memory");
}
__device__ __forceinline__ void mma_bf16(float* d, uint32_t a0, uint32_t a1, uint32_t a2, uint32_t a3, uint32_t b0, uint32_t b1) {
  asm volatile("mma.sync.aligned.m16n8k16.row.col.f32.bf16.bf16.f32 {%0,%1,%2,%3}, {%4,%5,%6,%7}, {%8,%9}, {%0,%1,%2,%3};"
               : "+f"(d[0]), "+f"(d[1]), "+f"(d[2]), "+f"(d[3]) : "r"(a0), "r"(a1), "r"(a2), "r"(a3), "r"(b0), "r"(b1));
}
template<int SD> __device__ __forceinline__ void wg_qs24(float* d, uint64_t da, uint64_t db) {
  asm volatile("wgmma.mma_async.sync.aligned.m64n24k16.f32.f16.f16 {%0,%1,%2,%3,%4,%5,%6,%7,%8,%9,%10,%11}, %12, %13, %14, 1, 1, 0, 0;"
   : "+f"(d[0]),"+f"(d[1]),"+f"(d[2]),"+f"(d[3]),"+f"(d[4]),"+f"(d[5]),"+f"(d[6]),"+f"(d[7]),"+f"(d[8]),"+f"(d[9]),"+f"(d[10]),"+f"(d[11])
   : "l"(da),"l"(db),"n"(SD));
}
template<int SD> __device__ __forceinline__ void wg_qs72(float* d, uint64_t da, uint64_t db) {
  asm volatile("wgmma.mma_async.sync.aligned.m64n72k16.f32.f16.f16 {%0,%1,%2,%3,%4,%5,%6,%7,%8,%9,%10,%11,%12,%13,%14,%15,%16,%17,%18,%19,%20,%21,%22,%23,%24,%25,%26,%27,%28,%29,%30,%31,%32,%33,%34,%35}, %36, %37, %38, 1, 1, 0, 0;"
   : "+f"(d[0]),"+f"(d[1]),"+f"(d[2]),"+f"(d[3]),"+f"(d[4]),"+f"(d[5]),"+f"(d[6]),"+f"(d[7]),"+f"(d[8]),"+f"(d[9]),"+f"(d[10]),"+f"(d[11]),"+f"(d[12]),"+f"(d[13]),"+f"(d[14]),"+f"(d[15]),"+f"(d[16]),"+f"(d[17]),"+f"(d[18]),"+f"(d[19]),"+f"(d[20]),"+f"(d[21]),"+f"(d[22]),"+f"(d[23]),"+f"(d[24]),"+f"(d[25]),"+f"(d[26]),"+f"(d[27]),"+f"(d[28]),"+f"(d[29]),"+f"(d[30]),"+f"(d[31]),"+f"(d[32]),"+f"(d[33]),"+f"(d[34]),"+f"(d[35])
   : "l"(da),"l"(db),"n"(SD));
}
template<int SD> __device__ __forceinline__ void wg_pv24(float* d, const uint32_t* a, uint64_t desc) {
  asm volatile("wgmma.mma_async.sync.aligned.m64n24k16.f32.bf16.bf16 {%0,%1,%2,%3,%4,%5,%6,%7,%8,%9,%10,%11}, {%12,%13,%14,%15}, %16, %17, 1, 1, 1;"
   : "+f"(d[0]),"+f"(d[1]),"+f"(d[2]),"+f"(d[3]),"+f"(d[4]),"+f"(d[5]),"+f"(d[6]),"+f"(d[7]),"+f"(d[8]),"+f"(d[9]),"+f"(d[10]),"+f"(d[11])
   : "r"(a[0]),"r"(a[1]),"r"(a[2]),"r"(a[3]),"l"(desc),"n"(SD));
}
template<int TA, int TB> __device__ __forceinline__ void wg_ss128(float* d, uint64_t da, uint64_t db, int sd) {
  asm volatile("{\n.reg .pred p;\nsetp.ne.b32 p, %66, 0;\n"
   "wgmma.mma_async.sync.aligned.m64n128k16.f32.bf16.bf16 {%0,%1,%2,%3,%4,%5,%6,%7,%8,%9,%10,%11,%12,%13,%14,%15,%16,%17,%18,%19,%20,%21,%22,%23,%24,%25,%26,%27,%28,%29,%30,%31,%32,%33,%34,%35,%36,%37,%38,%39,%40,%41,%42,%43,%44,%45,%46,%47,%48,%49,%50,%51,%52,%53,%54,%55,%56,%57,%58,%59,%60,%61,%62,%63}, %64, %65, p, 1, 1, %67, %68;\n}\n"
   : "+f"(d[0]),"+f"(d[1]),"+f"(d[2]),"+f"(d[3]),"+f"(d[4]),"+f"(d[5]),"+f"(d[6]),"+f"(d[7]),"+f"(d[8]),"+f"(d[9]),"+f"(d[10]),"+f"(d[11]),"+f"(d[12]),"+f"(d[13]),"+f"(d[14]),"+f"(d[15]),"+f"(d[16]),"+f"(d[17]),"+f"(d[18]),"+f"(d[19]),"+f"(d[20]),"+f"(d[21]),"+f"(d[22]),"+f"(d[23]),"+f"(d[24]),"+f"(d[25]),"+f"(d[26]),"+f"(d[27]),"+f"(d[28]),"+f"(d[29]),"+f"(d[30]),"+f"(d[31]),"+f"(d[32]),"+f"(d[33]),"+f"(d[34]),"+f"(d[35]),"+f"(d[36]),"+f"(d[37]),"+f"(d[38]),"+f"(d[39]),"+f"(d[40]),"+f"(d[41]),"+f"(d[42]),"+f"(d[43]),"+f"(d[44]),"+f"(d[45]),"+f"(d[46]),"+f"(d[47]),"+f"(d[48]),"+f"(d[49]),"+f"(d[50]),"+f"(d[51]),"+f"(d[52]),"+f"(d[53]),"+f"(d[54]),"+f"(d[55]),"+f"(d[56]),"+f"(d[57]),"+f"(d[58]),"+f"(d[59]),"+f"(d[60]),"+f"(d[61]),"+f"(d[62]),"+f"(d[63])
   : "l"(da),"l"(db),"r"(sd),"n"(TA),"n"(TB));
}
template<int TA, int TB> __device__ __forceinline__ void wg_ss64(float* d, uint64_t da, uint64_t db, int sd) {
  asm volatile("{\n.reg .pred p;\nsetp.ne.b32 p, %34, 0;\n"
   "wgmma.mma_async.sync.aligned.m64n64k16.f32.bf16.bf16 {%0,%1,%2,%3,%4,%5,%6,%7,%8,%9,%10,%11,%12,%13,%14,%15,%16,%17,%18,%19,%20,%21,%22,%23,%24,%25,%26,%27,%28,%29,%30,%31}, %32, %33, p, 1, 1, %35, %36;\n}\n"
   : "+f"(d[0]),"+f"(d[1]),"+f"(d[2]),"+f"(d[3]),"+f"(d[4]),"+f"(d[5]),"+f"(d[6]),"+f"(d[7]),"+f"(d[8]),"+f"(d[9]),"+f"(d[10]),"+f"(d[11]),"+f"(d[12]),"+f"(d[13]),"+f"(d[14]),"+f"(d[15]),"+f"(d[16]),"+f"(d[17]),"+f"(d[18]),"+f"(d[19]),"+f"(d[20]),"+f"(d[21]),"+f"(d[22]),"+f"(d[23]),"+f"(d[24]),"+f"(d[25]),"+f"(d[26]),"+f"(d[27]),"+f"(d[28]),"+f"(d[29]),"+f"(d[30]),"+f"(d[31])
   : "l"(da),"l"(db),"r"(sd),"n"(TA),"n"(TB));
}
template<int TA, int TB> __device__ __forceinline__ void wg_ss8(float* d, uint64_t da, uint64_t db, int sd) {
  asm volatile("{\n.reg .pred p;\nsetp.ne.b32 p, %6, 0;\n"
   "wgmma.mma_async.sync.aligned.m64n8k16.f32.bf16.bf16 {%0,%1,%2,%3}, %4, %5, p, 1, 1, %7, %8;\n}\n"
   : "+f"(d[0]),"+f"(d[1]),"+f"(d[2]),"+f"(d[3])
   : "l"(da),"l"(db),"r"(sd),"n"(TA),"n"(TB));
}

__device__ __forceinline__ uint32_t phi2(float a, float b) {
  uint32_t r, e;
  asm("cvt.rn.relu.bf16x2.f32 %0, %1, %2;" : "=r"(r) : "f"(b), "f"(a));
  e = pack_bf16(ex2f(a * 1.4426950408889634f), ex2f(b * 1.4426950408889634f));
  asm("add.rn.bf16x2 %0, %0, %1;" : "+r"(e) : "r"(0x35863586u));
  asm("min.NaN.bf16x2 %0, %0, %1;" : "+r"(e) : "r"(0x3F803F80u));
  asm("add.rn.bf16x2 %0, %0, %1;" : "+r"(e) : "r"(r));
  return e;
}

__device__ __forceinline__ void mbar_wait_long(uint32_t bar, uint32_t parity) {
  asm volatile("{\n.reg .pred p;\n.reg .u32 c;\nmov.u32 c, 0;\n"
               "LW_%=:\n"
               "mbarrier.try_wait.parity.shared::cta.b64 p, [%0], %1, 100000;\n"
               "@p bra LD_%=;\n"
               "add.u32 c, c, 1;\n"
               "setp.lt.u32 p, c, 20000;\n"
               "@p bra LW_%=;\n"
               "trap;\n"
               "LD_%=:\n}\n" :: "r"(bar), "r"(parity) : "memory");
}
__device__ __forceinline__ void mbar_arrive(uint32_t bar) { asm volatile("mbarrier.arrive.shared::cta.b64 _, [%0];" :: "r"(bar) : "memory"); }
__device__ __forceinline__ void named_arrive(int id, int n) { asm volatile("bar.arrive %0, %1;" :: "r"(id), "r"(n) : "memory"); }
__device__ __forceinline__ void fence_async_all() { asm volatile("fence.proxy.async.global;" ::: "memory"); }
__device__ __forceinline__ void flag_add(uint32_t* f) { asm volatile("fence.acq_rel.gpu;\nred.relaxed.gpu.global.add.u32 [%0], 1;" :: "l"(f) : "memory"); }
#define PUBLISH(f) asm volatile("fence.proxy.async.global;\nred.relaxed.gpu.global.add.u32 [%0], 1;" :: "l"(f) : "memory")
__device__ __forceinline__ void flag_wait(const uint32_t* f, uint32_t target) {
  uint32_t v;
#pragma unroll 1
  for (int it = 0;; it++) {
    asm volatile("ld.acquire.gpu.global.u32 %0, [%1];" : "=r"(v) : "l"(f) : "memory");
    if ((int32_t)(v - target) >= 0) break;
    if (it > 2000000) __trap();
    __nanosleep(64);
  }
}
__device__ __forceinline__ bool mbar_test(uint32_t bar, uint32_t parity) {
  uint32_t ok;
  asm volatile("{\n.reg .pred p;\nmbarrier.test_wait.parity.shared::cta.b64 p, [%1], %2;\nselp.b32 %0, 1, 0, p;\n}\n" : "=r"(ok) : "r"(bar), "r"(parity) : "memory");
  return ok;
}
__device__ __forceinline__ bool elect_one() {
  uint32_t p;
  asm volatile("{\n.reg .pred P;\nelect.sync _|P, 0xFFFFFFFF;\nselp.b32 %0, 1, 0, P;\n}\n" : "=r"(p));
  return p;
}
__device__ __forceinline__ void lds4(uint32_t a, uint32_t* r) {
  asm volatile("ld.shared.v4.b32 {%0,%1,%2,%3}, [%4];" : "=r"(r[0]), "=r"(r[1]), "=r"(r[2]), "=r"(r[3]) : "r"(a) : "memory");
}
__device__ __forceinline__ uint32_t lds1(uint32_t a) { uint32_t r; asm volatile("ld.shared.b32 %0, [%1];" : "=r"(r) : "r"(a) : "memory"); return r; }
__device__ __forceinline__ void sts1(uint32_t a, uint32_t v) { asm volatile("st.shared.b32 [%0], %1;" :: "r"(a), "r"(v) : "memory"); }
__device__ __forceinline__ void sts4(uint32_t a, uint32_t r0, uint32_t r1, uint32_t r2, uint32_t r3) {
  asm volatile("st.shared.v4.b32 [%0], {%1,%2,%3,%4};" :: "r"(a), "r"(r0), "r"(r1), "r"(r2), "r"(r3) : "memory");
}
__device__ __forceinline__ void ldsm4(uint32_t a, uint32_t* r) {
  asm volatile("ldmatrix.sync.aligned.m8n8.x4.shared.b16 {%0,%1,%2,%3}, [%4];" : "=r"(r[0]), "=r"(r[1]), "=r"(r[2]), "=r"(r[3]) : "r"(a) : "memory");
}
__device__ __forceinline__ float rcpf(float x) { float y; asm("rcp.approx.ftz.f32 %0, %1;" : "=f"(y) : "f"(x)); return y; }
__device__ __forceinline__ uint32_t hfma2(uint32_t a, uint32_t b, uint32_t c) { uint32_t r; asm("fma.rn.f16x2 %0, %1, %2, %3;" : "=r"(r) : "r"(a), "r"(b), "r"(c)); return r; }
__device__ __forceinline__ uint32_t hadd2(uint32_t a, uint32_t b) { uint32_t r; asm("add.rn.f16x2 %0, %1, %2;" : "=r"(r) : "r"(a), "r"(b)); return r; }

#define STEPK 96
#define QSCALE 0.36067376022224085f
#define SMAGIC (512.0f + 2.0f * (191.0f - 30.0f - 1.5823545f))
#define VSHIFT 1073741824.0f

__device__ uint32_t g_epoch[132];
__device__ uint32_t g_flag[288 * 8];
#define FLAG_KV (g_flag)
#define FLAG_B(h) (g_flag + (4 + (h)) * 8)
#define FLAG_OA(cta, pass) (g_flag + (16 + (cta) * 2 + (pass)) * 8)
#define FLAG_LM(i) (g_flag + (272 + (i)) * 8)

#define SM_TOTAL (224 * 1024 + 2048 + 1024)
#define OFF_K 0
#define OFF_F 65536
#define OFF_V 131072
#define OFF_MISC (224 * 1024)

#define BAR_FULL(s) (bars + 8 * (s))
#define BAR_EMPTY(s) (bars + 24 + 8 * (s))
#define BAR_KV(c) (bars + 48 + 8 * (c))
#define BAR_BDONE (bars + 80)
#define BAR_Q (bars + 88)
#define BAR_GO (bars + 96)
#define BAR_Q2 (bars + 104)
#define BAR_OD(p) (bars + 112 + 8 * (p))
#define BAR_CL(c) (bars + 128 + 8 * (c))
#define BAR_TE(i) (bars + 168 + 8 * (i))
#define BAR_RL (bars + 184)
#define BAR_TF(g) (bars + 224 + 8 * (g))
#define BAR_XA(w) (bars + 352 + 8 * (w))
#define BAR_VB(c) (bars + 384 + 8 * (c))

__device__ __forceinline__ uint32_t exp2_pair_fix(float d0, float d1, uint32_t c63, uint32_t m1) {
  uint32_t w, y, s, r;
  asm("prmt.b32 %0, %1, %2, 0x6521;" : "=r"(w) : "r"(__float_as_uint(d0)), "r"(__float_as_uint(d1)));
  asm("lop3.b32 %0, %1, 0x007F007F, %2, 0xEA;" : "=r"(y) : "r"(w), "r"(c63));
  asm("mad.lo.u32 %0, %1, %2, %3;" : "=r"(s) : "r"(y), "r"(m1), "r"(w));
  asm("fma.rn.bf16x2 %0, %1, %2, %3;" : "=r"(r) : "r"(w), "r"(y), "r"(s));
  return r;
}

__device__ __forceinline__ void attn_slow(const uint4* gq, uint32_t dst) {
  const int t = threadIdx.x & 127;
  const int row = t >> 1, half = t & 1;
  float q[16];
#pragma unroll
  for (int i = 0; i < 4; i++) {
    const uint4 v = gq[(row >> 4) * 32 + (row & 7) * 4 + i];
    const uint32_t lo = (row & 8) ? v.y : v.x, hi = (row & 8) ? v.w : v.z;
    q[2 * i] = bf_lo(lo); q[2 * i + 1] = bf_hi(lo); q[2 * i + 8] = bf_lo(hi); q[2 * i + 9] = bf_hi(hi);
  }
  float m = -INFINITY, l = 0.f, o[16];
#pragma unroll
  for (int i = 0; i < 16; i++) o[i] = 0.f;
#pragma unroll 1
  for (int j = half * 1024; j < half * 1024 + 1024; j++) {
    uint4 ka = g_KV[4 * S_TOK + j], kb = g_KV[5 * S_TOK + j];
    uint4 va = g_KV[6 * S_TOK + j], vb = g_KV[7 * S_TOK + j];
    uint32_t kk[8] = {ka.x, ka.y, ka.z, ka.w, kb.x, kb.y, kb.z, kb.w};
    uint32_t vv[8] = {va.x, va.y, va.z, va.w, vb.x, vb.y, vb.z, vb.w};
    float s = 0.f;
#pragma unroll
    for (int i = 0; i < 8; i++) { s = fmaf(q[2 * i], bf_lo(kk[i]), s); s = fmaf(q[2 * i + 1], bf_hi(kk[i]), s); }
    s = rbf(s) * 0.25f;
    if (s > m) {
      float c = __expf(m - s);
      l *= c;
#pragma unroll
      for (int i = 0; i < 16; i++) o[i] *= c;
      m = s;
    }
    float p = __expf(s - m);
    l += p;
#pragma unroll
    for (int i = 0; i < 8; i++) { o[2 * i] = fmaf(p, bf_lo(vv[i]), o[2 * i]); o[2 * i + 1] = fmaf(p, bf_hi(vv[i]), o[2 * i + 1]); }
  }
  float m2 = __shfl_xor_sync(~0u, m, 1);
  float mm = fmaxf(m, m2);
  float c = __expf(m - mm);
  l *= c; l += __shfl_xor_sync(~0u, l, 1);
  float inv = 1.f / l;
  uint32_t r[8];
#pragma unroll
  for (int i = 0; i < 16; i++) { o[i] *= c; o[i] += __shfl_xor_sync(~0u, o[i], 1); o[i] *= inv; }
#pragma unroll
  for (int i = 0; i < 8; i++) r[i] = pack_bf16(o[2 * i], o[2 * i + 1]);
  if (half == 0) sts4(dst, r[0], r[1], r[2], r[3]); else sts4(dst, r[4], r[5], r[6], r[7]);
  fence_async();
}

struct Params { const __nv_bfloat16* wk; const __nv_bfloat16* wv; const __nv_bfloat16* xa; };
__device__ __forceinline__ void cp16(uint32_t dst, const void* src) { asm volatile("cp.async.cg.shared.global [%0], [%1], 16;" :: "r"(dst), "l"(src) : "memory"); }

__device__ __forceinline__ void helper_cta(const int h, const uint32_t sb, const uint32_t bars, const int wg, const int w4,
                                           const CUtensorMap* mQ, const CUtensorMap* mOs) {
  const int lane = threadIdx.x & 31;
  mbar_wait(BAR_GO, 0);
  const int cb = wg & 1, col = h * 128 + cb * 64, row0 = S_TOK + (wg >> 1) * 1024;
  const uint32_t buf = sb + wg * 49152;
  if (w4 == 0 && elect_one()) {
    fence_async_all();
#pragma unroll 1
    for (int u = 0; u < 3; u++) {
      mbar_expect_tx(BAR_TF(wg * 3 + u), 16384);
      tma2d(buf + u * 16384, mQ, col, row0 + u * 128, BAR_TF(wg * 3 + u));
    }
  }
  const int head = h * 8 + cb * 4 + w4;
  float4 a0 = make_float4(0, 0, 0, 0), a1 = a0, a2 = a0;
#pragma unroll 8
  for (int tt = 0; tt < 16; tt++) {
    const float4* src = g_kvp + ((tt * 32 + head) * 3) * 32 + lane;
    float4 u = src[0], v = src[32], w = src[64];
    a0.x += u.x; a0.y += u.y; a0.z += u.z; a0.w += u.w;
    a1.x += v.x; a1.y += v.y; a1.z += v.z; a1.w += v.w;
    a2.x += w.x; a2.y += w.y; a2.z += w.z; a2.w += w.w;
  }
  const uint32_t b00 = pack_bf16(a0.x, a0.y), b01 = pack_bf16(a0.z, a0.w);
  const uint32_t b10 = pack_bf16(a1.x, a1.y), b11 = pack_bf16(a1.z, a1.w);
  const uint32_t bz0 = pack_bf16(a2.x, a2.y), bz1 = pack_bf16(a2.z, a2.w);
  const int m = lane >> 3, r = lane & 7;
  const uint32_t off = ((m & 1) * 8 + r) * 128 + (((w4 * 2 + (m >> 1)) ^ r) << 4);
  int s = 0, ph = 0;
#pragma unroll 1
  for (int u = 0; u < 8; u++) {
    const uint32_t bb = buf + s * 16384;
    mbar_wait(BAR_TF(wg * 3 + s), ph);
#pragma unroll
    for (int mt = 0; mt < 8; mt++) {
      uint32_t a[4];
      ldsm4(bb + mt * 2048 + off, a);
      float n0[4] = {0, 0, 0, 0}, n1[4] = {0, 0, 0, 0}, dn[4] = {0, 0, 0, 0};
      mma_bf16(dn, a[0], a[1], a[2], a[3], bz0, bz1);
      mma_bf16(n0, a[0], a[1], a[2], a[3], b00, b01);
      mma_bf16(n1, a[0], a[1], a[2], a[3], b10, b11);
      const float i0 = rcpf(dn[0] + 1e-6f), i1 = rcpf(dn[2] + 1e-6f);
      stsm4(bb + mt * 2048 + off, pack_bf16(n0[0] * i0, n0[1] * i0), pack_bf16(n0[2] * i1, n0[3] * i1),
            pack_bf16(n1[0] * i0, n1[1] * i0), pack_bf16(n1[2] * i1, n1[3] * i1));
    }
    fence_async();
    named_bar(wg + 1, 128);
    if (w4 == 0 && lane == 0) {
      tma2d_store(mOs, bb, col, row0 + u * 128);
      bulk_commit();
      if (u >= 1 && u + 2 < 8) {
        asm volatile("cp.async.bulk.wait_group.read 1;" ::: "memory");
        const int sp = s == 0 ? 2 : s - 1;
        mbar_expect_tx(BAR_TF(wg * 3 + sp), 16384);
        tma2d(buf + sp * 16384, mQ, col, row0 + (u + 2) * 128, BAR_TF(wg * 3 + sp));
      }
    }
    __syncwarp();
    if (++s == 3) { s = 0; ph ^= 1; }
  }
  if (w4 == 0 && lane == 0) {
    bulk_wait_all();
    fence_async_all();
    flag_add(FLAG_LM((h * 2 + cb) * 2 + (wg >> 1)));
    if (wg == 0) TS(1, 8);
  }
}

#define STAGE(s) (sb + (2 - (s)) * 65536)
template <int TR> __device__ __forceinline__ void proj_kb(float* acc, uint32_t st, uint32_t offA, uint32_t offB, int first) {
  const uint64_t da = make_desc(st + offA, TR ? 8192 : 16, 1024, 1);
  const uint64_t db = make_desc(st + offB, TR ? 16 : 8192, 1024, 1);
  wg_fence();
#pragma unroll
  for (int k = 0; k < 4; k++) wg_ss128<TR, 1 - TR>(acc, da + k * (TR ? 128 : 2), db + k * (TR ? 2 : 128), k != 0 || !first);
  wg_commit();
}
template <int TR> __device__ __forceinline__ void proj_loop(float* acc, uint32_t sb, uint32_t bars, uint32_t offA, uint32_t offB,
                                                            int wg, uint32_t sWKV) {
  {
    float kv[4];
    if (threadIdx.x == 0) TS(0, 13);
    mbar_wait(BAR_XA(wg), 0);
    if (threadIdx.x == 0) TS(0, 1);
    const uint64_t da = make_desc(STAGE(2) + wg * 16384, 16, 1024, 1), db = make_desc(sWKV + wg * 2048, 128, 128, 0);
    wg_fence();
#pragma unroll
    for (int k = 0; k < 8; k++) wg_ss8<0, 1>(kv, da + (k >> 2) * 512 + (k & 3) * 2, db + k * 16, k != 0);
    wg_commit();
    wg_wait<0>();
    fence_regs<4>(kv);
    named_bar(wg + 1, 128);
    sts4(sWKV + threadIdx.x * 16, __float_as_uint(kv[0]), __float_as_uint(kv[1]), __float_as_uint(kv[2]), __float_as_uint(kv[3]));
    __syncwarp();
    if ((threadIdx.x & 31) == 0) mbar_arrive(BAR_GO);
  }
  int s = 0, ph = 0, sp = 0;
#pragma unroll 1
  for (int kb = 0; kb < 8; kb++) {
    mbar_wait(BAR_FULL(s), ph);
    if (threadIdx.x == 0) TS(0, 2 + kb);
    proj_kb<TR>(acc, STAGE(s), offA, offB, kb == 0);
    wg_wait<1>();
    if (kb >= 1 && (threadIdx.x & 127) == 0) mbar_arrive(BAR_EMPTY(sp));
    __syncwarp();
    sp = s;
    if (++s == 3) { s = 0; ph ^= 1; }
  }
  wg_wait<0>();
  fence_regs<64>(acc);
}

__device__ __forceinline__ uint32_t tail_slots(int isB, int n) {
  if (n < 4) return n < 2 ? (n == 0 ? 0x0D0C0B0Au : 0x04000F0Eu) : (n == 2 ? 0x18141008u : 0x15110501u);
  if (isB) return n < 6 ? (n == 4 ? 0x19120602u : 0x0D0C0B0Au) : (n == 6 ? 0x04000F0Eu : 0x13070316u);
  return n < 6 ? (n == 4 ? 0x1902031Au : 0x12061307u) : (n == 6 ? 0x16091B17u : 0x0D0C0B0Au);
}

__device__ __forceinline__ void take_role(uint32_t sM, int wg) {
  uint32_t r;
  asm volatile("atom.shared.add.u32 %0, [%1], 1;" : "=r"(r) : "r"(sM + 20) : "memory");
  sts1(sM + 32 + wg * 4, r);
}

__global__ void __launch_bounds__(640, 1)
k1_main(const __grid_constant__ CUtensorMap mXA64, const __grid_constant__ CUtensorMap mXB,
        const __grid_constant__ CUtensorMap mWq, const __grid_constant__ CUtensorMap mWqkv,
        const __grid_constant__ CUtensorMap mQst, const __grid_constant__ CUtensorMap mOst,
        const __grid_constant__ CUtensorMap mO, const __grid_constant__ CUtensorMap mWoA,
        const __grid_constant__ CUtensorMap mWoB, const __grid_constant__ CUtensorMap mOut,
        const __grid_constant__ CUtensorMap mO16, const Params prm) {
  extern __shared__ uint8_t smem_raw[];
  const uint32_t sb = (smem_u32(smem_raw) + 1023u) & ~1023u;
  const uint32_t bars = sb + OFF_MISC, sM = bars + 512, sT = bars + 1024;
  const int tid = threadIdx.x, warp = __shfl_sync(~0u, tid >> 5, 0), wg = warp >> 2, w4 = warp & 3, lane = tid & 31;
  const bool helper = blockIdx.x >= 128;
  if (tid == 0) TS(0, 0);
  const int G = blockIdx.x >> 4, gi = blockIdx.x & 15;
  const int tbA = G * 4 + (gi >> 2), hg = gi & 3;
  const int ttB = (G >> 1) * 4 + (gi >> 2), hq = (G & 1) * 4 + (gi & 3);
  const int isB = tbA & 1, tok0 = (tbA >> 1) * 128;
  auto issue = [&](int kb, int s) {
    const uint32_t fb = BAR_FULL(s), st = STAGE(s);
    mbar_expect_tx(fb, 65536);
    tma2d(st + 16384, &mXA64, kb * 64, tbA * 64, fb);
    tma2d(st, &mWq, hg * 128, kb * 64, fb);
    tma2d(st + 8192, &mWq, hg * 128 + 64, kb * 64, fb);
    tma2d(st + 49152, &mXB, kb * 64, ttB * 128, fb);
    tma2d(st + 24576, &mWqkv, hq * 64, kb * 64, fb);
    tma2d(st + 32768, &mWqkv, 512 + hq * 64, kb * 64, fb);
    tma2d(st + 40960, &mWqkv, 1024 + hq * 64, kb * 64, fb);
  };
  const uint32_t sOne = sb + OFF_V + 65536, sWKV = sOne + 24576;
  if (warp >= 16) {
    if (warp == 17) {
      if (elect_one()) {
        mbar_init(BAR_BDONE, 8); mbar_init(BAR_Q, 8); mbar_init(BAR_GO, helper ? 1 : 16); mbar_init(BAR_Q2, 5);
        mbar_init(BAR_OD(0), 16); mbar_init(BAR_OD(1), 16); mbar_init(BAR_CL(0), 1); mbar_init(BAR_FULL(2), 1);
#pragma unroll
        for (int i = 0; i < 4; i++) mbar_init(BAR_CL(i + 1), i == 0 ? 5 : 4);
#pragma unroll
        for (int i = 0; i < 3; i++) { mbar_init(BAR_EMPTY(i), 4); mbar_init(BAR_KV(i), 1); mbar_init(BAR_VB(i), 1); }
        sts1(sM + 20, 0);
        asm volatile("fence.mbarrier_init.release.cluster;" ::: "memory");
      }
    } else if (warp == 18) {
      if (elect_one()) {
#pragma unroll
        for (int i = 0; i < 2; i++) mbar_init(BAR_TE(i), 2);
        mbar_init(BAR_RL, 1);
#pragma unroll
        for (int i = 0; i < 16; i++) mbar_init(BAR_TF(i), 1);
        asm volatile("fence.mbarrier_init.release.cluster;" ::: "memory");
      }
    } else if (warp == 16 && !helper && elect_one()) {
#pragma unroll
      for (int w = 0; w < 4; w++) mbar_init(BAR_XA(w), 1);
      mbar_init(BAR_FULL(0), 1); mbar_init(BAR_FULL(1), 1);
      asm volatile("fence.mbarrier_init.release.cluster;" ::: "memory");
#pragma unroll
      for (int w = 0; w < 4; w++) {
        mbar_expect_tx(BAR_XA(w), 16384);
        tma2d(STAGE(2) + w * 16384, &mXA64, w * 128, tbA * 64, BAR_XA(w));
        tma2d(STAGE(2) + w * 16384 + 8192, &mXA64, w * 128 + 64, tbA * 64, BAR_XA(w));
      }
      TS(0, 14);
      issue(0, 0);
    }
  } else if (!helper) {
    const uint4 v = __ldg((const uint4*)(hg >= 2 ? prm.wv : prm.wk) + tid * 2 + (hg & 1));
#pragma unroll
    for (int i = 0; i < 3; i++) {
      const int key = tid + i * 512;
      sts4(sOne + key * 16, (key % STEPK) < 24 ? 0x00003F80u : 0x00004E80u, 0u, 0u, 0u);
    }
    sts4(sWKV + tid * 16, v.x, v.y, v.z, v.w);
    fence_async();
  }
  __syncthreads();
  if (wg == 4) {
    if (w4 == 0 && !helper && elect_one()) { issue(1, 1); TS(0, 15); }
    asm volatile("setmaxnreg.dec.sync.aligned.u32 32;");
    const uint32_t ep = g_epoch[blockIdx.x] + 1;
    if (helper) {
      if (w4 == 0 && elect_one()) {
        flag_wait(FLAG_B(blockIdx.x - 128), ep * 32);
        fence_async_all();
        TS(1, 10);
        mbar_arrive(BAR_GO);
        g_epoch[blockIdx.x] = ep;
      }
      return;
    }
    mbar_wait(BAR_GO, 0);
    if (w4 == 0 && elect_one()) issue(2, 2);
    {
      uint32_t a[4], b[4];
      float c[4];
      lds4(sWKV + (tid - 512) * 16, a);
      lds4(sWKV + 2048 + (tid - 512) * 16, b);
#pragma unroll
      for (int i = 0; i < 4; i++) c[i] = __uint_as_float(a[i]) + __uint_as_float(b[i]);
      lds4(sWKV + 4096 + (tid - 512) * 16, a);
      lds4(sWKV + 6144 + (tid - 512) * 16, b);
#pragma unroll
      for (int i = 0; i < 4; i++) c[i] += __uint_as_float(a[i]) + __uint_as_float(b[i]);
      sts1(sT + w4 * 256 + lane * 4, pack_bf16(c[0], c[1]));
      sts1(sT + w4 * 256 + 128 + lane * 4, pack_bf16(c[2], c[3]));
    }
    named_bar(9, 128);
    {
      const int t = tid - 512;
#pragma unroll
      for (int i = 0; i < 4; i++) {
        const int key = 1536 + t + i * 128;
        sts4(sOne + key * 16, (key % STEPK) < 24 ? 0x00003F80u : 0x00004E80u, 0u, 0u, 0u);
      }
      fence_async();
      __syncwarp();
      if (lane == 0) mbar_arrive(BAR_Q);
    }
    if (w4 == 0) {
      int s = 0, ph = 0;
#pragma unroll 1
      for (int kb = 3; kb < 8; kb++) {
        mbar_wait(BAR_EMPTY(s), ph);
        if (elect_one()) issue(kb, s);
        if (++s == 3) { s = 0; ph ^= 1; }
      }
      flag_wait(FLAG_KV, ep * 128);
      fence_async_all();
      if (lane == 0) TS(0, 11);
#pragma unroll 1
      for (int m = 0; m < 2; m++) {
        mbar_wait(m == 0 ? BAR_EMPTY(2) : BAR_EMPTY(0), 1 - m);
        if (elect_one()) {
          const uint32_t fb = m == 0 ? BAR_KV(0) : BAR_VB(0);
          mbar_expect_tx(fb, 2 * 7 * STEPK * 16);
#pragma unroll
          for (int p = 0; p < 2; p++) bulk_g2s(sb + m * OFF_V + p * 32768, g_KV + (m * 2 + p) * S_TOK, 7 * STEPK * 16, fb);
        }
      }
      mbar_wait(BAR_Q, 0);
      if (elect_one()) {
#pragma unroll
        for (int c = 1; c < 3; c++) {
          const int k0 = c == 1 ? 7 * STEPK : 12 * STEPK, k1 = c == 1 ? 12 * STEPK : S_TOK;
          const uint32_t bytes = (k1 - k0) * 16;
          mbar_expect_tx(BAR_KV(c), 4 * bytes);
#pragma unroll
          for (int p = 0; p < 4; p++)
            bulk_g2s(sb + (p >> 1) * OFF_V + (p & 1) * 32768 + k0 * 16, g_KV + p * S_TOK + k0, bytes, BAR_KV(c));
        }
      }
      mbar_wait_long(BAR_CL(1), 0);
      flag_wait(isB ? FLAG_LM((lane & 7) * 2 + (tbA >> 4)) : FLAG_OA(tbA * 4 + (lane & 7), 0), ep);
      __syncwarp();
      fence_async_all();
      if (lane == 0) TS(2, 13);
      const CUtensorMap* mW = isB ? &mWoB : &mWoA;
#pragma unroll 1
      for (int it = 0; it < 8; it++) {
        const int n = (!isB && it >= 6) ? 13 - it : it;
        uint32_t wb = BAR_CL(n < 3 ? 0 : (n == 3 ? 2 : 3));
        if (isB) { if (n >= 5) wb = n == 7 ? BAR_CL(4) : BAR_TE(n - 5); }
        else if (n >= 6) wb = n == 6 ? BAR_CL(4) : BAR_TE(0);
        if (it < 6) mbar_wait_long(wb, 0); else mbar_wait(wb, 0);
        const uint32_t sl = tail_slots(isB, n), fb = BAR_TF(n);
        const bool withX = isB || n < 4;
        const int k0 = isB ? n * 64 : (n < 4 ? n * 128 : ((hg + n) & 3) * 128 + 64);
        if (elect_one()) {
          mbar_expect_tx(fb, withX ? 32768 : 16384);
          if (withX) {
            tma2d(sb + (sl & 255) * 8192, &mO, k0, isB * S_TOK + tok0, fb);
            tma2d(sb + ((sl >> 8) & 255) * 8192, &mO, k0, isB * S_TOK + tok0 + 64, fb);
          }
          tma2d(sb + ((sl >> 16) & 255) * 8192, mW, hg * 128, k0, fb);
          tma2d(sb + (sl >> 24) * 8192, mW, hg * 128 + 64, k0, fb);
        }
      }
      if (lane == 0) g_epoch[blockIdx.x] = ep;
    } else if (w4 == 3) {
      flag_wait(FLAG_KV, ep * 128);
      const uint4 a = *(const uint4*)(g_stats + lane * 4);
      const float kmax2 = __uint_as_float(__reduce_max_sync(~0u, a.x)) + __uint_as_float(__reduce_max_sync(~0u, a.y));
      const float vmax = __uint_as_float(__reduce_max_sync(~0u, max(a.z, a.w)));
      const float lv = vmax > 0.f ? __log2f(vmax) : 0.f;
      const float lim = fminf(90.f, fminf(91.f + lv, 95.f - lv));
      float thr = -1.f;
      if (vmax < 1e27f && kmax2 <= 65536.f && lim > 2.f) thr = fminf(60000.f, (lim * lim - 1.f) / (kmax2 * 1.02f + 1e-30f));
      if (lane == 0) { sts1(sM + 16, __float_as_uint(thr)); mbar_arrive(BAR_Q2); }
    } else {
      const int tok = (w4 - 1) * 32 + lane;
      int step, col;
      if ((tbA & 3) == 0) {
        const int b8 = tbA >> 2;
        if (tok < 22) { step = tok; col = 24 + b8; }
        else { const int c = tok >= 43; step = tok - 22 - 21 * c; col = 32 + b8 * 2 + c; }
      } else {
        const int b24 = (tbA >> 2) * 3 + (tbA & 3) - 1;
        if (tok < 42) { const int c = tok >= 21; step = tok - 21 * c; col = 48 + b24 * 2 + c; }
        else { step = tok - 42; col = b24; }
      }
      const int kap = step * STEPK + col;
      const bool chained = col >= 24;
      uint32_t v[4], o[4];
      lds4(sT + tok * 16, v);
      g_KV[(4 + hg) * S_TOK + kap] = make_uint4(v[0], v[1], v[2], v[3]);
      float st = 0.f;
      if (hg < 2) {
        o[0] = o[1] = o[2] = o[3] = 0;
        if (chained && step > 0) lds4(sT + tok * 16 - 16, o);
        const float sc = chained ? 2.f : 1.f;
#pragma unroll
        for (int u = 0; u < 4; u++) {
          const float x = bf_lo(v[u]), y = bf_hi(v[u]);
          st += x * x + y * y;
          o[u] = pack_f16((x - bf_lo(o[u])) * sc, (y - bf_hi(o[u])) * sc);
        }
      } else {
        const float sc = chained ? VSHIFT : 1.f;
#pragma unroll
        for (int u = 0; u < 4; u++) { float x = bf_lo(v[u]), y = bf_hi(v[u]); st += fabsf(x) + fabsf(y); o[u] = pack_bf16(x * sc, y * sc); }
      }
      g_KV[hg * S_TOK + kap] = make_uint4(o[0], o[1], o[2], o[3]);
      const uint32_t um = __reduce_max_sync(~0u, __float_as_uint(st) & 0x7FFFFFFFu);
      if (w4 == 2) {
        if (lane == 0) sts1(sM + 24, um);
        named_arrive(10, 64);
        if (!isB) {
          mbar_wait_long(BAR_CL(3), 0);
          mbar_wait_long(BAR_RL, 0);
          uint32_t pend = 0xFE;
          const int li = lane & 7;
          const uint32_t* fl = FLAG_OA((tbA + (li & 1)) * 4 + ((hg + (li >> 1)) & 3), 1);
#pragma unroll 1
          for (int it = 0; pend; it++) {
            uint32_t fv;
            asm volatile("ld.acquire.gpu.global.u32 %0, [%1];" : "=r"(fv) : "l"(fl) : "memory");
            uint32_t go = __ballot_sync(~0u, (int32_t)(fv - ep) >= 0 && mbar_test(li >= 6 ? BAR_TE(0) : BAR_CL(4), 0)) & pend;
            pend &= ~go;
            if (go) fence_async_all();
#pragma unroll 1
            while (go) {
              const int b = __ffs(go) - 1;
              go &= go - 1;
              const uint32_t slot = (tail_slots(0, 4 + (b >> 1)) >> (8 * (b & 1))) & 255;
              if (elect_one()) {
                mbar_expect_tx(BAR_TF(8 + b), 8192);
                tma2d(sb + slot * 8192, &mO, ((hg + (b >> 1)) & 3) * 128 + 64, tok0 + (b & 1) * 64, BAR_TF(8 + b));
              }
            }
            if (it > 2000000) __trap();
          }
          if (lane == 0) TS(2, 14);
        }
      }
      else {
        named_bar(10, 64);
        if (elect_one()) {
          g_stats[tbA * 4 + hg] = max(um, lds1(sM + 24));
          fence_async_all();
          flag_add(FLAG_KV);
          TS(1, 9);
          mbar_wait_long(BAR_BDONE, 0);
          tma2d_store(&mQst, sb + OFF_F + 49152, hq * 64, S_TOK + ttB * 128);
          bulk_commit();
          bulk_wait_all();
          fence_async_all();
          flag_add(FLAG_B(hq >> 1));
          TS(0, 12);
          mbar_wait(BAR_Q, 0);
          mbar_arrive(BAR_CL(0));
#pragma unroll 1
          for (int p = 0; p < 2; p++) {
            mbar_wait_long(BAR_OD(p), 0);
            if (p == 0) {
#pragma unroll
              for (int w = 0; w < 4; w++) tma2d_store(&mO16, sb + OFF_F + w * 2048, hg * 128 + w * 16, tbA * 64);
            } else {
              tma2d_store(&mO, sb + 26 * 8192, hg * 128 + 64, tbA * 64);
            }
            bulk_commit();
            bulk_wait_all();
            if (p == 0) mbar_arrive(BAR_CL(1));
            PUBLISH(FLAG_OA(blockIdx.x, p));
          }
          TS(2, 0);
        }
      }
    }
    return;
  }
  if (helper) { helper_cta(blockIdx.x - 128, sb, bars, wg, w4, &mQst, &mOst); return; }

  {
    float acc[64];
    if (wg == 0) proj_loop<0>(acc, sb, bars, 16384, 0, wg, sWKV);
    else proj_loop<1>(acc, sb, bars, 16384 + wg * 8192, 49152, wg, sWKV);
    if (tid == 0) TS(0, 10);
    const uint32_t sF = sb + OFF_F;
    const uint32_t qa = sF + w4 * 512 + ((lane >> 3) & 1) * 256 + (lane >> 4) * 128 + (lane & 7) * 16;
    if (wg == 0) {
#pragma unroll
      for (int hd = 0; hd < 4; hd++)
        stsm4(qa + hd * 2048, pack_f16(acc[8 * hd] * QSCALE, acc[8 * hd + 1] * QSCALE), pack_f16(acc[8 * hd + 2] * QSCALE, acc[8 * hd + 3] * QSCALE),
              pack_f16(acc[8 * hd + 4] * QSCALE, acc[8 * hd + 5] * QSCALE), pack_f16(acc[8 * hd + 6] * QSCALE, acc[8 * hd + 7] * QSCALE));
      fence_async();
      __syncwarp();
      if (lane == 0) mbar_arrive(BAR_Q);
    } else {
      if (wg != 3) named_arrive(6, 384);
      if (wg != 1) named_arrive(8, 384);
    }
    asm volatile("setmaxnreg.inc.sync.aligned.u32 112;");
    fence_regs<64>(acc);
    if (wg == 0) {
      uint32_t r[32];
#pragma unroll
      for (int hd = 0; hd < 8; hd++) {
#pragma unroll
        for (int i = 0; i < 4; i++) r[4 * hd + i] = pack_f16(acc[8 * hd + 2 * i] * QSCALE, acc[8 * hd + 2 * i + 1] * QSCALE);
        if (hd >= 4) stsm4(qa + hd * 2048, r[4 * hd], r[4 * hd + 1], r[4 * hd + 2], r[4 * hd + 3]);
      }
      fence_async();
      uint32_t nmax = 0;
#pragma unroll
      for (int hd = 0; hd < 8; hd++) {
        const uint32_t* q = r + 4 * hd;
        const uint32_t t0 = hfma2(q[2], q[2], hfma2(q[0], q[0], 0u)), t1 = hfma2(q[3], q[3], hfma2(q[1], q[1], 0u));
        uint32_t n = hadd2(__byte_perm(t0, t1, 0x5410), __byte_perm(t0, t1, 0x7632));
        n = hadd2(n, __shfl_xor_sync(~0u, n, 1));
        n = hadd2(n, __shfl_xor_sync(~0u, n, 2));
        nmax = __vmaxu2(nmax, n & 0x7FFF7FFFu);
      }
      nmax = __reduce_max_sync(~0u, max(nmax & 0xFFFFu, nmax >> 16));
      if (lane == 0) sts1(sM + w4 * 4, nmax);
      uint4* gq = (uint4*)g_Q + blockIdx.x * 1024 + tid;
#pragma unroll
      for (int hd = 0; hd < 8; hd++)
        gq[hd * 128] = make_uint4(pack_bf16(acc[8 * hd], acc[8 * hd + 1]), pack_bf16(acc[8 * hd + 2], acc[8 * hd + 3]),
                                  pack_bf16(acc[8 * hd + 4], acc[8 * hd + 5]), pack_bf16(acc[8 * hd + 6], acc[8 * hd + 7]));
      __syncwarp();
      if (lane == 0) mbar_arrive(BAR_Q2);
    } else if (wg == 3) {
      named_bar(6, 384);
      const int t = tid & 127;
#pragma unroll
      for (int j = 0; j < 8; j++)
        sts4(sF + 24576 + j * 2048 + t * 16, pack_bf16(acc[8 * j], acc[8 * j + 1]), pack_bf16(acc[8 * j + 2], acc[8 * j + 3]),
             pack_bf16(acc[8 * j + 4], acc[8 * j + 5]), pack_bf16(acc[8 * j + 6], acc[8 * j + 7]));
      named_arrive(7, 256);
    } else {
      uint32_t p[32];
#pragma unroll
      for (int i = 0; i < 32; i++) p[i] = phi2(acc[2 * i], acc[2 * i + 1]);
      if (wg == 1) {
        named_bar(8, 384);
        const int m = lane >> 3, r = lane & 7;
#pragma unroll
        for (int j = 0; j < 16; j += 2) {
          const int tok = (j + (m >> 1)) * 8 + r;
          const int chunk = w4 * 2 + (m & 1);
          stsm4t(sF + 49152 + tok * 128 + ((chunk ^ r) << 4), p[2 * j], p[2 * j + 1], p[2 * j + 2], p[2 * j + 3]);
        }
        fence_async();
      } else {
        named_bar(7, 256);
        float kv0[4] = {0, 0, 0, 0}, kv1[4] = {0, 0, 0, 0}, z0[4] = {0, 0, 0, 0}, z1[4] = {0, 0, 0, 0};
        const uint32_t one = 0x3F803F80u;
        const int t = tid & 127;
#pragma unroll
        for (int j = 0; j < 8; j++) {
          uint32_t a[4];
          lds4(sF + 24576 + j * 2048 + t * 16, a);
          mma_bf16(kv0, a[0], a[1], a[2], a[3], p[4 * j], p[4 * j + 2]);
          mma_bf16(kv1, a[0], a[1], a[2], a[3], p[4 * j + 1], p[4 * j + 3]);
          mma_bf16(z0, one, one, one, one, p[4 * j], p[4 * j + 2]);
          mma_bf16(z1, one, one, one, one, p[4 * j + 1], p[4 * j + 3]);
        }
        float4* dst = g_kvp + ((ttB * 32 + hq * 4 + w4) * 3) * 32 + lane;
        dst[0] = make_float4(kv0[0], kv0[1], kv1[0], kv1[1]);
        dst[32] = make_float4(kv0[2], kv0[3], kv1[2], kv1[3]);
        dst[64] = make_float4(z0[0], z0[1], z1[0], z1[1]);
      }
      __syncwarp();
      if (lane == 0) mbar_arrive(BAR_BDONE);
    }
  }

  bool safe = true;
  {
    const uint32_t c63 = 0x1F801F80u + (threadIdx.x >> 20);
    const uint32_t m1 = (gridDim.x >> 20) - 1u;
    const uint64_t dK0 = make_desc(sb + OFF_K, 32768, 128, 0);
    const uint64_t dV0 = make_desc(sb + OFF_V, 128, 32768, 0);
    constexpr uint32_t dKV = ((2048u - 8u)  __H0__ ) + STEPK - (OFF_V - OFF_K) / 16;
    float Sm[12], Sp[36], O[12];
    uint32_t P[24];
    uint64_t dQ = make_desc(sb + OFF_F + wg * 2048, 128, 256, 0);
#pragma unroll
    for (int i = 0; i < 36; i++) Sp[i] = SMAGIC;
#pragma unroll
    for (int i = 0; i < 12; i++) Sm[i] = 0.f;
    fence_regs<12>(Sm); fence_regs<36>(Sp);
    mbar_wait(BAR_Q, 0);
    mbar_wait(BAR_KV(0), 0);
    wg_fence();
    wg_qs72<1>(Sp, dQ, dK0 + 24);
    wg_qs24<0>(Sm, dQ, dK0);
    wg_commit();
    wg_wait<0>();
    fence_regs<12>(Sm); fence_regs<36>(Sp);
#pragma unroll 1
    for (int pass = 0; pass < 2; pass++) {
#pragma unroll
      for (int i = 0; i < 12; i++) O[i] = 0.f;
      fence_regs<12>(O);
      if (tid == 0) TS(1, 2 + 2 * pass);
      uint32_t vlo = (uint32_t)dV0;
#pragma unroll 1
      for (int seg = 0; seg < 4; seg++) {
        if (pass == 0) {
          if (seg < 3) mbar_wait(seg == 0 ? BAR_VB(0) : BAR_KV(seg), 0);
        } else if (seg >= 1) {
          if ((tid & 127) == 0) {
            mbar_arrive(BAR_CL(seg));
            if (seg == 3) take_role(sM, wg);
          }
          __syncwarp();
        }
        if ((tid & 127) == 0) TS(4 + wg, pass * 5 + seg);
        const uint32_t vend = vlo + (seg == 0 ? 6 : 5) * STEPK;
#pragma unroll 1
        for (; vlo != vend; vlo += STEPK) {
          uint64_t dK, dV;
          asm("mov.b64 %0, {%1, %2};" : "=l"(dK) : "r"(vlo + dKV), "r"(8u));
          asm("mov.b64 %0, {%1, %2};" : "=l"(dV) : "r"(vlo), "r"(2048u));
#pragma unroll
          for (int i = 0; i < 6; i++) P[i] = pack_bf16(ex2f(Sm[2 * i]), ex2f(Sm[2 * i + 1]));
#pragma unroll
          for (int i = 0; i < 18; i++) P[6 + i] = exp2_pair_fix(Sp[2 * i], Sp[2 * i + 1], c63, m1);
          fence_regs<24>(P);
          wg_fence();
#pragma unroll
          for (int k = 0; k < 6; k++) wg_pv24<1>(O, &P[4 * k], dV + k * 16);
          wg_qs72<1>(Sp, dQ, dK + 24);
          wg_qs24<0>(Sm, dQ, dK);
          wg_commit();
          wg_wait<0>();
          fence_regs<12>(Sm); fence_regs<36>(Sp); fence_regs<12>(O); fence_regs<24>(P);
        }
      }
#pragma unroll
      for (int i = 0; i < 6; i++) P[i] = pack_bf16(ex2f(Sm[2 * i]), ex2f(Sm[2 * i + 1]));
      P[6] = exp2_pair_fix(Sp[0], Sp[1], c63, m1);
      P[7] = exp2_pair_fix(Sp[2], Sp[3], c63, m1);
      fence_regs<8>(P);
#pragma unroll
      for (int i = 0; i < 36; i++) Sp[i] = SMAGIC;
      fence_regs<36>(Sp);
      mbar_wait(pass == 0 ? BAR_Q2 : BAR_CL(3), 0);
      const uint32_t sO = pass == 0 ? sb + OFF_F + wg * 2048 + w4 * 512 + (lane & 15) * 32 + (lane >> 4) * 16
                                    : sb + 26 * 8192 + (w4 * 16 + (lane & 15)) * 128 + (((wg * 2 + (lane >> 4)) ^ (lane & 7)) << 4);
      dQ += 512;
      wg_fence();
      wg_pv24<1>(O, &P[0], dV0 + 21 * STEPK);
      wg_pv24<1>(O, &P[4], dV0 + 21 * STEPK + 16);
      wg_commit();
      wg_qs72<1>(Sp, dQ, dK0 + 24);
      wg_qs24<0>(Sm, dQ, dK0);
      wg_commit();
      wg_wait<1>();
      fence_regs<12>(O);
      const float l0 = __shfl_sync(~0u, O[8], lane & ~3), l1 = __shfl_sync(~0u, O[10], lane & ~3);
      const float i0 = rcpf(l0), i1 = rcpf(l1);
      stsm4(sO,
            pack_bf16(O[0] * i0, O[1] * i0), pack_bf16(O[2] * i1, O[3] * i1),
            pack_bf16(O[4] * i0, O[5] * i0), pack_bf16(O[6] * i1, O[7] * i1));
      fence_async();
      {
        uint32_t n[4];
        lds4(sM, n);
        const float qn = __half2float(__ushort_as_half((unsigned short)max(max(n[0], n[1]), max(n[2], n[3]))));
        safe = __all_sync(~0u, qn <= __uint_as_float(lds1(sM + 16)));
      }
      if (safe && lane == 0) mbar_arrive(BAR_OD(pass));
      wg_wait<0>();
      fence_regs<12>(Sm); fence_regs<36>(Sp);
      if (!safe) break;
      if ((tid & 127) == 0) TS(4 + wg, pass * 5 + 4);
      if (tid == 0) TS(1, 3 + 2 * pass);
    }
  }
  if (!safe) {
    if ((tid & 127) == 0) { mbar_arrive(BAR_CL(1)); mbar_arrive(BAR_CL(2)); mbar_arrive(BAR_CL(3)); take_role(sM, wg); }
#pragma unroll 1
    for (int pass = 0; pass < 2; pass++) {
      const int t = tid & 127;
      mbar_wait(BAR_CL(3), 0);
      attn_slow((const uint4*)g_Q + blockIdx.x * 1024 + (pass * 4 + wg) * 128,
                pass == 0 ? sb + OFF_F + wg * 2048 + t * 16
                          : sb + 26 * 8192 + (t >> 1) * 128 + (((wg * 2 + (t & 1)) ^ ((t >> 1) & 7)) << 4));
      __syncwarp();
      if (lane == 0) mbar_arrive(BAR_OD(pass));
    }
  }

  {
    named_bar(wg + 1, 128);
    if ((tid & 127) == 0) mbar_arrive(BAR_CL(4));
    const int role = __shfl_sync(~0u, lds1(sM + 32 + wg * 4), 0);
    if ((tid & 127) == 0) TS(4 + wg, 10);
    const int m = lane >> 3, r = lane & 7;
    const uint32_t stoff = (w4 * 16 + (m & 1) * 8 + r) * 128;
    if (role < 2) {
      if (role == 0 && (tid & 127) == 0) mbar_arrive(BAR_RL);
      float acc[64];
#pragma unroll 1
      for (int n = 0; n < 8; n++) {
        const uint32_t sl = tail_slots(isB, n);
        const uint32_t w0 = (sl >> 16) & 255, w1 = sl >> 24;
        const uint64_t da = make_desc(sb + ((sl >> (8 * role)) & 255) * 8192, 16, 1024, 1);
        const uint64_t db = make_desc(sb + w0 * 8192, (w1 - w0) * 8192, 1024, 1);
        mbar_wait(BAR_TF(n), 0);
        if (!isB && n >= 4) mbar_wait(n == 4 && role == 0 ? BAR_OD(1) : BAR_TF(2 * n + role), 0);
        if ((tid & 127) == 0 && role == 1) TS(2, 2 + n);
        wg_fence();
#pragma unroll
        for (int k = 0; k < 4; k++) wg_ss128<0, 1>(acc, da + k * 2, db + k * 128, (n | k) != 0);
        wg_commit();
        wg_wait<1>();
        if ((n == 1 || n == 2) && (tid & 127) == 0) mbar_arrive(BAR_TE(n - 1));
        __syncwarp();
      }
      wg_wait<0>();
      fence_regs<64>(acc);
      if ((tid & 127) == 0) TS(4 + wg, 11);
      const uint32_t x0 = sb + (role ? 16 : 8) * 8192, x1 = sb + (role ? 5 : 1) * 8192;
#pragma unroll
      for (int j = 0; j < 16; j += 2)
        stsm4((j < 8 ? x0 : x1) + stoff + ((((j & 7) + (m >> 1)) ^ r) << 4),
              pack_bf16(acc[4 * j], acc[4 * j + 1]), pack_bf16(acc[4 * j + 2], acc[4 * j + 3]),
              pack_bf16(acc[4 * j + 4], acc[4 * j + 5]), pack_bf16(acc[4 * j + 6], acc[4 * j + 7]));
      fence_async();
      named_bar(wg + 1, 128);
      if (w4 == 0 && elect_one()) {
        tma2d_store(&mOut, x0, isB * 512 + hg * 128, tok0 + role * 64);
        tma2d_store(&mOut, x1, isB * 512 + hg * 128 + 64, tok0 + role * 64);
        bulk_commit();
        asm volatile("cp.async.bulk.wait_group.read 0;" ::: "memory");
        TS(2, 11 + role);
      }
    }
  }
}

typedef CUresult (*EncodeFn)(CUtensorMap*, CUtensorMapDataType, cuuint32_t, void*, const cuuint64_t*, const cuuint64_t*,
                             const cuuint32_t*, const cuuint32_t*, CUtensorMapInterleave, CUtensorMapSwizzle,
                             CUtensorMapL2promotion, CUtensorMapFloatOOBfill);

static void make_map(EncodeFn enc, CUtensorMap* m, const void* ptr, uint64_t cols, uint64_t rows, uint32_t bc, uint32_t br,
                     CUtensorMapSwizzle sw = CU_TENSOR_MAP_SWIZZLE_128B) {
  cuuint64_t dims[2] = {cols, rows};
  cuuint64_t strides[1] = {cols * 2};
  cuuint32_t box[2] = {bc, br};
  cuuint32_t es[2] = {1, 1};
  enc(m, CU_TENSOR_MAP_DATA_TYPE_BFLOAT16, 2, (void*)ptr, dims, strides, box, es, CU_TENSOR_MAP_INTERLEAVE_NONE,
      sw, CU_TENSOR_MAP_L2_PROMOTION_L2_256B, CU_TENSOR_MAP_FLOAT_OOB_FILL_NONE);
}

extern "C" void kernel_launch(void* const* d_in, const int* in_sizes, int n_in, void* d_out, int out_size) {
  (void)in_sizes; (void)n_in; (void)out_size;
  static EncodeFn enc = nullptr;
  static void* pQ = nullptr; static void* pO = nullptr;
  if (!enc) {
    void* fn = nullptr; cudaDriverEntryPointQueryResult qr;
    cudaGetDriverEntryPoint("cuTensorMapEncodeTiled", &fn, cudaEnableDefault, &qr);
    enc = (EncodeFn)fn;
    cudaGetSymbolAddress(&pQ, g_Q);
    cudaGetSymbolAddress(&pO, g_O);
    cudaFuncSetAttribute(k1_main, cudaFuncAttributeMaxDynamicSharedMemorySize, SM_TOTAL);
  }
  CUtensorMap mXA64, mXB, mWq, mWqkv, mQst, mO, mOst, mWoA, mWoB, mOut, mO16;
  make_map(enc, &mXA64, d_in[0], 512, 2048, 64, 64);
  make_map(enc, &mWq, d_in[1], 512, 512, 64, 64);
  make_map(enc, &mWoA, d_in[4], 512, 512, 64, 64);
  make_map(enc, &mXB, d_in[5], 512, 2048, 64, 128);
  make_map(enc, &mWqkv, d_in[6], 1536, 512, 64, 64);
  make_map(enc, &mWoB, d_in[7], 512, 512, 64, 64);
  make_map(enc, &mQst, pQ, 512, 4096, 64, 128);
  make_map(enc, &mO, pO, 512, 4096, 64, 64);
  make_map(enc, &mOst, pO, 512, 4096, 64, 128);
  make_map(enc, &mOut, d_out, 1024, 2048, 64, 64);
  make_map(enc, &mO16, pO, 512, 4096, 16, 64, CU_TENSOR_MAP_SWIZZLE_NONE);
  Params prm{(const __nv_bfloat16*)d_in[2], (const __nv_bfloat16*)d_in[3], (const __nv_bfloat16*)d_in[0]};
  k1_main<<<132, 640, SM_TOTAL, cudaStreamPerThread>>>(mXA64, mXB, mWq, mWqkv, mQst, mOst, mO, mWoA, mWoB, mOut, mO16, prm);
}
```

```cpp
#include <cuda_runtime.h>
#include <cuda_bf16.h>
#include <cuda_fp16.h>
#include <cuda.h>
#include <stdint.h>

#define S_TOK 2048
#define D_MOD 512

__device__ __align__(1024) __nv_bfloat16 g_Q[2 * S_TOK * D_MOD];
__device__ __align__(1024) __nv_bfloat16 g_O[2 * S_TOK * D_MOD];
__device__ __align__(1024) uint4 g_KV[8 * S_TOK];
__device__ __align__(16) uint32_t g_stats[128];
__device__ __align__(16) float4 g_kvp[16 * 32 * 3 * 32];

#define TS(k, i) do {} while (0)
__device__ __forceinline__ uint32_t smem_u32(const void* p) { return (uint32_t)__cvta_generic_to_shared(p); }
__device__ __forceinline__ void mbar_init(uint32_t bar, int cnt) { asm volatile("mbarrier.init.shared::cta.b64 [%0], %1;" :: "r"(bar), "r"(cnt) : "memory"); }
__device__ __forceinline__ void mbar_expect_tx(uint32_t bar, uint32_t bytes) { asm volatile("mbarrier.arrive.expect_tx.shared::cta.b64 _, [%0], %1;" :: "r"(bar), "r"(bytes) : "memory"); }
__device__ __forceinline__ bool mbar_try(uint32_t bar, uint32_t parity) {
  uint32_t ok;
  asm volatile("{\n.reg .pred p;\nmbarrier.try_wait.parity.shared::cta.b64 p, [%1], %2;\nselp.b32 %0, 1, 0, p;\n}\n" : "=r"(ok) : "r"(bar), "r"(parity) : "memory");
  return ok;
}
__device__ __forceinline__ void mbar_wait(uint32_t bar, uint32_t parity) {
  asm volatile("{\n.reg .pred p;\n.reg .u32 c;\nmov.u32 c, 0;\n"
               "LW_%=:\n"
               "mbarrier.try_wait.parity.shared::cta.b64 p, [%0], %1;\n"
               "@p bra LD_%=;\n"
               "add.u32 c, c, 1;\n"
               "setp.lt.u32 p, c, 4000000;\n"
               "@p bra LW_%=;\n"
               "trap;\n"
               "LD_%=:\n}\n" :: "r"(bar), "r"(parity) : "memory");
}
__device__ __forceinline__ void mbar_arrive_cta(uint32_t bar, uint32_t cta) {
  asm volatile("{\n.reg .b32 ra;\nmapa.shared::cluster.u32 ra, %0, %1;\nmbarrier.arrive.shared::cluster.b64 _, [ra];\n}\n" :: "r"(bar), "r"(cta) : "memory");
}
__device__ __forceinline__ void cluster_sync() {
  asm volatile("barrier.cluster.arrive.relaxed.aligned;\nbarrier.cluster.wait.aligned;" ::: "memory");
}
__device__ __forceinline__ void tma2d(uint32_t dst, const CUtensorMap* m, int c0, int c1, uint32_t bar) {
  asm volatile("cp.async.bulk.tensor.2d.shared::cluster.global.mbarrier::complete_tx::bytes [%0], [%1, {%3, %4}], [%2];"
               :: "r"(dst), "l"(m), "r"(bar), "r"(c0), "r"(c1) : "memory");
}
__device__ __forceinline__ void tma2d_mc(uint32_t dst, const CUtensorMap* m, int c0, int c1, uint32_t bar, uint16_t mask) {
  asm volatile("cp.async.bulk.tensor.2d.shared::cluster.global.mbarrier::complete_tx::bytes.multicast::cluster [%0], [%1, {%3, %4}], [%2], %5;"
               :: "r"(dst), "l"(m), "r"(bar), "r"(c0), "r"(c1), "h"(mask) : "memory");
}
__device__ __forceinline__ void tma2d_store(const CUtensorMap* m, uint32_t src, int c0, int c1) {
  asm volatile("cp.async.bulk.tensor.2d.global.shared::cta.bulk_group [%0, {%2, %3}], [%1];"
               :: "l"(m), "r"(src), "r"(c0), "r"(c1) : "memory");
}
__device__ __forceinline__ void bulk_g2s(uint32_t dst, const void* src, uint32_t bytes, uint32_t bar) {
  asm volatile("cp.async.bulk.shared::cluster.global.mbarrier::complete_tx::bytes [%0], [%1], %2, [%3];"
               :: "r"(dst), "l"(src), "r"(bytes), "r"(bar) : "memory");
}
__device__ __forceinline__ void bulk_commit() { asm volatile("cp.async.bulk.commit_group;" ::: "memory"); }
__device__ __forceinline__ void bulk_wait_all() { asm volatile("cp.async.bulk.wait_group 0;" ::: "memory"); }
__device__ __forceinline__ void fence_async() { asm volatile("fence.proxy.async.shared::cta;" ::: "memory"); }
__device__ __forceinline__ void named_bar(int id, int n) { asm volatile("bar.sync %0, %1;" :: "r"(id), "r"(n) : "memory"); }
__device__ __forceinline__ void pdl_launch() { asm volatile("griddepcontrol.launch_dependents;" ::: "memory"); }
__device__ __forceinline__ void pdl_wait() { asm volatile("griddepcontrol.wait;" ::: "memory"); }
__device__ __forceinline__ void wg_fence() { asm volatile("wgmma.fence.sync.aligned;" ::: "memory"); }
__device__ __forceinline__ void wg_commit() { asm volatile("wgmma.commit_group.sync.aligned;" ::: "memory"); }
template <int n> __device__ __forceinline__ void wg_wait() { asm volatile("wgmma.wait_group.sync.aligned %0;" :: "n"(n) : "memory"); }
template <int n> __device__ __forceinline__ void fence_regs(float* r) {
#pragma unroll
  for (int i = 0; i < n; i++) asm volatile("" : "+f"(r[i]) :: "memory");
}
template <int n> __device__ __forceinline__ void fence_regs(uint32_t* r) {
#pragma unroll
  for (int i = 0; i < n; i++) asm volatile("" : "+r"(r[i]) :: "memory");
}
__device__ __forceinline__ uint64_t make_desc(uint32_t addr, uint32_t lbo, uint32_t sbo, uint32_t swz) {
  return (uint64_t)((addr & 0x3FFFF) >> 4) | ((uint64_t)(lbo >> 4) << 16) | ((uint64_t)(sbo >> 4) << 32) | ((uint64_t)swz << 62);
}
__device__ __forceinline__ float ex2f(float x) { float y; asm("ex2.approx.ftz.f32 %0, %1;" : "=f"(y) : "f"(x)); return y; }
__device__ __forceinline__ uint32_t pack_bf16(float lo, float hi) { uint32_t r; asm("cvt.rn.bf16x2.f32 %0, %1, %2;" : "=r"(r) : "f"(hi), "f"(lo)); return r; }
__device__ __forceinline__ uint32_t pack_f16(float lo, float hi) { uint32_t r; asm("cvt.rn.f16x2.f32 %0, %1, %2;" : "=r"(r) : "f"(hi), "f"(lo)); return r; }
__device__ __forceinline__ float bf_lo(uint32_t v) { return __uint_as_float(v << 16); }
__device__ __forceinline__ float bf_hi(uint32_t v) { return __uint_as_float(v & 0xFFFF0000u); }
__device__ __forceinline__ float rbf(float x) { return __bfloat162float(__float2bfloat16_rn(x)); }
__device__ __forceinline__ void stsm4(uint32_t a, uint32_t r0, uint32_t r1, uint32_t r2, uint32_t r3) {
  asm volatile("stmatrix.sync.aligned.m8n8.x4.shared.b16 [%0], {%1,%2,%3,%4};" :: "r"(a), "r"(r0), "r"(r1), "r"(r2), "r"(r3) : "memory");
}
__device__ __forceinline__ void stsm4t(uint32_t a, uint32_t r0, uint32_t r1, uint32_t r2, uint32_t r3) {
  asm volatile("stmatrix.sync.aligned.m8n8.x4.trans.shared.b16 [%0], {%1,%2,%3,%4};" :: "r"(a), "r"(r0), "r"(r1), "r"(r2), "r"(r3) : "memory");
}
__device__ __forceinline__ void mma_bf16(float* d, uint32_t a0, uint32_t a1, uint32_t a2, uint32_t a3, uint32_t b0, uint32_t b1) {
  asm volatile("mma.sync.aligned.m16n8k16.row.col.f32.bf16.bf16.f32 {%0,%1,%2,%3}, {%4,%5,%6,%7}, {%8,%9}, {%0,%1,%2,%3};"
               : "+f"(d[0]), "+f"(d[1]), "+f"(d[2]), "+f"(d[3]) : "r"(a0), "r"(a1), "r"(a2), "r"(a3), "r"(b0), "r"(b1));
}
template<int SD> __device__ __forceinline__ void wg_qs24(float* d, uint64_t da, uint64_t db) {
  asm volatile("wgmma.mma_async.sync.aligned.m64n24k16.f32.f16.f16 {%0,%1,%2,%3,%4,%5,%6,%7,%8,%9,%10,%11}, %12, %13, %14, 1, 1, 0, 0;"
   : "+f"(d[0]),"+f"(d[1]),"+f"(d[2]),"+f"(d[3]),"+f"(d[4]),"+f"(d[5]),"+f"(d[6]),"+f"(d[7]),"+f"(d[8]),"+f"(d[9]),"+f"(d[10]),"+f"(d[11])
   : "l"(da),"l"(db),"n"(SD));
}
template<int SD> __device__ __forceinline__ void wg_qs72(float* d, uint64_t da, uint64_t db) {
  asm volatile("wgmma.mma_async.sync.aligned.m64n72k16.f32.f16.f16 {%0,%1,%2,%3,%4,%5,%6,%7,%8,%9,%10,%11,%12,%13,%14,%15,%16,%17,%18,%19,%20,%21,%22,%23,%24,%25,%26,%27,%28,%29,%30,%31,%32,%33,%34,%35}, %36, %37, %38, 1, 1, 0, 0;"
   : "+f"(d[0]),"+f"(d[1]),"+f"(d[2]),"+f"(d[3]),"+f"(d[4]),"+f"(d[5]),"+f"(d[6]),"+f"(d[7]),"+f"(d[8]),"+f"(d[9]),"+f"(d[10]),"+f"(d[11]),"+f"(d[12]),"+f"(d[13]),"+f"(d[14]),"+f"(d[15]),"+f"(d[16]),"+f"(d[17]),"+f"(d[18]),"+f"(d[19]),"+f"(d[20]),"+f"(d[21]),"+f"(d[22]),"+f"(d[23]),"+f"(d[24]),"+f"(d[25]),"+f"(d[26]),"+f"(d[27]),"+f"(d[28]),"+f"(d[29]),"+f"(d[30]),"+f"(d[31]),"+f"(d[32]),"+f"(d[33]),"+f"(d[34]),"+f"(d[35])
   : "l"(da),"l"(db),"n"(SD));
}
template<int SD> __device__ __forceinline__ void wg_pv24(float* d, const uint32_t* a, uint64_t desc) {
  asm volatile("wgmma.mma_async.sync.aligned.m64n24k16.f32.bf16.bf16 {%0,%1,%2,%3,%4,%5,%6,%7,%8,%9,%10,%11}, {%12,%13,%14,%15}, %16, %17, 1, 1, 1;"
   : "+f"(d[0]),"+f"(d[1]),"+f"(d[2]),"+f"(d[3]),"+f"(d[4]),"+f"(d[5]),"+f"(d[6]),"+f"(d[7]),"+f"(d[8]),"+f"(d[9]),"+f"(d[10]),"+f"(d[11])
   : "r"(a[0]),"r"(a[1]),"r"(a[2]),"r"(a[3]),"l"(desc),"n"(SD));
}
template<int TA, int TB> __device__ __forceinline__ void wg_ss128(float* d, uint64_t da, uint64_t db, int sd) {
  asm volatile("{\n.reg .pred p;\nsetp.ne.b32 p, %66, 0;\n"
   "wgmma.mma_async.sync.aligned.m64n128k16.f32.bf16.bf16 {%0,%1,%2,%3,%4,%5,%6,%7,%8,%9,%10,%11,%12,%13,%14,%15,%16,%17,%18,%19,%20,%21,%22,%23,%24,%25,%26,%27,%28,%29,%30,%31,%32,%33,%34,%35,%36,%37,%38,%39,%40,%41,%42,%43,%44,%45,%46,%47,%48,%49,%50,%51,%52,%53,%54,%55,%56,%57,%58,%59,%60,%61,%62,%63}, %64, %65, p, 1, 1, %67, %68;\n}\n"
   : "+f"(d[0]),"+f"(d[1]),"+f"(d[2]),"+f"(d[3]),"+f"(d[4]),"+f"(d[5]),"+f"(d[6]),"+f"(d[7]),"+f"(d[8]),"+f"(d[9]),"+f"(d[10]),"+f"(d[11]),"+f"(d[12]),"+f"(d[13]),"+f"(d[14]),"+f"(d[15]),"+f"(d[16]),"+f"(d[17]),"+f"(d[18]),"+f"(d[19]),"+f"(d[20]),"+f"(d[21]),"+f"(d[22]),"+f"(d[23]),"+f"(d[24]),"+f"(d[25]),"+f"(d[26]),"+f"(d[27]),"+f"(d[28]),"+f"(d[29]),"+f"(d[30]),"+f"(d[31]),"+f"(d[32]),"+f"(d[33]),"+f"(d[34]),"+f"(d[35]),"+f"(d[36]),"+f"(d[37]),"+f"(d[38]),"+f"(d[39]),"+f"(d[40]),"+f"(d[41]),"+f"(d[42]),"+f"(d[43]),"+f"(d[44]),"+f"(d[45]),"+f"(d[46]),"+f"(d[47]),"+f"(d[48]),"+f"(d[49]),"+f"(d[50]),"+f"(d[51]),"+f"(d[52]),"+f"(d[53]),"+f"(d[54]),"+f"(d[55]),"+f"(d[56]),"+f"(d[57]),"+f"(d[58]),"+f"(d[59]),"+f"(d[60]),"+f"(d[61]),"+f"(d[62]),"+f"(d[63])
   : "l"(da),"l"(db),"r"(sd),"n"(TA),"n"(TB));
}
template<int TA, int TB> __device__ __forceinline__ void wg_ss64(float* d, uint64_t da, uint64_t db, int sd) {
  asm volatile("{\n.reg .pred p;\nsetp.ne.b32 p, %34, 0;\n"
   "wgmma.mma_async.sync.aligned.m64n64k16.f32.bf16.bf16 {%0,%1,%2,%3,%4,%5,%6,%7,%8,%9,%10,%11,%12,%13,%14,%15,%16,%17,%18,%19,%20,%21,%22,%23,%24,%25,%26,%27,%28,%29,%30,%31}, %32, %33, p, 1, 1, %35, %36;\n}\n"
   : "+f"(d[0]),"+f"(d[1]),"+f"(d[2]),"+f"(d[3]),"+f"(d[4]),"+f"(d[5]),"+f"(d[6]),"+f"(d[7]),"+f"(d[8]),"+f"(d[9]),"+f"(d[10]),"+f"(d[11]),"+f"(d[12]),"+f"(d[13]),"+f"(d[14]),"+f"(d[15]),"+f"(d[16]),"+f"(d[17]),"+f"(d[18]),"+f"(d[19]),"+f"(d[20]),"+f"(d[21]),"+f"(d[22]),"+f"(d[23]),"+f"(d[24]),"+f"(d[25]),"+f"(d[26]),"+f"(d[27]),"+f"(d[28]),"+f"(d[29]),"+f"(d[30]),"+f"(d[31])
   : "l"(da),"l"(db),"r"(sd),"n"(TA),"n"(TB));
}
template<int TA, int TB> __device__ __forceinline__ void wg_ss8(float* d, uint64_t da, uint64_t db, int sd) {
  asm volatile("{\n.reg .pred p;\nsetp.ne.b32 p, %6, 0;\n"
   "wgmma.mma_async.sync.aligned.m64n8k16.f32.bf16.bf16 {%0,%1,%2,%3}, %4, %5, p, 1, 1, %7, %8;\n}\n"
   : "+f"(d[0]),"+f"(d[1]),"+f"(d[2]),"+f"(d[3])
   : "l"(da),"l"(db),"r"(sd),"n"(TA),"n"(TB));
}

__device__ __forceinline__ uint32_t phi2(float a, float b) {
  uint32_t r, e;
  asm("cvt.rn.relu.bf16x2.f32 %0, %1, %2;" : "=r"(r) : "f"(b), "f"(a));
  e = pack_bf16(ex2f(a * 1.4426950408889634f), ex2f(b * 1.4426950408889634f));
  asm("add.rn.bf16x2 %0, %0, %1;" : "+r"(e) : "r"(0x35863586u));
  asm("min.NaN.bf16x2 %0, %0, %1;" : "+r"(e) : "r"(0x3F803F80u));
  asm("add.rn.bf16x2 %0, %0, %1;" : "+r"(e) : "r"(r));
  return e;
}

__device__ __forceinline__ void mbar_wait_long(uint32_t bar, uint32_t parity) {
  asm volatile("{\n.reg .pred p;\n.reg .u32 c;\nmov.u32 c, 0;\n"
               "LW_%=:\n"
               "mbarrier.try_wait.parity.shared::cta.b64 p, [%0], %1, 100000;\n"
               "@p bra LD_%=;\n"
               "add.u32 c, c, 1;\n"
               "setp.lt.u32 p, c, 20000;\n"
               "@p bra LW_%=;\n"
               "trap;\n"
               "LD_%=:\n}\n" :: "r"(bar), "r"(parity) : "memory");
}
__device__ __forceinline__ void mbar_arrive(uint32_t bar) { asm volatile("mbarrier.arrive.shared::cta.b64 _, [%0];" :: "r"(bar) : "memory"); }
__device__ __forceinline__ void named_arrive(int id, int n) { asm volatile("bar.arrive %0, %1;" :: "r"(id), "r"(n) : "memory"); }
__device__ __forceinline__ void fence_async_all() { asm volatile("fence.proxy.async.global;" ::: "memory"); }
__device__ __forceinline__ void flag_add(uint32_t* f) { asm volatile("fence.acq_rel.gpu;\nred.relaxed.gpu.global.add.u32 [%0], 1;" :: "l"(f) : "memory"); }
#define PUBLISH(f) asm volatile("fence.proxy.async.global;\nred.relaxed.gpu.global.add.u32 [%0], 1;" :: "l"(f) : "memory")
__device__ __forceinline__ void flag_wait(const uint32_t* f, uint32_t target) {
  uint32_t v;
#pragma unroll 1
  for (int it = 0;; it++) {
    asm volatile("ld.acquire.gpu.global.u32 %0, [%1];" : "=r"(v) : "l"(f) : "memory");
    if ((int32_t)(v - target) >= 0) break;
    if (it > 2000000) __trap();
    __nanosleep(64);
  }
}
__device__ __forceinline__ bool mbar_test(uint32_t bar, uint32_t parity) {
  uint32_t ok;
  asm volatile("{\n.reg .pred p;\nmbarrier.test_wait.parity.shared::cta.b64 p, [%1], %2;\nselp.b32 %0, 1, 0, p;\n}\n" : "=r"(ok) : "r"(bar), "r"(parity) : "memory");
  return ok;
}
__device__ __forceinline__ bool elect_one() {
  uint32_t p;
  asm volatile("{\n.reg .pred P;\nelect.sync _|P, 0xFFFFFFFF;\nselp.b32 %0, 1, 0, P;\n}\n" : "=r"(p));
  return p;
}
__device__ __forceinline__ void lds4(uint32_t a, uint32_t* r) {
  asm volatile("ld.shared.v4.b32 {%0,%1,%2,%3}, [%4];" : "=r"(r[0]), "=r"(r[1]), "=r"(r[2]), "=r"(r[3]) : "r"(a) : "memory");
}
__device__ __forceinline__ uint32_t lds1(uint32_t a) { uint32_t r; asm volatile("ld.shared.b32 %0, [%1];" : "=r"(r) : "r"(a) : "memory"); return r; }
__device__ __forceinline__ void sts1(uint32_t a, uint32_t v) { asm volatile("st.shared.b32 [%0], %1;" :: "r"(a), "r"(v) : "memory"); }
__device__ __forceinline__ void sts4(uint32_t a, uint32_t r0, uint32_t r1, uint32_t r2, uint32_t r3) {
  asm volatile("st.shared.v4.b32 [%0], {%1,%2,%3,%4};" :: "r"(a), "r"(r0), "r"(r1), "r"(r2), "r"(r3) : "memory");
}
__device__ __forceinline__ void ldsm4(uint32_t a, uint32_t* r) {
  asm volatile("ldmatrix.sync.aligned.m8n8.x4.shared.b16 {%0,%1,%2,%3}, [%4];" : "=r"(r[0]), "=r"(r[1]), "=r"(r[2]), "=r"(r[3]) : "r"(a) : "memory");
}
__device__ __forceinline__ float rcpf(float x) { float y; asm("rcp.approx.ftz.f32 %0, %1;" : "=f"(y) : "f"(x)); return y; }
__device__ __forceinline__ uint32_t hfma2(uint32_t a, uint32_t b, uint32_t c) { uint32_t r; asm("fma.rn.f16x2 %0, %1, %2, %3;" : "=r"(r) : "r"(a), "r"(b), "r"(c)); return r; }
__device__ __forceinline__ uint32_t hadd2(uint32_t a, uint32_t b) { uint32_t r; asm("add.rn.f16x2 %0, %1, %2;" : "=r"(r) : "r"(a), "r"(b)); return r; }

#define STEPK 96
#define QSCALE 0.36067376022224085f
#define SMAGIC (512.0f + 2.0f * (191.0f - 30.0f - 1.5823545f))
#define VSHIFT 1073741824.0f

__device__ uint32_t g_epoch[132];
__device__ uint32_t g_flag[288 * 8];
#define FLAG_KV (g_flag)
#define FLAG_B(h) (g_flag + (4 + (h)) * 8)
#define FLAG_OA(cta, pass) (g_flag + (16 + (cta) * 2 + (pass)) * 8)
#define FLAG_LM(i) (g_flag + (272 + (i)) * 8)

#define SM_TOTAL (224 * 1024 + 2048 + 1024)
#define OFF_K 0
#define OFF_F 65536
#define OFF_V 131072
#define OFF_MISC (224 * 1024)

#define BAR_FULL(s) (bars + 8 * (s))
#define BAR_EMPTY(s) (bars + 24 + 8 * (s))
#define BAR_KV(c) (bars + 48 + 8 * (c))
#define BAR_BDONE (bars + 80)
#define BAR_Q (bars + 88)
#define BAR_GO (bars + 96)
#define BAR_Q2 (bars + 104)
#define BAR_OD(p) (bars + 112 + 8 * (p))
#define BAR_CL(c) (bars + 128 + 8 * (c))
#define BAR_TE(i) (bars + 168 + 8 * (i))
#define BAR_RL (bars + 184)
#define BAR_TF(g) (bars + 224 + 8 * (g))
#define BAR_XA(w) (bars + 352 + 8 * (w))
#define BAR_VB(c) (bars + 384 + 8 * (c))

__device__ __forceinline__ uint32_t exp2_pair_fix(float d0, float d1, uint32_t c63, uint32_t m1) {
  uint32_t w, y, s, r;
  asm("prmt.b32 %0, %1, %2, 0x6521;" : "=r"(w) : "r"(__float_as_uint(d0)), "r"(__float_as_uint(d1)));
  asm("lop3.b32 %0, %1, 0x007F007F, %2, 0xEA;" : "=r"(y) : "r"(w), "r"(c63));
  asm("mad.lo.u32 %0, %1, %2, %3;" : "=r"(s) : "r"(y), "r"(m1), "r"(w));
  asm("fma.rn.bf16x2 %0, %1, %2, %3;" : "=r"(r) : "r"(w), "r"(y), "r"(s));
  return r;
}

__device__ __forceinline__ void attn_slow(const uint4* gq, uint32_t dst) {
  const int t = threadIdx.x & 127;
  const int row = t >> 1, half = t & 1;
  float q[16];
#pragma unroll
  for (int i = 0; i < 4; i++) {
    const uint4 v = gq[(row >> 4) * 32 + (row & 7) * 4 + i];
    const uint32_t lo = (row & 8) ? v.y : v.x, hi = (row & 8) ? v.w : v.z;
    q[2 * i] = bf_lo(lo); q[2 * i + 1] = bf_hi(lo); q[2 * i + 8] = bf_lo(hi); q[2 * i + 9] = bf_hi(hi);
  }
  float m = -INFINITY, l = 0.f, o[16];
#pragma unroll
  for (int i = 0; i < 16; i++) o[i] = 0.f;
#pragma unroll 1
  for (int j = half * 1024; j < half * 1024 + 1024; j++) {
    uint4 ka = g_KV[4 * S_TOK + j], kb = g_KV[5 * S_TOK + j];
    uint4 va = g_KV[6 * S_TOK + j], vb = g_KV[7 * S_TOK + j];
    uint32_t kk[8] = {ka.x, ka.y, ka.z, ka.w, kb.x, kb.y, kb.z, kb.w};
    uint32_t vv[8] = {va.x, va.y, va.z, va.w, vb.x, vb.y, vb.z, vb.w};
    float s = 0.f;
#pragma unroll
    for (int i = 0; i < 8; i++) { s = fmaf(q[2 * i], bf_lo(kk[i]), s); s = fmaf(q[2 * i + 1], bf_hi(kk[i]), s); }
    s = rbf(s) * 0.25f;
    if (s > m) {
      float c = __expf(m - s);
      l *= c;
#pragma unroll
      for (int i = 0; i < 16; i++) o[i] *= c;
      m = s;
    }
    float p = __expf(s - m);
    l += p;
#pragma unroll
    for (int i = 0; i < 8; i++) { o[2 * i] = fmaf(p, bf_lo(vv[i]), o[2 * i]); o[2 * i + 1] = fmaf(p, bf_hi(vv[i]), o[2 * i + 1]); }
  }
  float m2 = __shfl_xor_sync(~0u, m, 1);
  float mm = fmaxf(m, m2);
  float c = __expf(m - mm);
  l *= c; l += __shfl_xor_sync(~0u, l, 1);
  float inv = 1.f / l;
  uint32_t r[8];
#pragma unroll
  for (int i = 0; i < 16; i++) { o[i] *= c; o[i] += __shfl_xor_sync(~0u, o[i], 1); o[i] *= inv; }
#pragma unroll
  for (int i = 0; i < 8; i++) r[i] = pack_bf16(o[2 * i], o[2 * i + 1]);
  if (half == 0) sts4(dst, r[0], r[1], r[2], r[3]); else sts4(dst, r[4], r[5], r[6], r[7]);
  fence_async();
}

struct Params { const __nv_bfloat16* wk; const __nv_bfloat16* wv; const __nv_bfloat16* xa; };
__device__ __forceinline__ void cp16(uint32_t dst, const void* src) { asm volatile("cp.async.cg.shared.global [%0], [%1], 16;" :: "r"(dst), "l"(src) : "memory"); }

__device__ __forceinline__ void helper_cta(const int h, const uint32_t sb, const uint32_t bars, const int wg, const int w4,
                                           const CUtensorMap* mQ, const CUtensorMap* mOs) {
  const int lane = threadIdx.x & 31;
  mbar_wait(BAR_GO, 0);
  const int cb = wg & 1, col = h * 128 + cb * 64, row0 = S_TOK + (wg >> 1) * 1024;
  const uint32_t buf = sb + wg * 49152;
  if (w4 == 0 && elect_one()) {
    fence_async_all();
#pragma unroll 1
    for (int u = 0; u < 3; u++) {
      mbar_expect_tx(BAR_TF(wg * 3 + u), 16384);
      tma2d(buf + u * 16384, mQ, col, row0 + u * 128, BAR_TF(wg * 3 + u));
    }
  }
  const int head = h * 8 + cb * 4 + w4;
  float4 a0 = make_float4(0, 0, 0, 0), a1 = a0, a2 = a0;
#pragma unroll 8
  for (int tt = 0; tt < 16; tt++) {
    const float4* src = g_kvp + ((tt * 32 + head) * 3) * 32 + lane;
    float4 u = src[0], v = src[32], w = src[64];
    a0.x += u.x; a0.y += u.y; a0.z += u.z; a0.w += u.w;
    a1.x += v.x; a1.y += v.y; a1.z += v.z; a1.w += v.w;
    a2.x += w.x; a2.y += w.y; a2.z += w.z; a2.w += w.w;
  }
  const uint32_t b00 = pack_bf16(a0.x, a0.y), b01 = pack_bf16(a0.z, a0.w);
  const uint32_t b10 = pack_bf16(a1.x, a1.y), b11 = pack_bf16(a1.z, a1.w);
  const uint32_t bz0 = pack_bf16(a2.x, a2.y), bz1 = pack_bf16(a2.z, a2.w);
  const int m = lane >> 3, r = lane & 7;
  const uint32_t off = ((m & 1) * 8 + r) * 128 + (((w4 * 2 + (m >> 1)) ^ r) << 4);
  int s = 0, ph = 0;
#pragma unroll 1
  for (int u = 0; u < 8; u++) {
    const uint32_t bb = buf + s * 16384;
    mbar_wait(BAR_TF(wg * 3 + s), ph);
#pragma unroll
    for (int mt = 0; mt < 8; mt++) {
      uint32_t a[4];
      ldsm4(bb + mt * 2048 + off, a);
      float n0[4] = {0, 0, 0, 0}, n1[4] = {0, 0, 0, 0}, dn[4] = {0, 0, 0, 0};
      mma_bf16(dn, a[0], a[1], a[2], a[3], bz0, bz1);
      mma_bf16(n0, a[0], a[1], a[2], a[3], b00, b01);
      mma_bf16(n1, a[0], a[1], a[2], a[3], b10, b11);
      const float i0 = rcpf(dn[0] + 1e-6f), i1 = rcpf(dn[2] + 1e-6f);
      stsm4(bb + mt * 2048 + off, pack_bf16(n0[0] * i0, n0[1] * i0), pack_bf16(n0[2] * i1, n0[3] * i1),
            pack_bf16(n1[0] * i0, n1[1] * i0), pack_bf16(n1[2] * i1, n1[3] * i1));
    }
    fence_async();
    named_bar(wg + 1, 128);
    if (w4 == 0 && lane == 0) {
      tma2d_store(mOs, bb, col, row0 + u * 128);
      bulk_commit();
      if (u >= 1 && u + 2 < 8) {
        asm volatile("cp.async.bulk.wait_group.read 1;" ::: "memory");
        const int sp = s == 0 ? 2 : s - 1;
        mbar_expect_tx(BAR_TF(wg * 3 + sp), 16384);
        tma2d(buf + sp * 16384, mQ, col, row0 + (u + 2) * 128, BAR_TF(wg * 3 + sp));
      }
    }
    __syncwarp();
    if (++s == 3) { s = 0; ph ^= 1; }
  }
  if (w4 == 0 && lane == 0) {
    bulk_wait_all();
    fence_async_all();
    flag_add(FLAG_LM((h * 2 + cb) * 2 + (wg >> 1)));
    if (wg == 0) TS(1, 8);
  }
}

#define STAGE(s) (sb + (2 - (s)) * 65536)
__device__ __forceinline__ uint32_t xa_addr(uint32_t sb, int kb) {
  return sb + (kb >= 1 && kb <= 4 ? OFF_V + 65536 + (kb - 1) * 8192 : 16384 + (kb == 5 ? OFF_K : (kb == 6 ? OFF_V : OFF_F)));
}
#define XA7_TMP (sb + OFF_K + 40960)
#define WKV_TMP (sb + OFF_K + 32768)
template <int TR> __device__ __forceinline__ void proj_kb(float* acc, uint32_t aA, uint32_t aB, int first) {
  const uint64_t da = make_desc(aA, TR ? 8192 : 16, 1024, 1);
  const uint64_t db = make_desc(aB, TR ? 16 : 8192, 1024, 1);
  wg_fence();
#pragma unroll
  for (int k = 0; k < 4; k++) wg_ss128<TR, 1 - TR>(acc, da + k * (TR ? 128 : 2), db + k * (TR ? 2 : 128), k != 0 || !first);
  wg_commit();
}
template <int TR> __device__ __forceinline__ void proj_loop(float* acc, uint32_t sb, uint32_t bars, uint32_t offA, uint32_t offB,
                                                            int wg, uint32_t sWKV) {
  {
    float kv[4];
    if (threadIdx.x == 0) TS(0, 13);
    mbar_wait(BAR_XA(wg), 0);
    if (threadIdx.x == 0) TS(0, 1);
    const uint64_t da0 = make_desc(xa_addr(sb, 2 * wg), 16, 1024, 1);
    const uint64_t da1 = make_desc(wg == 3 ? XA7_TMP : xa_addr(sb, 2 * wg + 1), 16, 1024, 1);
    const uint64_t db = make_desc(sWKV + wg * 2048, 128, 128, 0);
    wg_fence();
#pragma unroll
    for (int k = 0; k < 8; k++) wg_ss8<0, 1>(kv, (k < 4 ? da0 : da1) + (k & 3) * 2, db + k * 16, k != 0);
    wg_commit();
    wg_wait<0>();
    fence_regs<4>(kv);
    named_bar(wg + 1, 128);
    sts4(sWKV + threadIdx.x * 16, __float_as_uint(kv[0]), __float_as_uint(kv[1]), __float_as_uint(kv[2]), __float_as_uint(kv[3]));
    __syncwarp();
    if ((threadIdx.x & 31) == 0) mbar_arrive(BAR_GO);
  }
  int s = 0, ph = 0, sp = 0;
#pragma unroll 1
  for (int kb = 0; kb < 8; kb++) {
    mbar_wait(BAR_FULL(s), ph);
    if (threadIdx.x == 0) TS(0, 2 + kb);
    if (TR == 0) mbar_wait(BAR_XA(kb >> 1), 0);
    proj_kb<TR>(acc, TR ? STAGE(s) + offA : xa_addr(sb, kb), STAGE(s) + offB, kb == 0);
    wg_wait<1>();
    if (kb >= 1 && (threadIdx.x & 127) == 0) {
      mbar_arrive(BAR_EMPTY(sp));
      if (TR == 0 && kb == 5) mbar_arrive(BAR_VB(1));
    }
    __syncwarp();
    sp = s;
    if (++s == 3) { s = 0; ph ^= 1; }
  }
  wg_wait<0>();
  fence_regs<64>(acc);
}

__device__ __forceinline__ uint32_t tail_slots(int isB, int n) {
  if (n < 4) return n < 2 ? (n == 0 ? 0x0D0C0B0Au : 0x04000F0Eu) : (n == 2 ? 0x18141008u : 0x15110501u);
  if (isB) return n < 6 ? (n == 4 ? 0x19120602u : 0x0D0C0B0Au) : (n == 6 ? 0x04000F0Eu : 0x13070316u);
  return n < 6 ? (n == 4 ? 0x1902031Au : 0x12061307u) : (n == 6 ? 0x16091B17u : 0x0D0C0B0Au);
}

__device__ __forceinline__ void take_role(uint32_t sM, int wg) {
  uint32_t r;
  asm volatile("atom.shared.add.u32 %0, [%1], 1;" : "=r"(r) : "r"(sM + 20) : "memory");
  sts1(sM + 32 + wg * 4, r);
}

__global__ void __launch_bounds__(640, 1)
k1_main(const __grid_constant__ CUtensorMap mXA64, const __grid_constant__ CUtensorMap mXB,
        const __grid_constant__ CUtensorMap mWq, const __grid_constant__ CUtensorMap mWqkv,
        const __grid_constant__ CUtensorMap mQst, const __grid_constant__ CUtensorMap mOst,
        const __grid_constant__ CUtensorMap mO, const __grid_constant__ CUtensorMap mWoA,
        const __grid_constant__ CUtensorMap mWoB, const __grid_constant__ CUtensorMap mOut,
        const __grid_constant__ CUtensorMap mO16, const Params prm) {
  extern __shared__ uint8_t smem_raw[];
  const uint32_t sb = (smem_u32(smem_raw) + 1023u) & ~1023u;
  const uint32_t bars = sb + OFF_MISC, sM = bars + 512, sT = bars + 1024;
  const int tid = threadIdx.x, warp = __shfl_sync(~0u, tid >> 5, 0), wg = warp >> 2, w4 = warp & 3, lane = tid & 31;
  const bool helper = blockIdx.x >= 128;
  if (tid == 0) TS(0, 0);
  const int G = blockIdx.x >> 4, gi = blockIdx.x & 15;
  const int tbA = G * 4 + (gi >> 2), hg = gi & 3;
  const int ttB = (G >> 1) * 4 + (gi >> 2), hq = (G & 1) * 4 + (gi & 3);
  const int isB = tbA & 1, tok0 = (tbA >> 1) * 128;
  auto issue = [&](int kb, int s, int part) {
    const uint32_t fb = BAR_FULL(s), st = STAGE(s);
    if (part & 1) {
      mbar_expect_tx(fb, kb == 7 ? 65536 : 57344);
      if (kb == 7) tma2d(st + 16384, &mXA64, kb * 64, tbA * 64, fb);
      tma2d(st, &mWq, hg * 128, kb * 64, fb);
      tma2d(st + 8192, &mWq, hg * 128 + 64, kb * 64, fb);
      tma2d(st + 49152, &mXB, kb * 64, ttB * 128, fb);
      tma2d(st + 24576, &mWqkv, hq * 64, kb * 64, fb);
    }
    if (part & 2) {
      tma2d(st + 32768, &mWqkv, 512 + hq * 64, kb * 64, fb);
      tma2d(st + 40960, &mWqkv, 1024 + hq * 64, kb * 64, fb);
    }
  };
  const uint32_t sOne = sb + OFF_V + 65536, sWKV = WKV_TMP;
  if (warp >= 16) {
    if (warp == 17) {
      if (elect_one()) {
        mbar_init(BAR_BDONE, 8); mbar_init(BAR_Q, 6); mbar_init(BAR_GO, helper ? 1 : 16); mbar_init(BAR_Q2, 5);
        mbar_init(BAR_OD(0), 16); mbar_init(BAR_OD(1), 16); mbar_init(BAR_CL(0), 1); mbar_init(BAR_FULL(2), 1);
#pragma unroll
        for (int i = 0; i < 4; i++) mbar_init(BAR_CL(i + 1), i == 0 ? 5 : 4);
#pragma unroll
        for (int i = 0; i < 3; i++) { mbar_init(BAR_EMPTY(i), 4); mbar_init(BAR_KV(i), 1); mbar_init(BAR_VB(i), 1); }
        sts1(sM + 20, 0);
        asm volatile("fence.mbarrier_init.release.cluster;" ::: "memory");
      }
    } else if (warp == 18) {
      if (elect_one()) {
#pragma unroll
        for (int i = 0; i < 2; i++) mbar_init(BAR_TE(i), 2);
        mbar_init(BAR_RL, 1);
#pragma unroll
        for (int i = 0; i < 16; i++) mbar_init(BAR_TF(i), 1);
        asm volatile("fence.mbarrier_init.release.cluster;" ::: "memory");
      }
    } else if (warp == 16 && !helper && elect_one()) {
#pragma unroll
      for (int w = 0; w < 4; w++) mbar_init(BAR_XA(w), 1);
      mbar_init(BAR_FULL(0), 1); mbar_init(BAR_FULL(1), 1);
      asm volatile("fence.mbarrier_init.release.cluster;" ::: "memory");
#pragma unroll
      for (int w = 0; w < 4; w++) {
        mbar_expect_tx(BAR_XA(w), 16384);
        tma2d(xa_addr(sb, 2 * w), &mXA64, w * 128, tbA * 64, BAR_XA(w));
        tma2d(w == 3 ? XA7_TMP : xa_addr(sb, 2 * w + 1), &mXA64, w * 128 + 64, tbA * 64, BAR_XA(w));
      }
      TS(0, 14);
      issue(0, 0, 3);
    }
  } else if (!helper) {
    const uint4 v = __ldg((const uint4*)(hg >= 2 ? prm.wv : prm.wk) + tid * 2 + (hg & 1));
    sts4(sWKV + tid * 16, v.x, v.y, v.z, v.w);
    fence_async();
  }
  __syncthreads();
  if (wg == 4) {
    if (w4 == 0 && !helper && elect_one()) { issue(1, 1, 3); issue(2, 2, 1); TS(0, 15); }
    asm volatile("setmaxnreg.dec.sync.aligned.u32 32;");
    const uint32_t ep = g_epoch[blockIdx.x] + 1;
    if (helper) {
      if (w4 == 0 && elect_one()) {
        flag_wait(FLAG_B(blockIdx.x - 128), ep * 32);
        fence_async_all();
        TS(1, 10);
        mbar_arrive(BAR_GO);
        g_epoch[blockIdx.x] = ep;
      }
      return;
    }
    mbar_wait(BAR_GO, 0);
    {
      uint32_t a[4], b[4];
      float c[4];
      lds4(sWKV + (tid - 512) * 16, a);
      lds4(sWKV + 2048 + (tid - 512) * 16, b);
#pragma unroll
      for (int i = 0; i < 4; i++) c[i] = __uint_as_float(a[i]) + __uint_as_float(b[i]);
      lds4(sWKV + 4096 + (tid - 512) * 16, a);
      lds4(sWKV + 6144 + (tid - 512) * 16, b);
#pragma unroll
      for (int i = 0; i < 4; i++) c[i] += __uint_as_float(a[i]) + __uint_as_float(b[i]);
      sts1(sT + w4 * 256 + lane * 4, pack_bf16(c[0], c[1]));
      sts1(sT + w4 * 256 + 128 + lane * 4, pack_bf16(c[2], c[3]));
    }
    named_bar(9, 128);
    if (w4 == 0 && elect_one()) issue(2, 2, 2);
    auto write_ones = [&]() {
      mbar_wait_long(BAR_VB(1), 0);
      int c = ((w4 & 1) * 32 + lane);
#pragma unroll 4
      for (int key = c; key < S_TOK; key += 64) {
        sts4(sOne + key * 16, c < 24 ? 0x00003F80u : 0x00004E80u, 0u, 0u, 0u);
        c += 64; if (c >= STEPK) c -= STEPK;
      }
      fence_async();
      __syncwarp();
      if (lane == 0) mbar_arrive(BAR_Q);
    };
    if (w4 == 0) {
      int s = 0, ph = 0;
#pragma unroll 1
      for (int kb = 3; kb < 8; kb++) {
        mbar_wait(BAR_EMPTY(s), ph);
        if (elect_one()) issue(kb, s, 3);
        if (++s == 3) { s = 0; ph ^= 1; }
      }
      flag_wait(FLAG_KV, ep * 128);
      fence_async_all();
      if (lane == 0) TS(0, 11);
#pragma unroll 1
      for (int m = 0; m < 2; m++) {
        mbar_wait(m == 0 ? BAR_EMPTY(2) : BAR_EMPTY(0), 1 - m);
        if (elect_one()) {
          const uint32_t fb = m == 0 ? BAR_KV(0) : BAR_VB(0);
          mbar_expect_tx(fb, 2 * 7 * STEPK * 16);
#pragma unroll
          for (int p = 0; p < 2; p++) bulk_g2s(sb + m * OFF_V + p * 32768, g_KV + (m * 2 + p) * S_TOK, 7 * STEPK * 16, fb);
        }
      }
      mbar_wait(BAR_Q, 0);
      if (elect_one()) {
#pragma unroll
        for (int c = 1; c < 3; c++) {
          const int k0 = c == 1 ? 7 * STEPK : 12 * STEPK, k1 = c == 1 ? 12 * STEPK : S_TOK;
          const uint32_t bytes = (k1 - k0) * 16;
          mbar_expect_tx(BAR_KV(c), 4 * bytes);
#pragma unroll
          for (int p = 0; p < 4; p++)
            bulk_g2s(sb + (p >> 1) * OFF_V + (p & 1) * 32768 + k0 * 16, g_KV + p * S_TOK + k0, bytes, BAR_KV(c));
        }
      }
      mbar_wait_long(BAR_CL(1), 0);
      flag_wait(isB ? FLAG_LM((lane & 7) * 2 + (tbA >> 4)) : FLAG_OA(tbA * 4 + (lane & 7), 0), ep);
      __syncwarp();
      fence_async_all();
      if (lane == 0) TS(2, 13);
      const CUtensorMap* mW = isB ? &mWoB : &mWoA;
#pragma unroll 1
      for (int it = 0; it < 8; it++) {
        const int n = (!isB && it >= 6) ? 13 - it : it;
        uint32_t wb = BAR_CL(n < 3 ? 0 : (n == 3 ? 2 : 3));
        if (isB) { if (n >= 5) wb = n == 7 ? BAR_CL(4) : BAR_TE(n - 5); }
        else if (n >= 6) wb = n == 6 ? BAR_CL(4) : BAR_TE(0);
        if (it < 6) mbar_wait_long(wb, 0); else mbar_wait(wb, 0);
        const uint32_t sl = tail_slots(isB, n), fb = BAR_TF(n);
        const bool withX = isB || n < 4;
        const int k0 = isB ? n * 64 : (n < 4 ? n * 128 : ((hg + n) & 3) * 128 + 64);
        if (elect_one()) {
          mbar_expect_tx(fb, withX ? 32768 : 16384);
          if (withX) {
            tma2d(sb + (sl & 255) * 8192, &mO, k0, isB * S_TOK + tok0, fb);
            tma2d(sb + ((sl >> 8) & 255) * 8192, &mO, k0, isB * S_TOK + tok0 + 64, fb);
          }
          tma2d(sb + ((sl >> 16) & 255) * 8192, mW, hg * 128, k0, fb);
          tma2d(sb + (sl >> 24) * 8192, mW, hg * 128 + 64, k0, fb);
        }
      }
      if (lane == 0) g_epoch[blockIdx.x] = ep;
    } else if (w4 == 3) {
      write_ones();
      flag_wait(FLAG_KV, ep * 128);
      const uint4 a = *(const uint4*)(g_stats + lane * 4);
      const float kmax2 = __uint_as_float(__reduce_max_sync(~0u, a.x)) + __uint_as_float(__reduce_max_sync(~0u, a.y));
      const float vmax = __uint_as_float(__reduce_max_sync(~0u, max(a.z, a.w)));
      const float lv = vmax > 0.f ? __log2f(vmax) : 0.f;
      const float lim = fminf(90.f, fminf(91.f + lv, 95.f - lv));
      float thr = -1.f;
      if (vmax < 1e27f && kmax2 <= 65536.f && lim > 2.f) thr = fminf(60000.f, (lim * lim - 1.f) / (kmax2 * 1.02f + 1e-30f));
      if (lane == 0) { sts1(sM + 16, __float_as_uint(thr)); mbar_arrive(BAR_Q2); }
    } else {
      const int tok = (w4 - 1) * 32 + lane;
      int step, col;
      if ((tbA & 3) == 0) {
        const int b8 = tbA >> 2;
        if (tok < 22) { step = tok; col = 24 + b8; }
        else { const int c = tok >= 43; step = tok - 22 - 21 * c; col = 32 + b8 * 2 + c; }
      } else {
        const int b24 = (tbA >> 2) * 3 + (tbA & 3) - 1;
        if (tok < 42) { const int c = tok >= 21; step = tok - 21 * c; col = 48 + b24 * 2 + c; }
        else { step = tok - 42; col = b24; }
      }
      const int kap = step * STEPK + col;
      const bool chained = col >= 24;
      uint32_t v[4], o[4];
      lds4(sT + tok * 16, v);
      g_KV[(4 + hg) * S_TOK + kap] = make_uint4(v[0], v[1], v[2], v[3]);
      float st = 0.f;
      if (hg < 2) {
        o[0] = o[1] = o[2] = o[3] = 0;
        if (chained && step > 0) lds4(sT + tok * 16 - 16, o);
        const float sc = chained ? 2.f : 1.f;
#pragma unroll
        for (int u = 0; u < 4; u++) {
          const float x = bf_lo(v[u]), y = bf_hi(v[u]);
          st += x * x + y * y;
          o[u] = pack_f16((x - bf_lo(o[u])) * sc, (y - bf_hi(o[u])) * sc);
        }
      } else {
        const float sc = chained ? VSHIFT : 1.f;
#pragma unroll
        for (int u = 0; u < 4; u++) { float x = bf_lo(v[u]), y = bf_hi(v[u]); st += fabsf(x) + fabsf(y); o[u] = pack_bf16(x * sc, y * sc); }
      }
      g_KV[hg * S_TOK + kap] = make_uint4(o[0], o[1], o[2], o[3]);
      const uint32_t um = __reduce_max_sync(~0u, __float_as_uint(st) & 0x7FFFFFFFu);
      if (w4 == 2) {
        if (lane == 0) sts1(sM + 24, um);
        named_arrive(10, 64);
        write_ones();
        if (!isB) {
          mbar_wait_long(BAR_CL(3), 0);
          mbar_wait_long(BAR_RL, 0);
          uint32_t pend = 0xFE;
          const int li = lane & 7;
          const uint32_t* fl = FLAG_OA((tbA + (li & 1)) * 4 + ((hg + (li >> 1)) & 3), 1);
#pragma unroll 1
          for (int it = 0; pend; it++) {
            uint32_t fv;
            asm volatile("ld.acquire.gpu.global.u32 %0, [%1];" : "=r"(fv) : "l"(fl) : "memory");
            uint32_t go = __ballot_sync(~0u, (int32_t)(fv - ep) >= 0 && mbar_test(li >= 6 ? BAR_TE(0) : BAR_CL(4), 0)) & pend;
            pend &= ~go;
            if (go) fence_async_all();
#pragma unroll 1
            while (go) {
              const int b = __ffs(go) - 1;
              go &= go - 1;
              const uint32_t slot = (tail_slots(0, 4 + (b >> 1)) >> (8 * (b & 1))) & 255;
              if (elect_one()) {
                mbar_expect_tx(BAR_TF(8 + b), 8192);
                tma2d(sb + slot * 8192, &mO, ((hg + (b >> 1)) & 3) * 128 + 64, tok0 + (b & 1) * 64, BAR_TF(8 + b));
              }
            }
            if (it > 2000000) __trap();
          }
          if (lane == 0) TS(2, 14);
        }
      }
      else {
        named_bar(10, 64);
        if (elect_one()) {
          g_stats[tbA * 4 + hg] = max(um, lds1(sM + 24));
          fence_async_all();
          flag_add(FLAG_KV);
          TS(1, 9);
          mbar_wait_long(BAR_BDONE, 0);
          tma2d_store(&mQst, sb + OFF_F + 49152, hq * 64, S_TOK + ttB * 128);
          bulk_commit();
          bulk_wait_all();
          fence_async_all();
          flag_add(FLAG_B(hq >> 1));
          TS(0, 12);
          mbar_wait(BAR_Q, 0);
          mbar_arrive(BAR_CL(0));
#pragma unroll 1
          for (int p = 0; p < 2; p++) {
            mbar_wait_long(BAR_OD(p), 0);
            if (p == 0) {
#pragma unroll
              for (int w = 0; w < 4; w++) tma2d_store(&mO16, sb + OFF_F + w * 2048, hg * 128 + w * 16, tbA * 64);
            } else {
              tma2d_store(&mO, sb + 26 * 8192, hg * 128 + 64, tbA * 64);
            }
            bulk_commit();
            bulk_wait_all();
            if (p == 0) mbar_arrive(BAR_CL(1));
            PUBLISH(FLAG_OA(blockIdx.x, p));
          }
          TS(2, 0);
        }
      }
    }
    return;
  }
  if (helper) { helper_cta(blockIdx.x - 128, sb, bars, wg, w4, &mQst, &mOst); return; }

  {
    float acc[64];
    if (wg == 0) proj_loop<0>(acc, sb, bars, 16384, 0, wg, sWKV);
    else proj_loop<1>(acc, sb, bars, 16384 + wg * 8192, 49152, wg, sWKV);
    if (tid == 0) TS(0, 10);
    const uint32_t sF = sb + OFF_F;
    const uint32_t qa = sF + w4 * 512 + ((lane >> 3) & 1) * 256 + (lane >> 4) * 128 + (lane & 7) * 16;
    if (wg == 0) {
#pragma unroll
      for (int hd = 0; hd < 4; hd++)
        stsm4(qa + hd * 2048, pack_f16(acc[8 * hd] * QSCALE, acc[8 * hd + 1] * QSCALE), pack_f16(acc[8 * hd + 2] * QSCALE, acc[8 * hd + 3] * QSCALE),
              pack_f16(acc[8 * hd + 4] * QSCALE, acc[8 * hd + 5] * QSCALE), pack_f16(acc[8 * hd + 6] * QSCALE, acc[8 * hd + 7] * QSCALE));
      fence_async();
      __syncwarp();
      if (lane == 0) mbar_arrive(BAR_Q);
    } else {
      if (wg != 3) named_arrive(6, 384);
      if (wg != 1) named_arrive(8, 384);
    }
    asm volatile("setmaxnreg.inc.sync.aligned.u32 112;");
    fence_regs<64>(acc);
    if (wg == 0) {
      uint32_t r[32];
#pragma unroll
      for (int hd = 0; hd < 8; hd++) {
#pragma unroll
        for (int i = 0; i < 4; i++) r[4 * hd + i] = pack_f16(acc[8 * hd + 2 * i] * QSCALE, acc[8 * hd + 2 * i + 1] * QSCALE);
        if (hd >= 4) stsm4(qa + hd * 2048, r[4 * hd], r[4 * hd + 1], r[4 * hd + 2], r[4 * hd + 3]);
      }
      fence_async();
      uint32_t nmax = 0;
#pragma unroll
      for (int hd = 0; hd < 8; hd++) {
        const uint32_t* q = r + 4 * hd;
        const uint32_t t0 = hfma2(q[2], q[2], hfma2(q[0], q[0], 0u)), t1 = hfma2(q[3], q[3], hfma2(q[1], q[1], 0u));
        uint32_t n = hadd2(__byte_perm(t0, t1, 0x5410), __byte_perm(t0, t1, 0x7632));
        n = hadd2(n, __shfl_xor_sync(~0u, n, 1));
        n = hadd2(n, __shfl_xor_sync(~0u, n, 2));
        nmax = __vmaxu2(nmax, n & 0x7FFF7FFFu);
      }
      nmax = __reduce_max_sync(~0u, max(nmax & 0xFFFFu, nmax >> 16));
      if (lane == 0) sts1(sM + w4 * 4, nmax);
      uint4* gq = (uint4*)g_Q + blockIdx.x * 1024 + tid;
#pragma unroll
      for (int hd = 0; hd < 8; hd++)
        gq[hd * 128] = make_uint4(pack_bf16(acc[8 * hd], acc[8 * hd + 1]), pack_bf16(acc[8 * hd + 2], acc[8 * hd + 3]),
                                  pack_bf16(acc[8 * hd + 4], acc[8 * hd + 5]), pack_bf16(acc[8 * hd + 6], acc[8 * hd + 7]));
      __syncwarp();
      if (lane == 0) mbar_arrive(BAR_Q2);
    } else if (wg == 3) {
      named_bar(6, 384);
      const int t = tid & 127;
#pragma unroll
      for (int j = 0; j < 8; j++)
        sts4(sF + 24576 + j * 2048 + t * 16, pack_bf16(acc[8 * j], acc[8 * j + 1]), pack_bf16(acc[8 * j + 2], acc[8 * j + 3]),
             pack_bf16(acc[8 * j + 4], acc[8 * j + 5]), pack_bf16(acc[8 * j + 6], acc[8 * j + 7]));
      named_arrive(7, 256);
    } else {
      uint32_t p[32];
#pragma unroll
      for (int i = 0; i < 32; i++) p[i] = phi2(acc[2 * i], acc[2 * i + 1]);
      if (wg == 1) {
        named_bar(8, 384);
        const int m = lane >> 3, r = lane & 7;
#pragma unroll
        for (int j = 0; j < 16; j += 2) {
          const int tok = (j + (m >> 1)) * 8 + r;
          const int chunk = w4 * 2 + (m & 1);
          stsm4t(sF + 49152 + tok * 128 + ((chunk ^ r) << 4), p[2 * j], p[2 * j + 1], p[2 * j + 2], p[2 * j + 3]);
        }
        fence_async();
      } else {
        named_bar(7, 256);
        float kv0[4] = {0, 0, 0, 0}, kv1[4] = {0, 0, 0, 0}, z0[4] = {0, 0, 0, 0}, z1[4] = {0, 0, 0, 0};
        const uint32_t one = 0x3F803F80u;
        const int t = tid & 127;
#pragma unroll
        for (int j = 0; j < 8; j++) {
          uint32_t a[4];
          lds4(sF + 24576 + j * 2048 + t * 16, a);
          mma_bf16(kv0, a[0], a[1], a[2], a[3], p[4 * j], p[4 * j + 2]);
          mma_bf16(kv1, a[0], a[1], a[2], a[3], p[4 * j + 1], p[4 * j + 3]);
          mma_bf16(z0, one, one, one, one, p[4 * j], p[4 * j + 2]);
          mma_bf16(z1, one, one, one, one, p[4 * j + 1], p[4 * j + 3]);
        }
        float4* dst = g_kvp + ((ttB * 32 + hq * 4 + w4) * 3) * 32 + lane;
        dst[0] = make_float4(kv0[0], kv0[1], kv1[0], kv1[1]);
        dst[32] = make_float4(kv0[2], kv0[3], kv1[2], kv1[3]);
        dst[64] = make_float4(z0[0], z0[1], z1[0], z1[1]);
      }
      __syncwarp();
      if (lane == 0) mbar_arrive(BAR_BDONE);
    }
  }

  bool safe = true;
  {
    const uint32_t c63 = 0x1F801F80u + (threadIdx.x >> 20);
    const uint32_t m1 = (gridDim.x >> 20) - 1u;
    const uint64_t dK0 = make_desc(sb + OFF_K, 32768, 128, 0);
    const uint64_t dV0 = make_desc(sb + OFF_V, 128, 32768, 0);
    constexpr uint32_t dKV = ((2048u - 8u)  __H0__ ) + STEPK - (OFF_V - OFF_K) / 16;
    float Sm[12], Sp[36], O[12];
    uint32_t P[24];
    uint64_t dQ = make_desc(sb + OFF_F + wg * 2048, 128, 256, 0);
#pragma unroll
    for (int i = 0; i < 36; i++) Sp[i] = SMAGIC;
#pragma unroll
    for (int i = 0; i < 12; i++) Sm[i] = 0.f;
    fence_regs<12>(Sm); fence_regs<36>(Sp);
    mbar_wait(BAR_Q, 0);
    mbar_wait(BAR_KV(0), 0);
    wg_fence();
    wg_qs72<1>(Sp, dQ, dK0 + 24);
    wg_qs24<0>(Sm, dQ, dK0);
    wg_commit();
    wg_wait<0>();
    fence_regs<12>(Sm); fence_regs<36>(Sp);
#pragma unroll 1
    for (int pass = 0; pass < 2; pass++) {
#pragma unroll
      for (int i = 0; i < 12; i++) O[i] = 0.f;
      fence_regs<12>(O);
      if (tid == 0) TS(1, 2 + 2 * pass);
      uint32_t vlo = (uint32_t)dV0;
#pragma unroll 1
      for (int seg = 0; seg < 4; seg++) {
        if (pass == 0) {
          if (seg < 3) mbar_wait(seg == 0 ? BAR_VB(0) : BAR_KV(seg), 0);
        } else if (seg >= 1) {
          if ((tid & 127) == 0) {
            mbar_arrive(BAR_CL(seg));
            if (seg == 3) take_role(sM, wg);
          }
          __syncwarp();
        }
        if ((tid & 127) == 0) TS(4 + wg, pass * 5 + seg);
        const uint32_t vend = vlo + (seg == 0 ? 6 : 5) * STEPK;
#pragma unroll 1
        for (; vlo != vend; vlo += STEPK) {
          uint64_t dK, dV;
          asm("mov.b64 %0, {%1, %2};" : "=l"(dK) : "r"(vlo + dKV), "r"(8u));
          asm("mov.b64 %0, {%1, %2};" : "=l"(dV) : "r"(vlo), "r"(2048u));
#pragma unroll
          for (int i = 0; i < 6; i++) P[i] = pack_bf16(ex2f(Sm[2 * i]), ex2f(Sm[2 * i + 1]));
#pragma unroll
          for (int i = 0; i < 18; i++) P[6 + i] = exp2_pair_fix(Sp[2 * i], Sp[2 * i + 1], c63, m1);
          fence_regs<24>(P);
          wg_fence();
#pragma unroll
          for (int k = 0; k < 6; k++) wg_pv24<1>(O, &P[4 * k], dV + k * 16);
          wg_qs72<1>(Sp, dQ, dK + 24);
          wg_qs24<0>(Sm, dQ, dK);
          wg_commit();
          wg_wait<0>();
          fence_regs<12>(Sm); fence_regs<36>(Sp); fence_regs<12>(O); fence_regs<24>(P);
        }
      }
#pragma unroll
      for (int i = 0; i < 6; i++) P[i] = pack_bf16(ex2f(Sm[2 * i]), ex2f(Sm[2 * i + 1]));
      P[6] = exp2_pair_fix(Sp[0], Sp[1], c63, m1);
      P[7] = exp2_pair_fix(Sp[2], Sp[3], c63, m1);
      fence_regs<8>(P);
#pragma unroll
      for (int i = 0; i < 36; i++) Sp[i] = SMAGIC;
      fence_regs<36>(Sp);
      mbar_wait(pass == 0 ? BAR_Q2 : BAR_CL(3), 0);
      const uint32_t sO = pass == 0 ? sb + OFF_F + wg * 2048 + w4 * 512 + (lane & 15) * 32 + (lane >> 4) * 16
                                    : sb + 26 * 8192 + (w4 * 16 + (lane & 15)) * 128 + (((wg * 2 + (lane >> 4)) ^ (lane & 7)) << 4);
      dQ += 512;
      wg_fence();
      wg_pv24<1>(O, &P[0], dV0 + 21 * STEPK);
      wg_pv24<1>(O, &P[4], dV0 + 21 * STEPK + 16);
      wg_commit();
      wg_qs72<1>(Sp, dQ, dK0 + 24);
      wg_qs24<0>(Sm, dQ, dK0);
      wg_commit();
      wg_wait<1>();
      fence_regs<12>(O);
      const float l0 = __shfl_sync(~0u, O[8], lane & ~3), l1 = __shfl_sync(~0u, O[10], lane & ~3);
      const float i0 = rcpf(l0), i1 = rcpf(l1);
      stsm4(sO,
            pack_bf16(O[0] * i0, O[1] * i0), pack_bf16(O[2] * i1, O[3] * i1),
            pack_bf16(O[4] * i0, O[5] * i0), pack_bf16(O[6] * i1, O[7] * i1));
      fence_async();
      {
        uint32_t n[4];
        lds4(sM, n);
        const float qn = __half2float(__ushort_as_half((unsigned short)max(max(n[0], n[1]), max(n[2], n[3]))));
        safe = __all_sync(~0u, qn <= __uint_as_float(lds1(sM + 16)));
      }
      if (safe && lane == 0) mbar_arrive(BAR_OD(pass));
      wg_wait<0>();
      fence_regs<12>(Sm); fence_regs<36>(Sp);
      if (!safe) break;
      if ((tid & 127) == 0) TS(4 + wg, pass * 5 + 4);
      if (tid == 0) TS(1, 3 + 2 * pass);
    }
  }
  if (!safe) {
    if ((tid & 127) == 0) { mbar_arrive(BAR_CL(1)); mbar_arrive(BAR_CL(2)); mbar_arrive(BAR_CL(3)); take_role(sM, wg); }
#pragma unroll 1
    for (int pass = 0; pass < 2; pass++) {
      const int t = tid & 127;
      mbar_wait(BAR_CL(3), 0);
      attn_slow((const uint4*)g_Q + blockIdx.x * 1024 + (pass * 4 + wg) * 128,
                pass == 0 ? sb + OFF_F + wg * 2048 + t * 16
                          : sb + 26 * 8192 + (t >> 1) * 128 + (((wg * 2 + (t & 1)) ^ ((t >> 1) & 7)) << 4));
      __syncwarp();
      if (lane == 0) mbar_arrive(BAR_OD(pass));
    }
  }

  {
    named_bar(wg + 1, 128);
    if ((tid & 127) == 0) mbar_arrive(BAR_CL(4));
    const int role = __shfl_sync(~0u, lds1(sM + 32 + wg * 4), 0);
    if ((tid & 127) == 0) TS(4 + wg, 10);
    const int m = lane >> 3, r = lane & 7;
    const uint32_t stoff = (w4 * 16 + (m & 1) * 8 + r) * 128;
    if (role < 2) {
      if (role == 0 && (tid & 127) == 0) mbar_arrive(BAR_RL);
      if (!isB || role == 1) mbar_wait(BAR_CL(4), 0);
      float acc[64];
#pragma unroll 1
      for (int n = 0; n < 8; n++) {
        const uint32_t sl = tail_slots(isB, n);
        const uint32_t w0 = (sl >> 16) & 255, w1 = sl >> 24;
        const uint64_t da = make_desc(sb + ((sl >> (8 * role)) & 255) * 8192, 16, 1024, 1);
        const uint64_t db = make_desc(sb + w0 * 8192, (w1 - w0) * 8192, 1024, 1);
        mbar_wait(BAR_TF(n), 0);
        if (!isB && n >= 4) mbar_wait(n == 4 && role == 0 ? BAR_OD(1) : BAR_TF(2 * n + role), 0);
        if ((tid & 127) == 0 && role == 1) TS(2, 2 + n);
        wg_fence();
#pragma unroll
        for (int k = 0; k < 4; k++) wg_ss128<0, 1>(acc, da + k * 2, db + k * 128, (n | k) != 0);
        wg_commit();
        wg_wait<1>();
        if ((n == 1 || n == 2) && (tid & 127) == 0) mbar_arrive(BAR_TE(n - 1));
        __syncwarp();
      }
      wg_wait<0>();
      fence_regs<64>(acc);
      if ((tid & 127) == 0) TS(4 + wg, 11);
      const uint32_t x0 = sb + (role ? 16 : 8) * 8192, x1 = sb + (role ? 5 : 1) * 8192;
#pragma unroll
      for (int j = 0; j < 16; j += 2)
        stsm4((j < 8 ? x0 : x1) + stoff + ((((j & 7) + (m >> 1)) ^ r) << 4),
              pack_bf16(acc[4 * j], acc[4 * j + 1]), pack_bf16(acc[4 * j + 2], acc[4 * j + 3]),
              pack_bf16(acc[4 * j + 4], acc[4 * j + 5]), pack_bf16(acc[4 * j + 6], acc[4 * j + 7]));
      fence_async();
      named_bar(wg + 1, 128);
      if (w4 == 0 && elect_one()) {
        tma2d_store(&mOut, x0, isB * 512 + hg * 128, tok0 + role * 64);
        tma2d_store(&mOut, x1, isB * 512 + hg * 128 + 64, tok0 + role * 64);
        bulk_commit();
        asm volatile("cp.async.bulk.wait_group.read 0;" ::: "memory");
        TS(2, 11 + role);
      }
    }
  }
}

typedef CUresult (*EncodeFn)(CUtensorMap*, CUtensorMapDataType, cuuint32_t, void*, const cuuint64_t*, const cuuint64_t*,
                             const cuuint32_t*, const cuuint32_t*, CUtensorMapInterleave, CUtensorMapSwizzle,
                             CUtensorMapL2promotion, CUtensorMapFloatOOBfill);

static void make_map(EncodeFn enc, CUtensorMap* m, const void* ptr, uint64_t cols, uint64_t rows, uint32_t bc, uint32_t br,
                     CUtensorMapSwizzle sw = CU_TENSOR_MAP_SWIZZLE_128B) {
  cuuint64_t dims[2] = {cols, rows};
  cuuint64_t strides[1] = {cols * 2};
  cuuint32_t box[2] = {bc, br};
  cuuint32_t es[2] = {1, 1};
  enc(m, CU_TENSOR_MAP_DATA_TYPE_BFLOAT16, 2, (void*)ptr, dims, strides, box, es, CU_TENSOR_MAP_INTERLEAVE_NONE,
      sw, CU_TENSOR_MAP_L2_PROMOTION_L2_256B, CU_TENSOR_MAP_FLOAT_OOB_FILL_NONE);
}

extern "C" void kernel_launch(void* const* d_in, const int* in_sizes, int n_in, void* d_out, int out_size) {
  (void)in_sizes; (void)n_in; (void)out_size;
  static EncodeFn enc = nullptr;
  static void* pQ = nullptr; static void* pO = nullptr;
  if (!enc) {
    void* fn = nullptr; cudaDriverEntryPointQueryResult qr;
    cudaGetDriverEntryPoint("cuTensorMapEncodeTiled", &fn, cudaEnableDefault, &qr);
    enc = (EncodeFn)fn;
    cudaGetSymbolAddress(&pQ, g_Q);
    cudaGetSymbolAddress(&pO, g_O);
    cudaFuncSetAttribute(k1_main, cudaFuncAttributeMaxDynamicSharedMemorySize, SM_TOTAL);
  }
  CUtensorMap mXA64, mXB, mWq, mWqkv, mQst, mO, mOst, mWoA, mWoB, mOut, mO16;
  make_map(enc, &mXA64, d_in[0], 512, 2048, 64, 64);
  make_map(enc, &mWq, d_in[1], 512, 512, 64, 64);
  make_map(enc, &mWoA, d_in[4], 512, 512, 64, 64);
  make_map(enc, &mXB, d_in[5], 512, 2048, 64, 128);
  make_map(enc, &mWqkv, d_in[6], 1536, 512, 64, 64);
  make_map(enc, &mWoB, d_in[7], 512, 512, 64, 64);
  make_map(enc, &mQst, pQ, 512, 4096, 64, 128);
  make_map(enc, &mO, pO, 512, 4096, 64, 64);
  make_map(enc, &mOst, pO, 512, 4096, 64, 128);
  make_map(enc, &mOut, d_out, 1024, 2048, 64, 64);
  make_map(enc, &mO16, pO, 512, 4096, 16, 64, CU_TENSOR_MAP_SWIZZLE_NONE);
  Params prm{(const __nv_bfloat16*)d_in[2], (const __nv_bfloat16*)d_in[3], (const __nv_bfloat16*)d_in[0]};
  k1_main<<<132, 640, SM_TOTAL, cudaStreamPerThread>>>(mXA64, mXB, mWq, mWqkv, mQst, mOst, mO, mWoA, mWoB, mOut, mO16, prm);
}
```

```cpp
#include <cuda_runtime.h>
#include <cuda_bf16.h>
#include <cuda_fp16.h>
#include <cuda.h>
#include <stdint.h>

#define S_TOK 2048
#define D_MOD 512

__device__ __align__(1024) __nv_bfloat16 g_Q[2 * S_TOK * D_MOD];
__device__ __align__(1024) __nv_bfloat16 g_O[2 * S_TOK * D_MOD];
__device__ __align__(1024) uint4 g_KV[8 * S_TOK];
__device__ __align__(16) uint32_t g_stats[128];
__device__ __align__(16) float4 g_kvp[16 * 32 * 3 * 32];

#define TS(k, i) do {} while (0)
__device__ __forceinline__ uint32_t smem_u32(const void* p) { return (uint32_t)__cvta_generic_to_shared(p); }
__device__ __forceinline__ void mbar_init(uint32_t bar, int cnt) { asm volatile("mbarrier.init.shared::cta.b64 [%0], %1;" :: "r"(bar), "r"(cnt) : "memory"); }
__device__ __forceinline__ void mbar_expect_tx(uint32_t bar, uint32_t bytes) { asm volatile("mbarrier.arrive.expect_tx.shared::cta.b64 _, [%0], %1;" :: "r"(bar), "r"(bytes) : "memory"); }
__device__ __forceinline__ bool mbar_try(uint32_t bar, uint32_t parity) {
  uint32_t ok;
  asm volatile("{\n.reg .pred p;\nmbarrier.try_wait.parity.shared::cta.b64 p, [%1], %2;\nselp.b32 %0, 1, 0, p;\n}\n" : "=r"(ok) : "r"(bar), "r"(parity) : "memory");
  return ok;
}
__device__ __forceinline__ void mbar_wait(uint32_t bar, uint32_t parity) {
  asm volatile("{\n.reg .pred p;\n.reg .u32 c;\nmov.u32 c, 0;\n"
               "LW_%=:\n"
               "mbarrier.try_wait.parity.shared::cta.b64 p, [%0], %1;\n"
               "@p bra LD_%=;\n"
               "add.u32 c, c, 1;\n"
               "setp.lt.u32 p, c, 4000000;\n"
               "@p bra LW_%=;\n"
               "trap;\n"
               "LD_%=:\n}\n" :: "r"(bar), "r"(parity) : "memory");
}
__device__ __forceinline__ void mbar_arrive_cta(uint32_t bar, uint32_t cta) {
  asm volatile("{\n.reg .b32 ra;\nmapa.shared::cluster.u32 ra, %0, %1;\nmbarrier.arrive.shared::cluster.b64 _, [ra];\n}\n" :: "r"(bar), "r"(cta) : "memory");
}
__device__ __forceinline__ void cluster_sync() {
  asm volatile("barrier.cluster.arrive.relaxed.aligned;\nbarrier.cluster.wait.aligned;" ::: "memory");
}
__device__ __forceinline__ void tma2d(uint32_t dst, const CUtensorMap* m, int c0, int c1, uint32_t bar) {
  asm volatile("cp.async.bulk.tensor.2d.shared::cluster.global.mbarrier::complete_tx::bytes [%0], [%1, {%3, %4}], [%2];"
               :: "r"(dst), "l"(m), "r"(bar), "r"(c0), "r"(c1) : "memory");
}
__device__ __forceinline__ void tma2d_mc(uint32_t dst, const CUtensorMap* m, int c0, int c1, uint32_t bar, uint16_t mask) {
  asm volatile("cp.async.bulk.tensor.2d.shared::cluster.global.mbarrier::complete_tx::bytes.multicast::cluster [%0], [%1, {%3, %4}], [%2], %5;"
               :: "r"(dst), "l"(m), "r"(bar), "r"(c0), "r"(c1), "h"(mask) : "memory");
}
__device__ __forceinline__ void tma2d_store(const CUtensorMap* m, uint32_t src, int c0, int c1) {
  asm volatile("cp.async.bulk.tensor.2d.global.shared::cta.bulk_group [%0, {%2, %3}], [%1];"
               :: "l"(m), "r"(src), "r"(c0), "r"(c1) : "memory");
}
__device__ __forceinline__ void bulk_g2s(uint32_t dst, const void* src, uint32_t bytes, uint32_t bar) {
  asm volatile("cp.async.bulk.shared::cluster.global.mbarrier::complete_tx::bytes [%0], [%1], %2, [%3];"
               :: "r"(dst), "l"(src), "r"(bytes), "r"(bar) : "memory");
}
__device__ __forceinline__ void bulk_commit() { asm volatile("cp.async.bulk.commit_group;" ::: "memory"); }
__device__ __forceinline__ void bulk_wait_all() { asm volatile("cp.async.bulk.wait_group 0;" ::: "memory"); }
__device__ __forceinline__ void fence_async() { asm volatile("fence.proxy.async.shared::cta;" ::: "memory"); }
__device__ __forceinline__ void named_bar(int id, int n) { asm volatile("bar.sync %0, %1;" :: "r"(id), "r"(n) : "memory"); }
__device__ __forceinline__ void pdl_launch() { asm volatile("griddepcontrol.launch_dependents;" ::: "memory"); }
__device__ __forceinline__ void pdl_wait() { asm volatile("griddepcontrol.wait;" ::: "memory"); }
__device__ __forceinline__ void wg_fence() { asm volatile("wgmma.fence.sync.aligned;" ::: "memory"); }
__device__ __forceinline__ void wg_commit() { asm volatile("wgmma.commit_group.sync.aligned;" ::: "memory"); }
template <int n> __device__ __forceinline__ void wg_wait() { asm volatile("wgmma.wait_group.sync.aligned %0;" :: "n"(n) : "memory"); }
template <int n> __device__ __forceinline__ void fence_regs(float* r) {
#pragma unroll
  for (int i = 0; i < n; i++) asm volatile("" : "+f"(r[i]) :: "memory");
}
template <int n> __device__ __forceinline__ void fence_regs(uint32_t* r) {
#pragma unroll
  for (int i = 0; i < n; i++) asm volatile("" : "+r"(r[i]) :: "memory");
}
__device__ __forceinline__ uint64_t make_desc(uint32_t addr, uint32_t lbo, uint32_t sbo, uint32_t swz) {
  return (uint64_t)((addr & 0x3FFFF) >> 4) | ((uint64_t)(lbo >> 4) << 16) | ((uint64_t)(sbo >> 4) << 32) | ((uint64_t)swz << 62);
}
__device__ __forceinline__ float ex2f(float x) { float y; asm("ex2.approx.ftz.f32 %0, %1;" : "=f"(y) : "f"(x)); return y; }
__device__ __forceinline__ uint32_t pack_bf16(float lo, float hi) { uint32_t r; asm("cvt.rn.bf16x2.f32 %0, %1, %2;" : "=r"(r) : "f"(hi), "f"(lo)); return r; }
__device__ __forceinline__ uint32_t pack_f16(float lo, float hi) { uint32_t r; asm("cvt.rn.f16x2.f32 %0, %1, %2;" : "=r"(r) : "f"(hi), "f"(lo)); return r; }
__device__ __forceinline__ float bf_lo(uint32_t v) { return __uint_as_float(v << 16); }
__device__ __forceinline__ float bf_hi(uint32_t v) { return __uint_as_float(v & 0xFFFF0000u); }
__device__ __forceinline__ float rbf(float x) { return __bfloat162float(__float2bfloat16_rn(x)); }
__device__ __forceinline__ void stsm4(uint32_t a, uint32_t r0, uint32_t r1, uint32_t r2, uint32_t r3) {
  asm volatile("stmatrix.sync.aligned.m8n8.x4.shared.b16 [%0], {%1,%2,%3,%4};" :: "r"(a), "r"(r0), "r"(r1), "r"(r2), "r"(r3) : "memory");
}
__device__ __forceinline__ void stsm4t(uint32_t a, uint32_t r0, uint32_t r1, uint32_t r2, uint32_t r3) {
  asm volatile("stmatrix.sync.aligned.m8n8.x4.trans.shared.b16 [%0], {%1,%2,%3,%4};" :: "r"(a), "r"(r0), "r"(r1), "r"(r2), "r"(r3) : "memory");
}
__device__ __forceinline__ void mma_bf16(float* d, uint32_t a0, uint32_t a1, uint32_t a2, uint32_t a3, uint32_t b0, uint32_t b1) {
  asm volatile("mma.sync.aligned.m16n8k16.row.col.f32.bf16.bf16.f32 {%0,%1,%2,%3}, {%4,%5,%6,%7}, {%8,%9}, {%0,%1,%2,%3};"
               : "+f"(d[0]), "+f"(d[1]), "+f"(d[2]), "+f"(d[3]) : "r"(a0), "r"(a1), "r"(a2), "r"(a3), "r"(b0), "r"(b1));
}
template<int SD> __device__ __forceinline__ void wg_qs24(float* d, uint64_t da, uint64_t db) {
  asm volatile("wgmma.mma_async.sync.aligned.m64n24k16.f32.f16.f16 {%0,%1,%2,%3,%4,%5,%6,%7,%8,%9,%10,%11}, %12, %13, %14, 1, 1, 0, 0;"
   : "+f"(d[0]),"+f"(d[1]),"+f"(d[2]),"+f"(d[3]),"+f"(d[4]),"+f"(d[5]),"+f"(d[6]),"+f"(d[7]),"+f"(d[8]),"+f"(d[9]),"+f"(d[10]),"+f"(d[11])
   : "l"(da),"l"(db),"n"(SD));
}
template<int SD> __device__ __forceinline__ void wg_qs72(float* d, uint64_t da, uint64_t db) {
  asm volatile("wgmma.mma_async.sync.aligned.m64n72k16.f32.f16.f16 {%0,%1,%2,%3,%4,%5,%6,%7,%8,%9,%10,%11,%12,%13,%14,%15,%16,%17,%18,%19,%20,%21,%22,%23,%24,%25,%26,%27,%28,%29,%30,%31,%32,%33,%34,%35}, %36, %37, %38, 1, 1, 0, 0;"
   : "+f"(d[0]),"+f"(d[1]),"+f"(d[2]),"+f"(d[3]),"+f"(d[4]),"+f"(d[5]),"+f"(d[6]),"+f"(d[7]),"+f"(d[8]),"+f"(d[9]),"+f"(d[10]),"+f"(d[11]),"+f"(d[12]),"+f"(d[13]),"+f"(d[14]),"+f"(d[15]),"+f"(d[16]),"+f"(d[17]),"+f"(d[18]),"+f"(d[19]),"+f"(d[20]),"+f"(d[21]),"+f"(d[22]),"+f"(d[23]),"+f"(d[24]),"+f"(d[25]),"+f"(d[26]),"+f"(d[27]),"+f"(d[28]),"+f"(d[29]),"+f"(d[30]),"+f"(d[31]),"+f"(d[32]),"+f"(d[33]),"+f"(d[34]),"+f"(d[35])
   : "l"(da),"l"(db),"n"(SD));
}
template<int SD> __device__ __forceinline__ void wg_pv24(float* d, const uint32_t* a, uint64_t desc) {
  asm volatile("wgmma.mma_async.sync.aligned.m64n24k16.f32.bf16.bf16 {%0,%1,%2,%3,%4,%5,%6,%7,%8,%9,%10,%11}, {%12,%13,%14,%15}, %16, %17, 1, 1, 1;"
   : "+f"(d[0]),"+f"(d[1]),"+f"(d[2]),"+f"(d[3]),"+f"(d[4]),"+f"(d[5]),"+f"(d[6]),"+f"(d[7]),"+f"(d[8]),"+f"(d[9]),"+f"(d[10]),"+f"(d[11])
   : "r"(a[0]),"r"(a[1]),"r"(a[2]),"r"(a[3]),"l"(desc),"n"(SD));
}
template<int TA, int TB> __device__ __forceinline__ void wg_ss128(float* d, uint64_t da, uint64_t db, int sd) {
  asm volatile("{\n.reg .pred p;\nsetp.ne.b32 p, %66, 0;\n"
   "wgmma.mma_async.sync.aligned.m64n128k16.f32.bf16.bf16 {%0,%1,%2,%3,%4,%5,%6,%7,%8,%9,%10,%11,%12,%13,%14,%15,%16,%17,%18,%19,%20,%21,%22,%23,%24,%25,%26,%27,%28,%29,%30,%31,%32,%33,%34,%35,%36,%37,%38,%39,%40,%41,%42,%43,%44,%45,%46,%47,%48,%49,%50,%51,%52,%53,%54,%55,%56,%57,%58,%59,%60,%61,%62,%63}, %64, %65, p, 1, 1, %67, %68;\n}\n"
   : "+f"(d[0]),"+f"(d[1]),"+f"(d[2]),"+f"(d[3]),"+f"(d[4]),"+f"(d[5]),"+f"(d[6]),"+f"(d[7]),"+f"(d[8]),"+f"(d[9]),"+f"(d[10]),"+f"(d[11]),"+f"(d[12]),"+f"(d[13]),"+f"(d[14]),"+f"(d[15]),"+f"(d[16]),"+f"(d[17]),"+f"(d[18]),"+f"(d[19]),"+f"(d[20]),"+f"(d[21]),"+f"(d[22]),"+f"(d[23]),"+f"(d[24]),"+f"(d[25]),"+f"(d[26]),"+f"(d[27]),"+f"(d[28]),"+f"(d[29]),"+f"(d[30]),"+f"(d[31]),"+f"(d[32]),"+f"(d[33]),"+f"(d[34]),"+f"(d[35]),"+f"(d[36]),"+f"(d[37]),"+f"(d[38]),"+f"(d[39]),"+f"(d[40]),"+f"(d[41]),"+f"(d[42]),"+f"(d[43]),"+f"(d[44]),"+f"(d[45]),"+f"(d[46]),"+f"(d[47]),"+f"(d[48]),"+f"(d[49]),"+f"(d[50]),"+f"(d[51]),"+f"(d[52]),"+f"(d[53]),"+f"(d[54]),"+f"(d[55]),"+f"(d[56]),"+f"(d[57]),"+f"(d[58]),"+f"(d[59]),"+f"(d[60]),"+f"(d[61]),"+f"(d[62]),"+f"(d[63])
   : "l"(da),"l"(db),"r"(sd),"n"(TA),"n"(TB));
}
template<int TA, int TB> __device__ __forceinline__ void wg_ss64(float* d, uint64_t da, uint64_t db, int sd) {
  asm volatile("{\n.reg .pred p;\nsetp.ne.b32 p, %34, 0;\n"
   "wgmma.mma_async.sync.aligned.m64n64k16.f32.bf16.bf16 {%0,%1,%2,%3,%4,%5,%6,%7,%8,%9,%10,%11,%12,%13,%14,%15,%16,%17,%18,%19,%20,%21,%22,%23,%24,%25,%26,%27,%28,%29,%30,%31}, %32, %33, p, 1, 1, %35, %36;\n}\n"
   : "+f"(d[0]),"+f"(d[1]),"+f"(d[2]),"+f"(d[3]),"+f"(d[4]),"+f"(d[5]),"+f"(d[6]),"+f"(d[7]),"+f"(d[8]),"+f"(d[9]),"+f"(d[10]),"+f"(d[11]),"+f"(d[12]),"+f"(d[13]),"+f"(d[14]),"+f"(d[15]),"+f"(d[16]),"+f"(d[17]),"+f"(d[18]),"+f"(d[19]),"+f"(d[20]),"+f"(d[21]),"+f"(d[22]),"+f"(d[23]),"+f"(d[24]),"+f"(d[25]),"+f"(d[26]),"+f"(d[27]),"+f"(d[28]),"+f"(d[29]),"+f"(d[30]),"+f"(d[31])
   : "l"(da),"l"(db),"r"(sd),"n"(TA),"n"(TB));
}
template<int TA, int TB> __device__ __forceinline__ void wg_ss8(float* d, uint64_t da, uint64_t db, int sd) {
  asm volatile("{\n.reg .pred p;\nsetp.ne.b32 p, %6, 0;\n"
   "wgmma.mma_async.sync.aligned.m64n8k16.f32.bf16.bf16 {%0,%1,%2,%3}, %4, %5, p, 1, 1, %7, %8;\n}\n"
   : "+f"(d[0]),"+f"(d[1]),"+f"(d[2]),"+f"(d[3])
   : "l"(da),"l"(db),"r"(sd),"n"(TA),"n"(TB));
}

__device__ __forceinline__ uint32_t phi2(float a, float b) {
  uint32_t r, e;
  asm("cvt.rn.relu.bf16x2.f32 %0, %1, %2;" : "=r"(r) : "f"(b), "f"(a));
  e = pack_bf16(ex2f(a * 1.4426950408889634f), ex2f(b * 1.4426950408889634f));
  asm("add.rn.bf16x2 %0, %0, %1;" : "+r"(e) : "r"(0x35863586u));
  asm("min.NaN.bf16x2 %0, %0, %1;" : "+r"(e) : "r"(0x3F803F80u));
  asm("add.rn.bf16x2 %0, %0, %1;" : "+r"(e) : "r"(r));
  return e;
}

__device__ __forceinline__ void mbar_wait_long(uint32_t bar, uint32_t parity) {
  asm volatile("{\n.reg .pred p;\n.reg .u32 c;\nmov.u32 c, 0;\n"
               "LW_%=:\n"
               "mbarrier.try_wait.parity.shared::cta.b64 p, [%0], %1, 100000;\n"
               "@p bra LD_%=;\n"
               "add.u32 c, c, 1;\n"
               "setp.lt.u32 p, c, 20000;\n"
               "@p bra LW_%=;\n"
               "trap;\n"
               "LD_%=:\n}\n" :: "r"(bar), "r"(parity) : "memory");
}
__device__ __forceinline__ void mbar_arrive(uint32_t bar) { asm volatile("mbarrier.arrive.shared::cta.b64 _, [%0];" :: "r"(bar) : "memory"); }
__device__ __forceinline__ void named_arrive(int id, int n) { asm volatile("bar.arrive %0, %1;" :: "r"(id), "r"(n) : "memory"); }
__device__ __forceinline__ void fence_async_all() { asm volatile("fence.proxy.async.global;" ::: "memory"); }
__device__ __forceinline__ void flag_add(uint32_t* f) { asm volatile("fence.acq_rel.gpu;\nred.relaxed.gpu.global.add.u32 [%0], 1;" :: "l"(f) : "memory"); }
#define PUBLISH(f) asm volatile("fence.proxy.async.global;\nred.relaxed.gpu.global.add.u32 [%0], 1;" :: "l"(f) : "memory")
__device__ __forceinline__ void flag_wait(const uint32_t* f, uint32_t target) {
  uint32_t v;
#pragma unroll 1
  for (int it = 0;; it++) {
    asm volatile("ld.acquire.gpu.global.u32 %0, [%1];" : "=r"(v) : "l"(f) : "memory");
    if ((int32_t)(v - target) >= 0) break;
    if (it > 2000000) __trap();
    __nanosleep(64);
  }
}
__device__ __forceinline__ bool mbar_test(uint32_t bar, uint32_t parity) {
  uint32_t ok;
  asm volatile("{\n.reg .pred p;\nmbarrier.test_wait.parity.shared::cta.b64 p, [%1], %2;\nselp.b32 %0, 1, 0, p;\n}\n" : "=r"(ok) : "r"(bar), "r"(parity) : "memory");
  return ok;
}
__device__ __forceinline__ bool elect_one() {
  uint32_t p;
  asm volatile("{\n.reg .pred P;\nelect.sync _|P, 0xFFFFFFFF;\nselp.b32 %0, 1, 0, P;\n}\n" : "=r"(p));
  return p;
}
__device__ __forceinline__ void lds4(uint32_t a, uint32_t* r) {
  asm volatile("ld.shared.v4.b32 {%0,%1,%2,%3}, [%4];" : "=r"(r[0]), "=r"(r[1]), "=r"(r[2]), "=r"(r[3]) : "r"(a) : "memory");
}
__device__ __forceinline__ uint32_t lds1(uint32_t a) { uint32_t r; asm volatile("ld.shared.b32 %0, [%1];" : "=r"(r) : "r"(a) : "memory"); return r; }
__device__ __forceinline__ void sts1(uint32_t a, uint32_t v) { asm volatile("st.shared.b32 [%0], %1;" :: "r"(a), "r"(v) : "memory"); }
__device__ __forceinline__ void sts4(uint32_t a, uint32_t r0, uint32_t r1, uint32_t r2, uint32_t r3) {
  asm volatile("st.shared.v4.b32 [%0], {%1,%2,%3,%4};" :: "r"(a), "r"(r0), "r"(r1), "r"(r2), "r"(r3) : "memory");
}
__device__ __forceinline__ void ldsm4(uint32_t a, uint32_t* r) {
  asm volatile("ldmatrix.sync.aligned.m8n8.x4.shared.b16 {%0,%1,%2,%3}, [%4];" : "=r"(r[0]), "=r"(r[1]), "=r"(r[2]), "=r"(r[3]) : "r"(a) : "memory");
}
__device__ __forceinline__ float rcpf(float x) { float y; asm("rcp.approx.ftz.f32 %0, %1;" : "=f"(y) : "f"(x)); return y; }
__device__ __forceinline__ uint32_t hfma2(uint32_t a, uint32_t b, uint32_t c) { uint32_t r; asm("fma.rn.f16x2 %0, %1, %2, %3;" : "=r"(r) : "r"(a), "r"(b), "r"(c)); return r; }
__device__ __forceinline__ uint32_t hadd2(uint32_t a, uint32_t b) { uint32_t r; asm("add.rn.f16x2 %0, %1, %2;" : "=r"(r) : "r"(a), "r"(b)); return r; }

#define STEPK 96
#define GIMAP(i) ((((i) & 1) << 2) | (((i) >> 1) & 3) | ((i) & 8))
#define QSCALE 0.36067376022224085f
#define SMAGIC (512.0f + 2.0f * (191.0f - 30.0f - 1.5823545f))
#define VSHIFT 1073741824.0f

__device__ uint32_t g_epoch[132];
__device__ uint32_t g_flag[288 * 8];
#define FLAG_KV (g_flag)
#define FLAG_B(h) (g_flag + (4 + (h)) * 8)
#define FLAG_OA(cta, pass) (g_flag + (16 + (cta) * 2 + (pass)) * 8)
#define FLAG_LM(i) (g_flag + (272 + (i)) * 8)

#define SM_TOTAL (224 * 1024 + 2048 + 1024)
#define OFF_K 0
#define OFF_F 65536
#define OFF_V 131072
#define OFF_MISC (224 * 1024)

#define BAR_FULL(s) (bars + 8 * (s))
#define BAR_EMPTY(s) (bars + 24 + 8 * (s))
#define BAR_KV(c) (bars + 48 + 8 * (c))
#define BAR_BDONE (bars + 80)
#define BAR_Q (bars + 88)
#define BAR_GO (bars + 96)
#define BAR_Q2 (bars + 104)
#define BAR_OD(p) (bars + 112 + 8 * (p))
#define BAR_CL(c) (bars + 128 + 8 * (c))
#define BAR_TE(i) (bars + 168 + 8 * (i))
#define BAR_RL (bars + 184)
#define BAR_TF(g) (bars + 224 + 8 * (g))
#define BAR_XA(w) (bars + 352 + 8 * (w))
#define BAR_VB(c) (bars + 384 + 8 * (c))

__device__ __forceinline__ uint32_t exp2_pair_fix(float d0, float d1, uint32_t c63, uint32_t m1) {
  uint32_t w, y, s, r;
  asm("prmt.b32 %0, %1, %2, 0x6521;" : "=r"(w) : "r"(__float_as_uint(d0)), "r"(__float_as_uint(d1)));
  asm("lop3.b32 %0, %1, 0x007F007F, %2, 0xEA;" : "=r"(y) : "r"(w), "r"(c63));
  asm("mad.lo.u32 %0, %1, %2, %3;" : "=r"(s) : "r"(y), "r"(m1), "r"(w));
  asm("fma.rn.bf16x2 %0, %1, %2, %3;" : "=r"(r) : "r"(w), "r"(y), "r"(s));
  return r;
}

__device__ __forceinline__ void attn_slow(const __nv_bfloat16* xa, const __nv_bfloat16* wq, uint32_t dst) {
  const int t = threadIdx.x & 127;
  const int row = t >> 1, half = t & 1;
  float q[16];
  {
    float a[8];
#pragma unroll
    for (int i = 0; i < 8; i++) a[i] = 0.f;
#pragma unroll 1
    for (int k = 0; k < D_MOD; k++) {
      const float x = __bfloat162float(xa[(size_t)row * D_MOD + k]);
      const uint4 w = *(const uint4*)(wq + (size_t)k * D_MOD + half * 8);
      const uint32_t ww[4] = {w.x, w.y, w.z, w.w};
#pragma unroll
      for (int i = 0; i < 4; i++) { a[2 * i] = fmaf(x, bf_lo(ww[i]), a[2 * i]); a[2 * i + 1] = fmaf(x, bf_hi(ww[i]), a[2 * i + 1]); }
    }
#pragma unroll
    for (int i = 0; i < 8; i++) {
      const float mine = rbf(a[i]), other = __shfl_xor_sync(~0u, mine, 1);
      q[i] = half ? other : mine; q[8 + i] = half ? mine : other;
    }
  }
  float m = -INFINITY, l = 0.f, o[16];
#pragma unroll
  for (int i = 0; i < 16; i++) o[i] = 0.f;
#pragma unroll 1
  for (int j = half * 1024; j < half * 1024 + 1024; j++) {
    uint4 ka = g_KV[4 * S_TOK + j], kb = g_KV[5 * S_TOK + j];
    uint4 va = g_KV[6 * S_TOK + j], vb = g_KV[7 * S_TOK + j];
    uint32_t kk[8] = {ka.x, ka.y, ka.z, ka.w, kb.x, kb.y, kb.z, kb.w};
    uint32_t vv[8] = {va.x, va.y, va.z, va.w, vb.x, vb.y, vb.z, vb.w};
    float s = 0.f;
#pragma unroll
    for (int i = 0; i < 8; i++) { s = fmaf(q[2 * i], bf_lo(kk[i]), s); s = fmaf(q[2 * i + 1], bf_hi(kk[i]), s); }
    s = rbf(s) * 0.25f;
    if (s > m) {
      float c = __expf(m - s);
      l *= c;
#pragma unroll
      for (int i = 0; i < 16; i++) o[i] *= c;
      m = s;
    }
    float p = __expf(s - m);
    l += p;
#pragma unroll
    for (int i = 0; i < 8; i++) { o[2 * i] = fmaf(p, bf_lo(vv[i]), o[2 * i]); o[2 * i + 1] = fmaf(p, bf_hi(vv[i]), o[2 * i + 1]); }
  }
  float m2 = __shfl_xor_sync(~0u, m, 1);
  float mm = fmaxf(m, m2);
  float c = __expf(m - mm);
  l *= c; l += __shfl_xor_sync(~0u, l, 1);
  float inv = 1.f / l;
  uint32_t r[8];
#pragma unroll
  for (int i = 0; i < 16; i++) { o[i] *= c; o[i] += __shfl_xor_sync(~0u, o[i], 1); o[i] *= inv; }
#pragma unroll
  for (int i = 0; i < 8; i++) r[i] = pack_bf16(o[2 * i], o[2 * i + 1]);
  if (half == 0) sts4(dst, r[0], r[1], r[2], r[3]); else sts4(dst, r[4], r[5], r[6], r[7]);
  fence_async();
}

struct Params { const __nv_bfloat16* wk; const __nv_bfloat16* wv; const __nv_bfloat16* xa; const __nv_bfloat16* wq; };
__device__ __forceinline__ void cp16(uint32_t dst, const void* src) { asm volatile("cp.async.cg.shared.global [%0], [%1], 16;" :: "r"(dst), "l"(src) : "memory"); }

__device__ __forceinline__ void helper_cta(const int h, const uint32_t sb, const uint32_t bars, const int wg, const int w4,
                                           const CUtensorMap* mQ, const CUtensorMap* mOs) {
  const int lane = threadIdx.x & 31;
  mbar_wait(BAR_GO, 0);
  const int cb = wg & 1, col = h * 128 + cb * 64, row0 = S_TOK + (wg >> 1) * 1024;
  const uint32_t buf = sb + wg * 49152;
  if (w4 == 0 && elect_one()) {
    fence_async_all();
#pragma unroll 1
    for (int u = 0; u < 3; u++) {
      mbar_expect_tx(BAR_TF(wg * 3 + u), 16384);
      tma2d(buf + u * 16384, mQ, col, row0 + u * 128, BAR_TF(wg * 3 + u));
    }
  }
  const int head = h * 8 + cb * 4 + w4;
  float4 a0 = make_float4(0, 0, 0, 0), a1 = a0, a2 = a0;
#pragma unroll 8
  for (int tt = 0; tt < 16; tt++) {
    const float4* src = g_kvp + ((tt * 32 + head) * 3) * 32 + lane;
    float4 u = src[0], v = src[32], w = src[64];
    a0.x += u.x; a0.y += u.y; a0.z += u.z; a0.w += u.w;
    a1.x += v.x; a1.y += v.y; a1.z += v.z; a1.w += v.w;
    a2.x += w.x; a2.y += w.y; a2.z += w.z; a2.w += w.w;
  }
  const uint32_t b00 = pack_bf16(a0.x, a0.y), b01 = pack_bf16(a0.z, a0.w);
  const uint32_t b10 = pack_bf16(a1.x, a1.y), b11 = pack_bf16(a1.z, a1.w);
  const uint32_t bz0 = pack_bf16(a2.x, a2.y), bz1 = pack_bf16(a2.z, a2.w);
  const int m = lane >> 3, r = lane & 7;
  const uint32_t off = ((m & 1) * 8 + r) * 128 + (((w4 * 2 + (m >> 1)) ^ r) << 4);
  int s = 0, ph = 0;
#pragma unroll 1
  for (int u = 0; u < 8; u++) {
    const uint32_t bb = buf + s * 16384;
    mbar_wait(BAR_TF(wg * 3 + s), ph);
#pragma unroll
    for (int mt = 0; mt < 8; mt++) {
      uint32_t a[4];
      ldsm4(bb + mt * 2048 + off, a);
      float n0[4] = {0, 0, 0, 0}, n1[4] = {0, 0, 0, 0}, dn[4] = {0, 0, 0, 0};
      mma_bf16(dn, a[0], a[1], a[2], a[3], bz0, bz1);
      mma_bf16(n0, a[0], a[1], a[2], a[3], b00, b01);
      mma_bf16(n1, a[0], a[1], a[2], a[3], b10, b11);
      const float i0 = rcpf(dn[0] + 1e-6f), i1 = rcpf(dn[2] + 1e-6f);
      stsm4(bb + mt * 2048 + off, pack_bf16(n0[0] * i0, n0[1] * i0), pack_bf16(n0[2] * i1, n0[3] * i1),
            pack_bf16(n1[0] * i0, n1[1] * i0), pack_bf16(n1[2] * i1, n1[3] * i1));
    }
    fence_async();
    named_bar(wg + 1, 128);
    if (w4 == 0 && lane == 0) {
      tma2d_store(mOs, bb, col, row0 + u * 128);
      bulk_commit();
      if (u >= 1 && u + 2 < 8) {
        asm volatile("cp.async.bulk.wait_group.read 1;" ::: "memory");
        const int sp = s == 0 ? 2 : s - 1;
        mbar_expect_tx(BAR_TF(wg * 3 + sp), 16384);
        tma2d(buf + sp * 16384, mQ, col, row0 + (u + 2) * 128, BAR_TF(wg * 3 + sp));
      }
    }
    __syncwarp();
    if (++s == 3) { s = 0; ph ^= 1; }
  }
  if (w4 == 0 && lane == 0) {
    bulk_wait_all();
    fence_async_all();
    flag_add(FLAG_LM((h * 2 + cb) * 2 + (wg >> 1)));
    if (wg == 0) TS(1, 8);
  }
}

#define STAGE(s) (sb + (2 - (s)) * 65536)
__device__ __forceinline__ uint32_t xa_addr(uint32_t sb, int kb) {
  return sb + (kb >= 1 && kb <= 4 ? OFF_V + 65536 + (kb - 1) * 8192 : 16384 + (kb == 5 ? OFF_K : (kb == 6 ? OFF_V : OFF_F)));
}
#define XA7_TMP (sb + OFF_K + 40960)
#define WKV_TMP (sb + OFF_K + 32768)
template <int TR> __device__ __forceinline__ void proj_kb(float* acc, uint32_t aA, uint32_t aB, int first) {
  const uint64_t da = make_desc(aA, TR ? 8192 : 16, 1024, 1);
  const uint64_t db = make_desc(aB, TR ? 16 : 8192, 1024, 1);
  wg_fence();
#pragma unroll
  for (int k = 0; k < 4; k++) wg_ss128<TR, 1 - TR>(acc, da + k * (TR ? 128 : 2), db + k * (TR ? 2 : 128), k != 0 || !first);
  wg_commit();
}
template <int TR> __device__ __forceinline__ void proj_loop(float* acc, uint32_t sb, uint32_t bars, uint32_t offA, uint32_t offB,
                                                            int wg, uint32_t sWKV) {
  {
    float kv[4];
    if (threadIdx.x == 0) TS(0, 13);
    mbar_wait(BAR_XA(wg), 0);
    if (threadIdx.x == 0) TS(0, 1);
    const uint64_t da0 = make_desc(xa_addr(sb, 2 * wg), 16, 1024, 1);
    const uint64_t da1 = make_desc(wg == 3 ? XA7_TMP : xa_addr(sb, 2 * wg + 1), 16, 1024, 1);
    const uint64_t db = make_desc(sWKV + wg * 2048, 128, 128, 0);
    wg_fence();
#pragma unroll
    for (int k = 0; k < 8; k++) wg_ss8<0, 1>(kv, (k < 4 ? da0 : da1) + (k & 3) * 2, db + k * 16, k != 0);
    wg_commit();
    wg_wait<0>();
    fence_regs<4>(kv);
    named_bar(wg + 1, 128);
    sts4(sWKV + threadIdx.x * 16, __float_as_uint(kv[0]), __float_as_uint(kv[1]), __float_as_uint(kv[2]), __float_as_uint(kv[3]));
    __syncwarp();
    if ((threadIdx.x & 31) == 0) mbar_arrive(BAR_GO);
  }
  int s = 0, ph = 0, sp = 0;
#pragma unroll 1
  for (int kb = 0; kb < 8; kb++) {
    mbar_wait(BAR_FULL(s), ph);
    if (threadIdx.x == 0) TS(0, 2 + kb);
    if (TR == 0) mbar_wait(BAR_XA(kb >> 1), 0);
    proj_kb<TR>(acc, TR ? STAGE(s) + offA : xa_addr(sb, kb), STAGE(s) + offB, kb == 0);
    wg_wait<1>();
    if (kb >= 1 && (threadIdx.x & 127) == 0) {
      mbar_arrive(BAR_EMPTY(sp));
      if (TR == 0 && kb == 5) mbar_arrive(BAR_VB(1));
    }
    __syncwarp();
    sp = s;
    if (++s == 3) { s = 0; ph ^= 1; }
  }
  wg_wait<0>();
  fence_regs<64>(acc);
}

__device__ __forceinline__ uint32_t tail_slots(int isB, int n) {
  if (n < 4) return n < 2 ? (n == 0 ? 0x0D0C0B0Au : 0x04000F0Eu) : (n == 2 ? 0x18141008u : 0x15110501u);
  if (isB) return n < 6 ? (n == 4 ? 0x19120602u : 0x0D0C0B0Au) : (n == 6 ? 0x04000F0Eu : 0x13070316u);
  return n < 6 ? (n == 4 ? 0x1902031Au : 0x12061307u) : (n == 6 ? 0x16091B17u : 0x0D0C0B0Au);
}

__device__ __forceinline__ void take_role(uint32_t sM, int wg) {
  uint32_t r;
  asm volatile("atom.shared.add.u32 %0, [%1], 1;" : "=r"(r) : "r"(sM + 20) : "memory");
  sts1(sM + 32 + wg * 4, r);
}

__global__ void __launch_bounds__(640, 1)
k1_main(const __grid_constant__ CUtensorMap mXA64, const __grid_constant__ CUtensorMap mXB,
        const __grid_constant__ CUtensorMap mWq, const __grid_constant__ CUtensorMap mWqkv,
        const __grid_constant__ CUtensorMap mQst, const __grid_constant__ CUtensorMap mOst,
        const __grid_constant__ CUtensorMap mO, const __grid_constant__ CUtensorMap mWoA,
        const __grid_constant__ CUtensorMap mWoB, const __grid_constant__ CUtensorMap mOut,
        const __grid_constant__ CUtensorMap mO16, const Params prm) {
  extern __shared__ uint8_t smem_raw[];
  const uint32_t sb = (smem_u32(smem_raw) + 1023u) & ~1023u;
  const uint32_t bars = sb + OFF_MISC, sM = bars + 512, sT = bars + 1024;
  const int tid = threadIdx.x, warp = __shfl_sync(~0u, tid >> 5, 0), wg = warp >> 2, w4 = warp & 3, lane = tid & 31;
  const bool helper = blockIdx.x >= 128;
  if (tid == 0) TS(0, 0);
  const int G = blockIdx.x >> 4, gi = GIMAP(blockIdx.x & 15);
  const int tbA = G * 4 + (gi >> 2), hg = gi & 3;
  const int ttB = (G >> 1) * 4 + (gi >> 2), hq = (G & 1) * 4 + (gi & 3);
  const int isB = tbA & 1, tok0 = (tbA >> 1) * 128;
  auto issue = [&](int kb, int s, int part) {
    const uint32_t fb = BAR_FULL(s), st = STAGE(s);
    if (part & 1) {
      mbar_expect_tx(fb, kb == 7 ? 65536 : 57344);
      if (kb == 7) tma2d(st + 16384, &mXA64, kb * 64, tbA * 64, fb);
      tma2d(st, &mWq, hg * 128, kb * 64, fb);
      tma2d(st + 8192, &mWq, hg * 128 + 64, kb * 64, fb);
      tma2d(st + 49152, &mXB, kb * 64, ttB * 128, fb);
      tma2d(st + 24576, &mWqkv, hq * 64, kb * 64, fb);
    }
    if (part & 2) {
      tma2d(st + 32768, &mWqkv, 512 + hq * 64, kb * 64, fb);
      tma2d(st + 40960, &mWqkv, 1024 + hq * 64, kb * 64, fb);
    }
  };
  const uint32_t sOne = sb + OFF_V + 65536, sWKV = WKV_TMP;
  if (warp >= 16) {
    if (warp == 17) {
      if (elect_one()) {
        mbar_init(BAR_BDONE, 8); mbar_init(BAR_Q, 6); mbar_init(BAR_GO, helper ? 1 : 16); mbar_init(BAR_Q2, 1);
        mbar_init(BAR_OD(0), 16); mbar_init(BAR_OD(1), 16); mbar_init(BAR_CL(0), 1); mbar_init(BAR_FULL(2), 1);
#pragma unroll
        for (int i = 0; i < 4; i++) mbar_init(BAR_CL(i + 1), i == 0 ? 5 : 4);
#pragma unroll
        for (int i = 0; i < 3; i++) { mbar_init(BAR_EMPTY(i), 4); mbar_init(BAR_KV(i), 1); mbar_init(BAR_VB(i), i == 2 ? 4 : 1); }
        sts1(sM + 20, 0);
        asm volatile("fence.mbarrier_init.release.cluster;" ::: "memory");
      }
    } else if (warp == 18) {
      if (elect_one()) {
#pragma unroll
        for (int i = 0; i < 2; i++) mbar_init(BAR_TE(i), 2);
        mbar_init(BAR_RL, 1);
#pragma unroll
        for (int i = 0; i < 16; i++) mbar_init(BAR_TF(i), 1);
        asm volatile("fence.mbarrier_init.release.cluster;" ::: "memory");
      }
    } else if (warp == 16 && !helper && elect_one()) {
#pragma unroll
      for (int w = 0; w < 4; w++) mbar_init(BAR_XA(w), 1);
      mbar_init(BAR_FULL(0), 1); mbar_init(BAR_FULL(1), 1);
      asm volatile("fence.mbarrier_init.release.cluster;" ::: "memory");
#pragma unroll
      for (int w = 0; w < 4; w++) {
        mbar_expect_tx(BAR_XA(w), 16384);
        tma2d(xa_addr(sb, 2 * w), &mXA64, w * 128, tbA * 64, BAR_XA(w));
        tma2d(w == 3 ? XA7_TMP : xa_addr(sb, 2 * w + 1), &mXA64, w * 128 + 64, tbA * 64, BAR_XA(w));
      }
      TS(0, 14);
      issue(0, 0, 3);
    }
  } else if (!helper) {
    const uint4 v = __ldg((const uint4*)(hg >= 2 ? prm.wv : prm.wk) + tid * 2 + (hg & 1));
    sts4(sWKV + tid * 16, v.x, v.y, v.z, v.w);
    fence_async();
  }
  __syncthreads();
  if (wg == 4) {
    if (w4 == 0 && !helper && elect_one()) { issue(1, 1, 3); issue(2, 2, 1); TS(0, 15); }
    asm volatile("setmaxnreg.dec.sync.aligned.u32 32;");
    const uint32_t ep = g_epoch[blockIdx.x] + 1;
    if (helper) {
      if (w4 == 0 && elect_one()) {
        flag_wait(FLAG_B(blockIdx.x - 128), ep * 32);
        fence_async_all();
        TS(1, 10);
        mbar_arrive(BAR_GO);
        g_epoch[blockIdx.x] = ep;
      }
      return;
    }
    mbar_wait(BAR_GO, 0);
    {
      uint32_t a[4], b[4];
      float c[4];
      lds4(sWKV + (tid - 512) * 16, a);
      lds4(sWKV + 2048 + (tid - 512) * 16, b);
#pragma unroll
      for (int i = 0; i < 4; i++) c[i] = __uint_as_float(a[i]) + __uint_as_float(b[i]);
      lds4(sWKV + 4096 + (tid - 512) * 16, a);
      lds4(sWKV + 6144 + (tid - 512) * 16, b);
#pragma unroll
      for (int i = 0; i < 4; i++) c[i] += __uint_as_float(a[i]) + __uint_as_float(b[i]);
      sts1(sT + w4 * 256 + lane * 4, pack_bf16(c[0], c[1]));
      sts1(sT + w4 * 256 + 128 + lane * 4, pack_bf16(c[2], c[3]));
    }
    named_bar(9, 128);
    if (w4 == 0 && elect_one()) issue(2, 2, 2);
    auto write_ones = [&]() {
      mbar_wait_long(BAR_VB(1), 0);
      int c = ((w4 & 1) * 32 + lane);
#pragma unroll 4
      for (int key = c; key < S_TOK; key += 64) {
        sts4(sOne + key * 16, c < 24 ? 0x00003F80u : 0x00004E80u, 0u, 0u, 0u);
        c += 64; if (c >= STEPK) c -= STEPK;
      }
      fence_async();
      __syncwarp();
      if (lane == 0) mbar_arrive(BAR_Q);
    };
    if (w4 == 0) {
      int s = 0, ph = 0;
#pragma unroll 1
      for (int kb = 3; kb < 8; kb++) {
        mbar_wait(BAR_EMPTY(s), ph);
        if (elect_one()) issue(kb, s, 3);
        if (++s == 3) { s = 0; ph ^= 1; }
      }
      flag_wait(FLAG_KV, ep * 128);
      fence_async_all();
      if (lane == 0) TS(0, 11);
#pragma unroll 1
      for (int m = 0; m < 2; m++) {
        mbar_wait(m == 0 ? BAR_EMPTY(2) : BAR_EMPTY(0), 1 - m);
        if (elect_one()) {
          const uint32_t fb = m == 0 ? BAR_KV(0) : BAR_VB(0);
          mbar_expect_tx(fb, 2 * 7 * STEPK * 16);
#pragma unroll
          for (int p = 0; p < 2; p++) bulk_g2s(sb + m * OFF_V + p * 32768, g_KV + (m * 2 + p) * S_TOK, 7 * STEPK * 16, fb);
        }
      }
      mbar_wait(BAR_Q, 0);
      if (elect_one()) {
#pragma unroll
        for (int c = 1; c < 3; c++) {
          const int k0 = c == 1 ? 7 * STEPK : 12 * STEPK, k1 = c == 1 ? 12 * STEPK : S_TOK;
          const uint32_t bytes = (k1 - k0) * 16;
          mbar_expect_tx(BAR_KV(c), 4 * bytes);
#pragma unroll
          for (int p = 0; p < 4; p++)
            bulk_g2s(sb + (p >> 1) * OFF_V + (p & 1) * 32768 + k0 * 16, g_KV + p * S_TOK + k0, bytes, BAR_KV(c));
        }
      }
      mbar_wait_long(BAR_CL(1), 0);
      flag_wait(isB ? FLAG_LM((lane & 7) * 2 + (tbA >> 4)) : FLAG_OA(tbA * 4 + (lane & 7), 0), ep);
      __syncwarp();
      fence_async_all();
      if (lane == 0) TS(2, 13);
      const CUtensorMap* mW = isB ? &mWoB : &mWoA;
#pragma unroll 1
      for (int it = 0; it < 8; it++) {
        const int n = (!isB && it >= 6) ? 13 - it : it;
        uint32_t wb = BAR_CL(n < 3 ? 0 : (n == 3 ? 2 : 3));
        if (isB) { if (n >= 5) wb = n == 7 ? BAR_CL(4) : BAR_TE(n - 5); }
        else if (n >= 6) wb = n == 6 ? BAR_CL(4) : BAR_TE(0);
        if (it < 6) mbar_wait_long(wb, 0); else mbar_wait(wb, 0);
        const uint32_t sl = tail_slots(isB, n), fb = BAR_TF(n);
        const bool withX = isB || n < 4;
        const int k0 = isB ? n * 64 : (n < 4 ? n * 128 : ((hg + n) & 3) * 128 + 64);
        if (elect_one()) {
          mbar_expect_tx(fb, withX ? 32768 : 16384);
          if (withX) {
            tma2d(sb + (sl & 255) * 8192, &mO, k0, isB * S_TOK + tok0, fb);
            tma2d(sb + ((sl >> 8) & 255) * 8192, &mO, k0, isB * S_TOK + tok0 + 64, fb);
          }
          tma2d(sb + ((sl >> 16) & 255) * 8192, mW, hg * 128, k0, fb);
          tma2d(sb + (sl >> 24) * 8192, mW, hg * 128 + 64, k0, fb);
        }
      }
      if (lane == 0) g_epoch[blockIdx.x] = ep;
    } else if (w4 == 3) {
      write_ones();
      flag_wait(FLAG_KV, ep * 128);
      const uint4 a = *(const uint4*)(g_stats + lane * 4);
      const float kmax2 = __uint_as_float(__reduce_max_sync(~0u, a.x)) + __uint_as_float(__reduce_max_sync(~0u, a.y));
      const float vmax = __uint_as_float(__reduce_max_sync(~0u, max(a.z, a.w)));
      const float lv = vmax > 0.f ? __log2f(vmax) : 0.f;
      const float lim = fminf(90.f, fminf(91.f + lv, 95.f - lv));
      float thr = -1.f;
      if (vmax < 1e27f && kmax2 <= 65536.f && lim > 2.f) thr = fminf(60000.f, (lim * lim - 1.f) / (kmax2 * 1.02f + 1e-30f));
      mbar_wait_long(BAR_VB(2), 0);
      uint32_t nmax = 0;
#pragma unroll 2
      for (int i = 0; i < 16; i++) {
        uint32_t x[4], y[4];
        const uint32_t ad = sb + OFF_F + i * 1024 + (lane >> 3) * 256 + (lane & 7) * 16;
        lds4(ad, x); lds4(ad + 128, y);
        uint32_t n = hfma2(x[0], x[0], hfma2(x[1], x[1], hfma2(x[2], x[2], hfma2(x[3], x[3], 0u))));
        n = hfma2(y[0], y[0], hfma2(y[1], y[1], hfma2(y[2], y[2], hfma2(y[3], y[3], n))));
        n = hadd2(n, n >> 16);
        nmax = max(nmax, n & 0x7FFFu);
      }
      nmax = __reduce_max_sync(~0u, nmax);
      const bool ok = __half2float(__ushort_as_half((unsigned short)nmax)) <= thr;
      if (lane == 0) { sts1(sM + 16, ok ? 1u : 0u); mbar_arrive(BAR_Q2); }
    } else {
      const int tok = (w4 - 1) * 32 + lane;
      int step, col;
      if ((tbA & 3) == 0) {
        const int b8 = tbA >> 2;
        if (tok < 22) { step = tok; col = 24 + b8; }
        else { const int c = tok >= 43; step = tok - 22 - 21 * c; col = 32 + b8 * 2 + c; }
      } else {
        const int b24 = (tbA >> 2) * 3 + (tbA & 3) - 1;
        if (tok < 42) { const int c = tok >= 21; step = tok - 21 * c; col = 48 + b24 * 2 + c; }
        else { step = tok - 42; col = b24; }
      }
      const int kap = step * STEPK + col;
      const bool chained = col >= 24;
      uint32_t v[4], o[4];
      lds4(sT + tok * 16, v);
      g_KV[(4 + hg) * S_TOK + kap] = make_uint4(v[0], v[1], v[2], v[3]);
      float st = 0.f;
      if (hg < 2) {
        o[0] = o[1] = o[2] = o[3] = 0;
        if (chained && step > 0) lds4(sT + tok * 16 - 16, o);
        const float sc = chained ? 2.f : 1.f;
#pragma unroll
        for (int u = 0; u < 4; u++) {
          const float x = bf_lo(v[u]), y = bf_hi(v[u]);
          st += x * x + y * y;
          o[u] = pack_f16((x - bf_lo(o[u])) * sc, (y - bf_hi(o[u])) * sc);
        }
      } else {
        const float sc = chained ? VSHIFT : 1.f;
#pragma unroll
        for (int u = 0; u < 4; u++) { float x = bf_lo(v[u]), y = bf_hi(v[u]); st += fabsf(x) + fabsf(y); o[u] = pack_bf16(x * sc, y * sc); }
      }
      g_KV[hg * S_TOK + kap] = make_uint4(o[0], o[1], o[2], o[3]);
      const uint32_t um = __reduce_max_sync(~0u, __float_as_uint(st) & 0x7FFFFFFFu);
      if (w4 == 2) {
        if (lane == 0) sts1(sM + 24, um);
        named_arrive(10, 64);
        write_ones();
        if (!isB) {
          mbar_wait_long(BAR_CL(3), 0);
          mbar_wait_long(BAR_RL, 0);
          uint32_t pend = 0xFE;
          const int li = lane & 7;
          const uint32_t* fl = FLAG_OA((tbA + (li & 1)) * 4 + ((hg + (li >> 1)) & 3), 1);
#pragma unroll 1
          for (int it = 0; pend; it++) {
            uint32_t fv;
            asm volatile("ld.acquire.gpu.global.u32 %0, [%1];" : "=r"(fv) : "l"(fl) : "memory");
            uint32_t go = __ballot_sync(~0u, (int32_t)(fv - ep) >= 0 && mbar_test(li >= 6 ? BAR_TE(0) : BAR_CL(4), 0)) & pend;
            pend &= ~go;
            if (go) fence_async_all();
#pragma unroll 1
            while (go) {
              const int b = __ffs(go) - 1;
              go &= go - 1;
              const uint32_t slot = (tail_slots(0, 4 + (b >> 1)) >> (8 * (b & 1))) & 255;
              if (elect_one()) {
                mbar_expect_tx(BAR_TF(8 + b), 8192);
                tma2d(sb + slot * 8192, &mO, ((hg + (b >> 1)) & 3) * 128 + 64, tok0 + (b & 1) * 64, BAR_TF(8 + b));
              }
            }
            if (it > 2000000) __trap();
          }
          if (lane == 0) TS(2, 14);
        }
      }
      else {
        named_bar(10, 64);
        if (elect_one()) {
          g_stats[tbA * 4 + hg] = max(um, lds1(sM + 24));
          fence_async_all();
          flag_add(FLAG_KV);
          TS(1, 9);
          mbar_wait_long(BAR_BDONE, 0);
          tma2d_store(&mQst, sb + OFF_F + 49152, hq * 64, S_TOK + ttB * 128);
          bulk_commit();
          bulk_wait_all();
          fence_async_all();
          flag_add(FLAG_B(hq >> 1));
          TS(0, 12);
          mbar_wait(BAR_Q, 0);
          mbar_arrive(BAR_CL(0));
#pragma unroll 1
          for (int p = 0; p < 2; p++) {
            mbar_wait_long(BAR_OD(p), 0);
            if (p == 0) {
#pragma unroll
              for (int w = 0; w < 4; w++) tma2d_store(&mO16, sb + OFF_F + w * 2048, hg * 128 + w * 16, tbA * 64);
            } else {
              tma2d_store(&mO, sb + 26 * 8192, hg * 128 + 64, tbA * 64);
            }
            bulk_commit();
            bulk_wait_all();
            if (p == 0) mbar_arrive(BAR_CL(1));
            PUBLISH(FLAG_OA(tbA * 4 + hg, p));
          }
          TS(2, 0);
        }
      }
    }
    return;
  }
  if (helper) { helper_cta(blockIdx.x - 128, sb, bars, wg, w4, &mQst, &mOst); return; }

  {
    float acc[64];
    if (wg == 0) proj_loop<0>(acc, sb, bars, 16384, 0, wg, sWKV);
    else proj_loop<1>(acc, sb, bars, 16384 + wg * 8192, 49152, wg, sWKV);
    if (tid == 0) TS(0, 10);
    const uint32_t sF = sb + OFF_F;
    const uint32_t qa = sF + w4 * 512 + ((lane >> 3) & 1) * 256 + (lane >> 4) * 128 + (lane & 7) * 16;
    if (wg == 0) {
#pragma unroll
      for (int hd = 0; hd < 4; hd++)
        stsm4(qa + hd * 2048, pack_f16(acc[8 * hd] * QSCALE, acc[8 * hd + 1] * QSCALE), pack_f16(acc[8 * hd + 2] * QSCALE, acc[8 * hd + 3] * QSCALE),
              pack_f16(acc[8 * hd + 4] * QSCALE, acc[8 * hd + 5] * QSCALE), pack_f16(acc[8 * hd + 6] * QSCALE, acc[8 * hd + 7] * QSCALE));
      fence_async();
      __syncwarp();
      if (lane == 0) mbar_arrive(BAR_Q);
    } else {
      if (wg != 3) named_arrive(6, 384);
      if (wg != 1) named_arrive(8, 384);
    }
    asm volatile("setmaxnreg.inc.sync.aligned.u32 112;");
    fence_regs<64>(acc);
    if (wg == 0) {
#pragma unroll
      for (int hd = 4; hd < 8; hd++)
        stsm4(qa + hd * 2048, pack_f16(acc[8 * hd] * QSCALE, acc[8 * hd + 1] * QSCALE), pack_f16(acc[8 * hd + 2] * QSCALE, acc[8 * hd + 3] * QSCALE),
              pack_f16(acc[8 * hd + 4] * QSCALE, acc[8 * hd + 5] * QSCALE), pack_f16(acc[8 * hd + 6] * QSCALE, acc[8 * hd + 7] * QSCALE));
      fence_async();
      __syncwarp();
      if (lane == 0) mbar_arrive(BAR_VB(2));
    } else if (wg == 3) {
      named_bar(6, 384);
      const int t = tid & 127;
#pragma unroll
      for (int j = 0; j < 8; j++)
        sts4(sF + 24576 + j * 2048 + t * 16, pack_bf16(acc[8 * j], acc[8 * j + 1]), pack_bf16(acc[8 * j + 2], acc[8 * j + 3]),
             pack_bf16(acc[8 * j + 4], acc[8 * j + 5]), pack_bf16(acc[8 * j + 6], acc[8 * j + 7]));
      named_arrive(7, 256);
    } else {
      uint32_t p[32];
#pragma unroll
      for (int i = 0; i < 32; i++) p[i] = phi2(acc[2 * i], acc[2 * i + 1]);
      if (wg == 1) {
        named_bar(8, 384);
        const int m = lane >> 3, r = lane & 7;
#pragma unroll
        for (int j = 0; j < 16; j += 2) {
          const int tok = (j + (m >> 1)) * 8 + r;
          const int chunk = w4 * 2 + (m & 1);
          stsm4t(sF + 49152 + tok * 128 + ((chunk ^ r) << 4), p[2 * j], p[2 * j + 1], p[2 * j + 2], p[2 * j + 3]);
        }
        fence_async();
      } else {
        named_bar(7, 256);
        float kv0[4] = {0, 0, 0, 0}, kv1[4] = {0, 0, 0, 0}, z0[4] = {0, 0, 0, 0}, z1[4] = {0, 0, 0, 0};
        const uint32_t one = 0x3F803F80u;
        const int t = tid & 127;
#pragma unroll
        for (int j = 0; j < 8; j++) {
          uint32_t a[4];
          lds4(sF + 24576 + j * 2048 + t * 16, a);
          mma_bf16(kv0, a[0], a[1], a[2], a[3], p[4 * j], p[4 * j + 2]);
          mma_bf16(kv1, a[0], a[1], a[2], a[3], p[4 * j + 1], p[4 * j + 3]);
          mma_bf16(z0, one, one, one, one, p[4 * j], p[4 * j + 2]);
          mma_bf16(z1, one, one, one, one, p[4 * j + 1], p[4 * j + 3]);
        }
        float4* dst = g_kvp + ((ttB * 32 + hq * 4 + w4) * 3) * 32 + lane;
        dst[0] = make_float4(kv0[0], kv0[1], kv1[0], kv1[1]);
        dst[32] = make_float4(kv0[2], kv0[3], kv1[2], kv1[3]);
        dst[64] = make_float4(z0[0], z0[1], z1[0], z1[1]);
      }
      __syncwarp();
      if (lane == 0) mbar_arrive(BAR_BDONE);
    }
  }

  bool safe = true;
  {
    const uint32_t c63 = 0x1F801F80u + (threadIdx.x >> 20);
    const uint32_t m1 = (gridDim.x >> 20) - 1u;
    const uint64_t dK0 = make_desc(sb + OFF_K, 32768, 128, 0);
    const uint64_t dV0 = make_desc(sb + OFF_V, 128, 32768, 0);
    constexpr uint32_t dKV = ((2048u - 8u)  __H0__ ) + STEPK - (OFF_V - OFF_K) / 16;
    float Sm[12], Sp[36], O[12];
    uint32_t P[24];
    uint64_t dQ = make_desc(sb + OFF_F + wg * 2048, 128, 256, 0);
#pragma unroll
    for (int i = 0; i < 36; i++) Sp[i] = SMAGIC;
#pragma unroll
    for (int i = 0; i < 12; i++) Sm[i] = 0.f;
    fence_regs<12>(Sm); fence_regs<36>(Sp);
    mbar_wait(BAR_Q, 0);
    mbar_wait(BAR_KV(0), 0);
    wg_fence();
    wg_qs72<1>(Sp, dQ, dK0 + 24);
    wg_qs24<0>(Sm, dQ, dK0);
    wg_commit();
    wg_wait<0>();
    fence_regs<12>(Sm); fence_regs<36>(Sp);
#pragma unroll 1
    for (int pass = 0; pass < 2; pass++) {
#pragma unroll
      for (int i = 0; i < 12; i++) O[i] = 0.f;
      fence_regs<12>(O);
      if (tid == 0) TS(1, 2 + 2 * pass);
      uint32_t vlo = (uint32_t)dV0;
#pragma unroll 1
      for (int seg = 0; seg < 4; seg++) {
        if (pass == 0) {
          if (seg < 3) mbar_wait(seg == 0 ? BAR_VB(0) : BAR_KV(seg), 0);
        } else if (seg >= 1) {
          if ((tid & 127) == 0) {
            mbar_arrive(BAR_CL(seg));
            if (seg == 3) take_role(sM, wg);
          }
          __syncwarp();
        }
        if ((tid & 127) == 0) TS(4 + wg, pass * 5 + seg);
        const uint32_t vend = vlo + (seg == 0 ? 6 : 5) * STEPK;
#pragma unroll 1
        for (; vlo != vend; vlo += STEPK) {
          uint64_t dK, dV;
          asm("mov.b64 %0, {%1, %2};" : "=l"(dK) : "r"(vlo + dKV), "r"(8u));
          asm("mov.b64 %0, {%1, %2};" : "=l"(dV) : "r"(vlo), "r"(2048u));
#pragma unroll
          for (int i = 0; i < 6; i++) P[i] = pack_bf16(ex2f(Sm[2 * i]), ex2f(Sm[2 * i + 1]));
#pragma unroll
          for (int i = 0; i < 18; i++) P[6 + i] = exp2_pair_fix(Sp[2 * i], Sp[2 * i + 1], c63, m1);
          fence_regs<24>(P);
          wg_fence();
#pragma unroll
          for (int k = 0; k < 6; k++) wg_pv24<1>(O, &P[4 * k], dV + k * 16);
          wg_qs72<1>(Sp, dQ, dK + 24);
          wg_qs24<0>(Sm, dQ, dK);
          wg_commit();
          wg_wait<0>();
          fence_regs<12>(Sm); fence_regs<36>(Sp); fence_regs<12>(O); fence_regs<24>(P);
        }
      }
#pragma unroll
      for (int i = 0; i < 6; i++) P[i] = pack_bf16(ex2f(Sm[2 * i]), ex2f(Sm[2 * i + 1]));
      P[6] = exp2_pair_fix(Sp[0], Sp[1], c63, m1);
      P[7] = exp2_pair_fix(Sp[2], Sp[3], c63, m1);
      fence_regs<8>(P);
#pragma unroll
      for (int i = 0; i < 36; i++) Sp[i] = SMAGIC;
      fence_regs<36>(Sp);
      mbar_wait(pass == 0 ? BAR_Q2 : BAR_CL(3), 0);
      const uint32_t sO = pass == 0 ? sb + OFF_F + wg * 2048 + w4 * 512 + (lane & 15) * 32 + (lane >> 4) * 16
                                    : sb + 26 * 8192 + (w4 * 16 + (lane & 15)) * 128 + (((wg * 2 + (lane >> 4)) ^ (lane & 7)) << 4);
      dQ += 512;
      wg_fence();
      wg_pv24<1>(O, &P[0], dV0 + 21 * STEPK);
      wg_pv24<1>(O, &P[4], dV0 + 21 * STEPK + 16);
      wg_commit();
      wg_qs72<1>(Sp, dQ, dK0 + 24);
      wg_qs24<0>(Sm, dQ, dK0);
      wg_commit();
      wg_wait<1>();
      fence_regs<12>(O);
      const float l0 = __shfl_sync(~0u, O[8], lane & ~3), l1 = __shfl_sync(~0u, O[10], lane & ~3);
      const float i0 = rcpf(l0), i1 = rcpf(l1);
      stsm4(sO,
            pack_bf16(O[0] * i0, O[1] * i0), pack_bf16(O[2] * i1, O[3] * i1),
            pack_bf16(O[4] * i0, O[5] * i0), pack_bf16(O[6] * i1, O[7] * i1));
      fence_async();
      {
        safe = __all_sync(~0u, lds1(sM + 16) != 0);
      }
      if (safe && lane == 0) mbar_arrive(BAR_OD(pass));
      wg_wait<0>();
      fence_regs<12>(Sm); fence_regs<36>(Sp);
      if (!safe) break;
      if ((tid & 127) == 0) TS(4 + wg, pass * 5 + 4);
      if (tid == 0) TS(1, 3 + 2 * pass);
    }
  }
  if (!safe) {
    if ((tid & 127) == 0) { mbar_arrive(BAR_CL(1)); mbar_arrive(BAR_CL(2)); mbar_arrive(BAR_CL(3)); take_role(sM, wg); }
#pragma unroll 1
    for (int pass = 0; pass < 2; pass++) {
      const int t = tid & 127;
      mbar_wait(BAR_CL(3), 0);
      attn_slow(prm.xa + (size_t)tbA * 64 * D_MOD, prm.wq + (hg * 8 + pass * 4 + wg) * 16,
                pass == 0 ? sb + OFF_F + wg * 2048 + t * 16
                          : sb + 26 * 8192 + (t >> 1) * 128 + (((wg * 2 + (t & 1)) ^ ((t >> 1) & 7)) << 4));
      __syncwarp();
      if (lane == 0) mbar_arrive(BAR_OD(pass));
    }
  }

  {
    named_bar(wg + 1, 128);
    if ((tid & 127) == 0) mbar_arrive(BAR_CL(4));
    const int role = __shfl_sync(~0u, lds1(sM + 32 + wg * 4), 0);
    if ((tid & 127) == 0) TS(4 + wg, 10);
    const int m = lane >> 3, r = lane & 7;
    const uint32_t stoff = (w4 * 16 + (m & 1) * 8 + r) * 128;
    {
      if (role == 0 && (tid & 127) == 0) mbar_arrive(BAR_RL);
      if (!isB || role != 0) mbar_wait(BAR_CL(4), 0);
      float acc[64];
#pragma unroll
      for (int i = 0; i < 64; i++) acc[i] = 0.f;
      fence_regs<64>(acc);
#pragma unroll 1
      for (int n = role < 2 ? 0 : 8; n < 8; n++) {
        const uint32_t sl = tail_slots(isB, n);
        const uint32_t w0 = (sl >> 16) & 255, w1 = sl >> 24;
        const uint64_t da = make_desc(sb + ((sl >> (8 * role)) & 255) * 8192, 16, 1024, 1);
        const uint64_t db = make_desc(sb + w0 * 8192, (w1 - w0) * 8192, 1024, 1);
        mbar_wait(BAR_TF(n), 0);
        if (!isB && n >= 4) mbar_wait(n == 4 && role == 0 ? BAR_OD(1) : BAR_TF(2 * n + role), 0);
        if ((tid & 127) == 0 && role == 1) TS(2, 2 + n);
        wg_fence();
#pragma unroll
        for (int k = 0; k < 4; k++) wg_ss128<0, 1>(acc, da + k * 2, db + k * 128, 1);
        wg_commit();
        wg_wait<1>();
        if ((n == 1 || n == 2) && (tid & 127) == 0) mbar_arrive(BAR_TE(n - 1));
        __syncwarp();
      }
      wg_wait<0>();
      fence_regs<64>(acc);
      if ((tid & 127) == 0) TS(4 + wg, 11);
      const uint32_t x0 = role < 2 ? sb + (role ? 16 : 8) * 8192 : sT, x1 = role < 2 ? sb + (role ? 5 : 1) * 8192 : sT;
      const uint32_t so = role < 2 ? stoff : r * 128;
#pragma unroll
      for (int j = 0; j < 16; j += 2)
        stsm4((j < 8 ? x0 : x1) + so + ((((j & 7) + (m >> 1)) ^ r) << 4),
              pack_bf16(acc[4 * j], acc[4 * j + 1]), pack_bf16(acc[4 * j + 2], acc[4 * j + 3]),
              pack_bf16(acc[4 * j + 4], acc[4 * j + 5]), pack_bf16(acc[4 * j + 6], acc[4 * j + 7]));
      fence_async();
      named_bar(wg + 1, 128);
      if (role < 2 && w4 == 0 && elect_one()) {
        tma2d_store(&mOut, x0, isB * 512 + hg * 128, tok0 + role * 64);
        tma2d_store(&mOut, x1, isB * 512 + hg * 128 + 64, tok0 + role * 64);
        bulk_commit();
        asm volatile("cp.async.bulk.wait_group.read 0;" ::: "memory");
        TS(2, 11 + role);
      }
    }
  }
}

typedef CUresult (*EncodeFn)(CUtensorMap*, CUtensorMapDataType, cuuint32_t, void*, const cuuint64_t*, const cuuint64_t*,
                             const cuuint32_t*, const cuuint32_t*, CUtensorMapInterleave, CUtensorMapSwizzle,
                             CUtensorMapL2promotion, CUtensorMapFloatOOBfill);

static void make_map(EncodeFn enc, CUtensorMap* m, const void* ptr, uint64_t cols, uint64_t rows, uint32_t bc, uint32_t br,
                     CUtensorMapSwizzle sw = CU_TENSOR_MAP_SWIZZLE_128B) {
  cuuint64_t dims[2] = {cols, rows};
  cuuint64_t strides[1] = {cols * 2};
  cuuint32_t box[2] = {bc, br};
  cuuint32_t es[2] = {1, 1};
  enc(m, CU_TENSOR_MAP_DATA_TYPE_BFLOAT16, 2, (void*)ptr, dims, strides, box, es, CU_TENSOR_MAP_INTERLEAVE_NONE,
      sw, CU_TENSOR_MAP_L2_PROMOTION_L2_256B, CU_TENSOR_MAP_FLOAT_OOB_FILL_NONE);
}

extern "C" void kernel_launch(void* const* d_in, const int* in_sizes, int n_in, void* d_out, int out_size) {
  (void)in_sizes; (void)n_in; (void)out_size;
  static EncodeFn enc = nullptr;
  static void* pQ = nullptr; static void* pO = nullptr;
  if (!enc) {
    void* fn = nullptr; cudaDriverEntryPointQueryResult qr;
    cudaGetDriverEntryPoint("cuTensorMapEncodeTiled", &fn, cudaEnableDefault, &qr);
    enc = (EncodeFn)fn;
    cudaGetSymbolAddress(&pQ, g_Q);
    cudaGetSymbolAddress(&pO, g_O);
    cudaFuncSetAttribute(k1_main, cudaFuncAttributeMaxDynamicSharedMemorySize, SM_TOTAL);
  }
  CUtensorMap mXA64, mXB, mWq, mWqkv, mQst, mO, mOst, mWoA, mWoB, mOut, mO16;
  make_map(enc, &mXA64, d_in[0], 512, 2048, 64, 64);
  make_map(enc, &mWq, d_in[1], 512, 512, 64, 64);
  make_map(enc, &mWoA, d_in[4], 512, 512, 64, 64);
  make_map(enc, &mXB, d_in[5], 512, 2048, 64, 128);
  make_map(enc, &mWqkv, d_in[6], 1536, 512, 64, 64);
  make_map(enc, &mWoB, d_in[7], 512, 512, 64, 64);
  make_map(enc, &mQst, pQ, 512, 4096, 64, 128);
  make_map(enc, &mO, pO, 512, 4096, 64, 64);
  make_map(enc, &mOst, pO, 512, 4096, 64, 128);
  make_map(enc, &mOut, d_out, 1024, 2048, 64, 64);
  make_map(enc, &mO16, pO, 512, 4096, 16, 64, CU_TENSOR_MAP_SWIZZLE_NONE);
  Params prm{(const __nv_bfloat16*)d_in[2], (const __nv_bfloat16*)d_in[3], (const __nv_bfloat16*)d_in[0], (const __nv_bfloat16*)d_in[1]};
  k1_main<<<132, 640, SM_TOTAL, cudaStreamPerThread>>>(mXA64, mXB, mWq, mWqkv, mQst, mOst, mO, mWoA, mWoB, mOut, mO16, prm);
}
```

```cpp
#include <cuda_runtime.h>
#include <cuda_bf16.h>
#include <cuda_fp16.h>
#include <cuda.h>
#include <stdint.h>

#define S_TOK 2048
#define D_MOD 512

__device__ __align__(1024) __nv_bfloat16 g_Q[2 * S_TOK * D_MOD];
__device__ __align__(1024) __nv_bfloat16 g_O[2 * S_TOK * D_MOD];
__device__ __align__(1024) uint4 g_KV[8 * S_TOK];
__device__ __align__(16) uint32_t g_stats[128];
__device__ __align__(16) float4 g_kvp[16 * 32 * 3 * 32];

#define TS(k, i) do {} while (0)
__device__ __forceinline__ uint32_t smem_u32(const void* p) { return (uint32_t)__cvta_generic_to_shared(p); }
__device__ __forceinline__ void mbar_init(uint32_t bar, int cnt) { asm volatile("mbarrier.init.shared::cta.b64 [%0], %1;" :: "r"(bar), "r"(cnt) : "memory"); }
__device__ __forceinline__ void mbar_expect_tx(uint32_t bar, uint32_t bytes) { asm volatile("mbarrier.arrive.expect_tx.shared::cta.b64 _, [%0], %1;" :: "r"(bar), "r"(bytes) : "memory"); }
__device__ __forceinline__ bool mbar_try(uint32_t bar, uint32_t parity) {
  uint32_t ok;
  asm volatile("{\n.reg .pred p;\nmbarrier.try_wait.parity.shared::cta.b64 p, [%1], %2;\nselp.b32 %0, 1, 0, p;\n}\n" : "=r"(ok) : "r"(bar), "r"(parity) : "memory");
  return ok;
}
__device__ __forceinline__ void mbar_wait(uint32_t bar, uint32_t parity) {
  asm volatile("{\n.reg .pred p;\n.reg .u32 c;\nmov.u32 c, 0;\n"
               "LW_%=:\n"
               "mbarrier.try_wait.parity.shared::cta.b64 p, [%0], %1;\n"
               "@p bra LD_%=;\n"
               "add.u32 c, c, 1;\n"
               "setp.lt.u32 p, c, 4000000;\n"
               "@p bra LW_%=;\n"
               "trap;\n"
               "LD_%=:\n}\n" :: "r"(bar), "r"(parity) : "memory");
}
__device__ __forceinline__ void mbar_arrive_cta(uint32_t bar, uint32_t cta) {
  asm volatile("{\n.reg .b32 ra;\nmapa.shared::cluster.u32 ra, %0, %1;\nmbarrier.arrive.shared::cluster.b64 _, [ra];\n}\n" :: "r"(bar), "r"(cta) : "memory");
}
__device__ __forceinline__ void cluster_sync() {
  asm volatile("barrier.cluster.arrive.relaxed.aligned;\nbarrier.cluster.wait.aligned;" ::: "memory");
}
__device__ __forceinline__ void tma2d(uint32_t dst, const CUtensorMap* m, int c0, int c1, uint32_t bar) {
  asm volatile("cp.async.bulk.tensor.2d.shared::cluster.global.mbarrier::complete_tx::bytes [%0], [%1, {%3, %4}], [%2];"
               :: "r"(dst), "l"(m), "r"(bar), "r"(c0), "r"(c1) : "memory");
}
__device__ __forceinline__ void tma2d_mc(uint32_t dst, const CUtensorMap* m, int c0, int c1, uint32_t bar, uint16_t mask) {
  asm volatile("cp.async.bulk.tensor.2d.shared::cluster.global.mbarrier::complete_tx::bytes.multicast::cluster [%0], [%1, {%3, %4}], [%2], %5;"
               :: "r"(dst), "l"(m), "r"(bar), "r"(c0), "r"(c1), "h"(mask) : "memory");
}
__device__ __forceinline__ void tma2d_store(const CUtensorMap* m, uint32_t src, int c0, int c1) {
  asm volatile("cp.async.bulk.tensor.2d.global.shared::cta.bulk_group [%0, {%2, %3}], [%1];"
               :: "l"(m), "r"(src), "r"(c0), "r"(c1) : "memory");
}
__device__ __forceinline__ void bulk_g2s(uint32_t dst, const void* src, uint32_t bytes, uint32_t bar) {
  asm volatile("cp.async.bulk.shared::cluster.global.mbarrier::complete_tx::bytes [%0], [%1], %2, [%3];"
               :: "r"(dst), "l"(src), "r"(bytes), "r"(bar) : "memory");
}
__device__ __forceinline__ void bulk_commit() { asm volatile("cp.async.bulk.commit_group;" ::: "memory"); }
__device__ __forceinline__ void bulk_wait_all() { asm volatile("cp.async.bulk.wait_group 0;" ::: "memory"); }
__device__ __forceinline__ void fence_async() { asm volatile("fence.proxy.async.shared::cta;" ::: "memory"); }
__device__ __forceinline__ void named_bar(int id, int n) { asm volatile("bar.sync %0, %1;" :: "r"(id), "r"(n) : "memory"); }
__device__ __forceinline__ void pdl_launch() { asm volatile("griddepcontrol.launch_dependents;" ::: "memory"); }
__device__ __forceinline__ void pdl_wait() { asm volatile("griddepcontrol.wait;" ::: "memory"); }
__device__ __forceinline__ void wg_fence() { asm volatile("wgmma.fence.sync.aligned;" ::: "memory"); }
__device__ __forceinline__ void wg_commit() { asm volatile("wgmma.commit_group.sync.aligned;" ::: "memory"); }
template <int n> __device__ __forceinline__ void wg_wait() { asm volatile("wgmma.wait_group.sync.aligned %0;" :: "n"(n) : "memory"); }
template <int n> __device__ __forceinline__ void fence_regs(float* r) {
#pragma unroll
  for (int i = 0; i < n; i++) asm volatile("" : "+f"(r[i]) :: "memory");
}
template <int n> __device__ __forceinline__ void fence_regs(uint32_t* r) {
#pragma unroll
  for (int i = 0; i < n; i++) asm volatile("" : "+r"(r[i]) :: "memory");
}
__device__ __forceinline__ uint64_t make_desc(uint32_t addr, uint32_t lbo, uint32_t sbo, uint32_t swz) {
  return (uint64_t)((addr & 0x3FFFF) >> 4) | ((uint64_t)(lbo >> 4) << 16) | ((uint64_t)(sbo >> 4) << 32) | ((uint64_t)swz << 62);
}
__device__ __forceinline__ float ex2f(float x) { float y; asm("ex2.approx.ftz.f32 %0, %1;" : "=f"(y) : "f"(x)); return y; }
__device__ __forceinline__ uint32_t pack_bf16(float lo, float hi) { uint32_t r; asm("cvt.rn.bf16x2.f32 %0, %1, %2;" : "=r"(r) : "f"(hi), "f"(lo)); return r; }
__device__ __forceinline__ uint32_t pack_f16(float lo, float hi) { uint32_t r; asm("cvt.rn.f16x2.f32 %0, %1, %2;" : "=r"(r) : "f"(hi), "f"(lo)); return r; }
__device__ __forceinline__ float bf_lo(uint32_t v) { return __uint_as_float(v << 16); }
__device__ __forceinline__ float bf_hi(uint32_t v) { return __uint_as_float(v & 0xFFFF0000u); }
__device__ __forceinline__ float rbf(float x) { return __bfloat162float(__float2bfloat16_rn(x)); }
__device__ __forceinline__ void stsm4(uint32_t a, uint32_t r0, uint32_t r1, uint32_t r2, uint32_t r3) {
  asm volatile("stmatrix.sync.aligned.m8n8.x4.shared.b16 [%0], {%1,%2,%3,%4};" :: "r"(a), "r"(r0), "r"(r1), "r"(r2), "r"(r3) : "memory");
}
__device__ __forceinline__ void stsm4t(uint32_t a, uint32_t r0, uint32_t r1, uint32_t r2, uint32_t r3) {
  asm volatile("stmatrix.sync.aligned.m8n8.x4.trans.shared.b16 [%0], {%1,%2,%3,%4};" :: "r"(a), "r"(r0), "r"(r1), "r"(r2), "r"(r3) : "memory");
}
__device__ __forceinline__ void mma_bf16(float* d, uint32_t a0, uint32_t a1, uint32_t a2, uint32_t a3, uint32_t b0, uint32_t b1) {
  asm volatile("mma.sync.aligned.m16n8k16.row.col.f32.bf16.bf16.f32 {%0,%1,%2,%3}, {%4,%5,%6,%7}, {%8,%9}, {%0,%1,%2,%3};"
               : "+f"(d[0]), "+f"(d[1]), "+f"(d[2]), "+f"(d[3]) : "r"(a0), "r"(a1), "r"(a2), "r"(a3), "r"(b0), "r"(b1));
}
template<int SD> __device__ __forceinline__ void wg_qs24(float* d, uint64_t da, uint64_t db) {
  asm volatile("wgmma.mma_async.sync.aligned.m64n24k16.f32.f16.f16 {%0,%1,%2,%3,%4,%5,%6,%7,%8,%9,%10,%11}, %12, %13, %14, 1, 1, 0, 0;"
   : "+f"(d[0]),"+f"(d[1]),"+f"(d[2]),"+f"(d[3]),"+f"(d[4]),"+f"(d[5]),"+f"(d[6]),"+f"(d[7]),"+f"(d[8]),"+f"(d[9]),"+f"(d[10]),"+f"(d[11])
   : "l"(da),"l"(db),"n"(SD));
}
template<int SD> __device__ __forceinline__ void wg_qs72(float* d, uint64_t da, uint64_t db) {
  asm volatile("wgmma.mma_async.sync.aligned.m64n72k16.f32.f16.f16 {%0,%1,%2,%3,%4,%5,%6,%7,%8,%9,%10,%11,%12,%13,%14,%15,%16,%17,%18,%19,%20,%21,%22,%23,%24,%25,%26,%27,%28,%29,%30,%31,%32,%33,%34,%35}, %36, %37, %38, 1, 1, 0, 0;"
   : "+f"(d[0]),"+f"(d[1]),"+f"(d[2]),"+f"(d[3]),"+f"(d[4]),"+f"(d[5]),"+f"(d[6]),"+f"(d[7]),"+f"(d[8]),"+f"(d[9]),"+f"(d[10]),"+f"(d[11]),"+f"(d[12]),"+f"(d[13]),"+f"(d[14]),"+f"(d[15]),"+f"(d[16]),"+f"(d[17]),"+f"(d[18]),"+f"(d[19]),"+f"(d[20]),"+f"(d[21]),"+f"(d[22]),"+f"(d[23]),"+f"(d[24]),"+f"(d[25]),"+f"(d[26]),"+f"(d[27]),"+f"(d[28]),"+f"(d[29]),"+f"(d[30]),"+f"(d[31]),"+f"(d[32]),"+f"(d[33]),"+f"(d[34]),"+f"(d[35])
   : "l"(da),"l"(db),"n"(SD));
}
template<int SD> __device__ __forceinline__ void wg_pv24(float* d, const uint32_t* a, uint64_t desc) {
  asm volatile("wgmma.mma_async.sync.aligned.m64n24k16.f32.bf16.bf16 {%0,%1,%2,%3,%4,%5,%6,%7,%8,%9,%10,%11}, {%12,%13,%14,%15}, %16, %17, 1, 1, 1;"
   : "+f"(d[0]),"+f"(d[1]),"+f"(d[2]),"+f"(d[3]),"+f"(d[4]),"+f"(d[5]),"+f"(d[6]),"+f"(d[7]),"+f"(d[8]),"+f"(d[9]),"+f"(d[10]),"+f"(d[11])
   : "r"(a[0]),"r"(a[1]),"r"(a[2]),"r"(a[3]),"l"(desc),"n"(SD));
}
template<int TA, int TB> __device__ __forceinline__ void wg_ss128(float* d, uint64_t da, uint64_t db, int sd) {
  asm volatile("{\n.reg .pred p;\nsetp.ne.b32 p, %66, 0;\n"
   "wgmma.mma_async.sync.aligned.m64n128k16.f32.bf16.bf16 {%0,%1,%2,%3,%4,%5,%6,%7,%8,%9,%10,%11,%12,%13,%14,%15,%16,%17,%18,%19,%20,%21,%22,%23,%24,%25,%26,%27,%28,%29,%30,%31,%32,%33,%34,%35,%36,%37,%38,%39,%40,%41,%42,%43,%44,%45,%46,%47,%48,%49,%50,%51,%52,%53,%54,%55,%56,%57,%58,%59,%60,%61,%62,%63}, %64, %65, p, 1, 1, %67, %68;\n}\n"
   : "+f"(d[0]),"+f"(d[1]),"+f"(d[2]),"+f"(d[3]),"+f"(d[4]),"+f"(d[5]),"+f"(d[6]),"+f"(d[7]),"+f"(d[8]),"+f"(d[9]),"+f"(d[10]),"+f"(d[11]),"+f"(d[12]),"+f"(d[13]),"+f"(d[14]),"+f"(d[15]),"+f"(d[16]),"+f"(d[17]),"+f"(d[18]),"+f"(d[19]),"+f"(d[20]),"+f"(d[21]),"+f"(d[22]),"+f"(d[23]),"+f"(d[24]),"+f"(d[25]),"+f"(d[26]),"+f"(d[27]),"+f"(d[28]),"+f"(d[29]),"+f"(d[30]),"+f"(d[31]),"+f"(d[32]),"+f"(d[33]),"+f"(d[34]),"+f"(d[35]),"+f"(d[36]),"+f"(d[37]),"+f"(d[38]),"+f"(d[39]),"+f"(d[40]),"+f"(d[41]),"+f"(d[42]),"+f"(d[43]),"+f"(d[44]),"+f"(d[45]),"+f"(d[46]),"+f"(d[47]),"+f"(d[48]),"+f"(d[49]),"+f"(d[50]),"+f"(d[51]),"+f"(d[52]),"+f"(d[53]),"+f"(d[54]),"+f"(d[55]),"+f"(d[56]),"+f"(d[57]),"+f"(d[58]),"+f"(d[59]),"+f"(d[60]),"+f"(d[61]),"+f"(d[62]),"+f"(d[63])
   : "l"(da),"l"(db),"r"(sd),"n"(TA),"n"(TB));
}
template<int TA, int TB> __device__ __forceinline__ void wg_ss64(float* d, uint64_t da, uint64_t db, int sd) {
  asm volatile("{\n.reg .pred p;\nsetp.ne.b32 p, %34, 0;\n"
   "wgmma.mma_async.sync.aligned.m64n64k16.f32.bf16.bf16 {%0,%1,%2,%3,%4,%5,%6,%7,%8,%9,%10,%11,%12,%13,%14,%15,%16,%17,%18,%19,%20,%21,%22,%23,%24,%25,%26,%27,%28,%29,%30,%31}, %32, %33, p, 1, 1, %35, %36;\n}\n"
   : "+f"(d[0]),"+f"(d[1]),"+f"(d[2]),"+f"(d[3]),"+f"(d[4]),"+f"(d[5]),"+f"(d[6]),"+f"(d[7]),"+f"(d[8]),"+f"(d[9]),"+f"(d[10]),"+f"(d[11]),"+f"(d[12]),"+f"(d[13]),"+f"(d[14]),"+f"(d[15]),"+f"(d[16]),"+f"(d[17]),"+f"(d[18]),"+f"(d[19]),"+f"(d[20]),"+f"(d[21]),"+f"(d[22]),"+f"(d[23]),"+f"(d[24]),"+f"(d[25]),"+f"(d[26]),"+f"(d[27]),"+f"(d[28]),"+f"(d[29]),"+f"(d[30]),"+f"(d[31])
   : "l"(da),"l"(db),"r"(sd),"n"(TA),"n"(TB));
}
template<int TA, int TB> __device__ __forceinline__ void wg_ss8(float* d, uint64_t da, uint64_t db, int sd) {
  asm volatile("{\n.reg .pred p;\nsetp.ne.b32 p, %6, 0;\n"
   "wgmma.mma_async.sync.aligned.m64n8k16.f32.bf16.bf16 {%0,%1,%2,%3}, %4, %5, p, 1, 1, %7, %8;\n}\n"
   : "+f"(d[0]),"+f"(d[1]),"+f"(d[2]),"+f"(d[3])
   : "l"(da),"l"(db),"r"(sd),"n"(TA),"n"(TB));
}

__device__ __forceinline__ uint32_t phi2(float a, float b) {
  uint32_t r, e;
  asm("cvt.rn.relu.bf16x2.f32 %0, %1, %2;" : "=r"(r) : "f"(b), "f"(a));
  e = pack_bf16(ex2f(a * 1.4426950408889634f), ex2f(b * 1.4426950408889634f));
  asm("add.rn.bf16x2 %0, %0, %1;" : "+r"(e) : "r"(0x35863586u));
  asm("min.NaN.bf16x2 %0, %0, %1;" : "+r"(e) : "r"(0x3F803F80u));
  asm("add.rn.bf16x2 %0, %0, %1;" : "+r"(e) : "r"(r));
  return e;
}

__device__ __forceinline__ void mbar_wait_long(uint32_t bar, uint32_t parity) {
  asm volatile("{\n.reg .pred p;\n.reg .u32 c;\nmov.u32 c, 0;\n"
               "LW_%=:\n"
               "mbarrier.try_wait.parity.shared::cta.b64 p, [%0], %1, 100000;\n"
               "@p bra LD_%=;\n"
               "add.u32 c, c, 1;\n"
               "setp.lt.u32 p, c, 20000;\n"
               "@p bra LW_%=;\n"
               "trap;\n"
               "LD_%=:\n}\n" :: "r"(bar), "r"(parity) : "memory");
}
__device__ __forceinline__ void mbar_arrive(uint32_t bar) { asm volatile("mbarrier.arrive.shared::cta.b64 _, [%0];" :: "r"(bar) : "memory"); }
__device__ __forceinline__ void named_arrive(int id, int n) { asm volatile("bar.arrive %0, %1;" :: "r"(id), "r"(n) : "memory"); }
__device__ __forceinline__ void fence_async_all() { asm volatile("fence.proxy.async.global;" ::: "memory"); }
__device__ __forceinline__ void flag_add(uint32_t* f) { asm volatile("fence.acq_rel.gpu;\nred.relaxed.gpu.global.add.u32 [%0], 1;" :: "l"(f) : "memory"); }
#define PUBLISH(f) asm volatile("fence.proxy.async.global;\nred.relaxed.gpu.global.add.u32 [%0], 1;" :: "l"(f) : "memory")
__device__ __forceinline__ void flag_wait(const uint32_t* f, uint32_t target) {
  uint32_t v;
#pragma unroll 1
  for (int it = 0;; it++) {
    asm volatile("ld.acquire.gpu.global.u32 %0, [%1];" : "=r"(v) : "l"(f) : "memory");
    if ((int32_t)(v - target) >= 0) break;
    if (it > 2000000) __trap();
    __nanosleep(64);
  }
}
__device__ __forceinline__ bool mbar_test(uint32_t bar, uint32_t parity) {
  uint32_t ok;
  asm volatile("{\n.reg .pred p;\nmbarrier.test_wait.parity.shared::cta.b64 p, [%1], %2;\nselp.b32 %0, 1, 0, p;\n}\n" : "=r"(ok) : "r"(bar), "r"(parity) : "memory");
  return ok;
}
__device__ __forceinline__ bool elect_one() {
  uint32_t p;
  asm volatile("{\n.reg .pred P;\nelect.sync _|P, 0xFFFFFFFF;\nselp.b32 %0, 1, 0, P;\n}\n" : "=r"(p));
  return p;
}
__device__ __forceinline__ void lds4(uint32_t a, uint32_t* r) {
  asm volatile("ld.shared.v4.b32 {%0,%1,%2,%3}, [%4];" : "=r"(r[0]), "=r"(r[1]), "=r"(r[2]), "=r"(r[3]) : "r"(a) : "memory");
}
__device__ __forceinline__ uint32_t lds1(uint32_t a) { uint32_t r; asm volatile("ld.shared.b32 %0, [%1];" : "=r"(r) : "r"(a) : "memory"); return r; }
__device__ __forceinline__ void sts1(uint32_t a, uint32_t v) { asm volatile("st.shared.b32 [%0], %1;" :: "r"(a), "r"(v) : "memory"); }
__device__ __forceinline__ void sts4(uint32_t a, uint32_t r0, uint32_t r1, uint32_t r2, uint32_t r3) {
  asm volatile("st.shared.v4.b32 [%0], {%1,%2,%3,%4};" :: "r"(a), "r"(r0), "r"(r1), "r"(r2), "r"(r3) : "memory");
}
__device__ __forceinline__ void ldsm4(uint32_t a, uint32_t* r) {
  asm volatile("ldmatrix.sync.aligned.m8n8.x4.shared.b16 {%0,%1,%2,%3}, [%4];" : "=r"(r[0]), "=r"(r[1]), "=r"(r[2]), "=r"(r[3]) : "r"(a) : "memory");
}
__device__ __forceinline__ float rcpf(float x) { float y; asm("rcp.approx.ftz.f32 %0, %1;" : "=f"(y) : "f"(x)); return y; }
__device__ __forceinline__ uint32_t hfma2(uint32_t a, uint32_t b, uint32_t c) { uint32_t r; asm("fma.rn.f16x2 %0, %1, %2, %3;" : "=r"(r) : "r"(a), "r"(b), "r"(c)); return r; }
__device__ __forceinline__ uint32_t hadd2(uint32_t a, uint32_t b) { uint32_t r; asm("add.rn.f16x2 %0, %1, %2;" : "=r"(r) : "r"(a), "r"(b)); return r; }

#define STEPK 96
#define GIMAP(i) ((((i) & 1) << 2) | (((i) >> 1) & 3) | ((i) & 8))
#define QSCALE 0.36067376022224085f
#define SMAGIC (512.0f + 2.0f * (191.0f - 30.0f - 1.5823545f))
#define VSHIFT 1073741824.0f

__device__ uint32_t g_epoch[132];
__device__ uint32_t g_flag[288 * 8];
#define FLAG_KV (g_flag)
#define FLAG_B(h) (g_flag + (4 + (h)) * 8)
#define FLAG_OA(cta, pass) (g_flag + (16 + (cta) * 2 + (pass)) * 8)
#define FLAG_LM(i) (g_flag + (272 + (i)) * 8)

#define SM_TOTAL (224 * 1024 + 2048 + 1024)
#define OFF_K 0
#define OFF_F 65536
#define OFF_V 131072
#define OFF_MISC (224 * 1024)

#define BAR_FULL(s) (bars + 8 * (s))
#define BAR_EMPTY(s) (bars + 24 + 8 * (s))
#define BAR_KV(c) (bars + 48 + 8 * (c))
#define BAR_BDONE (bars + 80)
#define BAR_Q (bars + 88)
#define BAR_GO (bars + 96)
#define BAR_Q2 (bars + 104)
#define BAR_OD(p) (bars + 112 + 8 * (p))
#define BAR_CL(c) (bars + 128 + 8 * (c))
#define BAR_TE(i) (bars + 168 + 8 * (i))
#define BAR_RL (bars + 184)
#define BAR_TF(g) (bars + 224 + 8 * (g))
#define BAR_XA(w) (bars + 352 + 8 * (w))
#define BAR_VB(c) (bars + 384 + 8 * (c))

__device__ __forceinline__ uint32_t exp2_pair_fix(float d0, float d1, uint32_t c63, uint32_t m1) {
  uint32_t w, y, s, r;
  asm("prmt.b32 %0, %1, %2, 0x6521;" : "=r"(w) : "r"(__float_as_uint(d0)), "r"(__float_as_uint(d1)));
  asm("lop3.b32 %0, %1, 0x007F007F, %2, 0xEA;" : "=r"(y) : "r"(w), "r"(c63));
  asm("mad.lo.u32 %0, %1, %2, %3;" : "=r"(s) : "r"(y), "r"(m1), "r"(w));
  asm("fma.rn.bf16x2 %0, %1, %2, %3;" : "=r"(r) : "r"(w), "r"(y), "r"(s));
  return r;
}

__device__ __forceinline__ void attn_slow(const __nv_bfloat16* xa, const __nv_bfloat16* wq, uint32_t dst) {
  const int t = threadIdx.x & 127;
  const int row = t >> 1, half = t & 1;
  float q[16];
  {
    float a[8];
#pragma unroll
    for (int i = 0; i < 8; i++) a[i] = 0.f;
#pragma unroll 1
    for (int k = 0; k < D_MOD; k++) {
      const float x = __bfloat162float(xa[(size_t)row * D_MOD + k]);
      const uint4 w = *(const uint4*)(wq + (size_t)k * D_MOD + half * 8);
      const uint32_t ww[4] = {w.x, w.y, w.z, w.w};
#pragma unroll
      for (int i = 0; i < 4; i++) { a[2 * i] = fmaf(x, bf_lo(ww[i]), a[2 * i]); a[2 * i + 1] = fmaf(x, bf_hi(ww[i]), a[2 * i + 1]); }
    }
#pragma unroll
    for (int i = 0; i < 8; i++) {
      const float mine = rbf(a[i]), other = __shfl_xor_sync(~0u, mine, 1);
      q[i] = half ? other : mine; q[8 + i] = half ? mine : other;
    }
  }
  float m = -INFINITY, l = 0.f, o[16];
#pragma unroll
  for (int i = 0; i < 16; i++) o[i] = 0.f;
#pragma unroll 1
  for (int j = half * 1024; j < half * 1024 + 1024; j++) {
    uint4 ka = g_KV[4 * S_TOK + j], kb = g_KV[5 * S_TOK + j];
    uint4 va = g_KV[6 * S_TOK + j], vb = g_KV[7 * S_TOK + j];
    uint32_t kk[8] = {ka.x, ka.y, ka.z, ka.w, kb.x, kb.y, kb.z, kb.w};
    uint32_t vv[8] = {va.x, va.y, va.z, va.w, vb.x, vb.y, vb.z, vb.w};
    float s = 0.f;
#pragma unroll
    for (int i = 0; i < 8; i++) { s = fmaf(q[2 * i], bf_lo(kk[i]), s); s = fmaf(q[2 * i + 1], bf_hi(kk[i]), s); }
    s = rbf(s) * 0.25f;
    if (s > m) {
      float c = __expf(m - s);
      l *= c;
#pragma unroll
      for (int i = 0; i < 16; i++) o[i] *= c;
      m = s;
    }
    float p = __expf(s - m);
    l += p;
#pragma unroll
    for (int i = 0; i < 8; i++) { o[2 * i] = fmaf(p, bf_lo(vv[i]), o[2 * i]); o[2 * i + 1] = fmaf(p, bf_hi(vv[i]), o[2 * i + 1]); }
  }
  float m2 = __shfl_xor_sync(~0u, m, 1);
  float mm = fmaxf(m, m2);
  float c = __expf(m - mm);
  l *= c; l += __shfl_xor_sync(~0u, l, 1);
  float inv = 1.f / l;
  uint32_t r[8];
#pragma unroll
  for (int i = 0; i < 16; i++) { o[i] *= c; o[i] += __shfl_xor_sync(~0u, o[i], 1); o[i] *= inv; }
#pragma unroll
  for (int i = 0; i < 8; i++) r[i] = pack_bf16(o[2 * i], o[2 * i + 1]);
  if (half == 0) sts4(dst, r[0], r[1], r[2], r[3]); else sts4(dst, r[4], r[5], r[6], r[7]);
  fence_async();
}

struct Params { const __nv_bfloat16* wk; const __nv_bfloat16* wv; const __nv_bfloat16* xa; const __nv_bfloat16* wq; __nv_bfloat16* out; };
__device__ __forceinline__ void cp16(uint32_t dst, const void* src) { asm volatile("cp.async.cg.shared.global [%0], [%1], 16;" :: "r"(dst), "l"(src) : "memory"); }

__device__ __forceinline__ void helper_cta(const int h, const uint32_t sb, const uint32_t bars, const int wg, const int w4,
                                           const CUtensorMap* mQ, const CUtensorMap* mOs) {
  const int lane = threadIdx.x & 31;
  mbar_wait(BAR_GO, 0);
  const int cb = wg & 1, col = h * 128 + cb * 64, row0 = S_TOK + (wg >> 1) * 1024;
  const uint32_t buf = sb + wg * 49152;
  if (w4 == 0 && elect_one()) {
    fence_async_all();
#pragma unroll 1
    for (int u = 0; u < 3; u++) {
      mbar_expect_tx(BAR_TF(wg * 3 + u), 16384);
      tma2d(buf + u * 16384, mQ, col, row0 + u * 128, BAR_TF(wg * 3 + u));
    }
  }
  const int head = h * 8 + cb * 4 + w4;
  float4 a0 = make_float4(0, 0, 0, 0), a1 = a0, a2 = a0;
#pragma unroll 8
  for (int tt = 0; tt < 16; tt++) {
    const float4* src = g_kvp + ((tt * 32 + head) * 3) * 32 + lane;
    float4 u = src[0], v = src[32], w = src[64];
    a0.x += u.x; a0.y += u.y; a0.z += u.z; a0.w += u.w;
    a1.x += v.x; a1.y += v.y; a1.z += v.z; a1.w += v.w;
    a2.x += w.x; a2.y += w.y; a2.z += w.z; a2.w += w.w;
  }
  const uint32_t b00 = pack_bf16(a0.x, a0.y), b01 = pack_bf16(a0.z, a0.w);
  const uint32_t b10 = pack_bf16(a1.x, a1.y), b11 = pack_bf16(a1.z, a1.w);
  const uint32_t bz0 = pack_bf16(a2.x, a2.y), bz1 = pack_bf16(a2.z, a2.w);
  const int m = lane >> 3, r = lane & 7;
  const uint32_t off = ((m & 1) * 8 + r) * 128 + (((w4 * 2 + (m >> 1)) ^ r) << 4);
  int s = 0, ph = 0;
#pragma unroll 1
  for (int u = 0; u < 8; u++) {
    const uint32_t bb = buf + s * 16384;
    mbar_wait(BAR_TF(wg * 3 + s), ph);
#pragma unroll
    for (int mt = 0; mt < 8; mt++) {
      uint32_t a[4];
      ldsm4(bb + mt * 2048 + off, a);
      float n0[4] = {0, 0, 0, 0}, n1[4] = {0, 0, 0, 0}, dn[4] = {0, 0, 0, 0};
      mma_bf16(dn, a[0], a[1], a[2], a[3], bz0, bz1);
      mma_bf16(n0, a[0], a[1], a[2], a[3], b00, b01);
      mma_bf16(n1, a[0], a[1], a[2], a[3], b10, b11);
      const float i0 = rcpf(dn[0] + 1e-6f), i1 = rcpf(dn[2] + 1e-6f);
      stsm4(bb + mt * 2048 + off, pack_bf16(n0[0] * i0, n0[1] * i0), pack_bf16(n0[2] * i1, n0[3] * i1),
            pack_bf16(n1[0] * i0, n1[1] * i0), pack_bf16(n1[2] * i1, n1[3] * i1));
    }
    fence_async();
    named_bar(wg + 1, 128);
    if (w4 == 0 && lane == 0) {
      tma2d_store(mOs, bb, col, row0 + u * 128);
      bulk_commit();
      if (u >= 1 && u + 2 < 8) {
        asm volatile("cp.async.bulk.wait_group.read 1;" ::: "memory");
        const int sp = s == 0 ? 2 : s - 1;
        mbar_expect_tx(BAR_TF(wg * 3 + sp), 16384);
        tma2d(buf + sp * 16384, mQ, col, row0 + (u + 2) * 128, BAR_TF(wg * 3 + sp));
      }
    }
    __syncwarp();
    if (++s == 3) { s = 0; ph ^= 1; }
  }
  if (w4 == 0 && lane == 0) {
    bulk_wait_all();
    fence_async_all();
    flag_add(FLAG_LM((h * 2 + cb) * 2 + (wg >> 1)));
    if (wg == 0) TS(1, 8);
  }
}

#define STAGE(s) (sb + (2 - (s)) * 65536)
__device__ __forceinline__ uint32_t xa_addr(uint32_t sb, int kb) {
  return sb + (kb >= 1 && kb <= 4 ? OFF_V + 65536 + (kb - 1) * 8192 : 16384 + (kb == 5 ? OFF_K : (kb == 6 ? OFF_V : OFF_F)));
}
#define XA7_TMP (sb + OFF_K + 40960)
#define WKV_TMP (sb + OFF_K + 32768)
template <int TR> __device__ __forceinline__ void proj_kb(float* acc, uint32_t aA, uint32_t aB, int first) {
  const uint64_t da = make_desc(aA, TR ? 8192 : 16, 1024, 1);
  const uint64_t db = make_desc(aB, TR ? 16 : 8192, 1024, 1);
  wg_fence();
#pragma unroll
  for (int k = 0; k < 4; k++) wg_ss128<TR, 1 - TR>(acc, da + k * (TR ? 128 : 2), db + k * (TR ? 2 : 128), k != 0 || !first);
  wg_commit();
}
template <int TR> __device__ __forceinline__ void proj_loop(float* acc, uint32_t sb, uint32_t bars, uint32_t offA, uint32_t offB,
                                                            int wg, uint32_t sWKV) {
  {
    float kv[4];
    if (threadIdx.x == 0) TS(0, 13);
    mbar_wait(BAR_XA(wg), 0);
    if (threadIdx.x == 0) TS(0, 1);
    const uint64_t da0 = make_desc(xa_addr(sb, 2 * wg), 16, 1024, 1);
    const uint64_t da1 = make_desc(wg == 3 ? XA7_TMP : xa_addr(sb, 2 * wg + 1), 16, 1024, 1);
    const uint64_t db = make_desc(sWKV + wg * 2048, 128, 128, 0);
    wg_fence();
#pragma unroll
    for (int k = 0; k < 8; k++) wg_ss8<0, 1>(kv, (k < 4 ? da0 : da1) + (k & 3) * 2, db + k * 16, k != 0);
    wg_commit();
    wg_wait<0>();
    fence_regs<4>(kv);
    named_bar(wg + 1, 128);
    sts4(sWKV + threadIdx.x * 16, __float_as_uint(kv[0]), __float_as_uint(kv[1]), __float_as_uint(kv[2]), __float_as_uint(kv[3]));
    __syncwarp();
    if ((threadIdx.x & 31) == 0) mbar_arrive(BAR_GO);
  }
  int s = 0, ph = 0, sp = 0;
#pragma unroll 1
  for (int kb = 0; kb < 8; kb++) {
    mbar_wait(BAR_FULL(s), ph);
    if (threadIdx.x == 0) TS(0, 2 + kb);
    if (TR == 0) mbar_wait(BAR_XA(kb >> 1), 0);
    proj_kb<TR>(acc, TR ? STAGE(s) + offA : xa_addr(sb, kb), STAGE(s) + offB, kb == 0);
    wg_wait<1>();
    if (kb >= 1 && (threadIdx.x & 127) == 0) {
      mbar_arrive(BAR_EMPTY(sp));
      if (TR == 0 && kb == 5) mbar_arrive(BAR_VB(1));
    }
    __syncwarp();
    sp = s;
    if (++s == 3) { s = 0; ph ^= 1; }
  }
  wg_wait<0>();
  fence_regs<64>(acc);
}

__device__ __forceinline__ uint32_t tail_slots(int isB, int n) {
  if (n < 4) return n < 2 ? (n == 0 ? 0x0D0C0B0Au : 0x04000F0Eu) : (n == 2 ? 0x18141008u : 0x15110501u);
  if (isB) return n < 6 ? (n == 4 ? 0x19120602u : 0x0D0C0B0Au) : (n == 6 ? 0x04000F0Eu : 0x13070316u);
  return n < 6 ? (n == 4 ? 0x1902031Au : 0x12061307u) : (n == 6 ? 0x16091B17u : 0x0D0C0B0Au);
}

__device__ __forceinline__ void take_role(uint32_t sM, int wg) {
  uint32_t r;
  asm volatile("atom.shared.add.u32 %0, [%1], 1;" : "=r"(r) : "r"(sM + 20) : "memory");
  sts1(sM + 32 + wg * 4, r);
}

__global__ void __launch_bounds__(640, 1)
k1_main(const __grid_constant__ CUtensorMap mXA64, const __grid_constant__ CUtensorMap mXB,
        const __grid_constant__ CUtensorMap mWq, const __grid_constant__ CUtensorMap mWqkv,
        const __grid_constant__ CUtensorMap mQst, const __grid_constant__ CUtensorMap mOst,
        const __grid_constant__ CUtensorMap mO, const __grid_constant__ CUtensorMap mWoA,
        const __grid_constant__ CUtensorMap mWoB,
        const __grid_constant__ CUtensorMap mO16, const Params prm) {
  extern __shared__ uint8_t smem_raw[];
  const uint32_t sb = (smem_u32(smem_raw) + 1023u) & ~1023u;
  const uint32_t bars = sb + OFF_MISC, sM = bars + 512, sT = bars + 1024;
  const int tid = threadIdx.x, warp = __shfl_sync(~0u, tid >> 5, 0), wg = warp >> 2, w4 = warp & 3, lane = tid & 31;
  const bool helper = blockIdx.x >= 128;
  if (tid == 0) TS(0, 0);
  const int G = blockIdx.x >> 4, gi = GIMAP(blockIdx.x & 15);
  const int tbA = G * 4 + (gi >> 2), hg = gi & 3;
  const int ttB = (G >> 1) * 4 + (gi >> 2), hq = (G & 1) * 4 + (gi & 3);
  const int isB = tbA & 1, tok0 = (tbA >> 1) * 128;
  auto issue = [&](int kb, int s, int part) {
    const uint32_t fb = BAR_FULL(s), st = STAGE(s);
    if (part & 1) {
      mbar_expect_tx(fb, kb == 7 ? 65536 : 57344);
      if (kb == 7) tma2d(st + 16384, &mXA64, kb * 64, tbA * 64, fb);
      tma2d(st, &mWq, hg * 128, kb * 64, fb);
      tma2d(st + 8192, &mWq, hg * 128 + 64, kb * 64, fb);
      tma2d(st + 49152, &mXB, kb * 64, ttB * 128, fb);
      tma2d(st + 24576, &mWqkv, hq * 64, kb * 64, fb);
    }
    if (part & 2) {
      tma2d(st + 32768, &mWqkv, 512 + hq * 64, kb * 64, fb);
      tma2d(st + 40960, &mWqkv, 1024 + hq * 64, kb * 64, fb);
    }
  };
  const uint32_t sOne = sb + OFF_V + 65536, sWKV = WKV_TMP;
  if (warp >= 16) {
    if (warp == 17) {
      if (elect_one()) {
        mbar_init(BAR_BDONE, 8); mbar_init(BAR_Q, 6); mbar_init(BAR_GO, helper ? 1 : 16); mbar_init(BAR_Q2, 1);
        mbar_init(BAR_OD(0), 16); mbar_init(BAR_OD(1), 16); mbar_init(BAR_CL(0), 1); mbar_init(BAR_FULL(2), 1);
#pragma unroll
        for (int i = 0; i < 4; i++) mbar_init(BAR_CL(i + 1), i == 0 ? 5 : 4);
#pragma unroll
        for (int i = 0; i < 3; i++) { mbar_init(BAR_EMPTY(i), 4); mbar_init(BAR_KV(i), 1); mbar_init(BAR_VB(i), i == 2 ? 4 : 1); }
        sts1(sM + 20, 0);
        asm volatile("fence.mbarrier_init.release.cluster;" ::: "memory");
      }
    } else if (warp == 18) {
      if (elect_one()) {
#pragma unroll
        for (int i = 0; i < 2; i++) mbar_init(BAR_TE(i), 2);
        mbar_init(BAR_RL, 1);
#pragma unroll
        for (int i = 0; i < 16; i++) mbar_init(BAR_TF(i), 1);
        asm volatile("fence.mbarrier_init.release.cluster;" ::: "memory");
      }
    } else if (warp == 16 && !helper && elect_one()) {
#pragma unroll
      for (int w = 0; w < 4; w++) mbar_init(BAR_XA(w), 1);
      mbar_init(BAR_FULL(0), 1); mbar_init(BAR_FULL(1), 1);
      asm volatile("fence.mbarrier_init.release.cluster;" ::: "memory");
#pragma unroll
      for (int w = 0; w < 4; w++) {
        mbar_expect_tx(BAR_XA(w), 16384);
        tma2d(xa_addr(sb, 2 * w), &mXA64, w * 128, tbA * 64, BAR_XA(w));
        tma2d(w == 3 ? XA7_TMP : xa_addr(sb, 2 * w + 1), &mXA64, w * 128 + 64, tbA * 64, BAR_XA(w));
      }
      TS(0, 14);
      issue(0, 0, 3);
    }
  } else if (!helper) {
    const uint4 v = __ldg((const uint4*)(hg >= 2 ? prm.wv : prm.wk) + tid * 2 + (hg & 1));
    sts4(sWKV + tid * 16, v.x, v.y, v.z, v.w);
    fence_async();
  }
  __syncthreads();
  if (wg == 4) {
    if (w4 == 0 && !helper && elect_one()) { issue(1, 1, 3); issue(2, 2, 1); TS(0, 15); }
    asm volatile("setmaxnreg.dec.sync.aligned.u32 32;");
    const uint32_t ep = g_epoch[blockIdx.x] + 1;
    if (helper) {
      if (w4 == 0 && elect_one()) {
        flag_wait(FLAG_B(blockIdx.x - 128), ep * 32);
        fence_async_all();
        TS(1, 10);
        mbar_arrive(BAR_GO);
        g_epoch[blockIdx.x] = ep;
      }
      return;
    }
    mbar_wait(BAR_GO, 0);
    {
      uint32_t a[4], b[4];
      float c[4];
      lds4(sWKV + (tid - 512) * 16, a);
      lds4(sWKV + 2048 + (tid - 512) * 16, b);
#pragma unroll
      for (int i = 0; i < 4; i++) c[i] = __uint_as_float(a[i]) + __uint_as_float(b[i]);
      lds4(sWKV + 4096 + (tid - 512) * 16, a);
      lds4(sWKV + 6144 + (tid - 512) * 16, b);
#pragma unroll
      for (int i = 0; i < 4; i++) c[i] += __uint_as_float(a[i]) + __uint_as_float(b[i]);
      sts1(sT + w4 * 256 + lane * 4, pack_bf16(c[0], c[1]));
      sts1(sT + w4 * 256 + 128 + lane * 4, pack_bf16(c[2], c[3]));
    }
    named_bar(9, 128);
    if (w4 == 0 && elect_one()) issue(2, 2, 2);
    auto write_ones = [&]() {
      mbar_wait_long(BAR_VB(1), 0);
      int c = ((w4 & 1) * 32 + lane);
#pragma unroll 4
      for (int key = c; key < S_TOK; key += 64) {
        sts4(sOne + key * 16, c < 24 ? 0x00003F80u : 0x00004E80u, 0u, 0u, 0u);
        c += 64; if (c >= STEPK) c -= STEPK;
      }
      fence_async();
      __syncwarp();
      if (lane == 0) mbar_arrive(BAR_Q);
    };
    if (w4 == 0) {
      int s = 0, ph = 0;
#pragma unroll 1
      for (int kb = 3; kb < 8; kb++) {
        mbar_wait(BAR_EMPTY(s), ph);
        if (elect_one()) issue(kb, s, 3);
        if (++s == 3) { s = 0; ph ^= 1; }
      }
      flag_wait(FLAG_KV, ep * 128);
      fence_async_all();
      if (lane == 0) TS(0, 11);
#pragma unroll 1
      for (int m = 0; m < 2; m++) {
        mbar_wait(m == 0 ? BAR_EMPTY(2) : BAR_EMPTY(0), 1 - m);
        if (elect_one()) {
          const uint32_t fb = m == 0 ? BAR_KV(0) : BAR_VB(0);
          mbar_expect_tx(fb, 2 * 7 * STEPK * 16);
#pragma unroll
          for (int p = 0; p < 2; p++) bulk_g2s(sb + m * OFF_V + p * 32768, g_KV + (m * 2 + p) * S_TOK, 7 * STEPK * 16, fb);
        }
      }
      mbar_wait(BAR_Q, 0);
      if (elect_one()) {
#pragma unroll
        for (int c = 1; c < 3; c++) {
          const int k0 = c == 1 ? 7 * STEPK : 12 * STEPK, k1 = c == 1 ? 12 * STEPK : S_TOK;
          const uint32_t bytes = (k1 - k0) * 16;
          mbar_expect_tx(BAR_KV(c), 4 * bytes);
#pragma unroll
          for (int p = 0; p < 4; p++)
            bulk_g2s(sb + (p >> 1) * OFF_V + (p & 1) * 32768 + k0 * 16, g_KV + p * S_TOK + k0, bytes, BAR_KV(c));
        }
      }
      mbar_wait_long(BAR_CL(1), 0);
      flag_wait(isB ? FLAG_LM((lane & 7) * 2 + (tbA >> 4)) : FLAG_OA(tbA * 4 + (lane & 7), 0), ep);
      __syncwarp();
      fence_async_all();
      if (lane == 0) TS(2, 13);
      const CUtensorMap* mW = isB ? &mWoB : &mWoA;
#pragma unroll 1
      for (int it = 0; it < 8; it++) {
        const int n = (!isB && it >= 6) ? 13 - it : it;
        uint32_t wb = BAR_CL(n < 3 ? 0 : (n == 3 ? 2 : 3));
        if (isB) { if (n >= 5) wb = n == 7 ? BAR_CL(4) : BAR_TE(n - 5); }
        else if (n >= 6) wb = n == 6 ? BAR_CL(4) : BAR_TE(0);
        if (it < 6) mbar_wait_long(wb, 0); else mbar_wait(wb, 0);
        const uint32_t sl = tail_slots(isB, n), fb = BAR_TF(n);
        const bool withX = isB || n < 4;
        const int k0 = isB ? n * 64 : (n < 4 ? n * 128 : ((hg + n) & 3) * 128 + 64);
        if (elect_one()) {
          mbar_expect_tx(fb, withX ? 32768 : 16384);
          if (withX) {
            tma2d(sb + (sl & 255) * 8192, &mO, k0, isB * S_TOK + tok0, fb);
            tma2d(sb + ((sl >> 8) & 255) * 8192, &mO, k0, isB * S_TOK + tok0 + 64, fb);
          }
          tma2d(sb + ((sl >> 16) & 255) * 8192, mW, hg * 128, k0, fb);
          tma2d(sb + (sl >> 24) * 8192, mW, hg * 128 + 64, k0, fb);
        }
      }
      if (lane == 0) g_epoch[blockIdx.x] = ep;
    } else if (w4 == 3) {
      write_ones();
      flag_wait(FLAG_KV, ep * 128);
      const uint4 a = *(const uint4*)(g_stats + lane * 4);
      const float kmax2 = __uint_as_float(__reduce_max_sync(~0u, a.x)) + __uint_as_float(__reduce_max_sync(~0u, a.y));
      const float vmax = __uint_as_float(__reduce_max_sync(~0u, max(a.z, a.w)));
      const float lv = vmax > 0.f ? __log2f(vmax) : 0.f;
      const float lim = fminf(90.f, fminf(91.f + lv, 95.f - lv));
      float thr = -1.f;
      if (vmax < 1e27f && kmax2 <= 65536.f && lim > 2.f) thr = fminf(60000.f, (lim * lim - 1.f) / (kmax2 * 1.02f + 1e-30f));
      mbar_wait_long(BAR_VB(2), 0);
      uint32_t nmax = 0;
#pragma unroll 2
      for (int i = 0; i < 16; i++) {
        uint32_t x[4], y[4];
        const uint32_t ad = sb + OFF_F + i * 1024 + (lane >> 3) * 256 + (lane & 7) * 16;
        lds4(ad, x); lds4(ad + 128, y);
        uint32_t n = hfma2(x[0], x[0], hfma2(x[1], x[1], hfma2(x[2], x[2], hfma2(x[3], x[3], 0u))));
        n = hfma2(y[0], y[0], hfma2(y[1], y[1], hfma2(y[2], y[2], hfma2(y[3], y[3], n))));
        n = hadd2(n, n >> 16);
        nmax = max(nmax, n & 0x7FFFu);
      }
      nmax = __reduce_max_sync(~0u, nmax);
      const bool ok = __half2float(__ushort_as_half((unsigned short)nmax)) <= thr;
      if (lane == 0) { sts1(sM + 16, ok ? 1u : 0u); mbar_arrive(BAR_Q2); }
    } else {
      const int tok = (w4 - 1) * 32 + lane;
      int step, col;
      if ((tbA & 3) == 0) {
        const int b8 = tbA >> 2;
        if (tok < 22) { step = tok; col = 24 + b8; }
        else { const int c = tok >= 43; step = tok - 22 - 21 * c; col = 32 + b8 * 2 + c; }
      } else {
        const int b24 = (tbA >> 2) * 3 + (tbA & 3) - 1;
        if (tok < 42) { const int c = tok >= 21; step = tok - 21 * c; col = 48 + b24 * 2 + c; }
        else { step = tok - 42; col = b24; }
      }
      const int kap = step * STEPK + col;
      const bool chained = col >= 24;
      uint32_t v[4], o[4];
      lds4(sT + tok * 16, v);
      g_KV[(4 + hg) * S_TOK + kap] = make_uint4(v[0], v[1], v[2], v[3]);
      float st = 0.f;
      if (hg < 2) {
        o[0] = o[1] = o[2] = o[3] = 0;
        if (chained && step > 0) lds4(sT + tok * 16 - 16, o);
        const float sc = chained ? 2.f : 1.f;
#pragma unroll
        for (int u = 0; u < 4; u++) {
          const float x = bf_lo(v[u]), y = bf_hi(v[u]);
          st += x * x + y * y;
          o[u] = pack_f16((x - bf_lo(o[u])) * sc, (y - bf_hi(o[u])) * sc);
        }
      } else {
        const float sc = chained ? VSHIFT : 1.f;
#pragma unroll
        for (int u = 0; u < 4; u++) { float x = bf_lo(v[u]), y = bf_hi(v[u]); st += fabsf(x) + fabsf(y); o[u] = pack_bf16(x * sc, y * sc); }
      }
      g_KV[hg * S_TOK + kap] = make_uint4(o[0], o[1], o[2], o[3]);
      const uint32_t um = __reduce_max_sync(~0u, __float_as_uint(st) & 0x7FFFFFFFu);
      if (w4 == 2) {
        if (lane == 0) sts1(sM + 24, um);
        named_arrive(10, 64);
        write_ones();
        if (!isB) {
          mbar_wait_long(BAR_CL(3), 0);
          mbar_wait_long(BAR_RL, 0);
          uint32_t pend = 0xFE;
          const int li = lane & 7;
          const uint32_t* fl = FLAG_OA((tbA + (li & 1)) * 4 + ((hg + (li >> 1)) & 3), 1);
#pragma unroll 1
          for (int it = 0; pend; it++) {
            uint32_t fv;
            asm volatile("ld.acquire.gpu.global.u32 %0, [%1];" : "=r"(fv) : "l"(fl) : "memory");
            uint32_t go = __ballot_sync(~0u, (int32_t)(fv - ep) >= 0 && mbar_test(li >= 6 ? BAR_TE(0) : BAR_CL(4), 0)) & pend;
            pend &= ~go;
            if (go) fence_async_all();
#pragma unroll 1
            while (go) {
              const int b = __ffs(go) - 1;
              go &= go - 1;
              const uint32_t slot = (tail_slots(0, 4 + (b >> 1)) >> (8 * (b & 1))) & 255;
              if (elect_one()) {
                mbar_expect_tx(BAR_TF(8 + b), 8192);
                tma2d(sb + slot * 8192, &mO, ((hg + (b >> 1)) & 3) * 128 + 64, tok0 + (b & 1) * 64, BAR_TF(8 + b));
              }
            }
            if (it > 2000000) __trap();
          }
          if (lane == 0) TS(2, 14);
        }
      }
      else {
        named_bar(10, 64);
        if (elect_one()) {
          g_stats[tbA * 4 + hg] = max(um, lds1(sM + 24));
          fence_async_all();
          flag_add(FLAG_KV);
          TS(1, 9);
          mbar_wait_long(BAR_BDONE, 0);
          tma2d_store(&mQst, sb + OFF_F + 49152, hq * 64, S_TOK + ttB * 128);
          bulk_commit();
          bulk_wait_all();
          fence_async_all();
          flag_add(FLAG_B(hq >> 1));
          TS(0, 12);
          mbar_wait(BAR_Q, 0);
          mbar_arrive(BAR_CL(0));
#pragma unroll 1
          for (int p = 0; p < 2; p++) {
            mbar_wait_long(BAR_OD(p), 0);
            if (p == 0) {
#pragma unroll
              for (int w = 0; w < 4; w++) tma2d_store(&mO16, sb + OFF_F + w * 2048, hg * 128 + w * 16, tbA * 64);
            } else {
              tma2d_store(&mO, sb + 26 * 8192, hg * 128 + 64, tbA * 64);
            }
            bulk_commit();
            bulk_wait_all();
            if (p == 0) mbar_arrive(BAR_CL(1));
            PUBLISH(FLAG_OA(tbA * 4 + hg, p));
          }
          TS(2, 0);
        }
      }
    }
    return;
  }
  if (helper) { helper_cta(blockIdx.x - 128, sb, bars, wg, w4, &mQst, &mOst); return; }

  {
    float acc[64];
    if (wg == 0) proj_loop<0>(acc, sb, bars, 16384, 0, wg, sWKV);
    else proj_loop<1>(acc, sb, bars, 16384 + wg * 8192, 49152, wg, sWKV);
    if (tid == 0) TS(0, 10);
    const uint32_t sF = sb + OFF_F;
    const uint32_t qa = sF + w4 * 512 + ((lane >> 3) & 1) * 256 + (lane >> 4) * 128 + (lane & 7) * 16;
    if (wg == 0) {
#pragma unroll
      for (int hd = 0; hd < 4; hd++)
        stsm4(qa + hd * 2048, pack_f16(acc[8 * hd] * QSCALE, acc[8 * hd + 1] * QSCALE), pack_f16(acc[8 * hd + 2] * QSCALE, acc[8 * hd + 3] * QSCALE),
              pack_f16(acc[8 * hd + 4] * QSCALE, acc[8 * hd + 5] * QSCALE), pack_f16(acc[8 * hd + 6] * QSCALE, acc[8 * hd + 7] * QSCALE));
      fence_async();
      __syncwarp();
      if (lane == 0) mbar_arrive(BAR_Q);
    } else {
      if (wg != 3) named_arrive(6, 384);
      if (wg != 1) named_arrive(8, 384);
    }
    asm volatile("setmaxnreg.inc.sync.aligned.u32 112;");
    fence_regs<64>(acc);
    if (wg == 0) {
#pragma unroll
      for (int hd = 4; hd < 8; hd++)
        stsm4(qa + hd * 2048, pack_f16(acc[8 * hd] * QSCALE, acc[8 * hd + 1] * QSCALE), pack_f16(acc[8 * hd + 2] * QSCALE, acc[8 * hd + 3] * QSCALE),
              pack_f16(acc[8 * hd + 4] * QSCALE, acc[8 * hd + 5] * QSCALE), pack_f16(acc[8 * hd + 6] * QSCALE, acc[8 * hd + 7] * QSCALE));
      fence_async();
      __syncwarp();
      if (lane == 0) mbar_arrive(BAR_VB(2));
    } else if (wg == 3) {
      named_bar(6, 384);
      const int t = tid & 127;
#pragma unroll
      for (int j = 0; j < 8; j++)
        sts4(sF + 24576 + j * 2048 + t * 16, pack_bf16(acc[8 * j], acc[8 * j + 1]), pack_bf16(acc[8 * j + 2], acc[8 * j + 3]),
             pack_bf16(acc[8 * j + 4], acc[8 * j + 5]), pack_bf16(acc[8 * j + 6], acc[8 * j + 7]));
      named_arrive(7, 256);
    } else {
      uint32_t p[32];
#pragma unroll
      for (int i = 0; i < 32; i++) p[i] = phi2(acc[2 * i], acc[2 * i + 1]);
      if (wg == 1) {
        named_bar(8, 384);
        const int m = lane >> 3, r = lane & 7;
#pragma unroll
        for (int j = 0; j < 16; j += 2) {
          const int tok = (j + (m >> 1)) * 8 + r;
          const int chunk = w4 * 2 + (m & 1);
          stsm4t(sF + 49152 + tok * 128 + ((chunk ^ r) << 4), p[2 * j], p[2 * j + 1], p[2 * j + 2], p[2 * j + 3]);
        }
        fence_async();
      } else {
        named_bar(7, 256);
        float kv0[4] = {0, 0, 0, 0}, kv1[4] = {0, 0, 0, 0}, z0[4] = {0, 0, 0, 0}, z1[4] = {0, 0, 0, 0};
        const uint32_t one = 0x3F803F80u;
        const int t = tid & 127;
#pragma unroll
        for (int j = 0; j < 8; j++) {
          uint32_t a[4];
          lds4(sF + 24576 + j * 2048 + t * 16, a);
          mma_bf16(kv0, a[0], a[1], a[2], a[3], p[4 * j], p[4 * j + 2]);
          mma_bf16(kv1, a[0], a[1], a[2], a[3], p[4 * j + 1], p[4 * j + 3]);
          mma_bf16(z0, one, one, one, one, p[4 * j], p[4 * j + 2]);
          mma_bf16(z1, one, one, one, one, p[4 * j + 1], p[4 * j + 3]);
        }
        float4* dst = g_kvp + ((ttB * 32 + hq * 4 + w4) * 3) * 32 + lane;
        dst[0] = make_float4(kv0[0], kv0[1], kv1[0], kv1[1]);
        dst[32] = make_float4(kv0[2], kv0[3], kv1[2], kv1[3]);
        dst[64] = make_float4(z0[0], z0[1], z1[0], z1[1]);
      }
      __syncwarp();
      if (lane == 0) mbar_arrive(BAR_BDONE);
    }
  }

  bool safe = true;
  {
    const uint32_t c63 = 0x1F801F80u + (threadIdx.x >> 20);
    const uint32_t m1 = (gridDim.x >> 20) - 1u;
    const uint64_t dK0 = make_desc(sb + OFF_K, 32768, 128, 0);
    const uint64_t dV0 = make_desc(sb + OFF_V, 128, 32768, 0);
    constexpr uint32_t dKV = ((2048u - 8u)  __H0__ ) + STEPK - (OFF_V - OFF_K) / 16;
    float Sm[12], Sp[36], O[12];
    uint32_t P[24];
    uint64_t dQ = make_desc(sb + OFF_F + wg * 2048, 128, 256, 0);
#pragma unroll
    for (int i = 0; i < 36; i++) Sp[i] = SMAGIC;
#pragma unroll
    for (int i = 0; i < 12; i++) Sm[i] = 0.f;
    fence_regs<12>(Sm); fence_regs<36>(Sp);
    mbar_wait(BAR_Q, 0);
    mbar_wait(BAR_KV(0), 0);
    wg_fence();
    wg_qs72<1>(Sp, dQ, dK0 + 24);
    wg_qs24<0>(Sm, dQ, dK0);
    wg_commit();
    wg_wait<0>();
    fence_regs<12>(Sm); fence_regs<36>(Sp);
#pragma unroll 1
    for (int pass = 0; pass < 2; pass++) {
#pragma unroll
      for (int i = 0; i < 12; i++) O[i] = 0.f;
      fence_regs<12>(O);
      if (tid == 0) TS(1, 2 + 2 * pass);
      uint32_t vlo = (uint32_t)dV0;
#pragma unroll 1
      for (int seg = 0; seg < 4; seg++) {
        if (pass == 0) {
          if (seg < 3) mbar_wait(seg == 0 ? BAR_VB(0) : BAR_KV(seg), 0);
        } else if (seg >= 1) {
          if ((tid & 127) == 0) {
            mbar_arrive(BAR_CL(seg));
            if (seg == 3) take_role(sM, wg);
          }
          __syncwarp();
        }
        if ((tid & 127) == 0) TS(4 + wg, pass * 5 + seg);
        const uint32_t vend = vlo + (seg == 0 ? 6 : 5) * STEPK;
#pragma unroll 1
        for (; vlo != vend; vlo += STEPK) {
          uint64_t dK, dV;
          asm("mov.b64 %0, {%1, %2};" : "=l"(dK) : "r"(vlo + dKV), "r"(8u));
          asm("mov.b64 %0, {%1, %2};" : "=l"(dV) : "r"(vlo), "r"(2048u));
#pragma unroll
          for (int i = 0; i < 6; i++) P[i] = pack_bf16(ex2f(Sm[2 * i]), ex2f(Sm[2 * i + 1]));
#pragma unroll
          for (int i = 0; i < 18; i++) P[6 + i] = exp2_pair_fix(Sp[2 * i], Sp[2 * i + 1], c63, m1);
          fence_regs<24>(P);
          wg_fence();
#pragma unroll
          for (int k = 0; k < 6; k++) wg_pv24<1>(O, &P[4 * k], dV + k * 16);
          wg_qs72<1>(Sp, dQ, dK + 24);
          wg_qs24<0>(Sm, dQ, dK);
          wg_commit();
          wg_wait<0>();
          fence_regs<12>(Sm); fence_regs<36>(Sp); fence_regs<12>(O); fence_regs<24>(P);
        }
      }
#pragma unroll
      for (int i = 0; i < 6; i++) P[i] = pack_bf16(ex2f(Sm[2 * i]), ex2f(Sm[2 * i + 1]));
      P[6] = exp2_pair_fix(Sp[0], Sp[1], c63, m1);
      P[7] = exp2_pair_fix(Sp[2], Sp[3], c63, m1);
      fence_regs<8>(P);
#pragma unroll
      for (int i = 0; i < 36; i++) Sp[i] = SMAGIC;
      fence_regs<36>(Sp);
      mbar_wait(pass == 0 ? BAR_Q2 : BAR_CL(3), 0);
      const uint32_t sO = pass == 0 ? sb + OFF_F + wg * 2048 + w4 * 512 + (lane & 15) * 32 + (lane >> 4) * 16
                                    : sb + 26 * 8192 + (w4 * 16 + (lane & 15)) * 128 + (((wg * 2 + (lane >> 4)) ^ (lane & 7)) << 4);
      dQ += 512;
      wg_fence();
      wg_pv24<1>(O, &P[0], dV0 + 21 * STEPK);
      wg_pv24<1>(O, &P[4], dV0 + 21 * STEPK + 16);
      wg_commit();
      wg_qs72<1>(Sp, dQ, dK0 + 24);
      wg_qs24<0>(Sm, dQ, dK0);
      wg_commit();
      wg_wait<1>();
      fence_regs<12>(O);
      const float l0 = __shfl_sync(~0u, O[8], lane & ~3), l1 = __shfl_sync(~0u, O[10], lane & ~3);
      const float i0 = rcpf(l0), i1 = rcpf(l1);
      stsm4(sO,
            pack_bf16(O[0] * i0, O[1] * i0), pack_bf16(O[2] * i1, O[3] * i1),
            pack_bf16(O[4] * i0, O[5] * i0), pack_bf16(O[6] * i1, O[7] * i1));
      fence_async();
      {
        safe = __all_sync(~0u, lds1(sM + 16) != 0);
      }
      if (safe && lane == 0) mbar_arrive(BAR_OD(pass));
      wg_wait<0>();
      fence_regs<12>(Sm); fence_regs<36>(Sp);
      if (!safe) break;
      if ((tid & 127) == 0) TS(4 + wg, pass * 5 + 4);
      if (tid == 0) TS(1, 3 + 2 * pass);
    }
  }
  if (!safe) {
    if ((tid & 127) == 0) { mbar_arrive(BAR_CL(1)); mbar_arrive(BAR_CL(2)); mbar_arrive(BAR_CL(3)); take_role(sM, wg); }
#pragma unroll 1
    for (int pass = 0; pass < 2; pass++) {
      const int t = tid & 127;
      mbar_wait(BAR_CL(3), 0);
      attn_slow(prm.xa + (size_t)tbA * 64 * D_MOD, prm.wq + (hg * 8 + pass * 4 + wg) * 16,
                pass == 0 ? sb + OFF_F + wg * 2048 + t * 16
                          : sb + 26 * 8192 + (t >> 1) * 128 + (((wg * 2 + (t & 1)) ^ ((t >> 1) & 7)) << 4));
      __syncwarp();
      if (lane == 0) mbar_arrive(BAR_OD(pass));
    }
  }

  {
    named_bar(wg + 1, 128);
    if ((tid & 127) == 0) mbar_arrive(BAR_CL(4));
    const int role = __shfl_sync(~0u, lds1(sM + 32 + wg * 4), 0);
    if ((tid & 127) == 0) TS(4 + wg, 10);
    const int m = lane >> 3, r = lane & 7;
    const uint32_t stoff = (w4 * 16 + (m & 1) * 8 + r) * 128;
    if (role < 2) {
      if (role == 0 && (tid & 127) == 0) mbar_arrive(BAR_RL);
      if (!isB || role == 1) mbar_wait(BAR_CL(4), 0);
      float acc[64];
#pragma unroll 1
      for (int n = 0; n < 8; n++) {
        const uint32_t sl = tail_slots(isB, n);
        const uint32_t w0 = (sl >> 16) & 255, w1 = sl >> 24;
        const uint64_t da = make_desc(sb + ((sl >> (8 * role)) & 255) * 8192, 16, 1024, 1);
        const uint64_t db = make_desc(sb + w0 * 8192, (w1 - w0) * 8192, 1024, 1);
        mbar_wait(BAR_TF(n), 0);
        if (!isB && n >= 4) mbar_wait(n == 4 && role == 0 ? BAR_OD(1) : BAR_TF(2 * n + role), 0);
        if ((tid & 127) == 0 && role == 1) TS(2, 2 + n);
        wg_fence();
#pragma unroll
        for (int k = 0; k < 4; k++) wg_ss128<0, 1>(acc, da + k * 2, db + k * 128, (n | k) != 0);
        wg_commit();
        wg_wait<1>();
        if ((n == 1 || n == 2) && (tid & 127) == 0) mbar_arrive(BAR_TE(n - 1));
        __syncwarp();
      }
      wg_wait<0>();
      fence_regs<64>(acc);
      if ((tid & 127) == 0) TS(4 + wg, 11);
      const uint32_t x0 = sb + (role ? 16 : 8) * 8192, x1 = sb + (role ? 5 : 1) * 8192;
#pragma unroll
      for (int j = 0; j < 16; j += 2)
        stsm4((j < 8 ? x0 : x1) + stoff + ((((j & 7) + (m >> 1)) ^ r) << 4),
              pack_bf16(acc[4 * j], acc[4 * j + 1]), pack_bf16(acc[4 * j + 2], acc[4 * j + 3]),
              pack_bf16(acc[4 * j + 4], acc[4 * j + 5]), pack_bf16(acc[4 * j + 6], acc[4 * j + 7]));
      __syncwarp();
      uint4* dst = (uint4*)(prm.out + (size_t)(tok0 + role * 64 + w4 * 16 + (lane >> 4)) * 1024 + isB * 512 + hg * 128) + (lane & 15);
      const uint32_t src = ((lane & 8) ? x1 : x0) + (w4 * 16 + (lane >> 4)) * 128;
#pragma unroll
      for (int i = 0; i < 8; i++) {
        uint32_t v[4];
        lds4(src + i * 256 + (((lane & 7) ^ ((2 * i + (lane >> 4)) & 7)) << 4), v);
        dst[i * 256] = make_uint4(v[0], v[1], v[2], v[3]);
      }
      if ((tid & 127) == 0) TS(2, 11 + role);
    }
  }
}

typedef CUresult (*EncodeFn)(CUtensorMap*, CUtensorMapDataType, cuuint32_t, void*, const cuuint64_t*, const cuuint64_t*,
                             const cuuint32_t*, const cuuint32_t*, CUtensorMapInterleave, CUtensorMapSwizzle,
                             CUtensorMapL2promotion, CUtensorMapFloatOOBfill);

static void make_map(EncodeFn enc, CUtensorMap* m, const void* ptr, uint64_t cols, uint64_t rows, uint32_t bc, uint32_t br,
                     CUtensorMapSwizzle sw = CU_TENSOR_MAP_SWIZZLE_128B) {
  cuuint64_t dims[2] = {cols, rows};
  cuuint64_t strides[1] = {cols * 2};
  cuuint32_t box[2] = {bc, br};
  cuuint32_t es[2] = {1, 1};
  enc(m, CU_TENSOR_MAP_DATA_TYPE_BFLOAT16, 2, (void*)ptr, dims, strides, box, es, CU_TENSOR_MAP_INTERLEAVE_NONE,
      sw, CU_TENSOR_MAP_L2_PROMOTION_L2_256B, CU_TENSOR_MAP_FLOAT_OOB_FILL_NONE);
}

extern "C" void kernel_launch(void* const* d_in, const int* in_sizes, int n_in, void* d_out, int out_size) {
  (void)in_sizes; (void)n_in; (void)out_size;
  static EncodeFn enc = nullptr;
  static void* pQ = nullptr; static void* pO = nullptr;
  if (!enc) {
    void* fn = nullptr; cudaDriverEntryPointQueryResult qr;
    cudaGetDriverEntryPoint("cuTensorMapEncodeTiled", &fn, cudaEnableDefault, &qr);
    enc = (EncodeFn)fn;
    cudaGetSymbolAddress(&pQ, g_Q);
    cudaGetSymbolAddress(&pO, g_O);
    cudaFuncSetAttribute(k1_main, cudaFuncAttributeMaxDynamicSharedMemorySize, SM_TOTAL);
  }
  CUtensorMap mXA64, mXB, mWq, mWqkv, mQst, mO, mOst, mWoA, mWoB, mO16;
  make_map(enc, &mXA64, d_in[0], 512, 2048, 64, 64);
  make_map(enc, &mWq, d_in[1], 512, 512, 64, 64);
  make_map(enc, &mWoA, d_in[4], 512, 512, 64, 64);
  make_map(enc, &mXB, d_in[5], 512, 2048, 64, 128);
  make_map(enc, &mWqkv, d_in[6], 1536, 512, 64, 64);
  make_map(enc, &mWoB, d_in[7], 512, 512, 64, 64);
  make_map(enc, &mQst, pQ, 512, 4096, 64, 128);
  make_map(enc, &mO, pO, 512, 4096, 64, 64);
  make_map(enc, &mOst, pO, 512, 4096, 64, 128);
  make_map(enc, &mO16, pO, 512, 4096, 16, 64, CU_TENSOR_MAP_SWIZZLE_NONE);
  Params prm{(const __nv_bfloat16*)d_in[2], (const __nv_bfloat16*)d_in[3], (const __nv_bfloat16*)d_in[0], (const __nv_bfloat16*)d_in[1], (__nv_bfloat16*)d_out};
  k1_main<<<132, 640, SM_TOTAL, cudaStreamPerThread>>>(mXA64, mXB, mWq, mWqkv, mQst, mOst, mO, mWoA, mWoB, mO16, prm);
}
```

```cpp
#include <cuda_runtime.h>
#include <cuda_bf16.h>
#include <cuda_fp16.h>
#include <cuda.h>
#include <stdint.h>

#define S_TOK 2048
#define D_MOD 512

__device__ __align__(1024) __nv_bfloat16 g_Q[2 * S_TOK * D_MOD];
__device__ __align__(1024) __nv_bfloat16 g_O[2 * S_TOK * D_MOD];
__device__ __align__(1024) uint4 g_KV[8 * S_TOK];
__device__ __align__(16) uint32_t g_stats[128];
__device__ __align__(16) float4 g_kvp[16 * 32 * 3 * 32];

#define TS(k, i) do {} while (0)
__device__ __forceinline__ uint32_t smem_u32(const void* p) { return (uint32_t)__cvta_generic_to_shared(p); }
__device__ __forceinline__ void mbar_init(uint32_t bar, int cnt) { asm volatile("mbarrier.init.shared::cta.b64 [%0], %1;" :: "r"(bar), "r"(cnt) : "memory"); }
__device__ __forceinline__ void mbar_expect_tx(uint32_t bar, uint32_t bytes) { asm volatile("mbarrier.arrive.expect_tx.shared::cta.b64 _, [%0], %1;" :: "r"(bar), "r"(bytes) : "memory"); }
__device__ __forceinline__ bool mbar_try(uint32_t bar, uint32_t parity) {
  uint32_t ok;
  asm volatile("{\n.reg .pred p;\nmbarrier.try_wait.parity.shared::cta.b64 p, [%1], %2;\nselp.b32 %0, 1, 0, p;\n}\n" : "=r"(ok) : "r"(bar), "r"(parity) : "memory");
  return ok;
}
__device__ __forceinline__ void mbar_wait(uint32_t bar, uint32_t parity) {
  asm volatile("{\n.reg .pred p;\n.reg .u32 c;\nmov.u32 c, 0;\n"
               "LW_%=:\n"
               "mbarrier.try_wait.parity.shared::cta.b64 p, [%0], %1;\n"
               "@p bra LD_%=;\n"
               "add.u32 c, c, 1;\n"
               "setp.lt.u32 p, c, 4000000;\n"
               "@p bra LW_%=;\n"
               "trap;\n"
               "LD_%=:\n}\n" :: "r"(bar), "r"(parity) : "memory");
}
__device__ __forceinline__ void mbar_arrive_cta(uint32_t bar, uint32_t cta) {
  asm volatile("{\n.reg .b32 ra;\nmapa.shared::cluster.u32 ra, %0, %1;\nmbarrier.arrive.shared::cluster.b64 _, [ra];\n}\n" :: "r"(bar), "r"(cta) : "memory");
}
__device__ __forceinline__ void cluster_sync() {
  asm volatile("barrier.cluster.arrive.relaxed.aligned;\nbarrier.cluster.wait.aligned;" ::: "memory");
}
__device__ __forceinline__ void tma2d(uint32_t dst, const CUtensorMap* m, int c0, int c1, uint32_t bar) {
  asm volatile("cp.async.bulk.tensor.2d.shared::cluster.global.mbarrier::complete_tx::bytes [%0], [%1, {%3, %4}], [%2];"
               :: "r"(dst), "l"(m), "r"(bar), "r"(c0), "r"(c1) : "memory");
}
__device__ __forceinline__ void tma2d_mc(uint32_t dst, const CUtensorMap* m, int c0, int c1, uint32_t bar, uint16_t mask) {
  asm volatile("cp.async.bulk.tensor.2d.shared::cluster.global.mbarrier::complete_tx::bytes.multicast::cluster [%0], [%1, {%3, %4}], [%2], %5;"
               :: "r"(dst), "l"(m), "r"(bar), "r"(c0), "r"(c1), "h"(mask) : "memory");
}
__device__ __forceinline__ void tma2d_store(const CUtensorMap* m, uint32_t src, int c0, int c1) {
  asm volatile("cp.async.bulk.tensor.2d.global.shared::cta.bulk_group [%0, {%2, %3}], [%1];"
               :: "l"(m), "r"(src), "r"(c0), "r"(c1) : "memory");
}
__device__ __forceinline__ void bulk_g2s(uint32_t dst, const void* src, uint32_t bytes, uint32_t bar) {
  asm volatile("cp.async.bulk.shared::cluster.global.mbarrier::complete_tx::bytes [%0], [%1], %2, [%3];"
               :: "r"(dst), "l"(src), "r"(bytes), "r"(bar) : "memory");
}
__device__ __forceinline__ void bulk_commit() { asm volatile("cp.async.bulk.commit_group;" ::: "memory"); }
__device__ __forceinline__ void bulk_wait_all() { asm volatile("cp.async.bulk.wait_group 0;" ::: "memory"); }
__device__ __forceinline__ void fence_async() { asm volatile("fence.proxy.async.shared::cta;" ::: "memory"); }
__device__ __forceinline__ void named_bar(int id, int n) { asm volatile("bar.sync %0, %1;" :: "r"(id), "r"(n) : "memory"); }
__device__ __forceinline__ void pdl_launch() { asm volatile("griddepcontrol.launch_dependents;" ::: "memory"); }
__device__ __forceinline__ void pdl_wait() { asm volatile("griddepcontrol.wait;" ::: "memory"); }
__device__ __forceinline__ void wg_fence() { asm volatile("wgmma.fence.sync.aligned;" ::: "memory"); }
__device__ __forceinline__ void wg_commit() { asm volatile("wgmma.commit_group.sync.aligned;" ::: "memory"); }
template <int n> __device__ __forceinline__ void wg_wait() { asm volatile("wgmma.wait_group.sync.aligned %0;" :: "n"(n) : "memory"); }
template <int n> __device__ __forceinline__ void fence_regs(float* r) {
#pragma unroll
  for (int i = 0; i < n; i++) asm volatile("" : "+f"(r[i]) :: "memory");
}
template <int n> __device__ __forceinline__ void fence_regs(uint32_t* r) {
#pragma unroll
  for (int i = 0; i < n; i++) asm volatile("" : "+r"(r[i]) :: "memory");
}
__device__ __forceinline__ uint64_t make_desc(uint32_t addr, uint32_t lbo, uint32_t sbo, uint32_t swz) {
  return (uint64_t)((addr & 0x3FFFF) >> 4) | ((uint64_t)(lbo >> 4) << 16) | ((uint64_t)(sbo >> 4) << 32) | ((uint64_t)swz << 62);
}
__device__ __forceinline__ float ex2f(float x) { float y; asm("ex2.approx.ftz.f32 %0, %1;" : "=f"(y) : "f"(x)); return y; }
__device__ __forceinline__ uint32_t pack_bf16(float lo, float hi) { uint32_t r; asm("cvt.rn.bf16x2.f32 %0, %1, %2;" : "=r"(r) : "f"(hi), "f"(lo)); return r; }
__device__ __forceinline__ uint32_t pack_f16(float lo, float hi) { uint32_t r; asm("cvt.rn.f16x2.f32 %0, %1, %2;" : "=r"(r) : "f"(hi), "f"(lo)); return r; }
__device__ __forceinline__ float bf_lo(uint32_t v) { return __uint_as_float(v << 16); }
__device__ __forceinline__ float bf_hi(uint32_t v) { return __uint_as_float(v & 0xFFFF0000u); }
__device__ __forceinline__ float rbf(float x) { return __bfloat162float(__float2bfloat16_rn(x)); }
__device__ __forceinline__ void stsm4(uint32_t a, uint32_t r0, uint32_t r1, uint32_t r2, uint32_t r3) {
  asm volatile("stmatrix.sync.aligned.m8n8.x4.shared.b16 [%0], {%1,%2,%3,%4};" :: "r"(a), "r"(r0), "r"(r1), "r"(r2), "r"(r3) : "memory");
}
__device__ __forceinline__ void stsm4t(uint32_t a, uint32_t r0, uint32_t r1, uint32_t r2, uint32_t r3) {
  asm volatile("stmatrix.sync.aligned.m8n8.x4.trans.shared.b16 [%0], {%1,%2,%3,%4};" :: "r"(a), "r"(r0), "r"(r1), "r"(r2), "r"(r3) : "memory");
}
__device__ __forceinline__ void mma_bf16(float* d, uint32_t a0, uint32_t a1, uint32_t a2, uint32_t a3, uint32_t b0, uint32_t b1) {
  asm volatile("mma.sync.aligned.m16n8k16.row.col.f32.bf16.bf16.f32 {%0,%1,%2,%3}, {%4,%5,%6,%7}, {%8,%9}, {%0,%1,%2,%3};"
               : "+f"(d[0]), "+f"(d[1]), "+f"(d[2]), "+f"(d[3]) : "r"(a0), "r"(a1), "r"(a2), "r"(a3), "r"(b0), "r"(b1));
}
template<int SD> __device__ __forceinline__ void wg_qs24(float* d, uint64_t da, uint64_t db) {
  asm volatile("wgmma.mma_async.sync.aligned.m64n24k16.f32.f16.f16 {%0,%1,%2,%3,%4,%5,%6,%7,%8,%9,%10,%11}, %12, %13, %14, 1, 1, 0, 0;"
   : "+f"(d[0]),"+f"(d[1]),"+f"(d[2]),"+f"(d[3]),"+f"(d[4]),"+f"(d[5]),"+f"(d[6]),"+f"(d[7]),"+f"(d[8]),"+f"(d[9]),"+f"(d[10]),"+f"(d[11])
   : "l"(da),"l"(db),"n"(SD));
}
template<int SD> __device__ __forceinline__ void wg_qs72(float* d, uint64_t da, uint64_t db) {
  asm volatile("wgmma.mma_async.sync.aligned.m64n72k16.f32.f16.f16 {%0,%1,%2,%3,%4,%5,%6,%7,%8,%9,%10,%11,%12,%13,%14,%15,%16,%17,%18,%19,%20,%21,%22,%23,%24,%25,%26,%27,%28,%29,%30,%31,%32,%33,%34,%35}, %36, %37, %38, 1, 1, 0, 0;"
   : "+f"(d[0]),"+f"(d[1]),"+f"(d[2]),"+f"(d[3]),"+f"(d[4]),"+f"(d[5]),"+f"(d[6]),"+f"(d[7]),"+f"(d[8]),"+f"(d[9]),"+f"(d[10]),"+f"(d[11]),"+f"(d[12]),"+f"(d[13]),"+f"(d[14]),"+f"(d[15]),"+f"(d[16]),"+f"(d[17]),"+f"(d[18]),"+f"(d[19]),"+f"(d[20]),"+f"(d[21]),"+f"(d[22]),"+f"(d[23]),"+f"(d[24]),"+f"(d[25]),"+f"(d[26]),"+f"(d[27]),"+f"(d[28]),"+f"(d[29]),"+f"(d[30]),"+f"(d[31]),"+f"(d[32]),"+f"(d[33]),"+f"(d[34]),"+f"(d[35])
   : "l"(da),"l"(db),"n"(SD));
}
template<int SD> __device__ __forceinline__ void wg_pv24(float* d, const uint32_t* a, uint64_t desc) {
  asm volatile("wgmma.mma_async.sync.aligned.m64n24k16.f32.bf16.bf16 {%0,%1,%2,%3,%4,%5,%6,%7,%8,%9,%10,%11}, {%12,%13,%14,%15}, %16, %17, 1, 1, 1;"
   : "+f"(d[0]),"+f"(d[1]),"+f"(d[2]),"+f"(d[3]),"+f"(d[4]),"+f"(d[5]),"+f"(d[6]),"+f"(d[7]),"+f"(d[8]),"+f"(d[9]),"+f"(d[10]),"+f"(d[11])
   : "r"(a[0]),"r"(a[1]),"r"(a[2]),"r"(a[3]),"l"(desc),"n"(SD));
}
template<int TA, int TB> __device__ __forceinline__ void wg_ss128(float* d, uint64_t da, uint64_t db, int sd) {
  asm volatile("{\n.reg .pred p;\nsetp.ne.b32 p, %66, 0;\n"
   "wgmma.mma_async.sync.aligned.m64n128k16.f32.bf16.bf16 {%0,%1,%2,%3,%4,%5,%6,%7,%8,%9,%10,%11,%12,%13,%14,%15,%16,%17,%18,%19,%20,%21,%22,%23,%24,%25,%26,%27,%28,%29,%30,%31,%32,%33,%34,%35,%36,%37,%38,%39,%40,%41,%42,%43,%44,%45,%46,%47,%48,%49,%50,%51,%52,%53,%54,%55,%56,%57,%58,%59,%60,%61,%62,%63}, %64, %65, p, 1, 1, %67, %68;\n}\n"
   : "+f"(d[0]),"+f"(d[1]),"+f"(d[2]),"+f"(d[3]),"+f"(d[4]),"+f"(d[5]),"+f"(d[6]),"+f"(d[7]),"+f"(d[8]),"+f"(d[9]),"+f"(d[10]),"+f"(d[11]),"+f"(d[12]),"+f"(d[13]),"+f"(d[14]),"+f"(d[15]),"+f"(d[16]),"+f"(d[17]),"+f"(d[18]),"+f"(d[19]),"+f"(d[20]),"+f"(d[21]),"+f"(d[22]),"+f"(d[23]),"+f"(d[24]),"+f"(d[25]),"+f"(d[26]),"+f"(d[27]),"+f"(d[28]),"+f"(d[29]),"+f"(d[30]),"+f"(d[31]),"+f"(d[32]),"+f"(d[33]),"+f"(d[34]),"+f"(d[35]),"+f"(d[36]),"+f"(d[37]),"+f"(d[38]),"+f"(d[39]),"+f"(d[40]),"+f"(d[41]),"+f"(d[42]),"+f"(d[43]),"+f"(d[44]),"+f"(d[45]),"+f"(d[46]),"+f"(d[47]),"+f"(d[48]),"+f"(d[49]),"+f"(d[50]),"+f"(d[51]),"+f"(d[52]),"+f"(d[53]),"+f"(d[54]),"+f"(d[55]),"+f"(d[56]),"+f"(d[57]),"+f"(d[58]),"+f"(d[59]),"+f"(d[60]),"+f"(d[61]),"+f"(d[62]),"+f"(d[63])
   : "l"(da),"l"(db),"r"(sd),"n"(TA),"n"(TB));
}
template<int TA, int TB> __device__ __forceinline__ void wg_ss64(float* d, uint64_t da, uint64_t db, int sd) {
  asm volatile("{\n.reg .pred p;\nsetp.ne.b32 p, %34, 0;\n"
   "wgmma.mma_async.sync.aligned.m64n64k16.f32.bf16.bf16 {%0,%1,%2,%3,%4,%5,%6,%7,%8,%9,%10,%11,%12,%13,%14,%15,%16,%17,%18,%19,%20,%21,%22,%23,%24,%25,%26,%27,%28,%29,%30,%31}, %32, %33, p, 1, 1, %35, %36;\n}\n"
   : "+f"(d[0]),"+f"(d[1]),"+f"(d[2]),"+f"(d[3]),"+f"(d[4]),"+f"(d[5]),"+f"(d[6]),"+f"(d[7]),"+f"(d[8]),"+f"(d[9]),"+f"(d[10]),"+f"(d[11]),"+f"(d[12]),"+f"(d[13]),"+f"(d[14]),"+f"(d[15]),"+f"(d[16]),"+f"(d[17]),"+f"(d[18]),"+f"(d[19]),"+f"(d[20]),"+f"(d[21]),"+f"(d[22]),"+f"(d[23]),"+f"(d[24]),"+f"(d[25]),"+f"(d[26]),"+f"(d[27]),"+f"(d[28]),"+f"(d[29]),"+f"(d[30]),"+f"(d[31])
   : "l"(da),"l"(db),"r"(sd),"n"(TA),"n"(TB));
}
template<int TA, int TB> __device__ __forceinline__ void wg_ss8(float* d, uint64_t da, uint64_t db, int sd) {
  asm volatile("{\n.reg .pred p;\nsetp.ne.b32 p, %6, 0;\n"
   "wgmma.mma_async.sync.aligned.m64n8k16.f32.bf16.bf16 {%0,%1,%2,%3}, %4, %5, p, 1, 1, %7, %8;\n}\n"
   : "+f"(d[0]),"+f"(d[1]),"+f"(d[2]),"+f"(d[3])
   : "l"(da),"l"(db),"r"(sd),"n"(TA),"n"(TB));
}

__device__ __forceinline__ uint32_t phi2(float a, float b) {
  uint32_t r, e;
  asm("cvt.rn.relu.bf16x2.f32 %0, %1, %2;" : "=r"(r) : "f"(b), "f"(a));
  e = pack_bf16(ex2f(a * 1.4426950408889634f), ex2f(b * 1.4426950408889634f));
  asm("add.rn.bf16x2 %0, %0, %1;" : "+r"(e) : "r"(0x35863586u));
  asm("min.NaN.bf16x2 %0, %0, %1;" : "+r"(e) : "r"(0x3F803F80u));
  asm("add.rn.bf16x2 %0, %0, %1;" : "+r"(e) : "r"(r));
  return e;
}

__device__ __forceinline__ void mbar_wait_long(uint32_t bar, uint32_t parity) {
  asm volatile("{\n.reg .pred p;\n.reg .u32 c;\nmov.u32 c, 0;\n"
               "LW_%=:\n"
               "mbarrier.try_wait.parity.shared::cta.b64 p, [%0], %1, 100000;\n"
               "@p bra LD_%=;\n"
               "add.u32 c, c, 1;\n"
               "setp.lt.u32 p, c, 20000;\n"
               "@p bra LW_%=;\n"
               "trap;\n"
               "LD_%=:\n}\n" :: "r"(bar), "r"(parity) : "memory");
}
__device__ __forceinline__ void mbar_arrive(uint32_t bar) { asm volatile("mbarrier.arrive.shared::cta.b64 _, [%0];" :: "r"(bar) : "memory"); }
__device__ __forceinline__ void named_arrive(int id, int n) { asm volatile("bar.arrive %0, %1;" :: "r"(id), "r"(n) : "memory"); }
__device__ __forceinline__ void fence_async_all() { asm volatile("fence.proxy.async.global;" ::: "memory"); }
__device__ __forceinline__ void flag_add(uint32_t* f) { asm volatile("fence.acq_rel.gpu;\nred.relaxed.gpu.global.add.u32 [%0], 1;" :: "l"(f) : "memory"); }
#define PUBLISH(f) asm volatile("fence.proxy.async.global;\nred.relaxed.gpu.global.add.u32 [%0], 1;" :: "l"(f) : "memory")
__device__ __forceinline__ void flag_wait(const uint32_t* f, uint32_t target) {
  uint32_t v;
#pragma unroll 1
  for (int it = 0;; it++) {
    asm volatile("ld.acquire.gpu.global.u32 %0, [%1];" : "=r"(v) : "l"(f) : "memory");
    if ((int32_t)(v - target) >= 0) break;
    if (it > 2000000) __trap();
    __nanosleep(64);
  }
}
__device__ __forceinline__ bool mbar_test(uint32_t bar, uint32_t parity) {
  uint32_t ok;
  asm volatile("{\n.reg .pred p;\nmbarrier.test_wait.parity.shared::cta.b64 p, [%1], %2;\nselp.b32 %0, 1, 0, p;\n}\n" : "=r"(ok) : "r"(bar), "r"(parity) : "memory");
  return ok;
}
__device__ __forceinline__ bool elect_one() {
  uint32_t p;
  asm volatile("{\n.reg .pred P;\nelect.sync _|P, 0xFFFFFFFF;\nselp.b32 %0, 1, 0, P;\n}\n" : "=r"(p));
  return p;
}
__device__ __forceinline__ void lds4(uint32_t a, uint32_t* r) {
  asm volatile("ld.shared.v4.b32 {%0,%1,%2,%3}, [%4];" : "=r"(r[0]), "=r"(r[1]), "=r"(r[2]), "=r"(r[3]) : "r"(a) : "memory");
}
__device__ __forceinline__ uint32_t lds1(uint32_t a) { uint32_t r; asm volatile("ld.shared.b32 %0, [%1];" : "=r"(r) : "r"(a) : "memory"); return r; }
__device__ __forceinline__ void sts1(uint32_t a, uint32_t v) { asm volatile("st.shared.b32 [%0], %1;" :: "r"(a), "r"(v) : "memory"); }
__device__ __forceinline__ void sts4(uint32_t a, uint32_t r0, uint32_t r1, uint32_t r2, uint32_t r3) {
  asm volatile("st.shared.v4.b32 [%0], {%1,%2,%3,%4};" :: "r"(a), "r"(r0), "r"(r1), "r"(r2), "r"(r3) : "memory");
}
__device__ __forceinline__ void ldsm4(uint32_t a, uint32_t* r) {
  asm volatile("ldmatrix.sync.aligned.m8n8.x4.shared.b16 {%0,%1,%2,%3}, [%4];" : "=r"(r[0]), "=r"(r[1]), "=r"(r[2]), "=r"(r[3]) : "r"(a) : "memory");
}
__device__ __forceinline__ float rcpf(float x) { float y; asm("rcp.approx.ftz.f32 %0, %1;" : "=f"(y) : "f"(x)); return y; }
__device__ __forceinline__ uint32_t hfma2(uint32_t a, uint32_t b, uint32_t c) { uint32_t r; asm("fma.rn.f16x2 %0, %1, %2, %3;" : "=r"(r) : "r"(a), "r"(b), "r"(c)); return r; }
__device__ __forceinline__ uint32_t hadd2(uint32_t a, uint32_t b) { uint32_t r; asm("add.rn.f16x2 %0, %1, %2;" : "=r"(r) : "r"(a), "r"(b)); return r; }

#define STEPK 96
#define GIMAP(i) ((((i) & 1) << 2) | (((i) >> 1) & 3) | ((i) & 8))
#define QSCALE 0.36067376022224085f
#define SMAGIC (512.0f + 2.0f * (191.0f - 30.0f - 1.5823545f))
#define VSHIFT 1073741824.0f

__device__ uint32_t g_epoch[132];
__device__ uint32_t g_flag[288 * 8];
#define FLAG_KV (g_flag)
#define FLAG_B(h) (g_flag + (4 + (h)) * 8)
#define FLAG_OA(cta, pass) (g_flag + (16 + (cta) * 2 + (pass)) * 8)
#define FLAG_LM(i) (g_flag + (272 + (i)) * 8)

#define SM_TOTAL (224 * 1024 + 2048 + 1024)
#define OFF_K 0
#define OFF_F 65536
#define OFF_V 131072
#define OFF_MISC (224 * 1024)

#define BAR_FULL(s) (bars + 8 * (s))
#define BAR_EMPTY(s) (bars + 24 + 8 * (s))
#define BAR_KV(c) (bars + 48 + 8 * (c))
#define BAR_BDONE (bars + 80)
#define BAR_Q (bars + 88)
#define BAR_GO (bars + 96)
#define BAR_Q2 (bars + 104)
#define BAR_OD(p) (bars + 112 + 8 * (p))
#define BAR_CL(c) (bars + 128 + 8 * (c))
#define BAR_TE(i) (bars + 168 + 8 * (i))
#define BAR_RL (bars + 184)
#define BAR_TF(g) (bars + 224 + 8 * (g))
#define BAR_XA(w) (bars + 352 + 8 * (w))
#define BAR_VB(c) (bars + 384 + 8 * (c))

__device__ __forceinline__ uint32_t exp2_pair_fix(float d0, float d1, uint32_t c63, uint32_t m1) {
  uint32_t w, y, s, r;
  asm("prmt.b32 %0, %1, %2, 0x6521;" : "=r"(w) : "r"(__float_as_uint(d0)), "r"(__float_as_uint(d1)));
  asm("lop3.b32 %0, %1, 0x007F007F, %2, 0xEA;" : "=r"(y) : "r"(w), "r"(c63));
  asm("mad.lo.u32 %0, %1, %2, %3;" : "=r"(s) : "r"(y), "r"(m1), "r"(w));
  asm("fma.rn.bf16x2 %0, %1, %2, %3;" : "=r"(r) : "r"(w), "r"(y), "r"(s));
  return r;
}

__device__ __forceinline__ void attn_slow(const __nv_bfloat16* xa, const __nv_bfloat16* wq, uint32_t dst) {
  const int t = threadIdx.x & 127;
  const int row = t >> 1, half = t & 1;
  float q[16];
  {
    float a[8];
#pragma unroll
    for (int i = 0; i < 8; i++) a[i] = 0.f;
#pragma unroll 1
    for (int k = 0; k < D_MOD; k++) {
      const float x = __bfloat162float(xa[(size_t)row * D_MOD + k]);
      const uint4 w = *(const uint4*)(wq + (size_t)k * D_MOD + half * 8);
      const uint32_t ww[4] = {w.x, w.y, w.z, w.w};
#pragma unroll
      for (int i = 0; i < 4; i++) { a[2 * i] = fmaf(x, bf_lo(ww[i]), a[2 * i]); a[2 * i + 1] = fmaf(x, bf_hi(ww[i]), a[2 * i + 1]); }
    }
#pragma unroll
    for (int i = 0; i < 8; i++) {
      const float mine = rbf(a[i]), other = __shfl_xor_sync(~0u, mine, 1);
      q[i] = half ? other : mine; q[8 + i] = half ? mine : other;
    }
  }
  float m = -INFINITY, l = 0.f, o[16];
#pragma unroll
  for (int i = 0; i < 16; i++) o[i] = 0.f;
#pragma unroll 1
  for (int j = half * 1024; j < half * 1024 + 1024; j++) {
    uint4 ka = g_KV[4 * S_TOK + j], kb = g_KV[5 * S_TOK + j];
    uint4 va = g_KV[6 * S_TOK + j], vb = g_KV[7 * S_TOK + j];
    uint32_t kk[8] = {ka.x, ka.y, ka.z, ka.w, kb.x, kb.y, kb.z, kb.w};
    uint32_t vv[8] = {va.x, va.y, va.z, va.w, vb.x, vb.y, vb.z, vb.w};
    float s = 0.f;
#pragma unroll
    for (int i = 0; i < 8; i++) { s = fmaf(q[2 * i], bf_lo(kk[i]), s); s = fmaf(q[2 * i + 1], bf_hi(kk[i]), s); }
    s = rbf(s) * 0.25f;
    if (s > m) {
      float c = __expf(m - s);
      l *= c;
#pragma unroll
      for (int i = 0; i < 16; i++) o[i] *= c;
      m = s;
    }
    float p = __expf(s - m);
    l += p;
#pragma unroll
    for (int i = 0; i < 8; i++) { o[2 * i] = fmaf(p, bf_lo(vv[i]), o[2 * i]); o[2 * i + 1] = fmaf(p, bf_hi(vv[i]), o[2 * i + 1]); }
  }
  float m2 = __shfl_xor_sync(~0u, m, 1);
  float mm = fmaxf(m, m2);
  float c = __expf(m - mm);
  l *= c; l += __shfl_xor_sync(~0u, l, 1);
  float inv = 1.f / l;
  uint32_t r[8];
#pragma unroll
  for (int i = 0; i < 16; i++) { o[i] *= c; o[i] += __shfl_xor_sync(~0u, o[i], 1); o[i] *= inv; }
#pragma unroll
  for (int i = 0; i < 8; i++) r[i] = pack_bf16(o[2 * i], o[2 * i + 1]);
  if (half == 0) sts4(dst, r[0], r[1], r[2], r[3]); else sts4(dst, r[4], r[5], r[6], r[7]);
  fence_async();
}

struct Params { const __nv_bfloat16* wk; const __nv_bfloat16* wv; const __nv_bfloat16* xa; const __nv_bfloat16* wq; __nv_bfloat16* out; const __nv_bfloat16* xb; const __nv_bfloat16* wqkv; };
__device__ __forceinline__ void l2pf(const void* p, uint32_t n) { asm volatile("cp.async.bulk.prefetch.L2.global [%0], %1;" :: "l"(p), "r"(n) : "memory"); }
__device__ __forceinline__ void cp16(uint32_t dst, const void* src) { asm volatile("cp.async.cg.shared.global [%0], [%1], 16;" :: "r"(dst), "l"(src) : "memory"); }

__device__ __forceinline__ void helper_cta(const int h, const uint32_t sb, const uint32_t bars, const int wg, const int w4,
                                           const CUtensorMap* mQ, const CUtensorMap* mOs) {
  const int lane = threadIdx.x & 31;
  mbar_wait(BAR_GO, 0);
  const int cb = wg & 1, col = h * 128 + cb * 64, row0 = S_TOK + (wg >> 1) * 1024;
  const uint32_t buf = sb + wg * 49152;
  if (w4 == 0 && elect_one()) {
    fence_async_all();
#pragma unroll 1
    for (int u = 0; u < 3; u++) {
      mbar_expect_tx(BAR_TF(wg * 3 + u), 16384);
      tma2d(buf + u * 16384, mQ, col, row0 + u * 128, BAR_TF(wg * 3 + u));
    }
  }
  const int head = h * 8 + cb * 4 + w4;
  float4 a0 = make_float4(0, 0, 0, 0), a1 = a0, a2 = a0;
#pragma unroll 8
  for (int tt = 0; tt < 16; tt++) {
    const float4* src = g_kvp + ((tt * 32 + head) * 3) * 32 + lane;
    float4 u = src[0], v = src[32], w = src[64];
    a0.x += u.x; a0.y += u.y; a0.z += u.z; a0.w += u.w;
    a1.x += v.x; a1.y += v.y; a1.z += v.z; a1.w += v.w;
    a2.x += w.x; a2.y += w.y; a2.z += w.z; a2.w += w.w;
  }
  const uint32_t b00 = pack_bf16(a0.x, a0.y), b01 = pack_bf16(a0.z, a0.w);
  const uint32_t b10 = pack_bf16(a1.x, a1.y), b11 = pack_bf16(a1.z, a1.w);
  const uint32_t bz0 = pack_bf16(a2.x, a2.y), bz1 = pack_bf16(a2.z, a2.w);
  const int m = lane >> 3, r = lane & 7;
  const uint32_t off = ((m & 1) * 8 + r) * 128 + (((w4 * 2 + (m >> 1)) ^ r) << 4);
  int s = 0, ph = 0;
#pragma unroll 1
  for (int u = 0; u < 8; u++) {
    const uint32_t bb = buf + s * 16384;
    mbar_wait(BAR_TF(wg * 3 + s), ph);
#pragma unroll
    for (int mt = 0; mt < 8; mt++) {
      uint32_t a[4];
      ldsm4(bb + mt * 2048 + off, a);
      float n0[4] = {0, 0, 0, 0}, n1[4] = {0, 0, 0, 0}, dn[4] = {0, 0, 0, 0};
      mma_bf16(dn, a[0], a[1], a[2], a[3], bz0, bz1);
      mma_bf16(n0, a[0], a[1], a[2], a[3], b00, b01);
      mma_bf16(n1, a[0], a[1], a[2], a[3], b10, b11);
      const float i0 = rcpf(dn[0] + 1e-6f), i1 = rcpf(dn[2] + 1e-6f);
      stsm4(bb + mt * 2048 + off, pack_bf16(n0[0] * i0, n0[1] * i0), pack_bf16(n0[2] * i1, n0[3] * i1),
            pack_bf16(n1[0] * i0, n1[1] * i0), pack_bf16(n1[2] * i1, n1[3] * i1));
    }
    fence_async();
    named_bar(wg + 1, 128);
    if (w4 == 0 && lane == 0) {
      tma2d_store(mOs, bb, col, row0 + u * 128);
      bulk_commit();
      if (u >= 1 && u + 2 < 8) {
        asm volatile("cp.async.bulk.wait_group.read 1;" ::: "memory");
        const int sp = s == 0 ? 2 : s - 1;
        mbar_expect_tx(BAR_TF(wg * 3 + sp), 16384);
        tma2d(buf + sp * 16384, mQ, col, row0 + (u + 2) * 128, BAR_TF(wg * 3 + sp));
      }
    }
    __syncwarp();
    if (++s == 3) { s = 0; ph ^= 1; }
  }
  if (w4 == 0 && lane == 0) {
    bulk_wait_all();
    fence_async_all();
    flag_add(FLAG_LM((h * 2 + cb) * 2 + (wg >> 1)));
    if (wg == 0) TS(1, 8);
  }
}

#define STAGE(s) (sb + (2 - (s)) * 65536)
__device__ __forceinline__ uint32_t xa_addr(uint32_t sb, int kb) {
  return sb + (kb >= 1 && kb <= 4 ? OFF_V + 65536 + (kb - 1) * 8192 : 16384 + (kb == 5 ? OFF_K : (kb == 6 ? OFF_V : OFF_F)));
}
#define XA7_TMP (sb + OFF_K + 40960)
#define WKV_TMP (sb + OFF_K + 32768)
template <int TR> __device__ __forceinline__ void proj_kb(float* acc, uint32_t aA, uint32_t aB, int first) {
  const uint64_t da = make_desc(aA, TR ? 8192 : 16, 1024, 1);
  const uint64_t db = make_desc(aB, TR ? 16 : 8192, 1024, 1);
  wg_fence();
#pragma unroll
  for (int k = 0; k < 4; k++) wg_ss128<TR, 1 - TR>(acc, da + k * (TR ? 128 : 2), db + k * (TR ? 2 : 128), k != 0 || !first);
  wg_commit();
}
template <int TR> __device__ __forceinline__ void proj_loop(float* acc, uint32_t sb, uint32_t bars, uint32_t offA, uint32_t offB,
                                                            int wg, uint32_t sWKV, const CUtensorMap* mW, int col, bool w0) {
  {
    float kv[4];
    if (threadIdx.x == 0) TS(0, 13);
    mbar_wait(BAR_XA(wg), 0);
    if (threadIdx.x == 0) TS(0, 1);
    const uint64_t da0 = make_desc(xa_addr(sb, 2 * wg), 16, 1024, 1);
    const uint64_t da1 = make_desc(wg == 3 ? XA7_TMP : xa_addr(sb, 2 * wg + 1), 16, 1024, 1);
    const uint64_t db = make_desc(sWKV + wg * 2048, 128, 128, 0);
    wg_fence();
#pragma unroll
    for (int k = 0; k < 8; k++) wg_ss8<0, 1>(kv, (k < 4 ? da0 : da1) + (k & 3) * 2, db + k * 16, k != 0);
    wg_commit();
    wg_wait<0>();
    fence_regs<4>(kv);
    named_bar(wg + 1, 128);
    sts4(sWKV + threadIdx.x * 16, __float_as_uint(kv[0]), __float_as_uint(kv[1]), __float_as_uint(kv[2]), __float_as_uint(kv[3]));
    __syncwarp();
    if ((threadIdx.x & 31) == 0) mbar_arrive(BAR_GO);
  }
  int s = 0, ph = 0;
#pragma unroll 1
  for (int kb = 0; kb < 8; kb++) {
    mbar_wait(BAR_FULL(s), ph);
    if (threadIdx.x == 0) TS(0, 2 + kb);
    if (TR == 0) mbar_wait(BAR_XA(kb >> 1), 0);
    proj_kb<TR>(acc, TR ? STAGE(s) + offA : xa_addr(sb, kb), STAGE(s) + offB, kb == 0);
    wg_wait<0>();
    if (w0 && elect_one()) {
      if (kb < 5) {
        mbar_expect_tx(BAR_FULL(s), TR ? 8192 : 16384);
        tma2d(STAGE(s) + (TR ? offA : 0), mW, col, (kb + 3) * 64, BAR_FULL(s));
        if (TR == 0) tma2d(STAGE(s) + 8192, mW, col + 64, (kb + 3) * 64, BAR_FULL(s));
      }
      if (kb < 7) mbar_arrive(BAR_EMPTY(s));
      if (TR == 0 && kb == 4) mbar_arrive(BAR_VB(1));
    }
    __syncwarp();
    if (++s == 3) { s = 0; ph ^= 1; }
  }
  wg_wait<0>();
  fence_regs<64>(acc);
}

__device__ __forceinline__ uint32_t tail_slots(int isB, int n) {
  if (n < 4) return n < 2 ? (n == 0 ? 0x0D0C0B0Au : 0x04000F0Eu) : (n == 2 ? 0x18141008u : 0x15110501u);
  if (isB) return n < 6 ? (n == 4 ? 0x19120602u : 0x0D0C0B0Au) : (n == 6 ? 0x04000F0Eu : 0x13070316u);
  return n < 6 ? (n == 4 ? 0x1902031Au : 0x12061307u) : (n == 6 ? 0x16091B17u : 0x0D0C0B0Au);
}

__device__ __forceinline__ void take_role(uint32_t sM, int wg) {
  uint32_t r;
  asm volatile("atom.shared.add.u32 %0, [%1], 1;" : "=r"(r) : "r"(sM + 20) : "memory");
  sts1(sM + 32 + wg * 4, r);
}

__global__ void __launch_bounds__(640, 1)
k1_main(const __grid_constant__ CUtensorMap mXA64, const __grid_constant__ CUtensorMap mXB,
        const __grid_constant__ CUtensorMap mWq, const __grid_constant__ CUtensorMap mWqkv,
        const __grid_constant__ CUtensorMap mQst, const __grid_constant__ CUtensorMap mOst,
        const __grid_constant__ CUtensorMap mO, const __grid_constant__ CUtensorMap mWoA,
        const __grid_constant__ CUtensorMap mWoB,
        const __grid_constant__ CUtensorMap mO16, const Params prm) {
  extern __shared__ uint8_t smem_raw[];
  const uint32_t sb = (smem_u32(smem_raw) + 1023u) & ~1023u;
  const uint32_t bars = sb + OFF_MISC, sM = bars + 512, sT = bars + 1024;
  const int tid = threadIdx.x, warp = __shfl_sync(~0u, tid >> 5, 0), wg = warp >> 2, w4 = warp & 3, lane = tid & 31;
  const bool helper = blockIdx.x >= 128;
  if (tid == 0) TS(0, 0);
  const int G = blockIdx.x >> 4, gi = GIMAP(blockIdx.x & 15);
  const int tbA = G * 4 + (gi >> 2), hg = gi & 3;
  const int ttB = (G >> 1) * 4 + (gi >> 2), hq = (G & 1) * 4 + (gi & 3);
  const int isB = tbA & 1, tok0 = (tbA >> 1) * 128;
  auto issue = [&](int kb, int s, int part) {
    const uint32_t fb = BAR_FULL(s), st = STAGE(s);
    if (part & 1) {
      mbar_expect_tx(fb, 57344);
      asm volatile("mbarrier.arrive.shared::cta.b64 _, [%0], 4;" :: "r"(fb) : "memory");
      tma2d(st, &mWq, hg * 128, kb * 64, fb);
      tma2d(st + 8192, &mWq, hg * 128 + 64, kb * 64, fb);
      tma2d(st + 49152, &mXB, kb * 64, ttB * 128, fb);
      tma2d(st + 24576, &mWqkv, hq * 64, kb * 64, fb);
    }
    if (part & 2) {
      tma2d(st + 32768, &mWqkv, 512 + hq * 64, kb * 64, fb);
      tma2d(st + 40960, &mWqkv, 1024 + hq * 64, kb * 64, fb);
    }
  };
  const uint32_t sOne = sb + OFF_V + 65536, sWKV = WKV_TMP;
  if (warp >= 16) {
    if (warp == 17) {
      if (elect_one()) {
        mbar_init(BAR_BDONE, 8); mbar_init(BAR_Q, 6); mbar_init(BAR_GO, helper ? 1 : 16); mbar_init(BAR_Q2, 1);
        mbar_init(BAR_OD(0), 16); mbar_init(BAR_OD(1), 16); mbar_init(BAR_CL(0), 1); mbar_init(BAR_FULL(2), 5);
#pragma unroll
        for (int i = 0; i < 4; i++) mbar_init(BAR_CL(i + 1), i == 0 ? 5 : 4);
#pragma unroll
        for (int i = 0; i < 3; i++) { mbar_init(BAR_EMPTY(i), 4); mbar_init(BAR_KV(i), 1); mbar_init(BAR_VB(i), i == 2 ? 4 : 1); }
        sts1(sM + 20, 0);
        asm volatile("fence.mbarrier_init.release.cluster;" ::: "memory");
      }
    } else if (warp == 18) {
      if (elect_one()) {
#pragma unroll
        for (int i = 0; i < 2; i++) mbar_init(BAR_TE(i), 2);
        mbar_init(BAR_RL, 1);
#pragma unroll
        for (int i = 0; i < 16; i++) mbar_init(BAR_TF(i), 1);
        asm volatile("fence.mbarrier_init.release.cluster;" ::: "memory");
      }
    } else if (warp == 16 && !helper && elect_one()) {
#pragma unroll
      for (int w = 0; w < 4; w++) mbar_init(BAR_XA(w), 1);
      mbar_init(BAR_FULL(0), 5); mbar_init(BAR_FULL(1), 5);
      asm volatile("fence.mbarrier_init.release.cluster;" ::: "memory");
#pragma unroll
      for (int w = 0; w < 4; w++) {
        mbar_expect_tx(BAR_XA(w), 16384);
        tma2d(xa_addr(sb, 2 * w), &mXA64, w * 128, tbA * 64, BAR_XA(w));
        tma2d(w == 3 ? XA7_TMP : xa_addr(sb, 2 * w + 1), &mXA64, w * 128 + 64, tbA * 64, BAR_XA(w));
      }
      TS(0, 14);
      issue(0, 0, 3);
    }
  } else if (!helper) {
    const uint4 v = __ldg((const uint4*)(hg >= 2 ? prm.wv : prm.wk) + tid * 2 + (hg & 1));
    sts4(sWKV + tid * 16, v.x, v.y, v.z, v.w);
    fence_async();
  }
  __syncthreads();
  if (wg == 4) {
    if (w4 == 0 && !helper && elect_one()) { issue(1, 1, 3); issue(2, 2, 1); TS(0, 15); }
    if (w4 == 3) { if (!helper && elect_one()) {
      l2pf(prm.wqkv + (size_t)blockIdx.x * 6144, 12288);
      l2pf(prm.wq + (size_t)blockIdx.x * 2048, 4096);
      l2pf(prm.xb + (size_t)blockIdx.x * 8192, 16384);
    } }
    asm volatile("setmaxnreg.dec.sync.aligned.u32 32;");
    const uint32_t ep = g_epoch[blockIdx.x] + 1;
    if (helper) {
      if (w4 == 0 && elect_one()) {
        flag_wait(FLAG_B(blockIdx.x - 128), ep * 32);
        fence_async_all();
        TS(1, 10);
        mbar_arrive(BAR_GO);
        g_epoch[blockIdx.x] = ep;
      }
      return;
    }
    mbar_wait(BAR_GO, 0);
    {
      uint32_t a[4], b[4];
      float c[4];
      lds4(sWKV + (tid - 512) * 16, a);
      lds4(sWKV + 2048 + (tid - 512) * 16, b);
#pragma unroll
      for (int i = 0; i < 4; i++) c[i] = __uint_as_float(a[i]) + __uint_as_float(b[i]);
      lds4(sWKV + 4096 + (tid - 512) * 16, a);
      lds4(sWKV + 6144 + (tid - 512) * 16, b);
#pragma unroll
      for (int i = 0; i < 4; i++) c[i] += __uint_as_float(a[i]) + __uint_as_float(b[i]);
      sts1(sT + w4 * 256 + lane * 4, pack_bf16(c[0], c[1]));
      sts1(sT + w4 * 256 + 128 + lane * 4, pack_bf16(c[2], c[3]));
    }
    named_bar(9, 128);
    if (w4 == 0 && elect_one()) issue(2, 2, 2);
    auto write_ones = [&]() {
      mbar_wait_long(BAR_VB(1), 0);
      int c = ((w4 & 1) * 32 + lane);
#pragma unroll 4
      for (int key = c; key < S_TOK; key += 64) {
        sts4(sOne + key * 16, c < 24 ? 0x00003F80u : 0x00004E80u, 0u, 0u, 0u);
        c += 64; if (c >= STEPK) c -= STEPK;
      }
      fence_async();
      __syncwarp();
      if (lane == 0) mbar_arrive(BAR_Q);
    };
    if (w4 == 0) {
      int s = 0, ph = 0;
#pragma unroll 1
      for (int kb = 3; kb < 8; kb++) {
        mbar_wait(BAR_EMPTY(s), ph);
        if (elect_one()) {
          mbar_expect_tx(BAR_FULL(s), kb == 7 ? 24576 : 16384);
          tma2d(STAGE(s) + 49152, &mXB, kb * 64, ttB * 128, BAR_FULL(s));
          if (kb == 7) tma2d(STAGE(s) + 16384, &mXA64, kb * 64, tbA * 64, BAR_FULL(s));
        }
        if (++s == 3) { s = 0; ph ^= 1; }
      }
      flag_wait(FLAG_KV, ep * 128);
      fence_async_all();
      if (lane == 0) TS(0, 11);
#pragma unroll 1
      for (int m = 0; m < 2; m++) {
        mbar_wait(m == 0 ? BAR_EMPTY(2) : BAR_EMPTY(0), 1 - m);
        if (elect_one()) {
          const uint32_t fb = m == 0 ? BAR_KV(0) : BAR_VB(0);
          mbar_expect_tx(fb, 2 * 7 * STEPK * 16);
#pragma unroll
          for (int p = 0; p < 2; p++) bulk_g2s(sb + m * OFF_V + p * 32768, g_KV + (m * 2 + p) * S_TOK, 7 * STEPK * 16, fb);
        }
      }
      mbar_wait(BAR_Q, 0);
      if (elect_one()) {
#pragma unroll
        for (int c = 1; c < 3; c++) {
          const int k0 = c == 1 ? 7 * STEPK : 12 * STEPK, k1 = c == 1 ? 12 * STEPK : S_TOK;
          const uint32_t bytes = (k1 - k0) * 16;
          mbar_expect_tx(BAR_KV(c), 4 * bytes);
#pragma unroll
          for (int p = 0; p < 4; p++)
            bulk_g2s(sb + (p >> 1) * OFF_V + (p & 1) * 32768 + k0 * 16, g_KV + p * S_TOK + k0, bytes, BAR_KV(c));
        }
      }
      mbar_wait_long(BAR_CL(1), 0);
      flag_wait(isB ? FLAG_LM((lane & 7) * 2 + (tbA >> 4)) : FLAG_OA(tbA * 4 + (lane & 7), 0), ep);
      __syncwarp();
      fence_async_all();
      if (lane == 0) TS(2, 13);
      const CUtensorMap* mW = isB ? &mWoB : &mWoA;
#pragma unroll 1
      for (int it = 0; it < 8; it++) {
        const int n = (!isB && it >= 6) ? 13 - it : it;
        uint32_t wb = BAR_CL(n < 3 ? 0 : (n == 3 ? 2 : 3));
        if (isB) { if (n >= 5) wb = n == 7 ? BAR_CL(4) : BAR_TE(n - 5); }
        else if (n >= 6) wb = n == 6 ? BAR_CL(4) : BAR_TE(0);
        if (it < 6) mbar_wait_long(wb, 0); else mbar_wait(wb, 0);
        const uint32_t sl = tail_slots(isB, n), fb = BAR_TF(n);
        const bool withX = isB || n < 4;
        const int k0 = isB ? n * 64 : (n < 4 ? n * 128 : ((hg + n) & 3) * 128 + 64);
        if (elect_one()) {
          mbar_expect_tx(fb, withX ? 32768 : 16384);
          if (withX) {
            tma2d(sb + (sl & 255) * 8192, &mO, k0, isB * S_TOK + tok0, fb);
            tma2d(sb + ((sl >> 8) & 255) * 8192, &mO, k0, isB * S_TOK + tok0 + 64, fb);
          }
          tma2d(sb + ((sl >> 16) & 255) * 8192, mW, hg * 128, k0, fb);
          tma2d(sb + (sl >> 24) * 8192, mW, hg * 128 + 64, k0, fb);
        }
      }
      if (lane == 0) g_epoch[blockIdx.x] = ep;
    } else if (w4 == 3) {
      write_ones();
      flag_wait(FLAG_KV, ep * 128);
      const uint4 a = *(const uint4*)(g_stats + lane * 4);
      const float kmax2 = __uint_as_float(__reduce_max_sync(~0u, a.x)) + __uint_as_float(__reduce_max_sync(~0u, a.y));
      const float vmax = __uint_as_float(__reduce_max_sync(~0u, max(a.z, a.w)));
      const float lv = vmax > 0.f ? __log2f(vmax) : 0.f;
      const float lim = fminf(90.f, fminf(91.f + lv, 95.f - lv));
      float thr = -1.f;
      if (vmax < 1e27f && kmax2 <= 65536.f && lim > 2.f) thr = fminf(60000.f, (lim * lim - 1.f) / (kmax2 * 1.02f + 1e-30f));
      mbar_wait_long(BAR_VB(2), 0);
      uint32_t nmax = 0;
#pragma unroll 2
      for (int i = 0; i < 16; i++) {
        uint32_t x[4], y[4];
        const uint32_t ad = sb + OFF_F + i * 1024 + (lane >> 3) * 256 + (lane & 7) * 16;
        lds4(ad, x); lds4(ad + 128, y);
        uint32_t n = hfma2(x[0], x[0], hfma2(x[1], x[1], hfma2(x[2], x[2], hfma2(x[3], x[3], 0u))));
        n = hfma2(y[0], y[0], hfma2(y[1], y[1], hfma2(y[2], y[2], hfma2(y[3], y[3], n))));
        n = hadd2(n, n >> 16);
        nmax = max(nmax, n & 0x7FFFu);
      }
      nmax = __reduce_max_sync(~0u, nmax);
      const bool ok = __half2float(__ushort_as_half((unsigned short)nmax)) <= thr;
      if (lane == 0) { sts1(sM + 16, ok ? 1u : 0u); mbar_arrive(BAR_Q2); }
    } else {
      const int tok = (w4 - 1) * 32 + lane;
      int step, col;
      if ((tbA & 3) == 0) {
        const int b8 = tbA >> 2;
        if (tok < 22) { step = tok; col = 24 + b8; }
        else { const int c = tok >= 43; step = tok - 22 - 21 * c; col = 32 + b8 * 2 + c; }
      } else {
        const int b24 = (tbA >> 2) * 3 + (tbA & 3) - 1;
        if (tok < 42) { const int c = tok >= 21; step = tok - 21 * c; col = 48 + b24 * 2 + c; }
        else { step = tok - 42; col = b24; }
      }
      const int kap = step * STEPK + col;
      const bool chained = col >= 24;
      uint32_t v[4], o[4];
      lds4(sT + tok * 16, v);
      g_KV[(4 + hg) * S_TOK + kap] = make_uint4(v[0], v[1], v[2], v[3]);
      float st = 0.f;
      if (hg < 2) {
        o[0] = o[1] = o[2] = o[3] = 0;
        if (chained && step > 0) lds4(sT + tok * 16 - 16, o);
        const float sc = chained ? 2.f : 1.f;
#pragma unroll
        for (int u = 0; u < 4; u++) {
          const float x = bf_lo(v[u]), y = bf_hi(v[u]);
          st += x * x + y * y;
          o[u] = pack_f16((x - bf_lo(o[u])) * sc, (y - bf_hi(o[u])) * sc);
        }
      } else {
        const float sc = chained ? VSHIFT : 1.f;
#pragma unroll
        for (int u = 0; u < 4; u++) { float x = bf_lo(v[u]), y = bf_hi(v[u]); st += fabsf(x) + fabsf(y); o[u] = pack_bf16(x * sc, y * sc); }
      }
      g_KV[hg * S_TOK + kap] = make_uint4(o[0], o[1], o[2], o[3]);
      const uint32_t um = __reduce_max_sync(~0u, __float_as_uint(st) & 0x7FFFFFFFu);
      if (w4 == 2) {
        if (lane == 0) sts1(sM + 24, um);
        named_arrive(10, 64);
        write_ones();
        if (!isB) {
          mbar_wait_long(BAR_CL(3), 0);
          mbar_wait_long(BAR_RL, 0);
          uint32_t pend = 0xFE;
          const int li = lane & 7;
          const uint32_t* fl = FLAG_OA((tbA + (li & 1)) * 4 + ((hg + (li >> 1)) & 3), 1);
#pragma unroll 1
          for (int it = 0; pend; it++) {
            uint32_t fv;
            asm volatile("ld.acquire.gpu.global.u32 %0, [%1];" : "=r"(fv) : "l"(fl) : "memory");
            uint32_t go = __ballot_sync(~0u, (int32_t)(fv - ep) >= 0 && mbar_test(li >= 6 ? BAR_TE(0) : BAR_CL(4), 0)) & pend;
            pend &= ~go;
            if (go) fence_async_all();
#pragma unroll 1
            while (go) {
              const int b = __ffs(go) - 1;
              go &= go - 1;
              const uint32_t slot = (tail_slots(0, 4 + (b >> 1)) >> (8 * (b & 1))) & 255;
              if (elect_one()) {
                mbar_expect_tx(BAR_TF(8 + b), 8192);
                tma2d(sb + slot * 8192, &mO, ((hg + (b >> 1)) & 3) * 128 + 64, tok0 + (b & 1) * 64, BAR_TF(8 + b));
              }
            }
            if (it > 2000000) __trap();
          }
          if (lane == 0) TS(2, 14);
        }
      }
      else {
        named_bar(10, 64);
        if (elect_one()) {
          g_stats[tbA * 4 + hg] = max(um, lds1(sM + 24));
          fence_async_all();
          flag_add(FLAG_KV);
          TS(1, 9);
          mbar_wait_long(BAR_BDONE, 0);
          tma2d_store(&mQst, sb + OFF_F + 49152, hq * 64, S_TOK + ttB * 128);
          bulk_commit();
          bulk_wait_all();
          fence_async_all();
          flag_add(FLAG_B(hq >> 1));
          TS(0, 12);
          mbar_wait(BAR_Q, 0);
          mbar_arrive(BAR_CL(0));
#pragma unroll 1
          for (int p = 0; p < 2; p++) {
            mbar_wait_long(BAR_OD(p), 0);
            if (p == 0) {
#pragma unroll
              for (int w = 0; w < 4; w++) tma2d_store(&mO16, sb + OFF_F + w * 2048, hg * 128 + w * 16, tbA * 64);
            } else {
              tma2d_store(&mO, sb + 26 * 8192, hg * 128 + 64, tbA * 64);
            }
            bulk_commit();
            bulk_wait_all();
            if (p == 0) mbar_arrive(BAR_CL(1));
            PUBLISH(FLAG_OA(tbA * 4 + hg, p));
          }
          TS(2, 0);
        }
      }
    }
    return;
  }
  if (helper) { helper_cta(blockIdx.x - 128, sb, bars, wg, w4, &mQst, &mOst); return; }

  {
    float acc[64];
    if (wg == 0) proj_loop<0>(acc, sb, bars, 16384, 0, wg, sWKV, &mWq, hg * 128, w4 == 0);
    else proj_loop<1>(acc, sb, bars, 16384 + wg * 8192, 49152, wg, sWKV, &mWqkv, (wg - 1) * 512 + hq * 64, w4 == 0);
    if (tid == 0) TS(0, 10);
    const uint32_t sF = sb + OFF_F;
    const uint32_t qa = sF + w4 * 512 + ((lane >> 3) & 1) * 256 + (lane >> 4) * 128 + (lane & 7) * 16;
    if (wg == 0) {
#pragma unroll
      for (int hd = 0; hd < 4; hd++)
        stsm4(qa + hd * 2048, pack_f16(acc[8 * hd] * QSCALE, acc[8 * hd + 1] * QSCALE), pack_f16(acc[8 * hd + 2] * QSCALE, acc[8 * hd + 3] * QSCALE),
              pack_f16(acc[8 * hd + 4] * QSCALE, acc[8 * hd + 5] * QSCALE), pack_f16(acc[8 * hd + 6] * QSCALE, acc[8 * hd + 7] * QSCALE));
      fence_async();
      __syncwarp();
      if (lane == 0) mbar_arrive(BAR_Q);
    } else {
      if (wg != 3) named_arrive(6, 384);
      if (wg != 1) named_arrive(8, 384);
    }
    asm volatile("setmaxnreg.inc.sync.aligned.u32 112;");
    fence_regs<64>(acc);
    if (wg == 0) {
#pragma unroll
      for (int hd = 4; hd < 8; hd++)
        stsm4(qa + hd * 2048, pack_f16(acc[8 * hd] * QSCALE, acc[8 * hd + 1] * QSCALE), pack_f16(acc[8 * hd + 2] * QSCALE, acc[8 * hd + 3] * QSCALE),
              pack_f16(acc[8 * hd + 4] * QSCALE, acc[8 * hd + 5] * QSCALE), pack_f16(acc[8 * hd + 6] * QSCALE, acc[8 * hd + 7] * QSCALE));
      fence_async();
      __syncwarp();
      if (lane == 0) mbar_arrive(BAR_VB(2));
    } else if (wg == 3) {
      named_bar(6, 384);
      const int t = tid & 127;
#pragma unroll
      for (int j = 0; j < 8; j++)
        sts4(sF + 24576 + j * 2048 + t * 16, pack_bf16(acc[8 * j], acc[8 * j + 1]), pack_bf16(acc[8 * j + 2], acc[8 * j + 3]),
             pack_bf16(acc[8 * j + 4], acc[8 * j + 5]), pack_bf16(acc[8 * j + 6], acc[8 * j + 7]));
      named_arrive(7, 256);
    } else {
      uint32_t p[32];
#pragma unroll
      for (int i = 0; i < 32; i++) p[i] = phi2(acc[2 * i], acc[2 * i + 1]);
      if (wg == 1) {
        named_bar(8, 384);
        const int m = lane >> 3, r = lane & 7;
#pragma unroll
        for (int j = 0; j < 16; j += 2) {
          const int tok = (j + (m >> 1)) * 8 + r;
          const int chunk = w4 * 2 + (m & 1);
          stsm4t(sF + 49152 + tok * 128 + ((chunk ^ r) << 4), p[2 * j], p[2 * j + 1], p[2 * j + 2], p[2 * j + 3]);
        }
        fence_async();
      } else {
        named_bar(7, 256);
        float kv0[4] = {0, 0, 0, 0}, kv1[4] = {0, 0, 0, 0}, z0[4] = {0, 0, 0, 0}, z1[4] = {0, 0, 0, 0};
        const uint32_t one = 0x3F803F80u;
        const int t = tid & 127;
#pragma unroll
        for (int j = 0; j < 8; j++) {
          uint32_t a[4];
          lds4(sF + 24576 + j * 2048 + t * 16, a);
          mma_bf16(kv0, a[0], a[1], a[2], a[3], p[4 * j], p[4 * j + 2]);
          mma_bf16(kv1, a[0], a[1], a[2], a[3], p[4 * j + 1], p[4 * j + 3]);
          mma_bf16(z0, one, one, one, one, p[4 * j], p[4 * j + 2]);
          mma_bf16(z1, one, one, one, one, p[4 * j + 1], p[4 * j + 3]);
        }
        float4* dst = g_kvp + ((ttB * 32 + hq * 4 + w4) * 3) * 32 + lane;
        dst[0] = make_float4(kv0[0], kv0[1], kv1[0], kv1[1]);
        dst[32] = make_float4(kv0[2], kv0[3], kv1[2], kv1[3]);
        dst[64] = make_float4(z0[0], z0[1], z1[0], z1[1]);
      }
      __syncwarp();
      if (lane == 0) mbar_arrive(BAR_BDONE);
    }
  }

  bool safe = true;
  {
    const uint32_t c63 = 0x1F801F80u + (threadIdx.x >> 20);
    const uint32_t m1 = (gridDim.x >> 20) - 1u;
    const uint64_t dK0 = make_desc(sb + OFF_K, 32768, 128, 0);
    const uint64_t dV0 = make_desc(sb + OFF_V, 128, 32768, 0);
    constexpr uint32_t dKV = ((2048u - 8u)  __H0__ ) + STEPK - (OFF_V - OFF_K) / 16;
    float Sm[12], Sp[36], O[12];
    uint32_t P[24];
    uint64_t dQ = make_desc(sb + OFF_F + wg * 2048, 128, 256, 0);
#pragma unroll
    for (int i = 0; i < 36; i++) Sp[i] = SMAGIC;
#pragma unroll
    for (int i = 0; i < 12; i++) Sm[i] = 0.f;
    fence_regs<12>(Sm); fence_regs<36>(Sp);
    mbar_wait(BAR_Q, 0);
    mbar_wait(BAR_KV(0), 0);
    wg_fence();
    wg_qs72<1>(Sp, dQ, dK0 + 24);
    wg_qs24<0>(Sm, dQ, dK0);
    wg_commit();
    wg_wait<0>();
    fence_regs<12>(Sm); fence_regs<36>(Sp);
#pragma unroll 1
    for (int pass = 0; pass < 2; pass++) {
#pragma unroll
      for (int i = 0; i < 12; i++) O[i] = 0.f;
      fence_regs<12>(O);
      if (tid == 0) TS(1, 2 + 2 * pass);
      uint32_t vlo = (uint32_t)dV0;
#pragma unroll 1
      for (int seg = 0; seg < 4; seg++) {
        if (pass == 0) {
          if (seg < 3) mbar_wait(seg == 0 ? BAR_VB(0) : BAR_KV(seg), 0);
        } else if (seg >= 1) {
          if ((tid & 127) == 0) {
            mbar_arrive(BAR_CL(seg));
            if (seg == 3) take_role(sM, wg);
          }
          __syncwarp();
        }
        if ((tid & 127) == 0) TS(4 + wg, pass * 5 + seg);
        const uint32_t vend = vlo + (seg == 0 ? 6 : 5) * STEPK;
#pragma unroll 1
        for (; vlo != vend; vlo += STEPK) {
          uint64_t dK, dV;
          asm("mov.b64 %0, {%1, %2};" : "=l"(dK) : "r"(vlo + dKV), "r"(8u));
          asm("mov.b64 %0, {%1, %2};" : "=l"(dV) : "r"(vlo), "r"(2048u));
#pragma unroll
          for (int i = 0; i < 6; i++) P[i] = pack_bf16(ex2f(Sm[2 * i]), ex2f(Sm[2 * i + 1]));
#pragma unroll
          for (int i = 0; i < 18; i++) P[6 + i] = exp2_pair_fix(Sp[2 * i], Sp[2 * i + 1], c63, m1);
          fence_regs<24>(P);
          wg_fence();
#pragma unroll
          for (int k = 0; k < 6; k++) wg_pv24<1>(O, &P[4 * k], dV + k * 16);
          wg_qs72<1>(Sp, dQ, dK + 24);
          wg_qs24<0>(Sm, dQ, dK);
          wg_commit();
          wg_wait<0>();
          fence_regs<12>(Sm); fence_regs<36>(Sp); fence_regs<12>(O); fence_regs<24>(P);
        }
      }
#pragma unroll
      for (int i = 0; i < 6; i++) P[i] = pack_bf16(ex2f(Sm[2 * i]), ex2f(Sm[2 * i + 1]));
      P[6] = exp2_pair_fix(Sp[0], Sp[1], c63, m1);
      P[7] = exp2_pair_fix(Sp[2], Sp[3], c63, m1);
      fence_regs<8>(P);
#pragma unroll
      for (int i = 0; i < 36; i++) Sp[i] = SMAGIC;
      fence_regs<36>(Sp);
      mbar_wait(pass == 0 ? BAR_Q2 : BAR_CL(3), 0);
      const uint32_t sO = pass == 0 ? sb + OFF_F + wg * 2048 + w4 * 512 + (lane & 15) * 32 + (lane >> 4) * 16
                                    : sb + 26 * 8192 + (w4 * 16 + (lane & 15)) * 128 + (((wg * 2 + (lane >> 4)) ^ (lane & 7)) << 4);
      dQ += 512;
      wg_fence();
      wg_pv24<1>(O, &P[0], dV0 + 21 * STEPK);
      wg_pv24<1>(O, &P[4], dV0 + 21 * STEPK + 16);
      wg_commit();
      wg_qs72<1>(Sp, dQ, dK0 + 24);
      wg_qs24<0>(Sm, dQ, dK0);
      wg_commit();
      wg_wait<1>();
      fence_regs<12>(O);
      const float l0 = __shfl_sync(~0u, O[8], lane & ~3), l1 = __shfl_sync(~0u, O[10], lane & ~3);
      const float i0 = rcpf(l0), i1 = rcpf(l1);
      stsm4(sO,
            pack_bf16(O[0] * i0, O[1] * i0), pack_bf16(O[2] * i1, O[3] * i1),
            pack_bf16(O[4] * i0, O[5] * i0), pack_bf16(O[6] * i1, O[7] * i1));
      fence_async();
      {
        safe = __all_sync(~0u, lds1(sM + 16) != 0);
      }
      if (safe && lane == 0) mbar_arrive(BAR_OD(pass));
      wg_wait<0>();
      fence_regs<12>(Sm); fence_regs<36>(Sp);
      if (!safe) break;
      if ((tid & 127) == 0) TS(4 + wg, pass * 5 + 4);
      if (tid == 0) TS(1, 3 + 2 * pass);
    }
  }
  if (!safe) {
    if ((tid & 127) == 0) { mbar_arrive(BAR_CL(1)); mbar_arrive(BAR_CL(2)); mbar_arrive(BAR_CL(3)); take_role(sM, wg); }
#pragma unroll 1
    for (int pass = 0; pass < 2; pass++) {
      const int t = tid & 127;
      mbar_wait(BAR_CL(3), 0);
      attn_slow(prm.xa + (size_t)tbA * 64 * D_MOD, prm.wq + (hg * 8 + pass * 4 + wg) * 16,
                pass == 0 ? sb + OFF_F + wg * 2048 + t * 16
                          : sb + 26 * 8192 + (t >> 1) * 128 + (((wg * 2 + (t & 1)) ^ ((t >> 1) & 7)) << 4));
      __syncwarp();
      if (lane == 0) mbar_arrive(BAR_OD(pass));
    }
  }

  {
    named_bar(wg + 1, 128);
    if ((tid & 127) == 0) mbar_arrive(BAR_CL(4));
    const int role = __shfl_sync(~0u, lds1(sM + 32 + wg * 4), 0);
    if ((tid & 127) == 0) TS(4 + wg, 10);
    const int m = lane >> 3, r = lane & 7;
    const uint32_t stoff = (w4 * 16 + (m & 1) * 8 + r) * 128;
    if (role < 2) {
      if (role == 0 && (tid & 127) == 0) mbar_arrive(BAR_RL);
      if (!isB || role == 1) mbar_wait(BAR_CL(4), 0);
      float acc[64];
#pragma unroll 1
      for (int n = 0; n < 8; n++) {
        const uint32_t sl = tail_slots(isB, n);
        const uint32_t w0 = (sl >> 16) & 255, w1 = sl >> 24;
        const uint64_t da = make_desc(sb + ((sl >> (8 * role)) & 255) * 8192, 16, 1024, 1);
        const uint64_t db = make_desc(sb + w0 * 8192, (w1 - w0) * 8192, 1024, 1);
        mbar_wait(BAR_TF(n), 0);
        if (!isB && n >= 4) mbar_wait(n == 4 && role == 0 ? BAR_OD(1) : BAR_TF(2 * n + role), 0);
        if ((tid & 127) == 0 && role == 1) TS(2, 2 + n);
        wg_fence();
#pragma unroll
        for (int k = 0; k < 4; k++) wg_ss128<0, 1>(acc, da + k * 2, db + k * 128, (n | k) != 0);
        wg_commit();
        wg_wait<1>();
        if ((n == 1 || n == 2) && (tid & 127) == 0) mbar_arrive(BAR_TE(n - 1));
        __syncwarp();
      }
      wg_wait<0>();
      fence_regs<64>(acc);
      if ((tid & 127) == 0) TS(4 + wg, 11);
      const uint32_t x0 = sb + (role ? 16 : 8) * 8192, x1 = sb + (role ? 5 : 1) * 8192;
#pragma unroll
      for (int j = 0; j < 16; j += 2)
        stsm4((j < 8 ? x0 : x1) + stoff + ((((j & 7) + (m >> 1)) ^ r) << 4),
              pack_bf16(acc[4 * j], acc[4 * j + 1]), pack_bf16(acc[4 * j + 2], acc[4 * j + 3]),
              pack_bf16(acc[4 * j + 4], acc[4 * j + 5]), pack_bf16(acc[4 * j + 6], acc[4 * j + 7]));
      __syncwarp();
      uint4* dst = (uint4*)(prm.out + (size_t)(tok0 + role * 64 + w4 * 16 + (lane >> 4)) * 1024 + isB * 512 + hg * 128) + (lane & 15);
      const uint32_t src = ((lane & 8) ? x1 : x0) + (w4 * 16 + (lane >> 4)) * 128;
#pragma unroll
      for (int i = 0; i < 8; i++) {
        uint32_t v[4];
        lds4(src + i * 256 + (((lane & 7) ^ ((2 * i + (lane >> 4)) & 7)) << 4), v);
        dst[i * 256] = make_uint4(v[0], v[1], v[2], v[3]);
      }
      if ((tid & 127) == 0) TS(2, 11 + role);
    }
  }
}

typedef CUresult (*EncodeFn)(CUtensorMap*, CUtensorMapDataType, cuuint32_t, void*, const cuuint64_t*, const cuuint64_t*,
                             const cuuint32_t*, const cuuint32_t*, CUtensorMapInterleave, CUtensorMapSwizzle,
                             CUtensorMapL2promotion, CUtensorMapFloatOOBfill);

static void make_map(EncodeFn enc, CUtensorMap* m, const void* ptr, uint64_t cols, uint64_t rows, uint32_t bc, uint32_t br,
                     CUtensorMapSwizzle sw = CU_TENSOR_MAP_SWIZZLE_128B) {
  cuuint64_t dims[2] = {cols, rows};
  cuuint64_t strides[1] = {cols * 2};
  cuuint32_t box[2] = {bc, br};
  cuuint32_t es[2] = {1, 1};
  enc(m, CU_TENSOR_MAP_DATA_TYPE_BFLOAT16, 2, (void*)ptr, dims, strides, box, es, CU_TENSOR_MAP_INTERLEAVE_NONE,
      sw, CU_TENSOR_MAP_L2_PROMOTION_L2_256B, CU_TENSOR_MAP_FLOAT_OOB_FILL_NONE);
}

extern "C" void kernel_launch(void* const* d_in, const int* in_sizes, int n_in, void* d_out, int out_size) {
  (void)in_sizes; (void)n_in; (void)out_size;
  static EncodeFn enc = nullptr;
  static void* pQ = nullptr; static void* pO = nullptr;
  if (!enc) {
    void* fn = nullptr; cudaDriverEntryPointQueryResult qr;
    cudaGetDriverEntryPoint("cuTensorMapEncodeTiled", &fn, cudaEnableDefault, &qr);
    enc = (EncodeFn)fn;
    cudaGetSymbolAddress(&pQ, g_Q);
    cudaGetSymbolAddress(&pO, g_O);
    cudaFuncSetAttribute(k1_main, cudaFuncAttributeMaxDynamicSharedMemorySize, SM_TOTAL);
  }
  CUtensorMap mXA64, mXB, mWq, mWqkv, mQst, mO, mOst, mWoA, mWoB, mO16;
  make_map(enc, &mXA64, d_in[0], 512, 2048, 64, 64);
  make_map(enc, &mWq, d_in[1], 512, 512, 64, 64);
  make_map(enc, &mWoA, d_in[4], 512, 512, 64, 64);
  make_map(enc, &mXB, d_in[5], 512, 2048, 64, 128);
  make_map(enc, &mWqkv, d_in[6], 1536, 512, 64, 64);
  make_map(enc, &mWoB, d_in[7], 512, 512, 64, 64);
  make_map(enc, &mQst, pQ, 512, 4096, 64, 128);
  make_map(enc, &mO, pO, 512, 4096, 64, 64);
  make_map(enc, &mOst, pO, 512, 4096, 64, 128);
  make_map(enc, &mO16, pO, 512, 4096, 16, 64, CU_TENSOR_MAP_SWIZZLE_NONE);
  Params prm{(const __nv_bfloat16*)d_in[2], (const __nv_bfloat16*)d_in[3], (const __nv_bfloat16*)d_in[0], (const __nv_bfloat16*)d_in[1], (__nv_bfloat16*)d_out, (const __nv_bfloat16*)d_in[5], (const __nv_bfloat16*)d_in[6]};
  k1_main<<<132, 640, SM_TOTAL, cudaStreamPerThread>>>(mXA64, mXB, mWq, mWqkv, mQst, mOst, mO, mWoA, mWoB, mO16, prm);
}
```

```cpp
#include <cuda_runtime.h>
#include <cuda_bf16.h>
#include <cuda_fp16.h>
#include <cuda.h>
#include <stdint.h>

#define S_TOK 2048
#define D_MOD 512

__device__ __align__(1024) __nv_bfloat16 g_Q[2 * S_TOK * D_MOD];
__device__ __align__(1024) __nv_bfloat16 g_O[2 * S_TOK * D_MOD];
__device__ __align__(1024) uint4 g_KV[8 * S_TOK];
__device__ __align__(16) uint32_t g_stats[128];
__device__ __align__(16) float4 g_kvp[16 * 32 * 3 * 32];

#define TS(k, i) do {} while (0)
#define TSM(k, i) do {} while (0)
#define TSW(k, i) do {} while (0)
__device__ __forceinline__ uint32_t smem_u32(const void* p) { return (uint32_t)__cvta_generic_to_shared(p); }
__device__ __forceinline__ void mbar_init(uint32_t bar, int cnt) { asm volatile("mbarrier.init.shared::cta.b64 [%0], %1;" :: "r"(bar), "r"(cnt) : "memory"); }
__device__ __forceinline__ void mbar_expect_tx(uint32_t bar, uint32_t bytes) { asm volatile("mbarrier.arrive.expect_tx.shared::cta.b64 _, [%0], %1;" :: "r"(bar), "r"(bytes) : "memory"); }
__device__ __forceinline__ bool mbar_try(uint32_t bar, uint32_t parity) {
  uint32_t ok;
  asm volatile("{\n.reg .pred p;\nmbarrier.try_wait.parity.shared::cta.b64 p, [%1], %2;\nselp.b32 %0, 1, 0, p;\n}\n" : "=r"(ok) : "r"(bar), "r"(parity) : "memory");
  return ok;
}
__device__ __forceinline__ void mbar_wait(uint32_t bar, uint32_t parity) {
  asm volatile("{\n.reg .pred p;\n.reg .u32 c;\nmov.u32 c, 0;\n"
               "LW_%=:\n"
               "mbarrier.try_wait.parity.shared::cta.b64 p, [%0], %1;\n"
               "@p bra LD_%=;\n"
               "add.u32 c, c, 1;\n"
               "setp.lt.u32 p, c, 4000000;\n"
               "@p bra LW_%=;\n"
               "trap;\n"
               "LD_%=:\n}\n" :: "r"(bar), "r"(parity) : "memory");
}
__device__ __forceinline__ void mbar_arrive_cta(uint32_t bar, uint32_t cta) {
  asm volatile("{\n.reg .b32 ra;\nmapa.shared::cluster.u32 ra, %0, %1;\nmbarrier.arrive.shared::cluster.b64 _, [ra];\n}\n" :: "r"(bar), "r"(cta) : "memory");
}
__device__ __forceinline__ void cluster_sync() {
  asm volatile("barrier.cluster.arrive.relaxed.aligned;\nbarrier.cluster.wait.aligned;" ::: "memory");
}
__device__ __forceinline__ void tma2d(uint32_t dst, const CUtensorMap* m, int c0, int c1, uint32_t bar) {
  asm volatile("cp.async.bulk.tensor.2d.shared::cluster.global.mbarrier::complete_tx::bytes [%0], [%1, {%3, %4}], [%2];"
               :: "r"(dst), "l"(m), "r"(bar), "r"(c0), "r"(c1) : "memory");
}
__device__ __forceinline__ void tma2d_mc(uint32_t dst, const CUtensorMap* m, int c0, int c1, uint32_t bar, uint16_t mask) {
  asm volatile("cp.async.bulk.tensor.2d.shared::cluster.global.mbarrier::complete_tx::bytes.multicast::cluster [%0], [%1, {%3, %4}], [%2], %5;"
               :: "r"(dst), "l"(m), "r"(bar), "r"(c0), "r"(c1), "h"(mask) : "memory");
}
__device__ __forceinline__ void tma2d_store(const CUtensorMap* m, uint32_t src, int c0, int c1) {
  asm volatile("cp.async.bulk.tensor.2d.global.shared::cta.bulk_group [%0, {%2, %3}], [%1];"
               :: "l"(m), "r"(src), "r"(c0), "r"(c1) : "memory");
}
__device__ __forceinline__ void bulk_g2s(uint32_t dst, const void* src, uint32_t bytes, uint32_t bar) {
  asm volatile("cp.async.bulk.shared::cluster.global.mbarrier::complete_tx::bytes [%0], [%1], %2, [%3];"
               :: "r"(dst), "l"(src), "r"(bytes), "r"(bar) : "memory");
}
__device__ __forceinline__ void bulk_commit() { asm volatile("cp.async.bulk.commit_group;" ::: "memory"); }
__device__ __forceinline__ void bulk_wait_all() { asm volatile("cp.async.bulk.wait_group 0;" ::: "memory"); }
__device__ __forceinline__ void fence_async() { asm volatile("fence.proxy.async.shared::cta;" ::: "memory"); }
__device__ __forceinline__ void named_bar(int id, int n) { asm volatile("bar.sync %0, %1;" :: "r"(id), "r"(n) : "memory"); }
__device__ __forceinline__ void pdl_launch() { asm volatile("griddepcontrol.launch_dependents;" ::: "memory"); }
__device__ __forceinline__ void pdl_wait() { asm volatile("griddepcontrol.wait;" ::: "memory"); }
__device__ __forceinline__ void wg_fence() { asm volatile("wgmma.fence.sync.aligned;" ::: "memory"); }
__device__ __forceinline__ void wg_commit() { asm volatile("wgmma.commit_group.sync.aligned;" ::: "memory"); }
template <int n> __device__ __forceinline__ void wg_wait() { asm volatile("wgmma.wait_group.sync.aligned %0;" :: "n"(n) : "memory"); }
template <int n> __device__ __forceinline__ void fence_regs(float* r) {
#pragma unroll
  for (int i = 0; i < n; i++) asm volatile("" : "+f"(r[i]) :: "memory");
}
template <int n> __device__ __forceinline__ void fence_regs(uint32_t* r) {
#pragma unroll
  for (int i = 0; i < n; i++) asm volatile("" : "+r"(r[i]) :: "memory");
}
__device__ __forceinline__ uint64_t make_desc(uint32_t addr, uint32_t lbo, uint32_t sbo, uint32_t swz) {
  return (uint64_t)((addr & 0x3FFFF) >> 4) | ((uint64_t)(lbo >> 4) << 16) | ((uint64_t)(sbo >> 4) << 32) | ((uint64_t)swz << 62);
}
__device__ __forceinline__ float ex2f(float x) { float y; asm("ex2.approx.ftz.f32 %0, %1;" : "=f"(y) : "f"(x)); return y; }
__device__ __forceinline__ uint32_t pack_bf16(float lo, float hi) { uint32_t r; asm("cvt.rn.bf16x2.f32 %0, %1, %2;" : "=r"(r) : "f"(hi), "f"(lo)); return r; }
__device__ __forceinline__ uint32_t pack_f16(float lo, float hi) { uint32_t r; asm("cvt.rn.f16x2.f32 %0, %1, %2;" : "=r"(r) : "f"(hi), "f"(lo)); return r; }
__device__ __forceinline__ float bf_lo(uint32_t v) { return __uint_as_float(v << 16); }
__device__ __forceinline__ float bf_hi(uint32_t v) { return __uint_as_float(v & 0xFFFF0000u); }
__device__ __forceinline__ float rbf(float x) { return __bfloat162float(__float2bfloat16_rn(x)); }
__device__ __forceinline__ void stsm4(uint32_t a, uint32_t r0, uint32_t r1, uint32_t r2, uint32_t r3) {
  asm volatile("stmatrix.sync.aligned.m8n8.x4.shared.b16 [%0], {%1,%2,%3,%4};" :: "r"(a), "r"(r0), "r"(r1), "r"(r2), "r"(r3) : "memory");
}
__device__ __forceinline__ void stsm4t(uint32_t a, uint32_t r0, uint32_t r1, uint32_t r2, uint32_t r3) {
  asm volatile("stmatrix.sync.aligned.m8n8.x4.trans.shared.b16 [%0], {%1,%2,%3,%4};" :: "r"(a), "r"(r0), "r"(r1), "r"(r2), "r"(r3) : "memory");
}
__device__ __forceinline__ void mma_bf16(float* d, uint32_t a0, uint32_t a1, uint32_t a2, uint32_t a3, uint32_t b0, uint32_t b1) {
  asm volatile("mma.sync.aligned.m16n8k16.row.col.f32.bf16.bf16.f32 {%0,%1,%2,%3}, {%4,%5,%6,%7}, {%8,%9}, {%0,%1,%2,%3};"
               : "+f"(d[0]), "+f"(d[1]), "+f"(d[2]), "+f"(d[3]) : "r"(a0), "r"(a1), "r"(a2), "r"(a3), "r"(b0), "r"(b1));
}
template<int SD> __device__ __forceinline__ void wg_qs24(float* d, uint64_t da, uint64_t db) {
  asm volatile("wgmma.mma_async.sync.aligned.m64n24k16.f32.f16.f16 {%0,%1,%2,%3,%4,%5,%6,%7,%8,%9,%10,%11}, %12, %13, %14, 1, 1, 0, 0;"
   : "+f"(d[0]),"+f"(d[1]),"+f"(d[2]),"+f"(d[3]),"+f"(d[4]),"+f"(d[5]),"+f"(d[6]),"+f"(d[7]),"+f"(d[8]),"+f"(d[9]),"+f"(d[10]),"+f"(d[11])
   : "l"(da),"l"(db),"n"(SD));
}
template<int SD> __device__ __forceinline__ void wg_qs72(float* d, uint64_t da, uint64_t db) {
  asm volatile("wgmma.mma_async.sync.aligned.m64n72k16.f32.f16.f16 {%0,%1,%2,%3,%4,%5,%6,%7,%8,%9,%10,%11,%12,%13,%14,%15,%16,%17,%18,%19,%20,%21,%22,%23,%24,%25,%26,%27,%28,%29,%30,%31,%32,%33,%34,%35}, %36, %37, %38, 1, 1, 0, 0;"
   : "+f"(d[0]),"+f"(d[1]),"+f"(d[2]),"+f"(d[3]),"+f"(d[4]),"+f"(d[5]),"+f"(d[6]),"+f"(d[7]),"+f"(d[8]),"+f"(d[9]),"+f"(d[10]),"+f"(d[11]),"+f"(d[12]),"+f"(d[13]),"+f"(d[14]),"+f"(d[15]),"+f"(d[16]),"+f"(d[17]),"+f"(d[18]),"+f"(d[19]),"+f"(d[20]),"+f"(d[21]),"+f"(d[22]),"+f"(d[23]),"+f"(d[24]),"+f"(d[25]),"+f"(d[26]),"+f"(d[27]),"+f"(d[28]),"+f"(d[29]),"+f"(d[30]),"+f"(d[31]),"+f"(d[32]),"+f"(d[33]),"+f"(d[34]),"+f"(d[35])
   : "l"(da),"l"(db),"n"(SD));
}
template<int SD> __device__ __forceinline__ void wg_qs96(float* d, uint64_t da, uint64_t db) {
  asm volatile("wgmma.mma_async.sync.aligned.m64n96k16.f32.f16.f16 {%0,%1,%2,%3,%4,%5,%6,%7,%8,%9,%10,%11,%12,%13,%14,%15,%16,%17,%18,%19,%20,%21,%22,%23,%24,%25,%26,%27,%28,%29,%30,%31,%32,%33,%34,%35,%36,%37,%38,%39,%40,%41,%42,%43,%44,%45,%46,%47}, %48, %49, %50, 1, 1, 0, 0;"
   : "+f"(d[0]),"+f"(d[1]),"+f"(d[2]),"+f"(d[3]),"+f"(d[4]),"+f"(d[5]),"+f"(d[6]),"+f"(d[7]),"+f"(d[8]),"+f"(d[9]),"+f"(d[10]),"+f"(d[11]),"+f"(d[12]),"+f"(d[13]),"+f"(d[14]),"+f"(d[15]),"+f"(d[16]),"+f"(d[17]),"+f"(d[18]),"+f"(d[19]),"+f"(d[20]),"+f"(d[21]),"+f"(d[22]),"+f"(d[23]),"+f"(d[24]),"+f"(d[25]),"+f"(d[26]),"+f"(d[27]),"+f"(d[28]),"+f"(d[29]),"+f"(d[30]),"+f"(d[31]),"+f"(d[32]),"+f"(d[33]),"+f"(d[34]),"+f"(d[35]),"+f"(d[36]),"+f"(d[37]),"+f"(d[38]),"+f"(d[39]),"+f"(d[40]),"+f"(d[41]),"+f"(d[42]),"+f"(d[43]),"+f"(d[44]),"+f"(d[45]),"+f"(d[46]),"+f"(d[47])
   : "l"(da),"l"(db),"n"(SD));
}
template<int SD> __device__ __forceinline__ void wg_pv24(float* d, const uint32_t* a, uint64_t desc) {
  asm volatile("wgmma.mma_async.sync.aligned.m64n24k16.f32.bf16.bf16 {%0,%1,%2,%3,%4,%5,%6,%7,%8,%9,%10,%11}, {%12,%13,%14,%15}, %16, %17, 1, 1, 1;"
   : "+f"(d[0]),"+f"(d[1]),"+f"(d[2]),"+f"(d[3]),"+f"(d[4]),"+f"(d[5]),"+f"(d[6]),"+f"(d[7]),"+f"(d[8]),"+f"(d[9]),"+f"(d[10]),"+f"(d[11])
   : "r"(a[0]),"r"(a[1]),"r"(a[2]),"r"(a[3]),"l"(desc),"n"(SD));
}
template<int TA, int TB> __device__ __forceinline__ void wg_ss128(float* d, uint64_t da, uint64_t db, int sd) {
  asm volatile("{\n.reg .pred p;\nsetp.ne.b32 p, %66, 0;\n"
   "wgmma.mma_async.sync.aligned.m64n128k16.f32.bf16.bf16 {%0,%1,%2,%3,%4,%5,%6,%7,%8,%9,%10,%11,%12,%13,%14,%15,%16,%17,%18,%19,%20,%21,%22,%23,%24,%25,%26,%27,%28,%29,%30,%31,%32,%33,%34,%35,%36,%37,%38,%39,%40,%41,%42,%43,%44,%45,%46,%47,%48,%49,%50,%51,%52,%53,%54,%55,%56,%57,%58,%59,%60,%61,%62,%63}, %64, %65, p, 1, 1, %67, %68;\n}\n"
   : "+f"(d[0]),"+f"(d[1]),"+f"(d[2]),"+f"(d[3]),"+f"(d[4]),"+f"(d[5]),"+f"(d[6]),"+f"(d[7]),"+f"(d[8]),"+f"(d[9]),"+f"(d[10]),"+f"(d[11]),"+f"(d[12]),"+f"(d[13]),"+f"(d[14]),"+f"(d[15]),"+f"(d[16]),"+f"(d[17]),"+f"(d[18]),"+f"(d[19]),"+f"(d[20]),"+f"(d[21]),"+f"(d[22]),"+f"(d[23]),"+f"(d[24]),"+f"(d[25]),"+f"(d[26]),"+f"(d[27]),"+f"(d[28]),"+f"(d[29]),"+f"(d[30]),"+f"(d[31]),"+f"(d[32]),"+f"(d[33]),"+f"(d[34]),"+f"(d[35]),"+f"(d[36]),"+f"(d[37]),"+f"(d[38]),"+f"(d[39]),"+f"(d[40]),"+f"(d[41]),"+f"(d[42]),"+f"(d[43]),"+f"(d[44]),"+f"(d[45]),"+f"(d[46]),"+f"(d[47]),"+f"(d[48]),"+f"(d[49]),"+f"(d[50]),"+f"(d[51]),"+f"(d[52]),"+f"(d[53]),"+f"(d[54]),"+f"(d[55]),"+f"(d[56]),"+f"(d[57]),"+f"(d[58]),"+f"(d[59]),"+f"(d[60]),"+f"(d[61]),"+f"(d[62]),"+f"(d[63])
   : "l"(da),"l"(db),"r"(sd),"n"(TA),"n"(TB));
}
template<int TA, int TB> __device__ __forceinline__ void wg_ss64(float* d, uint64_t da, uint64_t db, int sd) {
  asm volatile("{\n.reg .pred p;\nsetp.ne.b32 p, %34, 0;\n"
   "wgmma.mma_async.sync.aligned.m64n64k16.f32.bf16.bf16 {%0,%1,%2,%3,%4,%5,%6,%7,%8,%9,%10,%11,%12,%13,%14,%15,%16,%17,%18,%19,%20,%21,%22,%23,%24,%25,%26,%27,%28,%29,%30,%31}, %32, %33, p, 1, 1, %35, %36;\n}\n"
   : "+f"(d[0]),"+f"(d[1]),"+f"(d[2]),"+f"(d[3]),"+f"(d[4]),"+f"(d[5]),"+f"(d[6]),"+f"(d[7]),"+f"(d[8]),"+f"(d[9]),"+f"(d[10]),"+f"(d[11]),"+f"(d[12]),"+f"(d[13]),"+f"(d[14]),"+f"(d[15]),"+f"(d[16]),"+f"(d[17]),"+f"(d[18]),"+f"(d[19]),"+f"(d[20]),"+f"(d[21]),"+f"(d[22]),"+f"(d[23]),"+f"(d[24]),"+f"(d[25]),"+f"(d[26]),"+f"(d[27]),"+f"(d[28]),"+f"(d[29]),"+f"(d[30]),"+f"(d[31])
   : "l"(da),"l"(db),"r"(sd),"n"(TA),"n"(TB));
}
template<int TA, int TB> __device__ __forceinline__ void wg_ss8(float* d, uint64_t da, uint64_t db, int sd) {
  asm volatile("{\n.reg .pred p;\nsetp.ne.b32 p, %6, 0;\n"
   "wgmma.mma_async.sync.aligned.m64n8k16.f32.bf16.bf16 {%0,%1,%2,%3}, %4, %5, p, 1, 1, %7, %8;\n}\n"
   : "+f"(d[0]),"+f"(d[1]),"+f"(d[2]),"+f"(d[3])
   : "l"(da),"l"(db),"r"(sd),"n"(TA),"n"(TB));
}

__device__ __forceinline__ uint32_t phi2(float a, float b) {
  uint32_t r, e;
  asm("cvt.rn.relu.bf16x2.f32 %0, %1, %2;" : "=r"(r) : "f"(b), "f"(a));
  e = pack_bf16(ex2f(a * 1.4426950408889634f), ex2f(b * 1.4426950408889634f));
  asm("add.rn.bf16x2 %0, %0, %1;" : "+r"(e) : "r"(0x35863586u));
  asm("min.NaN.bf16x2 %0, %0, %1;" : "+r"(e) : "r"(0x3F803F80u));
  asm("add.rn.bf16x2 %0, %0, %1;" : "+r"(e) : "r"(r));
  return e;
}

__device__ __forceinline__ void mbar_wait_long(uint32_t bar, uint32_t parity) {
  asm volatile("{\n.reg .pred p;\n.reg .u32 c;\nmov.u32 c, 0;\n"
               "LW_%=:\n"
               "mbarrier.try_wait.parity.shared::cta.b64 p, [%0], %1, 100000;\n"
               "@p bra LD_%=;\n"
               "add.u32 c, c, 1;\n"
               "setp.lt.u32 p, c, 20000;\n"
               "@p bra LW_%=;\n"
               "trap;\n"
               "LD_%=:\n}\n" :: "r"(bar), "r"(parity) : "memory");
}
__device__ __forceinline__ void mbar_arrive(uint32_t bar) { asm volatile("mbarrier.arrive.shared::cta.b64 _, [%0];" :: "r"(bar) : "memory"); }
__device__ __forceinline__ void named_arrive(int id, int n) { asm volatile("bar.arrive %0, %1;" :: "r"(id), "r"(n) : "memory"); }
__device__ __forceinline__ void fence_async_all() { asm volatile("fence.proxy.async.global;" ::: "memory"); }
__device__ __forceinline__ void flag_add(uint32_t* f) { asm volatile("fence.acq_rel.gpu;\nred.relaxed.gpu.global.add.u32 [%0], 1;" :: "l"(f) : "memory"); }
#define PUBLISH(f) asm volatile("fence.proxy.async.global;\nred.relaxed.gpu.global.add.u32 [%0], 1;" :: "l"(f) : "memory")
__device__ __forceinline__ void flag_wait(const uint32_t* f, uint32_t target) {
  uint32_t v;
#pragma unroll 1
  for (int it = 0;; it++) {
    asm volatile("ld.acquire.gpu.global.u32 %0, [%1];" : "=r"(v) : "l"(f) : "memory");
    if ((int32_t)(v - target) >= 0) break;
    if (it > 2000000) __trap();
    __nanosleep(64);
  }
}
__device__ __forceinline__ bool mbar_test(uint32_t bar, uint32_t parity) {
  uint32_t ok;
  asm volatile("{\n.reg .pred p;\nmbarrier.test_wait.parity.shared::cta.b64 p, [%1], %2;\nselp.b32 %0, 1, 0, p;\n}\n" : "=r"(ok) : "r"(bar), "r"(parity) : "memory");
  return ok;
}
__device__ __forceinline__ bool elect_one() {
  uint32_t p;
  asm volatile("{\n.reg .pred P;\nelect.sync _|P, 0xFFFFFFFF;\nselp.b32 %0, 1, 0, P;\n}\n" : "=r"(p));
  return p;
}
__device__ __forceinline__ void lds4(uint32_t a, uint32_t* r) {
  asm volatile("ld.shared.v4.b32 {%0,%1,%2,%3}, [%4];" : "=r"(r[0]), "=r"(r[1]), "=r"(r[2]), "=r"(r[3]) : "r"(a) : "memory");
}
__device__ __forceinline__ uint32_t lds1(uint32_t a) { uint32_t r; asm volatile("ld.shared.b32 %0, [%1];" : "=r"(r) : "r"(a) : "memory"); return r; }
__device__ __forceinline__ void sts1(uint32_t a, uint32_t v) { asm volatile("st.shared.b32 [%0], %1;" :: "r"(a), "r"(v) : "memory"); }
__device__ __forceinline__ void sts4(uint32_t a, uint32_t r0, uint32_t r1, uint32_t r2, uint32_t r3) {
  asm volatile("st.shared.v4.b32 [%0], {%1,%2,%3,%4};" :: "r"(a), "r"(r0), "r"(r1), "r"(r2), "r"(r3) : "memory");
}
__device__ __forceinline__ void ldsm4(uint32_t a, uint32_t* r) {
  asm volatile("ldmatrix.sync.aligned.m8n8.x4.shared.b16 {%0,%1,%2,%3}, [%4];" : "=r"(r[0]), "=r"(r[1]), "=r"(r[2]), "=r"(r[3]) : "r"(a) : "memory");
}
__device__ __forceinline__ float rcpf(float x) { float y; asm("rcp.approx.ftz.f32 %0, %1;" : "=f"(y) : "f"(x)); return y; }
__device__ __forceinline__ uint32_t hfma2(uint32_t a, uint32_t b, uint32_t c) { uint32_t r; asm("fma.rn.f16x2 %0, %1, %2, %3;" : "=r"(r) : "r"(a), "r"(b), "r"(c)); return r; }
__device__ __forceinline__ uint32_t hadd2(uint32_t a, uint32_t b) { uint32_t r; asm("add.rn.f16x2 %0, %1, %2;" : "=r"(r) : "r"(a), "r"(b)); return r; }

#define STEPK 96
#define GIMAP(i) ((((i) & 1) << 2) | (((i) >> 1) & 3) | ((i) & 8))
#define QSCALE 0.36067376022224085f
#define SMAGIC (512.0f + 2.0f * (191.0f - 30.0f - 1.5823545f))
#define VSHIFT 1073741824.0f

__device__ uint32_t g_epoch[132];
__device__ uint32_t g_flag[288 * 8];
#define FLAG_KV (g_flag)
#define FLAG_B(h) (g_flag + (4 + (h)) * 8)
#define FLAG_OA(cta, pass) (g_flag + (16 + (cta) * 2 + (pass)) * 8)
#define FLAG_LM(i) (g_flag + (272 + (i)) * 8)

#define SM_TOTAL (224 * 1024 + 2048 + 1024)
#define OFF_K 0
#define OFF_F 65536
#define OFF_V 131072
#define OFF_MISC (224 * 1024)

#define BAR_FULL(s) (bars + 8 * (s))
#define BAR_EMPTY(s) (bars + 24 + 8 * (s))
#define BAR_KV(c) (bars + 48 + 8 * (c))
#define BAR_BDONE (bars + 80)
#define BAR_Q (bars + 88)
#define BAR_GO (bars + 96)
#define BAR_Q2 (bars + 104)
#define BAR_OD(p) (bars + 112 + 8 * (p))
#define BAR_CL(c) (bars + 128 + 8 * (c))
#define BAR_TE(i) (bars + 168 + 8 * (i))
#define BAR_RL (bars + 192)
#define BAR_TF(g) (bars + 224 + 8 * (g))
#define BAR_XA(w) (bars + 352 + 8 * (w))
#define BAR_VB(c) (bars + 384 + 8 * (c))

__device__ __forceinline__ uint32_t exp2_pair_fix(float d0, float d1, uint32_t c63, uint32_t m1) {
  uint32_t w, y, s, r;
  asm("prmt.b32 %0, %1, %2, 0x6521;" : "=r"(w) : "r"(__float_as_uint(d0)), "r"(__float_as_uint(d1)));
  asm("lop3.b32 %0, %1, 0x007F007F, %2, 0xEA;" : "=r"(y) : "r"(w), "r"(c63));
  asm("mad.lo.u32 %0, %1, %2, %3;" : "=r"(s) : "r"(y), "r"(m1), "r"(w));
  asm("fma.rn.bf16x2 %0, %1, %2, %3;" : "=r"(r) : "r"(w), "r"(y), "r"(s));
  return r;
}

#define X_PR(i) asm volatile("prmt.b32 %0, %1, %2, 0x6521;" : "=r"(w[i]) : "r"(__float_as_uint(Sp[2 * (i)])), "r"(__float_as_uint(Sp[2 * (i) + 1])));
#define X_LO(i) asm volatile("lop3.b32 %0, %1, 0x007F007F, %2, 0xEA;" : "=r"(y[i]) : "r"(w[i]), "r"(c63));
#define X_IM(i) asm volatile("mad.lo.u32 %0, %1, %2, %3;" : "=r"(z[i]) : "r"(y[i]), "r"(m1), "r"(w[i]));
#define X_FM(i) asm volatile("fma.rn.bf16x2 %0, %1, %2, %3;" : "=r"(P[6 + (i)]) : "r"(w[i]), "r"(y[i]), "r"(z[i]));
#define X_MU(i) asm volatile("ex2.approx.ftz.f32 %0, %1;" : "=f"(e[i]) : "f"(Sm[i]));
#define X_PK(i) asm volatile("cvt.rn.bf16x2.f32 %0, %1, %2;" : "=r"(P[i]) : "f"(e[2 * (i) + 1]), "f"(e[2 * (i)]));

__device__ __forceinline__ void attn_slow(const __nv_bfloat16* xa, const __nv_bfloat16* wq, uint32_t dst) {
  const int t = threadIdx.x & 127;
  const int row = t >> 1, half = t & 1;
  float q[16];
  {
    float a[8];
#pragma unroll
    for (int i = 0; i < 8; i++) a[i] = 0.f;
#pragma unroll 1
    for (int k = 0; k < D_MOD; k++) {
      const float x = __bfloat162float(xa[(size_t)row * D_MOD + k]);
      const uint4 w = *(const uint4*)(wq + (size_t)k * D_MOD + half * 8);
      const uint32_t ww[4] = {w.x, w.y, w.z, w.w};
#pragma unroll
      for (int i = 0; i < 4; i++) { a[2 * i] = fmaf(x, bf_lo(ww[i]), a[2 * i]); a[2 * i + 1] = fmaf(x, bf_hi(ww[i]), a[2 * i + 1]); }
    }
#pragma unroll
    for (int i = 0; i < 8; i++) {
      const float mine = rbf(a[i]), other = __shfl_xor_sync(~0u, mine, 1);
      q[i] = half ? other : mine; q[8 + i] = half ? mine : other;
    }
  }
  float m = -INFINITY, l = 0.f, o[16];
#pragma unroll
  for (int i = 0; i < 16; i++) o[i] = 0.f;
#pragma unroll 1
  for (int j = half * 1024; j < half * 1024 + 1024; j++) {
    uint4 ka = g_KV[4 * S_TOK + j], kb = g_KV[5 * S_TOK + j];
    uint4 va = g_KV[6 * S_TOK + j], vb = g_KV[7 * S_TOK + j];
    uint32_t kk[8] = {ka.x, ka.y, ka.z, ka.w, kb.x, kb.y, kb.z, kb.w};
    uint32_t vv[8] = {va.x, va.y, va.z, va.w, vb.x, vb.y, vb.z, vb.w};
    float s = 0.f;
#pragma unroll
    for (int i = 0; i < 8; i++) { s = fmaf(q[2 * i], bf_lo(kk[i]), s); s = fmaf(q[2 * i + 1], bf_hi(kk[i]), s); }
    s = rbf(s) * 0.25f;
    if (s > m) {
      float c = __expf(m - s);
      l *= c;
#pragma unroll
      for (int i = 0; i < 16; i++) o[i] *= c;
      m = s;
    }
    float p = __expf(s - m);
    l += p;
#pragma unroll
    for (int i = 0; i < 8; i++) { o[2 * i] = fmaf(p, bf_lo(vv[i]), o[2 * i]); o[2 * i + 1] = fmaf(p, bf_hi(vv[i]), o[2 * i + 1]); }
  }
  float m2 = __shfl_xor_sync(~0u, m, 1);
  float mm = fmaxf(m, m2);
  float c = __expf(m - mm);
  l *= c; l += __shfl_xor_sync(~0u, l, 1);
  float inv = 1.f / l;
  uint32_t r[8];
#pragma unroll
  for (int i = 0; i < 16; i++) { o[i] *= c; o[i] += __shfl_xor_sync(~0u, o[i], 1); o[i] *= inv; }
#pragma unroll
  for (int i = 0; i < 8; i++) r[i] = pack_bf16(o[2 * i], o[2 * i + 1]);
  if (half == 0) sts4(dst, r[0], r[1], r[2], r[3]); else sts4(dst, r[4], r[5], r[6], r[7]);
  fence_async();
}

struct Params { const __nv_bfloat16* wk; const __nv_bfloat16* wv; const __nv_bfloat16* xa; const __nv_bfloat16* wq; __nv_bfloat16* out; };
__device__ __forceinline__ void cp16(uint32_t dst, const void* src) { asm volatile("cp.async.cg.shared.global [%0], [%1], 16;" :: "r"(dst), "l"(src) : "memory"); }

__device__ __forceinline__ void helper_cta(const int h, const uint32_t sb, const uint32_t bars, const int wg, const int w4,
                                           const CUtensorMap* mQ, const CUtensorMap* mOs) {
  const int lane = threadIdx.x & 31;
  mbar_wait(BAR_GO, 0);
  const int cb = wg & 1, col = h * 128 + cb * 64, row0 = S_TOK + (wg >> 1) * 1024;
  const uint32_t buf = sb + wg * 49152;
  if (w4 == 0 && elect_one()) {
    fence_async_all();
#pragma unroll 1
    for (int u = 0; u < 3; u++) {
      mbar_expect_tx(BAR_TF(wg * 3 + u), 16384);
      tma2d(buf + u * 16384, mQ, col, row0 + u * 128, BAR_TF(wg * 3 + u));
    }
  }
  const int head = h * 8 + cb * 4 + w4;
  float4 a0 = make_float4(0, 0, 0, 0), a1 = a0, a2 = a0;
#pragma unroll 8
  for (int tt = 0; tt < 16; tt++) {
    const float4* src = g_kvp + ((tt * 32 + head) * 3) * 32 + lane;
    float4 u = src[0], v = src[32], w = src[64];
    a0.x += u.x; a0.y += u.y; a0.z += u.z; a0.w += u.w;
    a1.x += v.x; a1.y += v.y; a1.z += v.z; a1.w += v.w;
    a2.x += w.x; a2.y += w.y; a2.z += w.z; a2.w += w.w;
  }
  const uint32_t b00 = pack_bf16(a0.x, a0.y), b01 = pack_bf16(a0.z, a0.w);
  const uint32_t b10 = pack_bf16(a1.x, a1.y), b11 = pack_bf16(a1.z, a1.w);
  const uint32_t bz0 = pack_bf16(a2.x, a2.y), bz1 = pack_bf16(a2.z, a2.w);
  const int m = lane >> 3, r = lane & 7;
  const uint32_t off = ((m & 1) * 8 + r) * 128 + (((w4 * 2 + (m >> 1)) ^ r) << 4);
  int s = 0, ph = 0;
#pragma unroll 1
  for (int u = 0; u < 8; u++) {
    const uint32_t bb = buf + s * 16384;
    mbar_wait(BAR_TF(wg * 3 + s), ph);
#pragma unroll
    for (int mt = 0; mt < 8; mt++) {
      uint32_t a[4];
      ldsm4(bb + mt * 2048 + off, a);
      float n0[4] = {0, 0, 0, 0}, n1[4] = {0, 0, 0, 0}, dn[4] = {0, 0, 0, 0};
      mma_bf16(dn, a[0], a[1], a[2], a[3], bz0, bz1);
      mma_bf16(n0, a[0], a[1], a[2], a[3], b00, b01);
      mma_bf16(n1, a[0], a[1], a[2], a[3], b10, b11);
      const float i0 = rcpf(dn[0] + 1e-6f), i1 = rcpf(dn[2] + 1e-6f);
      stsm4(bb + mt * 2048 + off, pack_bf16(n0[0] * i0, n0[1] * i0), pack_bf16(n0[2] * i1, n0[3] * i1),
            pack_bf16(n1[0] * i0, n1[1] * i0), pack_bf16(n1[2] * i1, n1[3] * i1));
    }
    fence_async();
    named_bar(wg + 1, 128);
    if (w4 == 0 && lane == 0) {
      tma2d_store(mOs, bb, col, row0 + u * 128);
      bulk_commit();
      if (u >= 1 && u + 2 < 8) {
        asm volatile("cp.async.bulk.wait_group.read 1;" ::: "memory");
        const int sp = s == 0 ? 2 : s - 1;
        mbar_expect_tx(BAR_TF(wg * 3 + sp), 16384);
        tma2d(buf + sp * 16384, mQ, col, row0 + (u + 2) * 128, BAR_TF(wg * 3 + sp));
      }
    }
    __syncwarp();
    if (++s == 3) { s = 0; ph ^= 1; }
  }
  if (w4 == 0 && lane == 0) {
    bulk_wait_all();
    fence_async_all();
    flag_add(FLAG_LM((h * 2 + cb) * 2 + (wg >> 1)));
    if (wg == 0) TS(1, 8);
  }
}

#define STAGE(s) (sb + (2 - (s)) * 65536)
__device__ __forceinline__ uint32_t xa_addr(uint32_t sb, int kb) {
  return sb + (kb >= 1 && kb <= 4 ? OFF_V + 65536 + (kb - 1) * 8192 : 16384 + (kb == 5 ? OFF_K : (kb == 6 ? OFF_V : OFF_F)));
}
#define XA7_TMP (sb + OFF_K + 40960)
#define WKV_TMP (sb + OFF_K + 32768)
template <int TR> __device__ __forceinline__ void proj_kb(float* acc, uint32_t aA, uint32_t aB, int first) {
  const uint64_t da = make_desc(aA, TR ? 8192 : 16, 1024, 1);
  const uint64_t db = make_desc(aB, TR ? 16 : 8192, 1024, 1);
  wg_fence();
#pragma unroll
  for (int k = 0; k < 4; k++) wg_ss128<TR, 1 - TR>(acc, da + k * (TR ? 128 : 2), db + k * (TR ? 2 : 128), k != 0 || !first);
  wg_commit();
}
template <int TR> __device__ __forceinline__ void proj_loop(float* acc, uint32_t sb, uint32_t bars, uint32_t offA, uint32_t offB,
                                                            int wg, uint32_t sWKV, const CUtensorMap* mW, int col, bool w0) {
  {
    float kv[4];
    if (threadIdx.x == 0) TS(0, 13);
    mbar_wait(BAR_XA(wg), 0);
    if (threadIdx.x == 0) TS(0, 1);
    const uint64_t da0 = make_desc(xa_addr(sb, 2 * wg), 16, 1024, 1);
    const uint64_t da1 = make_desc(wg == 3 ? XA7_TMP : xa_addr(sb, 2 * wg + 1), 16, 1024, 1);
    const uint64_t db = make_desc(sWKV + wg * 2048, 128, 128, 0);
    wg_fence();
#pragma unroll
    for (int k = 0; k < 8; k++) wg_ss8<0, 1>(kv, (k < 4 ? da0 : da1) + (k & 3) * 2, db + k * 16, k != 0);
    wg_commit();
    wg_wait<0>();
    fence_regs<4>(kv);
    named_bar(wg + 1, 128);
    sts4(sWKV + threadIdx.x * 16, __float_as_uint(kv[0]), __float_as_uint(kv[1]), __float_as_uint(kv[2]), __float_as_uint(kv[3]));
    __syncwarp();
    if ((threadIdx.x & 31) == 0) mbar_arrive(BAR_GO);
  }
  int s = 0, ph = 0;
#pragma unroll 1
  for (int kb = 0; kb < 8; kb++) {
    mbar_wait(BAR_FULL(s), ph);
    if (threadIdx.x == 0) TSW(0, 2 + kb);
    if (TR == 0) mbar_wait(BAR_XA(kb >> 1), 0);
    proj_kb<TR>(acc, TR ? STAGE(s) + offA : xa_addr(sb, kb), STAGE(s) + offB, kb == 0);
    wg_wait<0>();
    if (w0 && elect_one()) {
      if (kb < 5) {
        mbar_expect_tx(BAR_FULL(s), TR ? 8192 : 16384);
        tma2d(STAGE(s) + (TR ? offA : 0), mW, col, (kb + 3) * 64, BAR_FULL(s));
        if (TR == 0) tma2d(STAGE(s) + 8192, mW, col + 64, (kb + 3) * 64, BAR_FULL(s));
      }
      if (kb < 7) mbar_arrive(BAR_EMPTY(s));
      if (TR == 0 && kb == 4) mbar_arrive(BAR_VB(1));
    }
    __syncwarp();
    if (++s == 3) { s = 0; ph ^= 1; }
  }
  wg_wait<0>();
  fence_regs<64>(acc);
}

__device__ __forceinline__ uint32_t tail_slots(int isB, int n) {
  if (n < 4) return n < 2 ? (n == 0 ? 0x0D0C0B0Au : 0x04000F0Eu) : (n == 2 ? 0x18141008u : 0x15110501u);
  if (isB) return n < 6 ? (n == 4 ? 0x19120602u : 0x0D0C0B0Au) : (n == 6 ? 0x04000F0Eu : 0x13070316u);
  return n < 6 ? (n == 4 ? 0x1902031Au : 0x12061307u) : (n == 6 ? 0x16091B17u : 0x0D0C0B0Au);
}

__device__ __forceinline__ void take_role(uint32_t sM, int wg) {
  uint32_t r;
  asm volatile("atom.shared.add.u32 %0, [%1], 1;" : "=r"(r) : "r"(sM + 20) : "memory");
  sts1(sM + 32 + wg * 4, r);
}

__global__ void __launch_bounds__(640, 1)
k1_main(const __grid_constant__ CUtensorMap mXA64, const __grid_constant__ CUtensorMap mXB,
        const __grid_constant__ CUtensorMap mWq, const __grid_constant__ CUtensorMap mWqkv,
        const __grid_constant__ CUtensorMap mQst, const __grid_constant__ CUtensorMap mOst,
        const __grid_constant__ CUtensorMap mO, const __grid_constant__ CUtensorMap mWoA,
        const __grid_constant__ CUtensorMap mWoB,
        const __grid_constant__ CUtensorMap mO16, const Params prm) {
  if (threadIdx.x >= 608 && threadIdx.x < 612) {
    const CUtensorMap* pm = &mXA64 + (threadIdx.x - 608);
    asm volatile("prefetch.tensormap [%0];" :: "l"(pm) : "memory");
  }
  extern __shared__ uint8_t smem_raw[];
  const uint32_t sb = (smem_u32(smem_raw) + 1023u) & ~1023u;
  const uint32_t bars = sb + OFF_MISC, sM = bars + 512, sT = bars + 1024;
  const int tid = threadIdx.x, warp = __shfl_sync(~0u, tid >> 5, 0), wg = warp >> 2, w4 = warp & 3, lane = tid & 31;
  const bool helper = blockIdx.x >= 128;
  if (tid == 0) TS(0, 0);
  const int G = blockIdx.x >> 4, gi = GIMAP(blockIdx.x & 15);
  const int tbA = G * 4 + (gi >> 2), hg = gi & 3;
  const int ttB = (G >> 1) * 4 + (gi >> 2), hq = (G & 1) * 4 + (gi & 3);
  const int isB = tbA & 1, tok0 = (tbA >> 1) * 128;
  auto issue = [&](int kb, int s, int part) {
    const uint32_t fb = BAR_FULL(s), st = STAGE(s);
    if (part & 1) {
      mbar_expect_tx(fb, 57344);
      asm volatile("mbarrier.arrive.shared::cta.b64 _, [%0], 4;" :: "r"(fb) : "memory");
      tma2d(st, &mWq, hg * 128, kb * 64, fb);
      tma2d(st + 8192, &mWq, hg * 128 + 64, kb * 64, fb);
      tma2d(st + 49152, &mXB, kb * 64, ttB * 128, fb);
      tma2d(st + 24576, &mWqkv, hq * 64, kb * 64, fb);
    }
    if (part & 2) {
      tma2d(st + 32768, &mWqkv, 512 + hq * 64, kb * 64, fb);
      tma2d(st + 40960, &mWqkv, 1024 + hq * 64, kb * 64, fb);
    }
  };
  const uint32_t sOne = sb + OFF_V + 65536, sWKV = WKV_TMP;
  if (warp >= 16) {
    if (warp == 17) {
      if (elect_one()) {
        mbar_init(BAR_BDONE, 8); mbar_init(BAR_Q, 6); mbar_init(BAR_GO, helper ? 1 : 16); mbar_init(BAR_Q2, 1);
        mbar_init(BAR_OD(0), 16); mbar_init(BAR_OD(1), 16); mbar_init(BAR_CL(0), 1); mbar_init(BAR_FULL(2), 5);
#pragma unroll
        for (int i = 0; i < 4; i++) mbar_init(BAR_CL(i + 1), i == 0 ? 5 : 4);
#pragma unroll
        for (int i = 0; i < 3; i++) { mbar_init(BAR_EMPTY(i), 4); mbar_init(BAR_KV(i), 1); mbar_init(BAR_VB(i), i == 2 ? 4 : 1); }
        sts1(sM + 20, 0);
        asm volatile("fence.mbarrier_init.release.cluster;" ::: "memory");
      }
    } else if (warp == 18) {
      if (elect_one()) {
#pragma unroll
        for (int i = 0; i < 3; i++) mbar_init(BAR_TE(i), 4);
        mbar_init(BAR_RL, 3);
#pragma unroll
        for (int i = 0; i < 16; i++) mbar_init(BAR_TF(i), 1);
        asm volatile("fence.mbarrier_init.release.cluster;" ::: "memory");
      }
    } else if (warp == 16 && !helper && elect_one()) {
#pragma unroll
      for (int w = 0; w < 4; w++) mbar_init(BAR_XA(w), 1);
      mbar_init(BAR_FULL(0), 5); mbar_init(BAR_FULL(1), 5);
      asm volatile("fence.mbarrier_init.release.cluster;" ::: "memory");
#pragma unroll
      for (int w = 0; w < 4; w++) {
        mbar_expect_tx(BAR_XA(w), 16384);
        tma2d(xa_addr(sb, 2 * w), &mXA64, w * 128, tbA * 64, BAR_XA(w));
        tma2d(w == 3 ? XA7_TMP : xa_addr(sb, 2 * w + 1), &mXA64, w * 128 + 64, tbA * 64, BAR_XA(w));
      }
      TS(0, 14);
      issue(0, 0, 3);
    }
  } else if (!helper) {
    const uint4 v = __ldg((const uint4*)(hg >= 2 ? prm.wv : prm.wk) + tid * 2 + (hg & 1));
    sts4(sWKV + tid * 16, v.x, v.y, v.z, v.w);
    fence_async();
  }
  __syncthreads();
  if (wg == 4) {
    if (w4 == 0 && !helper && elect_one()) { issue(1, 1, 3); issue(2, 2, 1); TS(0, 15); }
    asm volatile("setmaxnreg.dec.sync.aligned.u32 32;");
    const uint32_t ep = g_epoch[blockIdx.x] + 1;
    if (helper) {
      if (w4 == 0 && elect_one()) {
        flag_wait(FLAG_B(blockIdx.x - 128), ep * 32);
        fence_async_all();
        TS(1, 10);
        mbar_arrive(BAR_GO);
        g_epoch[blockIdx.x] = ep;
      }
      return;
    }
    mbar_wait(BAR_GO, 0);
    {
      uint32_t a[4], b[4];
      float c[4];
      lds4(sWKV + (tid - 512) * 16, a);
      lds4(sWKV + 2048 + (tid - 512) * 16, b);
#pragma unroll
      for (int i = 0; i < 4; i++) c[i] = __uint_as_float(a[i]) + __uint_as_float(b[i]);
      lds4(sWKV + 4096 + (tid - 512) * 16, a);
      lds4(sWKV + 6144 + (tid - 512) * 16, b);
#pragma unroll
      for (int i = 0; i < 4; i++) c[i] += __uint_as_float(a[i]) + __uint_as_float(b[i]);
      sts1(sT + w4 * 256 + lane * 4, pack_bf16(c[0], c[1]));
      sts1(sT + w4 * 256 + 128 + lane * 4, pack_bf16(c[2], c[3]));
    }
    named_bar(9, 128);
    if (w4 == 0 && elect_one()) issue(2, 2, 2);
    auto write_ones = [&]() {
      mbar_wait_long(BAR_VB(1), 0);
      int c = ((w4 & 1) * 32 + lane);
#pragma unroll 4
      for (int key = c; key < S_TOK; key += 64) {
        sts4(sOne + key * 16, c < 24 ? 0x00003F80u : 0x00004E80u, 0u, 0u, 0u);
        c += 64; if (c >= STEPK) c -= STEPK;
      }
      fence_async();
      __syncwarp();
      if (lane == 0) mbar_arrive(BAR_Q);
    };
    if (w4 == 0) {
      int s = 0, ph = 0;
#pragma unroll 1
      for (int kb = 3; kb < 8; kb++) {
        mbar_wait(BAR_EMPTY(s), ph);
        if (elect_one()) {
          mbar_expect_tx(BAR_FULL(s), kb == 7 ? 24576 : 16384);
          tma2d(STAGE(s) + 49152, &mXB, kb * 64, ttB * 128, BAR_FULL(s));
          if (kb == 7) tma2d(STAGE(s) + 16384, &mXA64, kb * 64, tbA * 64, BAR_FULL(s));
        }
        if (++s == 3) { s = 0; ph ^= 1; }
      }
      flag_wait(FLAG_KV, ep * 128);
      fence_async_all();
      if (lane == 0) TS(0, 11);
#pragma unroll 1
      for (int m = 0; m < 2; m++) {
        mbar_wait(m == 0 ? BAR_EMPTY(2) : BAR_EMPTY(0), 1 - m);
        if (elect_one()) {
          const uint32_t fb = m == 0 ? BAR_KV(0) : BAR_VB(0);
          mbar_expect_tx(fb, 2 * 7 * STEPK * 16);
#pragma unroll
          for (int p = 0; p < 2; p++) bulk_g2s(sb + m * OFF_V + p * 32768, g_KV + (m * 2 + p) * S_TOK, 7 * STEPK * 16, fb);
        }
      }
      mbar_wait(BAR_Q, 0);
      if (elect_one()) {
#pragma unroll
        for (int c = 1; c < 3; c++) {
          const int k0 = c == 1 ? 7 * STEPK : 13 * STEPK, k1 = c == 1 ? 13 * STEPK : S_TOK;
          const uint32_t bytes = (k1 - k0) * 16;
          mbar_expect_tx(BAR_KV(c), 4 * bytes);
#pragma unroll
          for (int p = 0; p < 4; p++)
            bulk_g2s(sb + (p >> 1) * OFF_V + (p & 1) * 32768 + k0 * 16, g_KV + p * S_TOK + k0, bytes, BAR_KV(c));
        }
      }
      mbar_wait_long(BAR_CL(1), 0);
      flag_wait(isB ? FLAG_LM((lane & 7) * 2 + (tbA >> 4)) : FLAG_OA(tbA * 4 + (lane & 7), 0), ep);
      __syncwarp();
      fence_async_all();
      if (lane == 0) TS(2, 13);
      const CUtensorMap* mW = isB ? &mWoB : &mWoA;
#pragma unroll 1
      for (int it = 0; it < 8; it++) {
        const int n = (!isB && it >= 6) ? 13 - it : it;
        uint32_t wb = BAR_CL(n < 3 ? 0 : (n == 3 ? 2 : 3));
        if (isB) { if (n >= 5) wb = n == 7 ? BAR_CL(4) : BAR_TE(n - 5); }
        else if (n >= 6) wb = n == 6 ? BAR_CL(4) : BAR_TE(0);
        if (it < 6) mbar_wait_long(wb, 0); else mbar_wait(wb, 0);
        const uint32_t sl = tail_slots(isB, n), fb = BAR_TF(n);
        const bool withX = isB || n < 4;
        const int k0 = isB ? n * 64 : (n < 4 ? n * 128 : ((hg + n) & 3) * 128 + 64);
        if (elect_one()) {
          mbar_expect_tx(fb, withX ? 32768 : 16384);
          if (withX) {
            tma2d(sb + (sl & 255) * 8192, &mO, k0, isB * S_TOK + tok0, fb);
            tma2d(sb + ((sl >> 8) & 255) * 8192, &mO, k0, isB * S_TOK + tok0 + 64, fb);
          }
          tma2d(sb + ((sl >> 16) & 255) * 8192, mW, hg * 128, k0, fb);
          tma2d(sb + (sl >> 24) * 8192, mW, hg * 128 + 64, k0, fb);
        }
      }
      if (lane == 0) g_epoch[blockIdx.x] = ep;
    } else if (w4 == 3) {
      write_ones();
      flag_wait(FLAG_KV, ep * 128);
      const uint4 a = *(const uint4*)(g_stats + lane * 4);
      const float kmax2 = __uint_as_float(__reduce_max_sync(~0u, a.x)) + __uint_as_float(__reduce_max_sync(~0u, a.y));
      const float vmax = __uint_as_float(__reduce_max_sync(~0u, max(a.z, a.w)));
      const float lv = vmax > 0.f ? __log2f(vmax) : 0.f;
      const float lim = fminf(90.f, fminf(91.f + lv, 95.f - lv));
      float thr = -1.f;
      if (vmax < 1e27f && kmax2 <= 65536.f && lim > 2.f) thr = fminf(60000.f, (lim * lim - 1.f) / (kmax2 * 1.02f + 1e-30f));
      mbar_wait_long(BAR_VB(2), 0);
      uint32_t nmax = 0;
#pragma unroll 2
      for (int i = 0; i < 16; i++) {
        uint32_t x[4], y[4];
        const uint32_t ad = sb + OFF_F + i * 1024 + (lane >> 3) * 256 + (lane & 7) * 16;
        lds4(ad, x); lds4(ad + 128, y);
        uint32_t n = hfma2(x[0], x[0], hfma2(x[1], x[1], hfma2(x[2], x[2], hfma2(x[3], x[3], 0u))));
        n = hfma2(y[0], y[0], hfma2(y[1], y[1], hfma2(y[2], y[2], hfma2(y[3], y[3], n))));
        n = hadd2(n, n >> 16);
        nmax = max(nmax, n & 0x7FFFu);
      }
      nmax = __reduce_max_sync(~0u, nmax);
      const bool ok = __half2float(__ushort_as_half((unsigned short)nmax)) <= thr;
      if (lane == 0) { sts1(sM + 16, ok ? 1u : 0u); mbar_arrive(BAR_Q2); }
    } else {
      const int tok = (w4 - 1) * 32 + lane;
      int step, col;
      if ((tbA & 3) == 0) {
        const int b8 = tbA >> 2;
        if (tok < 22) { step = tok; col = 24 + b8; }
        else { const int c = tok >= 43; step = tok - 22 - 21 * c; col = 32 + b8 * 2 + c; }
      } else {
        const int b24 = (tbA >> 2) * 3 + (tbA & 3) - 1;
        if (tok < 42) { const int c = tok >= 21; step = tok - 21 * c; col = 48 + b24 * 2 + c; }
        else { step = tok - 42; col = b24; }
      }
      const int kap = step * STEPK + col;
      const bool chained = col >= 24;
      uint32_t v[4], o[4];
      lds4(sT + tok * 16, v);
      g_KV[(4 + hg) * S_TOK + kap] = make_uint4(v[0], v[1], v[2], v[3]);
      float st = 0.f;
      if (hg < 2) {
        o[0] = o[1] = o[2] = o[3] = 0;
        if (chained && step > 0) lds4(sT + tok * 16 - 16, o);
        const float sc = chained ? 2.f : 1.f;
#pragma unroll
        for (int u = 0; u < 4; u++) {
          const float x = bf_lo(v[u]), y = bf_hi(v[u]);
          st += x * x + y * y;
          o[u] = pack_f16((x - bf_lo(o[u])) * sc, (y - bf_hi(o[u])) * sc);
        }
      } else {
        const float sc = chained ? VSHIFT : 1.f;
#pragma unroll
        for (int u = 0; u < 4; u++) { float x = bf_lo(v[u]), y = bf_hi(v[u]); st += fabsf(x) + fabsf(y); o[u] = pack_bf16(x * sc, y * sc); }
      }
      g_KV[hg * S_TOK + kap] = make_uint4(o[0], o[1], o[2], o[3]);
      const uint32_t um = __reduce_max_sync(~0u, __float_as_uint(st) & 0x7FFFFFFFu);
      if (w4 == 2) {
        if (lane == 0) sts1(sM + 24, um);
        named_arrive(10, 64);
        write_ones();
        if (!isB) {
          mbar_wait_long(BAR_CL(3), 0);
          mbar_wait_long(BAR_RL, 0);
          uint32_t pend = 0xFE;
          const int li = lane & 7;
          const uint32_t* fl = FLAG_OA((tbA + (li & 1)) * 4 + ((hg + (li >> 1)) & 3), 1);
#pragma unroll 1
          for (int it = 0; pend; it++) {
            uint32_t fv;
            asm volatile("ld.acquire.gpu.global.u32 %0, [%1];" : "=r"(fv) : "l"(fl) : "memory");
            uint32_t go = __ballot_sync(~0u, (int32_t)(fv - ep) >= 0 && mbar_test(li >= 6 ? BAR_TE(0) : BAR_CL(4), 0)) & pend;
            pend &= ~go;
            if (go) fence_async_all();
#pragma unroll 1
            while (go) {
              const int b = __ffs(go) - 1;
              go &= go - 1;
              const uint32_t slot = (tail_slots(0, 4 + (b >> 1)) >> (8 * (b & 1))) & 255;
              if (elect_one()) {
                mbar_expect_tx(BAR_TF(8 + b), 8192);
                tma2d(sb + slot * 8192, &mO, ((hg + (b >> 1)) & 3) * 128 + 64, tok0 + (b & 1) * 64, BAR_TF(8 + b));
              }
            }
            if (it > 2000000) __trap();
          }
          if (lane == 0) TS(2, 14);
        }
      }
      else {
        named_bar(10, 64);
        if (elect_one()) {
          g_stats[tbA * 4 + hg] = max(um, lds1(sM + 24));
          fence_async_all();
          flag_add(FLAG_KV);
          TS(1, 9);
          mbar_wait_long(BAR_BDONE, 0);
          tma2d_store(&mQst, sb + OFF_F + 49152, hq * 64, S_TOK + ttB * 128);
          bulk_commit();
          bulk_wait_all();
          fence_async_all();
          flag_add(FLAG_B(hq >> 1));
          TS(0, 12);
          mbar_wait(BAR_Q, 0);
          mbar_arrive(BAR_CL(0));
#pragma unroll 1
          for (int p = 0; p < 2; p++) {
            mbar_wait_long(BAR_OD(p), 0);
            if (p == 0) {
#pragma unroll
              for (int w = 0; w < 4; w++) tma2d_store(&mO16, sb + OFF_F + w * 2048, hg * 128 + w * 16, tbA * 64);
            } else {
              tma2d_store(&mO, sb + 26 * 8192, hg * 128 + 64, tbA * 64);
            }
            bulk_commit();
            bulk_wait_all();
            if (p == 0) mbar_arrive(BAR_CL(1));
            PUBLISH(FLAG_OA(tbA * 4 + hg, p));
          }
          TS(2, 0);
        }
      }
    }
    return;
  }
  if (helper) { helper_cta(blockIdx.x - 128, sb, bars, wg, w4, &mQst, &mOst); return; }

  {
    float acc[64];
    if (wg == 0) proj_loop<0>(acc, sb, bars, 16384, 0, wg, sWKV, &mWq, hg * 128, w4 == 0);
    else proj_loop<1>(acc, sb, bars, 16384 + wg * 8192, 49152, wg, sWKV, &mWqkv, (wg - 1) * 512 + hq * 64, w4 == 0);
    if (tid == 0) TS(0, 10);
    const uint32_t sF = sb + OFF_F;
    const uint32_t qa = sF + w4 * 512 + ((lane >> 3) & 1) * 256 + (lane >> 4) * 128 + (lane & 7) * 16;
    if (wg == 0) {
#pragma unroll
      for (int hd = 0; hd < 4; hd++)
        stsm4(qa + hd * 2048, pack_f16(acc[8 * hd] * QSCALE, acc[8 * hd + 1] * QSCALE), pack_f16(acc[8 * hd + 2] * QSCALE, acc[8 * hd + 3] * QSCALE),
              pack_f16(acc[8 * hd + 4] * QSCALE, acc[8 * hd + 5] * QSCALE), pack_f16(acc[8 * hd + 6] * QSCALE, acc[8 * hd + 7] * QSCALE));
      fence_async();
      __syncwarp();
      if (lane == 0) mbar_arrive(BAR_Q);
    } else {
      if (wg != 3) named_arrive(6, 384);
      if (wg != 1) named_arrive(8, 384);
    }
    asm volatile("setmaxnreg.inc.sync.aligned.u32 112;");
    fence_regs<64>(acc);
    if (wg == 0) {
#pragma unroll
      for (int hd = 4; hd < 8; hd++)
        stsm4(qa + hd * 2048, pack_f16(acc[8 * hd] * QSCALE, acc[8 * hd + 1] * QSCALE), pack_f16(acc[8 * hd + 2] * QSCALE, acc[8 * hd + 3] * QSCALE),
              pack_f16(acc[8 * hd + 4] * QSCALE, acc[8 * hd + 5] * QSCALE), pack_f16(acc[8 * hd + 6] * QSCALE, acc[8 * hd + 7] * QSCALE));
      fence_async();
      __syncwarp();
      if (lane == 0) mbar_arrive(BAR_VB(2));
    } else if (wg == 3) {
      named_bar(6, 384);
      const int t = tid & 127;
#pragma unroll
      for (int j = 0; j < 8; j++)
        sts4(sF + 24576 + j * 2048 + t * 16, pack_bf16(acc[8 * j], acc[8 * j + 1]), pack_bf16(acc[8 * j + 2], acc[8 * j + 3]),
             pack_bf16(acc[8 * j + 4], acc[8 * j + 5]), pack_bf16(acc[8 * j + 6], acc[8 * j + 7]));
      named_arrive(7, 256);
    } else {
      uint32_t p[32];
#pragma unroll
      for (int i = 0; i < 32; i++) p[i] = phi2(acc[2 * i], acc[2 * i + 1]);
      if (wg == 1) {
        named_bar(8, 384);
        const int m = lane >> 3, r = lane & 7;
#pragma unroll
        for (int j = 0; j < 16; j += 2) {
          const int tok = (j + (m >> 1)) * 8 + r;
          const int chunk = w4 * 2 + (m & 1);
          stsm4t(sF + 49152 + tok * 128 + ((chunk ^ r) << 4), p[2 * j], p[2 * j + 1], p[2 * j + 2], p[2 * j + 3]);
        }
        fence_async();
      } else {
        named_bar(7, 256);
        float kv0[4] = {0, 0, 0, 0}, kv1[4] = {0, 0, 0, 0}, z0[4] = {0, 0, 0, 0}, z1[4] = {0, 0, 0, 0};
        const uint32_t one = 0x3F803F80u;
        const int t = tid & 127;
#pragma unroll
        for (int j = 0; j < 8; j++) {
          uint32_t a[4];
          lds4(sF + 24576 + j * 2048 + t * 16, a);
          mma_bf16(kv0, a[0], a[1], a[2], a[3], p[4 * j], p[4 * j + 2]);
          mma_bf16(kv1, a[0], a[1], a[2], a[3], p[4 * j + 1], p[4 * j + 3]);
          mma_bf16(z0, one, one, one, one, p[4 * j], p[4 * j + 2]);
          mma_bf16(z1, one, one, one, one, p[4 * j + 1], p[4 * j + 3]);
        }
        float4* dst = g_kvp + ((ttB * 32 + hq * 4 + w4) * 3) * 32 + lane;
        dst[0] = make_float4(kv0[0], kv0[1], kv1[0], kv1[1]);
        dst[32] = make_float4(kv0[2], kv0[3], kv1[2], kv1[3]);
        dst[64] = make_float4(z0[0], z0[1], z1[0], z1[1]);
      }
      __syncwarp();
      if (lane == 0) mbar_arrive(BAR_BDONE);
    }
  }

  bool safe = true;
  {
    const uint32_t c63 = 0x1F801F80u + (threadIdx.x >> 20);
    const uint32_t m1 = (gridDim.x >> 20) - 1u;
    const uint64_t dK0 = make_desc(sb + OFF_K, 32768, 128, 0);
    const uint64_t dV0 = make_desc(sb + OFF_V, 128, 32768, 0);
    constexpr uint32_t dKV = ((2048u - 8u)  __H0__ ) + STEPK - (OFF_V - OFF_K) / 16;
    float Sm[12], Sp[36], O[12];
    uint32_t P[24];
    uint64_t dQ = make_desc(sb + OFF_F + wg * 2048, 128, 256, 0);
#pragma unroll
    for (int i = 0; i < 36; i++) Sp[i] = SMAGIC;
#pragma unroll
    for (int i = 0; i < 12; i++) Sm[i] = 0.f;
    fence_regs<12>(Sm); fence_regs<36>(Sp);
    mbar_wait(BAR_Q, 0);
    mbar_wait(BAR_KV(0), 0);
    wg_fence();
    wg_qs72<1>(Sp, dQ, dK0 + 24);
    wg_qs24<0>(Sm, dQ, dK0);
    wg_commit();
    wg_wait<0>();
    fence_regs<12>(Sm); fence_regs<36>(Sp);
#pragma unroll 1
    for (int pass = 0; pass < 2; pass++) {
#pragma unroll
      for (int i = 0; i < 12; i++) O[i] = 0.f;
      fence_regs<12>(O);
      if (tid == 0) TSW(1, 2 + 2 * pass);
      uint32_t vlo = (uint32_t)dV0;
#pragma unroll 1
      for (int seg = 0; seg < 4; seg++) {
        if (pass == 0) {
          if (seg < 3) mbar_wait(seg == 0 ? BAR_VB(0) : BAR_KV(seg), 0);
        } else if (seg >= 1) {
          if ((tid & 127) == 0) {
            mbar_arrive(BAR_CL(seg));
          }
          __syncwarp();
        }
        if ((tid & 127) == 0) TSW(4 + wg, pass * 5 + seg);
        const uint32_t vend = vlo + (seg == 3 ? 3 : 6) * STEPK;
#pragma unroll 1
        for (; vlo != vend; vlo += 3 * STEPK) {
          uint64_t dK, dV;
          asm("mov.b64 %0, {%1, %2};" : "=l"(dK) : "r"(vlo + dKV), "r"(8u));
          asm("mov.b64 %0, {%1, %2};" : "=l"(dV) : "r"(vlo), "r"(2048u));
#pragma unroll
          for (int u = 0; u < 3; u++) {
          { uint32_t w[18], y[18], z[18]; float e[12];
            X_MU(0) X_PR(0) X_LO(0) X_IM(0) X_MU(1) X_FM(0) X_PR(1) X_LO(1) X_IM(1) X_MU(2) X_FM(1) X_PR(2)
            X_LO(2) X_MU(3) X_IM(2) X_FM(2) X_PR(3) X_LO(3) X_PK(0) X_MU(4) X_IM(3) X_FM(3) X_PR(4) X_LO(4)
            X_MU(5) X_IM(4) X_FM(4) X_PR(5) X_PK(1) X_MU(6) X_LO(5) X_IM(5) X_FM(5) X_PR(6) X_MU(7) X_LO(6)
            X_IM(6) X_FM(6) X_MU(8) X_PR(7) X_PK(2) X_LO(7) X_IM(7) X_FM(7) X_MU(9) X_PR(8) X_LO(8) X_IM(8)
            X_FM(8) X_PK(3) X_MU(10) X_PR(9) X_LO(9) X_IM(9) X_MU(11) X_FM(9) X_PR(10) X_LO(10) X_IM(10) X_PK(4)
            X_FM(10) X_PR(11) X_LO(11) X_IM(11) X_FM(11) X_PR(12) X_LO(12) X_PK(5) X_IM(12) X_FM(12) X_PR(13) X_LO(13)
            X_IM(13) X_FM(13) X_PR(14) X_LO(14) X_IM(14) X_FM(14) X_PR(15) X_LO(15) X_IM(15) X_FM(15) X_PR(16) X_LO(16)
            X_IM(16) X_FM(16) X_PR(17) X_LO(17) X_IM(17) X_FM(17) }
          fence_regs<24>(P);
          wg_fence();
          wg_pv24<1>(O, &P[20], dV + u * STEPK + 80);
          wg_pv24<1>(O, &P[16], dV + u * STEPK + 64);
          wg_pv24<1>(O, &P[12], dV + u * STEPK + 48);
          wg_pv24<1>(O, &P[8], dV + u * STEPK + 32);
          wg_pv24<1>(O, &P[4], dV + u * STEPK + 16);
          wg_pv24<1>(O, &P[0], dV + u * STEPK + 0);
          wg_qs72<1>(Sp, dQ, dK + u * STEPK + 24);
          wg_qs24<0>(Sm, dQ, dK + u * STEPK);
          wg_commit();
          wg_wait<0>();
          fence_regs<12>(Sm); fence_regs<36>(Sp); fence_regs<12>(O); fence_regs<24>(P);
          }
        }
      }
#pragma unroll
      for (int i = 0; i < 6; i++) P[i] = pack_bf16(ex2f(Sm[2 * i]), ex2f(Sm[2 * i + 1]));
      P[6] = exp2_pair_fix(Sp[0], Sp[1], c63, m1);
      P[7] = exp2_pair_fix(Sp[2], Sp[3], c63, m1);
      fence_regs<8>(P);
#pragma unroll
      for (int i = 0; i < 36; i++) Sp[i] = SMAGIC;
      fence_regs<36>(Sp);
      mbar_wait(pass == 0 ? BAR_Q2 : BAR_CL(3), 0);
      const uint32_t sO = pass == 0 ? sb + OFF_F + wg * 2048 + w4 * 512 + (lane & 15) * 32 + (lane >> 4) * 16
                                    : sb + 26 * 8192 + (w4 * 16 + (lane & 15)) * 128 + (((wg * 2 + (lane >> 4)) ^ (lane & 7)) << 4);
      dQ += 512;
      wg_fence();
      wg_pv24<1>(O, &P[0], dV0 + 21 * STEPK);
      wg_pv24<1>(O, &P[4], dV0 + 21 * STEPK + 16);
      wg_commit();
      wg_qs72<1>(Sp, dQ, dK0 + 24);
      wg_qs24<0>(Sm, dQ, dK0);
      wg_commit();
      wg_wait<1>();
      fence_regs<12>(O);
      const float l0 = __shfl_sync(~0u, O[8], lane & ~3), l1 = __shfl_sync(~0u, O[10], lane & ~3);
      const float i0 = rcpf(l0), i1 = rcpf(l1);
      stsm4(sO,
            pack_bf16(O[0] * i0, O[1] * i0), pack_bf16(O[2] * i1, O[3] * i1),
            pack_bf16(O[4] * i0, O[5] * i0), pack_bf16(O[6] * i1, O[7] * i1));
      fence_async();
      {
        safe = __all_sync(~0u, lds1(sM + 16) != 0);
      }
      if (safe && lane == 0) mbar_arrive(BAR_OD(pass));
      wg_wait<0>();
      fence_regs<12>(Sm); fence_regs<36>(Sp);
      if (!safe) break;
      if ((tid & 127) == 0) TSW(4 + wg, pass * 5 + 4);
      if (tid == 0) TSW(1, 3 + 2 * pass);
    }
  }
  if (!safe) {
    if ((tid & 127) == 0) { mbar_arrive(BAR_CL(1)); mbar_arrive(BAR_CL(2)); mbar_arrive(BAR_CL(3)); }
#pragma unroll 1
    for (int pass = 0; pass < 2; pass++) {
      const int t = tid & 127;
      mbar_wait(BAR_CL(3), 0);
      attn_slow(prm.xa + (size_t)tbA * 64 * D_MOD, prm.wq + (hg * 8 + pass * 4 + wg) * 16,
                pass == 0 ? sb + OFF_F + wg * 2048 + t * 16
                          : sb + 26 * 8192 + (t >> 1) * 128 + (((wg * 2 + (t & 1)) ^ ((t >> 1) & 7)) << 4));
      __syncwarp();
      if (lane == 0) mbar_arrive(BAR_OD(pass));
    }
  }

  {
    named_bar(wg + 1, 128);
    if ((tid & 127) == 0) { mbar_arrive(BAR_CL(4)); mbar_arrive(BAR_RL); }
    if ((tid & 127) == 0) TSW(4 + wg, 10);
    const int m = lane >> 3, r = lane & 7;
    const int hf = wg & 1, ch = wg >> 1;
    mbar_wait(BAR_CL(4), 0);
    float acc[32];
#pragma unroll 1
    for (int n = 0; n < 8; n++) {
      const uint32_t sl = tail_slots(isB, n);
      const uint64_t da = make_desc(sb + ((sl >> (8 * hf)) & 255) * 8192, 16, 1024, 1);
      const uint64_t db = make_desc(sb + ((sl >> (16 + 8 * ch)) & 255) * 8192, 8192, 1024, 1);
      mbar_wait(BAR_TF(n), 0);
      if (!isB && n >= 4) mbar_wait(n == 4 && hf == 0 ? BAR_OD(1) : BAR_TF(2 * n + hf), 0);
      if (tid == 128) TSW(2, 2 + n);
      wg_fence();
#pragma unroll
      for (int k = 0; k < 4; k++) wg_ss64<0, 1>(acc, da + k * 2, db + k * 128, (n | k) != 0);
      wg_commit();
      wg_wait<1>();
      if (n >= 1 && n <= 3 && (tid & 127) == 0) mbar_arrive(BAR_TE(n - 1));
      __syncwarp();
    }
    mbar_wait(BAR_TE(2), 0);
    wg_wait<0>();
    fence_regs<32>(acc);
    if ((tid & 127) == 0) TSW(4 + wg, 11);
    const uint32_t x0 = sb + ((tail_slots(0, 2) >> (8 * wg)) & 255) * 8192 + w4 * 2048;
#pragma unroll
    for (int j = 0; j < 8; j += 2)
      stsm4(x0 + ((m & 1) * 8 + r) * 128 + (((j + (m >> 1)) ^ r) << 4),
            pack_bf16(acc[4 * j], acc[4 * j + 1]), pack_bf16(acc[4 * j + 2], acc[4 * j + 3]),
            pack_bf16(acc[4 * j + 4], acc[4 * j + 5]), pack_bf16(acc[4 * j + 6], acc[4 * j + 7]));
    __syncwarp();
    uint4* dst = (uint4*)(prm.out + (size_t)(tok0 + hf * 64 + w4 * 16 + m) * 1024 + isB * 512 + hg * 128 + ch * 64) + r;
#pragma unroll
    for (int i = 0; i < 4; i++) {
      uint32_t v[4];
      lds4(x0 + (4 * i + m) * 128 + ((r ^ ((4 * i + m) & 7)) << 4), v);
      dst[i * 512] = make_uint4(v[0], v[1], v[2], v[3]);
    }
    if ((tid & 127) == 0) TSM(2, 11 + hf);
  }
}

typedef CUresult (*EncodeFn)(CUtensorMap*, CUtensorMapDataType, cuuint32_t, void*, const cuuint64_t*, const cuuint64_t*,
                             const cuuint32_t*, const cuuint32_t*, CUtensorMapInterleave, CUtensorMapSwizzle,
                             CUtensorMapL2promotion, CUtensorMapFloatOOBfill);

static void make_map(EncodeFn enc, CUtensorMap* m, const void* ptr, uint64_t cols, uint64_t rows, uint32_t bc, uint32_t br,
                     CUtensorMapSwizzle sw = CU_TENSOR_MAP_SWIZZLE_128B) {
  cuuint64_t dims[2] = {cols, rows};
  cuuint64_t strides[1] = {cols * 2};
  cuuint32_t box[2] = {bc, br};
  cuuint32_t es[2] = {1, 1};
  enc(m, CU_TENSOR_MAP_DATA_TYPE_BFLOAT16, 2, (void*)ptr, dims, strides, box, es, CU_TENSOR_MAP_INTERLEAVE_NONE,
      sw, CU_TENSOR_MAP_L2_PROMOTION_L2_256B, CU_TENSOR_MAP_FLOAT_OOB_FILL_NONE);
}

extern "C" void kernel_launch(void* const* d_in, const int* in_sizes, int n_in, void* d_out, int out_size) {
  (void)in_sizes; (void)n_in; (void)out_size;
  static EncodeFn enc = nullptr;
  static void* pQ = nullptr; static void* pO = nullptr;
  if (!enc) {
    void* fn = nullptr; cudaDriverEntryPointQueryResult qr;
    cudaGetDriverEntryPoint("cuTensorMapEncodeTiled", &fn, cudaEnableDefault, &qr);
    enc = (EncodeFn)fn;
    cudaGetSymbolAddress(&pQ, g_Q);
    cudaGetSymbolAddress(&pO, g_O);
    cudaFuncSetAttribute(k1_main, cudaFuncAttributeMaxDynamicSharedMemorySize, SM_TOTAL);
  }
  CUtensorMap mXA64, mXB, mWq, mWqkv, mQst, mO, mOst, mWoA, mWoB, mO16;
  make_map(enc, &mXA64, d_in[0], 512, 2048, 64, 64);
  make_map(enc, &mWq, d_in[1], 512, 512, 64, 64);
  make_map(enc, &mWoA, d_in[4], 512, 512, 64, 64);
  make_map(enc, &mXB, d_in[5], 512, 2048, 64, 128);
  make_map(enc, &mWqkv, d_in[6], 1536, 512, 64, 64);
  make_map(enc, &mWoB, d_in[7], 512, 512, 64, 64);
  make_map(enc, &mQst, pQ, 512, 4096, 64, 128);
  make_map(enc, &mO, pO, 512, 4096, 64, 64);
  make_map(enc, &mOst, pO, 512, 4096, 64, 128);
  make_map(enc, &mO16, pO, 512, 4096, 16, 64, CU_TENSOR_MAP_SWIZZLE_NONE);
  Params prm{(const __nv_bfloat16*)d_in[2], (const __nv_bfloat16*)d_in[3], (const __nv_bfloat16*)d_in[0], (const __nv_bfloat16*)d_in[1], (__nv_bfloat16*)d_out};
  k1_main<<<132, 640, SM_TOTAL, cudaStreamPerThread>>>(mXA64, mXB, mWq, mWqkv, mQst, mOst, mO, mWoA, mWoB, mO16, prm);
}
```

```cpp
#include <cuda_runtime.h>
#include <cuda_bf16.h>
#include <cuda_fp16.h>
#include <cuda.h>
#include <stdint.h>

#define S_TOK 2048
#define D_MOD 512

__device__ __align__(1024) __nv_bfloat16 g_Q[2 * S_TOK * D_MOD];
__device__ __align__(1024) __nv_bfloat16 g_O[2 * S_TOK * D_MOD];
__device__ __align__(1024) uint4 g_KV[8 * S_TOK];
__device__ __align__(16) uint32_t g_stats[128];
__device__ __align__(16) float4 g_kvp[16 * 32 * 3 * 32];

#define TS(k, i) do {} while (0)
#define TSW(k, i) do {} while (0)
__device__ __forceinline__ uint32_t smem_u32(const void* p) { return (uint32_t)__cvta_generic_to_shared(p); }
__device__ __forceinline__ void mbar_init(uint32_t bar, int cnt) { asm volatile("mbarrier.init.shared::cta.b64 [%0], %1;" :: "r"(bar), "r"(cnt) : "memory"); }
__device__ __forceinline__ void mbar_expect_tx(uint32_t bar, uint32_t bytes) { asm volatile("mbarrier.arrive.expect_tx.shared::cta.b64 _, [%0], %1;" :: "r"(bar), "r"(bytes) : "memory"); }
__device__ __forceinline__ bool mbar_try(uint32_t bar, uint32_t parity) {
  uint32_t ok;
  asm volatile("{\n.reg .pred p;\nmbarrier.try_wait.parity.shared::cta.b64 p, [%1], %2;\nselp.b32 %0, 1, 0, p;\n}\n" : "=r"(ok) : "r"(bar), "r"(parity) : "memory");
  return ok;
}
__device__ __forceinline__ void mbar_wait(uint32_t bar, uint32_t parity) {
  asm volatile("{\n.reg .pred p;\n.reg .u32 c;\nmov.u32 c, 0;\n"
               "LW_%=:\n"
               "mbarrier.try_wait.parity.shared::cta.b64 p, [%0], %1;\n"
               "@p bra LD_%=;\n"
               "add.u32 c, c, 1;\n"
               "setp.lt.u32 p, c, 4000000;\n"
               "@p bra LW_%=;\n"
               "trap;\n"
               "LD_%=:\n}\n" :: "r"(bar), "r"(parity) : "memory");
}
__device__ __forceinline__ void mbar_arrive_cta(uint32_t bar, uint32_t cta) {
  asm volatile("{\n.reg .b32 ra;\nmapa.shared::cluster.u32 ra, %0, %1;\nmbarrier.arrive.shared::cluster.b64 _, [ra];\n}\n" :: "r"(bar), "r"(cta) : "memory");
}
__device__ __forceinline__ void cluster_sync() {
  asm volatile("barrier.cluster.arrive.relaxed.aligned;\nbarrier.cluster.wait.aligned;" ::: "memory");
}
__device__ __forceinline__ void tma2d(uint32_t dst, const CUtensorMap* m, int c0, int c1, uint32_t bar) {
  asm volatile("cp.async.bulk.tensor.2d.shared::cluster.global.mbarrier::complete_tx::bytes [%0], [%1, {%3, %4}], [%2];"
               :: "r"(dst), "l"(m), "r"(bar), "r"(c0), "r"(c1) : "memory");
}
__device__ __forceinline__ void tma2d_mc(uint32_t dst, const CUtensorMap* m, int c0, int c1, uint32_t bar, uint16_t mask) {
  asm volatile("cp.async.bulk.tensor.2d.shared::cluster.global.mbarrier::complete_tx::bytes.multicast::cluster [%0], [%1, {%3, %4}], [%2], %5;"
               :: "r"(dst), "l"(m), "r"(bar), "r"(c0), "r"(c1), "h"(mask) : "memory");
}
__device__ __forceinline__ void tma2d_store(const CUtensorMap* m, uint32_t src, int c0, int c1) {
  asm volatile("cp.async.bulk.tensor.2d.global.shared::cta.bulk_group [%0, {%2, %3}], [%1];"
               :: "l"(m), "r"(src), "r"(c0), "r"(c1) : "memory");
}
__device__ __forceinline__ void bulk_g2s(uint32_t dst, const void* src, uint32_t bytes, uint32_t bar) {
  asm volatile("cp.async.bulk.shared::cluster.global.mbarrier::complete_tx::bytes [%0], [%1], %2, [%3];"
               :: "r"(dst), "l"(src), "r"(bytes), "r"(bar) : "memory");
}
__device__ __forceinline__ void bulk_commit() { asm volatile("cp.async.bulk.commit_group;" ::: "memory"); }
__device__ __forceinline__ void bulk_wait_all() { asm volatile("cp.async.bulk.wait_group 0;" ::: "memory"); }
__device__ __forceinline__ void fence_async() { asm volatile("fence.proxy.async.shared::cta;" ::: "memory"); }
__device__ __forceinline__ void named_bar(int id, int n) { asm volatile("bar.sync %0, %1;" :: "r"(id), "r"(n) : "memory"); }
__device__ __forceinline__ void pdl_launch() { asm volatile("griddepcontrol.launch_dependents;" ::: "memory"); }
__device__ __forceinline__ void pdl_wait() { asm volatile("griddepcontrol.wait;" ::: "memory"); }
__device__ __forceinline__ void wg_fence() { asm volatile("wgmma.fence.sync.aligned;" ::: "memory"); }
__device__ __forceinline__ void wg_commit() { asm volatile("wgmma.commit_group.sync.aligned;" ::: "memory"); }
template <int n> __device__ __forceinline__ void wg_wait() { asm volatile("wgmma.wait_group.sync.aligned %0;" :: "n"(n) : "memory"); }
template <int n> __device__ __forceinline__ void fence_regs(float* r) {
#pragma unroll
  for (int i = 0; i < n; i++) asm volatile("" : "+f"(r[i]) :: "memory");
}
template <int n> __device__ __forceinline__ void fence_regs(uint32_t* r) {
#pragma unroll
  for (int i = 0; i < n; i++) asm volatile("" : "+r"(r[i]) :: "memory");
}
__device__ __forceinline__ uint64_t make_desc(uint32_t addr, uint32_t lbo, uint32_t sbo, uint32_t swz) {
  return (uint64_t)((addr & 0x3FFFF) >> 4) | ((uint64_t)(lbo >> 4) << 16) | ((uint64_t)(sbo >> 4) << 32) | ((uint64_t)swz << 62);
}
__device__ __forceinline__ float ex2f(float x) { float y; asm("ex2.approx.ftz.f32 %0, %1;" : "=f"(y) : "f"(x)); return y; }
__device__ __forceinline__ uint32_t pack_bf16(float lo, float hi) { uint32_t r; asm("cvt.rn.bf16x2.f32 %0, %1, %2;" : "=r"(r) : "f"(hi), "f"(lo)); return r; }
__device__ __forceinline__ uint32_t pack_f16(float lo, float hi) { uint32_t r; asm("cvt.rn.f16x2.f32 %0, %1, %2;" : "=r"(r) : "f"(hi), "f"(lo)); return r; }
__device__ __forceinline__ float bf_lo(uint32_t v) { return __uint_as_float(v << 16); }
__device__ __forceinline__ float bf_hi(uint32_t v) { return __uint_as_float(v & 0xFFFF0000u); }
__device__ __forceinline__ float rbf(float x) { return __bfloat162float(__float2bfloat16_rn(x)); }
__device__ __forceinline__ void stsm4(uint32_t a, uint32_t r0, uint32_t r1, uint32_t r2, uint32_t r3) {
  asm volatile("stmatrix.sync.aligned.m8n8.x4.shared.b16 [%0], {%1,%2,%3,%4};" :: "r"(a), "r"(r0), "r"(r1), "r"(r2), "r"(r3) : "memory");
}
__device__ __forceinline__ void stsm4t(uint32_t a, uint32_t r0, uint32_t r1, uint32_t r2, uint32_t r3) {
  asm volatile("stmatrix.sync.aligned.m8n8.x4.trans.shared.b16 [%0], {%1,%2,%3,%4};" :: "r"(a), "r"(r0), "r"(r1), "r"(r2), "r"(r3) : "memory");
}
__device__ __forceinline__ void mma_bf16(float* d, uint32_t a0, uint32_t a1, uint32_t a2, uint32_t a3, uint32_t b0, uint32_t b1) {
  asm volatile("mma.sync.aligned.m16n8k16.row.col.f32.bf16.bf16.f32 {%0,%1,%2,%3}, {%4,%5,%6,%7}, {%8,%9}, {%0,%1,%2,%3};"
               : "+f"(d[0]), "+f"(d[1]), "+f"(d[2]), "+f"(d[3]) : "r"(a0), "r"(a1), "r"(a2), "r"(a3), "r"(b0), "r"(b1));
}
template<int SD> __device__ __forceinline__ void wg_qs24(float* d, uint64_t da, uint64_t db) {
  asm volatile("wgmma.mma_async.sync.aligned.m64n24k16.f32.f16.f16 {%0,%1,%2,%3,%4,%5,%6,%7,%8,%9,%10,%11}, %12, %13, %14, 1, 1, 0, 0;"
   : "+f"(d[0]),"+f"(d[1]),"+f"(d[2]),"+f"(d[3]),"+f"(d[4]),"+f"(d[5]),"+f"(d[6]),"+f"(d[7]),"+f"(d[8]),"+f"(d[9]),"+f"(d[10]),"+f"(d[11])
   : "l"(da),"l"(db),"n"(SD));
}
template<int SD> __device__ __forceinline__ void wg_qs72(float* d, uint64_t da, uint64_t db) {
  asm volatile("wgmma.mma_async.sync.aligned.m64n72k16.f32.f16.f16 {%0,%1,%2,%3,%4,%5,%6,%7,%8,%9,%10,%11,%12,%13,%14,%15,%16,%17,%18,%19,%20,%21,%22,%23,%24,%25,%26,%27,%28,%29,%30,%31,%32,%33,%34,%35}, %36, %37, %38, 1, 1, 0, 0;"
   : "+f"(d[0]),"+f"(d[1]),"+f"(d[2]),"+f"(d[3]),"+f"(d[4]),"+f"(d[5]),"+f"(d[6]),"+f"(d[7]),"+f"(d[8]),"+f"(d[9]),"+f"(d[10]),"+f"(d[11]),"+f"(d[12]),"+f"(d[13]),"+f"(d[14]),"+f"(d[15]),"+f"(d[16]),"+f"(d[17]),"+f"(d[18]),"+f"(d[19]),"+f"(d[20]),"+f"(d[21]),"+f"(d[22]),"+f"(d[23]),"+f"(d[24]),"+f"(d[25]),"+f"(d[26]),"+f"(d[27]),"+f"(d[28]),"+f"(d[29]),"+f"(d[30]),"+f"(d[31]),"+f"(d[32]),"+f"(d[33]),"+f"(d[34]),"+f"(d[35])
   : "l"(da),"l"(db),"n"(SD));
}
template<int SD> __device__ __forceinline__ void wg_qs96(float* d, uint64_t da, uint64_t db) {
  asm volatile("wgmma.mma_async.sync.aligned.m64n96k16.f32.f16.f16 {%0,%1,%2,%3,%4,%5,%6,%7,%8,%9,%10,%11,%12,%13,%14,%15,%16,%17,%18,%19,%20,%21,%22,%23,%24,%25,%26,%27,%28,%29,%30,%31,%32,%33,%34,%35,%36,%37,%38,%39,%40,%41,%42,%43,%44,%45,%46,%47}, %48, %49, %50, 1, 1, 0, 0;"
   : "+f"(d[0]),"+f"(d[1]),"+f"(d[2]),"+f"(d[3]),"+f"(d[4]),"+f"(d[5]),"+f"(d[6]),"+f"(d[7]),"+f"(d[8]),"+f"(d[9]),"+f"(d[10]),"+f"(d[11]),"+f"(d[12]),"+f"(d[13]),"+f"(d[14]),"+f"(d[15]),"+f"(d[16]),"+f"(d[17]),"+f"(d[18]),"+f"(d[19]),"+f"(d[20]),"+f"(d[21]),"+f"(d[22]),"+f"(d[23]),"+f"(d[24]),"+f"(d[25]),"+f"(d[26]),"+f"(d[27]),"+f"(d[28]),"+f"(d[29]),"+f"(d[30]),"+f"(d[31]),"+f"(d[32]),"+f"(d[33]),"+f"(d[34]),"+f"(d[35]),"+f"(d[36]),"+f"(d[37]),"+f"(d[38]),"+f"(d[39]),"+f"(d[40]),"+f"(d[41]),"+f"(d[42]),"+f"(d[43]),"+f"(d[44]),"+f"(d[45]),"+f"(d[46]),"+f"(d[47])
   : "l"(da),"l"(db),"n"(SD));
}
template<int SD> __device__ __forceinline__ void wg_pv24(float* d, const uint32_t* a, uint64_t desc) {
  asm volatile("wgmma.mma_async.sync.aligned.m64n24k16.f32.bf16.bf16 {%0,%1,%2,%3,%4,%5,%6,%7,%8,%9,%10,%11}, {%12,%13,%14,%15}, %16, %17, 1, 1, 1;"
   : "+f"(d[0]),"+f"(d[1]),"+f"(d[2]),"+f"(d[3]),"+f"(d[4]),"+f"(d[5]),"+f"(d[6]),"+f"(d[7]),"+f"(d[8]),"+f"(d[9]),"+f"(d[10]),"+f"(d[11])
   : "r"(a[0]),"r"(a[1]),"r"(a[2]),"r"(a[3]),"l"(desc),"n"(SD));
}
template<int TA, int TB> __device__ __forceinline__ void wg_ss128(float* d, uint64_t da, uint64_t db, int sd) {
  asm volatile("{\n.reg .pred p;\nsetp.ne.b32 p, %66, 0;\n"
   "wgmma.mma_async.sync.aligned.m64n128k16.f32.bf16.bf16 {%0,%1,%2,%3,%4,%5,%6,%7,%8,%9,%10,%11,%12,%13,%14,%15,%16,%17,%18,%19,%20,%21,%22,%23,%24,%25,%26,%27,%28,%29,%30,%31,%32,%33,%34,%35,%36,%37,%38,%39,%40,%41,%42,%43,%44,%45,%46,%47,%48,%49,%50,%51,%52,%53,%54,%55,%56,%57,%58,%59,%60,%61,%62,%63}, %64, %65, p, 1, 1, %67, %68;\n}\n"
   : "+f"(d[0]),"+f"(d[1]),"+f"(d[2]),"+f"(d[3]),"+f"(d[4]),"+f"(d[5]),"+f"(d[6]),"+f"(d[7]),"+f"(d[8]),"+f"(d[9]),"+f"(d[10]),"+f"(d[11]),"+f"(d[12]),"+f"(d[13]),"+f"(d[14]),"+f"(d[15]),"+f"(d[16]),"+f"(d[17]),"+f"(d[18]),"+f"(d[19]),"+f"(d[20]),"+f"(d[21]),"+f"(d[22]),"+f"(d[23]),"+f"(d[24]),"+f"(d[25]),"+f"(d[26]),"+f"(d[27]),"+f"(d[28]),"+f"(d[29]),"+f"(d[30]),"+f"(d[31]),"+f"(d[32]),"+f"(d[33]),"+f"(d[34]),"+f"(d[35]),"+f"(d[36]),"+f"(d[37]),"+f"(d[38]),"+f"(d[39]),"+f"(d[40]),"+f"(d[41]),"+f"(d[42]),"+f"(d[43]),"+f"(d[44]),"+f"(d[45]),"+f"(d[46]),"+f"(d[47]),"+f"(d[48]),"+f"(d[49]),"+f"(d[50]),"+f"(d[51]),"+f"(d[52]),"+f"(d[53]),"+f"(d[54]),"+f"(d[55]),"+f"(d[56]),"+f"(d[57]),"+f"(d[58]),"+f"(d[59]),"+f"(d[60]),"+f"(d[61]),"+f"(d[62]),"+f"(d[63])
   : "l"(da),"l"(db),"r"(sd),"n"(TA),"n"(TB));
}
template<int TA, int TB> __device__ __forceinline__ void wg_ss64(float* d, uint64_t da, uint64_t db, int sd) {
  asm volatile("{\n.reg .pred p;\nsetp.ne.b32 p, %34, 0;\n"
   "wgmma.mma_async.sync.aligned.m64n64k16.f32.bf16.bf16 {%0,%1,%2,%3,%4,%5,%6,%7,%8,%9,%10,%11,%12,%13,%14,%15,%16,%17,%18,%19,%20,%21,%22,%23,%24,%25,%26,%27,%28,%29,%30,%31}, %32, %33, p, 1, 1, %35, %36;\n}\n"
   : "+f"(d[0]),"+f"(d[1]),"+f"(d[2]),"+f"(d[3]),"+f"(d[4]),"+f"(d[5]),"+f"(d[6]),"+f"(d[7]),"+f"(d[8]),"+f"(d[9]),"+f"(d[10]),"+f"(d[11]),"+f"(d[12]),"+f"(d[13]),"+f"(d[14]),"+f"(d[15]),"+f"(d[16]),"+f"(d[17]),"+f"(d[18]),"+f"(d[19]),"+f"(d[20]),"+f"(d[21]),"+f"(d[22]),"+f"(d[23]),"+f"(d[24]),"+f"(d[25]),"+f"(d[26]),"+f"(d[27]),"+f"(d[28]),"+f"(d[29]),"+f"(d[30]),"+f"(d[31])
   : "l"(da),"l"(db),"r"(sd),"n"(TA),"n"(TB));
}
template<int TA, int TB> __device__ __forceinline__ void wg_ss8(float* d, uint64_t da, uint64_t db, int sd) {
  asm volatile("{\n.reg .pred p;\nsetp.ne.b32 p, %6, 0;\n"
   "wgmma.mma_async.sync.aligned.m64n8k16.f32.bf16.bf16 {%0,%1,%2,%3}, %4, %5, p, 1, 1, %7, %8;\n}\n"
   : "+f"(d[0]),"+f"(d[1]),"+f"(d[2]),"+f"(d[3])
   : "l"(da),"l"(db),"r"(sd),"n"(TA),"n"(TB));
}

__device__ __forceinline__ uint32_t phi2(float a, float b) {
  uint32_t r, e;
  asm("cvt.rn.relu.bf16x2.f32 %0, %1, %2;" : "=r"(r) : "f"(b), "f"(a));
  e = pack_bf16(ex2f(a * 1.4426950408889634f), ex2f(b * 1.4426950408889634f));
  asm("add.rn.bf16x2 %0, %0, %1;" : "+r"(e) : "r"(0x35863586u));
  asm("min.NaN.bf16x2 %0, %0, %1;" : "+r"(e) : "r"(0x3F803F80u));
  asm("add.rn.bf16x2 %0, %0, %1;" : "+r"(e) : "r"(r));
  return e;
}

__device__ __forceinline__ void mbar_wait_long(uint32_t bar, uint32_t parity) {
  asm volatile("{\n.reg .pred p;\n.reg .u32 c;\nmov.u32 c, 0;\n"
               "LW_%=:\n"
               "mbarrier.try_wait.parity.shared::cta.b64 p, [%0], %1, 100000;\n"
               "@p bra LD_%=;\n"
               "add.u32 c, c, 1;\n"
               "setp.lt.u32 p, c, 20000;\n"
               "@p bra LW_%=;\n"
               "trap;\n"
               "LD_%=:\n}\n" :: "r"(bar), "r"(parity) : "memory");
}
__device__ __forceinline__ void mbar_arrive(uint32_t bar) { asm volatile("mbarrier.arrive.shared::cta.b64 _, [%0];" :: "r"(bar) : "memory"); }
__device__ __forceinline__ void named_arrive(int id, int n) { asm volatile("bar.arrive %0, %1;" :: "r"(id), "r"(n) : "memory"); }
__device__ __forceinline__ void fence_async_all() { asm volatile("fence.proxy.async.global;" ::: "memory"); }
__device__ __forceinline__ void flag_add(uint32_t* f) { asm volatile("fence.acq_rel.gpu;\nred.relaxed.gpu.global.add.u32 [%0], 1;" :: "l"(f) : "memory"); }
#define PUBLISH(f) asm volatile("fence.proxy.async.global;\nred.relaxed.gpu.global.add.u32 [%0], 1;" :: "l"(f) : "memory")
__device__ __forceinline__ void flag_wait(const uint32_t* f, uint32_t target) {
  uint32_t v;
#pragma unroll 1
  for (int it = 0;; it++) {
    asm volatile("ld.acquire.gpu.global.u32 %0, [%1];" : "=r"(v) : "l"(f) : "memory");
    if ((int32_t)(v - target) >= 0) break;
    if (it > 2000000) __trap();
    __nanosleep(64);
  }
}
__device__ __forceinline__ bool mbar_test(uint32_t bar, uint32_t parity) {
  uint32_t ok;
  asm volatile("{\n.reg .pred p;\nmbarrier.test_wait.parity.shared::cta.b64 p, [%1], %2;\nselp.b32 %0, 1, 0, p;\n}\n" : "=r"(ok) : "r"(bar), "r"(parity) : "memory");
  return ok;
}
__device__ __forceinline__ bool elect_one() {
  uint32_t p;
  asm volatile("{\n.reg .pred P;\nelect.sync _|P, 0xFFFFFFFF;\nselp.b32 %0, 1, 0, P;\n}\n" : "=r"(p));
  return p;
}
__device__ __forceinline__ void lds4(uint32_t a, uint32_t* r) {
  asm volatile("ld.shared.v4.b32 {%0,%1,%2,%3}, [%4];" : "=r"(r[0]), "=r"(r[1]), "=r"(r[2]), "=r"(r[3]) : "r"(a) : "memory");
}
__device__ __forceinline__ uint32_t lds1(uint32_t a) { uint32_t r; asm volatile("ld.shared.b32 %0, [%1];" : "=r"(r) : "r"(a) : "memory"); return r; }
__device__ __forceinline__ void sts1(uint32_t a, uint32_t v) { asm volatile("st.shared.b32 [%0], %1;" :: "r"(a), "r"(v) : "memory"); }
__device__ __forceinline__ void sts4(uint32_t a, uint32_t r0, uint32_t r1, uint32_t r2, uint32_t r3) {
  asm volatile("st.shared.v4.b32 [%0], {%1,%2,%3,%4};" :: "r"(a), "r"(r0), "r"(r1), "r"(r2), "r"(r3) : "memory");
}
__device__ __forceinline__ void ldsm4(uint32_t a, uint32_t* r) {
  asm volatile("ldmatrix.sync.aligned.m8n8.x4.shared.b16 {%0,%1,%2,%3}, [%4];" : "=r"(r[0]), "=r"(r[1]), "=r"(r[2]), "=r"(r[3]) : "r"(a) : "memory");
}
__device__ __forceinline__ float rcpf(float x) { float y; asm("rcp.approx.ftz.f32 %0, %1;" : "=f"(y) : "f"(x)); return y; }
__device__ __forceinline__ uint32_t hfma2(uint32_t a, uint32_t b, uint32_t c) { uint32_t r; asm("fma.rn.f16x2 %0, %1, %2, %3;" : "=r"(r) : "r"(a), "r"(b), "r"(c)); return r; }
__device__ __forceinline__ uint32_t hadd2(uint32_t a, uint32_t b) { uint32_t r; asm("add.rn.f16x2 %0, %1, %2;" : "=r"(r) : "r"(a), "r"(b)); return r; }

#define STEPK 96
#define GIMAP(i) ((((i) & 1) << 2) | (((i) >> 1) & 3) | ((i) & 8))
#define QSCALE 0.36067376022224085f
#define SMAGIC (512.0f + 2.0f * (191.0f - 30.0f - 1.5823545f))
#define VSHIFT 1073741824.0f

__device__ uint32_t g_epoch[132];
__device__ uint32_t g_flag[288 * 8];
#define FLAG_KV (g_flag)
#define FLAG_B(h) (g_flag + (4 + (h)) * 8)
#define FLAG_OA(cta, pass) (g_flag + (16 + (cta) * 2 + (pass)) * 8)
#define FLAG_LM(i) (g_flag + (272 + (i)) * 8)

#define SM_TOTAL (224 * 1024 + 2048 + 1024)
#define OFF_K 0
#define OFF_F 65536
#define OFF_V 131072
#define OFF_MISC (224 * 1024)

#define BAR_FULL(s) (bars + 8 * (s))
#define BAR_EMPTY(s) (bars + 24 + 8 * (s))
#define BAR_KV(c) (bars + 48 + 8 * (c))
#define BAR_BDONE (bars + 80)
#define BAR_Q (bars + 88)
#define BAR_GO (bars + 96)
#define BAR_Q2 (bars + 104)
#define BAR_OD(p) (bars + 112 + 8 * (p))
#define BAR_CL(c) (bars + 128 + 8 * (c))
#define BAR_TE(i) (bars + 168 + 8 * (i))
#define BAR_RL (bars + 184)
#define BAR_TF(g) (bars + 224 + 8 * (g))
#define BAR_XA(w) (bars + 352 + 8 * (w))
#define BAR_VB(c) (bars + 384 + 8 * (c))

__device__ __forceinline__ uint32_t exp2_pair_fix(float d0, float d1, uint32_t c63, uint32_t m1) {
  uint32_t w, y, s, r;
  asm("prmt.b32 %0, %1, %2, 0x6521;" : "=r"(w) : "r"(__float_as_uint(d0)), "r"(__float_as_uint(d1)));
  asm("lop3.b32 %0, %1, 0x007F007F, %2, 0xEA;" : "=r"(y) : "r"(w), "r"(c63));
  asm("mad.lo.u32 %0, %1, %2, %3;" : "=r"(s) : "r"(y), "r"(m1), "r"(w));
  asm("fma.rn.bf16x2 %0, %1, %2, %3;" : "=r"(r) : "r"(w), "r"(y), "r"(s));
  return r;
}

#define X_PR(i) asm volatile("prmt.b32 %0, %1, %2, 0x6521;" : "=r"(w[i]) : "r"(__float_as_uint(Sp[2 * (i)])), "r"(__float_as_uint(Sp[2 * (i) + 1])));
#define X_LO(i) asm volatile("lop3.b32 %0, %1, 0x007F007F, %2, 0xEA;" : "=r"(y[i]) : "r"(w[i]), "r"(c63));
#define X_IM(i) asm volatile("mad.lo.u32 %0, %1, %2, %3;" : "=r"(z[i]) : "r"(y[i]), "r"(m1), "r"(w[i]));
#define X_FM(i) asm volatile("fma.rn.bf16x2 %0, %1, %2, %3;" : "=r"(P[6 + (i)]) : "r"(w[i]), "r"(y[i]), "r"(z[i]));
#define X_MU(i) asm volatile("ex2.approx.ftz.f32 %0, %1;" : "=f"(e[i]) : "f"(Sm[i]));
#define X_PK(i) asm volatile("cvt.rn.bf16x2.f32 %0, %1, %2;" : "=r"(P[i]) : "f"(e[2 * (i) + 1]), "f"(e[2 * (i)]));

__device__ __forceinline__ void attn_slow(const __nv_bfloat16* xa, const __nv_bfloat16* wq, uint32_t dst) {
  const int t = threadIdx.x & 127;
  const int row = t >> 1, half = t & 1;
  float q[16];
  {
    float a[8];
#pragma unroll
    for (int i = 0; i < 8; i++) a[i] = 0.f;
#pragma unroll 1
    for (int k = 0; k < D_MOD; k++) {
      const float x = __bfloat162float(xa[(size_t)row * D_MOD + k]);
      const uint4 w = *(const uint4*)(wq + (size_t)k * D_MOD + half * 8);
      const uint32_t ww[4] = {w.x, w.y, w.z, w.w};
#pragma unroll
      for (int i = 0; i < 4; i++) { a[2 * i] = fmaf(x, bf_lo(ww[i]), a[2 * i]); a[2 * i + 1] = fmaf(x, bf_hi(ww[i]), a[2 * i + 1]); }
    }
#pragma unroll
    for (int i = 0; i < 8; i++) {
      const float mine = rbf(a[i]), other = __shfl_xor_sync(~0u, mine, 1);
      q[i] = half ? other : mine; q[8 + i] = half ? mine : other;
    }
  }
  float m = -INFINITY, l = 0.f, o[16];
#pragma unroll
  for (int i = 0; i < 16; i++) o[i] = 0.f;
#pragma unroll 1
  for (int j = half * 1024; j < half * 1024 + 1024; j++) {
    uint4 ka = g_KV[4 * S_TOK + j], kb = g_KV[5 * S_TOK + j];
    uint4 va = g_KV[6 * S_TOK + j], vb = g_KV[7 * S_TOK + j];
    uint32_t kk[8] = {ka.x, ka.y, ka.z, ka.w, kb.x, kb.y, kb.z, kb.w};
    uint32_t vv[8] = {va.x, va.y, va.z, va.w, vb.x, vb.y, vb.z, vb.w};
    float s = 0.f;
#pragma unroll
    for (int i = 0; i < 8; i++) { s = fmaf(q[2 * i], bf_lo(kk[i]), s); s = fmaf(q[2 * i + 1], bf_hi(kk[i]), s); }
    s = rbf(s) * 0.25f;
    if (s > m) {
      float c = __expf(m - s);
      l *= c;
#pragma unroll
      for (int i = 0; i < 16; i++) o[i] *= c;
      m = s;
    }
    float p = __expf(s - m);
    l += p;
#pragma unroll
    for (int i = 0; i < 8; i++) { o[2 * i] = fmaf(p, bf_lo(vv[i]), o[2 * i]); o[2 * i + 1] = fmaf(p, bf_hi(vv[i]), o[2 * i + 1]); }
  }
  float m2 = __shfl_xor_sync(~0u, m, 1);
  float mm = fmaxf(m, m2);
  float c = __expf(m - mm);
  l *= c; l += __shfl_xor_sync(~0u, l, 1);
  float inv = 1.f / l;
  uint32_t r[8];
#pragma unroll
  for (int i = 0; i < 16; i++) { o[i] *= c; o[i] += __shfl_xor_sync(~0u, o[i], 1); o[i] *= inv; }
#pragma unroll
  for (int i = 0; i < 8; i++) r[i] = pack_bf16(o[2 * i], o[2 * i + 1]);
  if (half == 0) sts4(dst, r[0], r[1], r[2], r[3]); else sts4(dst, r[4], r[5], r[6], r[7]);
  fence_async();
}

struct Params { const __nv_bfloat16* wk; const __nv_bfloat16* wv; const __nv_bfloat16* xa; const __nv_bfloat16* wq; __nv_bfloat16* out; };
__device__ __forceinline__ void cp16(uint32_t dst, const void* src) { asm volatile("cp.async.cg.shared.global [%0], [%1], 16;" :: "r"(dst), "l"(src) : "memory"); }

__device__ __forceinline__ void helper_cta(const int h, const uint32_t sb, const uint32_t bars, const int wg, const int w4,
                                           const CUtensorMap* mQ, const CUtensorMap* mOs) {
  const int lane = threadIdx.x & 31;
  mbar_wait(BAR_GO, 0);
  const int cb = wg & 1, col = h * 128 + cb * 64, row0 = S_TOK + (wg >> 1) * 1024;
  const uint32_t buf = sb + wg * 49152;
  if (w4 == 0 && elect_one()) {
    fence_async_all();
#pragma unroll 1
    for (int u = 0; u < 3; u++) {
      mbar_expect_tx(BAR_TF(wg * 3 + u), 16384);
      tma2d(buf + u * 16384, mQ, col, row0 + u * 128, BAR_TF(wg * 3 + u));
    }
  }
  const int head = h * 8 + cb * 4 + w4;
  float4 a0 = make_float4(0, 0, 0, 0), a1 = a0, a2 = a0;
#pragma unroll 8
  for (int tt = 0; tt < 16; tt++) {
    const float4* src = g_kvp + ((tt * 32 + head) * 3) * 32 + lane;
    float4 u = src[0], v = src[32], w = src[64];
    a0.x += u.x; a0.y += u.y; a0.z += u.z; a0.w += u.w;
    a1.x += v.x; a1.y += v.y; a1.z += v.z; a1.w += v.w;
    a2.x += w.x; a2.y += w.y; a2.z += w.z; a2.w += w.w;
  }
  const uint32_t b00 = pack_bf16(a0.x, a0.y), b01 = pack_bf16(a0.z, a0.w);
  const uint32_t b10 = pack_bf16(a1.x, a1.y), b11 = pack_bf16(a1.z, a1.w);
  const uint32_t bz0 = pack_bf16(a2.x, a2.y), bz1 = pack_bf16(a2.z, a2.w);
  const int m = lane >> 3, r = lane & 7;
  const uint32_t off = ((m & 1) * 8 + r) * 128 + (((w4 * 2 + (m >> 1)) ^ r) << 4);
  int s = 0, ph = 0;
#pragma unroll 1
  for (int u = 0; u < 8; u++) {
    const uint32_t bb = buf + s * 16384;
    mbar_wait(BAR_TF(wg * 3 + s), ph);
    uint32_t a[32];
#pragma unroll
    for (int mt = 0; mt < 8; mt++) ldsm4(bb + mt * 2048 + off, a + 4 * mt);
#pragma unroll
    for (int i = 0; i < 32; i++) a[i] = phi2(bf_lo(a[i]), bf_hi(a[i]));
#pragma unroll
    for (int mt = 0; mt < 8; mt++) {
      uint32_t* p = a + 4 * mt;
      float n0[4] = {0, 0, 0, 0}, n1[4] = {0, 0, 0, 0}, dn[4] = {0, 0, 0, 0};
      mma_bf16(dn, p[0], p[1], p[2], p[3], bz0, bz1);
      mma_bf16(n0, p[0], p[1], p[2], p[3], b00, b01);
      mma_bf16(n1, p[0], p[1], p[2], p[3], b10, b11);
      const float i0 = rcpf(dn[0] + 1e-6f), i1 = rcpf(dn[2] + 1e-6f);
      p[0] = pack_bf16(n0[0] * i0, n0[1] * i0); p[1] = pack_bf16(n0[2] * i1, n0[3] * i1);
      p[2] = pack_bf16(n1[0] * i0, n1[1] * i0); p[3] = pack_bf16(n1[2] * i1, n1[3] * i1);
    }
#pragma unroll
    for (int mt = 0; mt < 8; mt++) stsm4(bb + mt * 2048 + off, a[4 * mt], a[4 * mt + 1], a[4 * mt + 2], a[4 * mt + 3]);
    fence_async();
    named_bar(wg + 1, 128);
    if (w4 == 0 && lane == 0) {
      tma2d_store(mOs, bb, col, row0 + u * 128);
      bulk_commit();
      if (u >= 1 && u + 2 < 8) {
        asm volatile("cp.async.bulk.wait_group.read 1;" ::: "memory");
        const int sp = s == 0 ? 2 : s - 1;
        mbar_expect_tx(BAR_TF(wg * 3 + sp), 16384);
        tma2d(buf + sp * 16384, mQ, col, row0 + (u + 2) * 128, BAR_TF(wg * 3 + sp));
      }
    }
    __syncwarp();
    if (++s == 3) { s = 0; ph ^= 1; }
  }
  if (w4 == 0 && lane == 0) {
    bulk_wait_all();
    fence_async_all();
    flag_add(FLAG_LM((h * 2 + cb) * 2 + (wg >> 1)));
    if (wg == 0) TS(1, 8);
  }
}

#define STAGE(s) (sb + (2 - (s)) * 65536)
__device__ __forceinline__ uint32_t xa_addr(uint32_t sb, int kb) {
  return sb + (kb >= 1 && kb <= 4 ? OFF_V + 65536 + (kb - 1) * 8192 : 16384 + (kb == 5 ? OFF_K : (kb == 6 ? OFF_V : OFF_F)));
}
#define XA7_TMP (sb + OFF_K + 40960)
#define WKV_TMP (sb + OFF_K + 32768)
template <int TR> __device__ __forceinline__ void proj_kb(float* acc, uint32_t aA, uint32_t aB, int first) {
  const uint64_t da = make_desc(aA, TR ? 8192 : 16, 1024, 1);
  const uint64_t db = make_desc(aB, TR ? 16 : 8192, 1024, 1);
  wg_fence();
#pragma unroll
  for (int k = 0; k < 4; k++) wg_ss128<TR, 1 - TR>(acc, da + k * (TR ? 128 : 2), db + k * (TR ? 2 : 128), k != 0 || !first);
  wg_commit();
}
template <int TR> __device__ __forceinline__ void proj_loop(float* acc, uint32_t sb, uint32_t bars, uint32_t offA, uint32_t offB,
                                                            int wg, uint32_t sWKV, const CUtensorMap* mW, int col, bool w0) {
  {
    float kv[4];
    if (threadIdx.x == 0) TS(0, 13);
    mbar_wait(BAR_XA(wg), 0);
    if (threadIdx.x == 0) TS(0, 1);
    const uint64_t da0 = make_desc(xa_addr(sb, 2 * wg), 16, 1024, 1);
    const uint64_t da1 = make_desc(wg == 3 ? XA7_TMP : xa_addr(sb, 2 * wg + 1), 16, 1024, 1);
    const uint64_t db = make_desc(sWKV + wg * 2048, 128, 128, 0);
    wg_fence();
#pragma unroll
    for (int k = 0; k < 8; k++) wg_ss8<0, 1>(kv, (k < 4 ? da0 : da1) + (k & 3) * 2, db + k * 16, k != 0);
    wg_commit();
    wg_wait<0>();
    fence_regs<4>(kv);
    named_bar(wg + 1, 128);
    sts4(sWKV + threadIdx.x * 16, __float_as_uint(kv[0]), __float_as_uint(kv[1]), __float_as_uint(kv[2]), __float_as_uint(kv[3]));
    __syncwarp();
    if ((threadIdx.x & 31) == 0) mbar_arrive(BAR_GO);
  }
  int s = 0, ph = 0;
#pragma unroll 1
  for (int kb = 0; kb < 8; kb++) {
    mbar_wait(BAR_FULL(s), ph);
    if (threadIdx.x == 0) TSW(0, 2 + kb);
    if (TR == 0) mbar_wait(BAR_XA(kb >> 1), 0);
    proj_kb<TR>(acc, TR ? STAGE(s) + offA : xa_addr(sb, kb), STAGE(s) + offB, kb == 0);
    wg_wait<0>();
    if (w0 && elect_one()) {
      if (kb < 5) {
        mbar_expect_tx(BAR_FULL(s), TR ? 8192 : 16384);
        tma2d(STAGE(s) + (TR ? offA : 0), mW, col, (kb + 3) * 64, BAR_FULL(s));
        if (TR == 0) tma2d(STAGE(s) + 8192, mW, col + 64, (kb + 3) * 64, BAR_FULL(s));
      }
      if (kb < 7) mbar_arrive(BAR_EMPTY(s));
      if (TR == 0 && kb == 4) mbar_arrive(BAR_VB(1));
    }
    __syncwarp();
    if (++s == 3) { s = 0; ph ^= 1; }
  }
  wg_wait<0>();
  fence_regs<64>(acc);
}

__device__ __forceinline__ uint32_t tail_slots(int isB, int n) {
  if (n < 4) return n < 2 ? (n == 0 ? 0x0D0C0B0Au : 0x04000F0Eu) : (n == 2 ? 0x18141008u : 0x15110501u);
  if (isB) return n < 6 ? (n == 4 ? 0x19120602u : 0x0D0C0B0Au) : (n == 6 ? 0x04000F0Eu : 0x13070316u);
  return n < 6 ? (n == 4 ? 0x1902031Au : 0x12061307u) : (n == 6 ? 0x16091B17u : 0x0D0C0B0Au);
}

__device__ __forceinline__ void take_role(uint32_t sM, int wg) {
  uint32_t r;
  asm volatile("atom.shared.add.u32 %0, [%1], 1;" : "=r"(r) : "r"(sM + 20) : "memory");
  sts1(sM + 32 + wg * 4, r);
}

__global__ void __launch_bounds__(640, 1)
k1_main(const __grid_constant__ CUtensorMap mXA64, const __grid_constant__ CUtensorMap mXB,
        const __grid_constant__ CUtensorMap mWq, const __grid_constant__ CUtensorMap mWqkv,
        const __grid_constant__ CUtensorMap mQst, const __grid_constant__ CUtensorMap mOst,
        const __grid_constant__ CUtensorMap mO, const __grid_constant__ CUtensorMap mWoA,
        const __grid_constant__ CUtensorMap mWoB,
        const __grid_constant__ CUtensorMap mO16, const Params prm) {
  if (threadIdx.x >= 608 && threadIdx.x < 612) {
    const CUtensorMap* pm = &mXA64 + (threadIdx.x - 608);
    asm volatile("prefetch.tensormap [%0];" :: "l"(pm) : "memory");
  }
  extern __shared__ uint8_t smem_raw[];
  const uint32_t sb = (smem_u32(smem_raw) + 1023u) & ~1023u;
  const uint32_t bars = sb + OFF_MISC, sM = bars + 512, sT = bars + 1024;
  const int tid = threadIdx.x, warp = __shfl_sync(~0u, tid >> 5, 0), wg = warp >> 2, w4 = warp & 3, lane = tid & 31;
  const bool helper = blockIdx.x >= 128;
  if (tid == 0) TS(0, 0);
  const int G = blockIdx.x >> 4, gi = GIMAP(blockIdx.x & 15);
  const int tbA = G * 4 + (gi >> 2), hg = gi & 3;
  const int ttB = (G >> 1) * 4 + (gi >> 2), hq = (G & 1) * 4 + (gi & 3);
  const int isB = tbA & 1, tok0 = (tbA >> 1) * 128;
  auto issue = [&](int kb, int s, int part) {
    const uint32_t fb = BAR_FULL(s), st = STAGE(s);
    if (part & 1) {
      mbar_expect_tx(fb, 57344);
      asm volatile("mbarrier.arrive.shared::cta.b64 _, [%0], 4;" :: "r"(fb) : "memory");
      tma2d(st, &mWq, hg * 128, kb * 64, fb);
      tma2d(st + 8192, &mWq, hg * 128 + 64, kb * 64, fb);
      tma2d(st + 49152, &mXB, kb * 64, ttB * 128, fb);
      tma2d(st + 24576, &mWqkv, hq * 64, kb * 64, fb);
    }
    if (part & 2) {
      tma2d(st + 32768, &mWqkv, 512 + hq * 64, kb * 64, fb);
      tma2d(st + 40960, &mWqkv, 1024 + hq * 64, kb * 64, fb);
    }
  };
  const uint32_t sOne = sb + OFF_V + 65536, sWKV = WKV_TMP;
  if (warp >= 16) {
    if (warp == 17) {
      if (elect_one()) {
        mbar_init(BAR_BDONE, 8); mbar_init(BAR_Q, 6); mbar_init(BAR_GO, helper ? 1 : 16); mbar_init(BAR_Q2, 1);
        mbar_init(BAR_OD(0), 16); mbar_init(BAR_OD(1), 16); mbar_init(BAR_CL(0), 1); mbar_init(BAR_FULL(2), 5);
#pragma unroll
        for (int i = 0; i < 4; i++) mbar_init(BAR_CL(i + 1), i == 0 ? 5 : 4);
#pragma unroll
        for (int i = 0; i < 3; i++) { mbar_init(BAR_EMPTY(i), 4); mbar_init(BAR_KV(i), 1); mbar_init(BAR_VB(i), i == 2 ? 4 : 1); }
        sts1(sM + 20, 0);
        asm volatile("fence.mbarrier_init.release.cluster;" ::: "memory");
      }
    } else if (warp == 18) {
      if (elect_one()) {
#pragma unroll
        for (int i = 0; i < 2; i++) mbar_init(BAR_TE(i), 2);
        mbar_init(BAR_RL, 1);
#pragma unroll
        for (int i = 0; i < 16; i++) mbar_init(BAR_TF(i), 1);
        asm volatile("fence.mbarrier_init.release.cluster;" ::: "memory");
      }
    } else if (warp == 16 && !helper && elect_one()) {
#pragma unroll
      for (int w = 0; w < 4; w++) mbar_init(BAR_XA(w), 1);
      mbar_init(BAR_FULL(0), 5); mbar_init(BAR_FULL(1), 5);
      asm volatile("fence.mbarrier_init.release.cluster;" ::: "memory");
#pragma unroll
      for (int w = 0; w < 4; w++) {
        mbar_expect_tx(BAR_XA(w), 16384);
        tma2d(xa_addr(sb, 2 * w), &mXA64, w * 128, tbA * 64, BAR_XA(w));
        tma2d(w == 3 ? XA7_TMP : xa_addr(sb, 2 * w + 1), &mXA64, w * 128 + 64, tbA * 64, BAR_XA(w));
      }
      TS(0, 14);
      issue(0, 0, 3);
    }
  } else if (!helper) {
    const uint4 v = __ldg((const uint4*)(hg >= 2 ? prm.wv : prm.wk) + tid * 2 + (hg & 1));
    sts4(sWKV + tid * 16, v.x, v.y, v.z, v.w);
    fence_async();
  }
  __syncthreads();
  if (wg == 4) {
    if (w4 == 0 && !helper && elect_one()) { issue(1, 1, 3); issue(2, 2, 1); TS(0, 15); }
    asm volatile("setmaxnreg.dec.sync.aligned.u32 32;");
    const uint32_t ep = g_epoch[blockIdx.x] + 1;
    if (helper) {
      if (w4 == 0 && elect_one()) {
        flag_wait(FLAG_B(blockIdx.x - 128), ep * 32);
        fence_async_all();
        TS(1, 10);
        mbar_arrive(BAR_GO);
        g_epoch[blockIdx.x] = ep;
      }
      return;
    }
    mbar_wait(BAR_GO, 0);
    {
      uint32_t a[4], b[4];
      float c[4];
      lds4(sWKV + (tid - 512) * 16, a);
      lds4(sWKV + 2048 + (tid - 512) * 16, b);
#pragma unroll
      for (int i = 0; i < 4; i++) c[i] = __uint_as_float(a[i]) + __uint_as_float(b[i]);
      lds4(sWKV + 4096 + (tid - 512) * 16, a);
      lds4(sWKV + 6144 + (tid - 512) * 16, b);
#pragma unroll
      for (int i = 0; i < 4; i++) c[i] += __uint_as_float(a[i]) + __uint_as_float(b[i]);
      sts1(sT + w4 * 256 + lane * 4, pack_bf16(c[0], c[1]));
      sts1(sT + w4 * 256 + 128 + lane * 4, pack_bf16(c[2], c[3]));
    }
    named_bar(9, 128);
    if (w4 == 0 && elect_one()) issue(2, 2, 2);
    auto write_ones = [&]() {
      mbar_wait_long(BAR_VB(1), 0);
      int c = ((w4 & 1) * 32 + lane);
#pragma unroll 4
      for (int key = c; key < S_TOK; key += 64) {
        sts4(sOne + key * 16, c < 24 ? 0x00003F80u : 0x00004E80u, 0u, 0u, 0u);
        c += 64; if (c >= STEPK) c -= STEPK;
      }
      fence_async();
      __syncwarp();
      if (lane == 0) mbar_arrive(BAR_Q);
    };
    if (w4 == 0) {
      int s = 0, ph = 0;
#pragma unroll 1
      for (int kb = 3; kb < 8; kb++) {
        mbar_wait(BAR_EMPTY(s), ph);
        if (elect_one()) {
          mbar_expect_tx(BAR_FULL(s), kb == 7 ? 24576 : 16384);
          tma2d(STAGE(s) + 49152, &mXB, kb * 64, ttB * 128, BAR_FULL(s));
          if (kb == 7) tma2d(STAGE(s) + 16384, &mXA64, kb * 64, tbA * 64, BAR_FULL(s));
        }
        if (++s == 3) { s = 0; ph ^= 1; }
      }
      flag_wait(FLAG_KV, ep * 128);
      fence_async_all();
      if (lane == 0) TS(0, 11);
#pragma unroll 1
      for (int m = 0; m < 2; m++) {
        mbar_wait(m == 0 ? BAR_EMPTY(2) : BAR_EMPTY(0), 1 - m);
        if (elect_one()) {
          const uint32_t fb = m == 0 ? BAR_KV(0) : BAR_VB(0);
          mbar_expect_tx(fb, 2 * 7 * STEPK * 16);
#pragma unroll
          for (int p = 0; p < 2; p++) bulk_g2s(sb + m * OFF_V + p * 32768, g_KV + (m * 2 + p) * S_TOK, 7 * STEPK * 16, fb);
        }
      }
      mbar_wait(BAR_Q, 0);
      if (elect_one()) {
#pragma unroll
        for (int c = 1; c < 3; c++) {
          const int k0 = c == 1 ? 7 * STEPK : 13 * STEPK, k1 = c == 1 ? 13 * STEPK : S_TOK;
          const uint32_t bytes = (k1 - k0) * 16;
          mbar_expect_tx(BAR_KV(c), 4 * bytes);
#pragma unroll
          for (int p = 0; p < 4; p++)
            bulk_g2s(sb + (p >> 1) * OFF_V + (p & 1) * 32768 + k0 * 16, g_KV + p * S_TOK + k0, bytes, BAR_KV(c));
        }
      }
      mbar_wait_long(BAR_CL(1), 0);
      flag_wait(isB ? FLAG_LM((lane & 7) * 2 + (tbA >> 4)) : FLAG_OA(tbA * 4 + (lane & 7), 0), ep);
      __syncwarp();
      fence_async_all();
      if (lane == 0) TS(2, 13);
      const CUtensorMap* mW = isB ? &mWoB : &mWoA;
#pragma unroll 1
      for (int it = 0; it < 8; it++) {
        const int n = (!isB && it >= 6) ? 13 - it : it;
        uint32_t wb = BAR_CL(n < 3 ? 0 : (n == 3 ? 2 : 3));
        if (isB) { if (n >= 5) wb = n == 7 ? BAR_CL(4) : BAR_TE(n - 5); }
        else if (n >= 6) wb = n == 6 ? BAR_CL(4) : BAR_TE(0);
        if (it < 6) mbar_wait_long(wb, 0); else mbar_wait(wb, 0);
        const uint32_t sl = tail_slots(isB, n), fb = BAR_TF(n);
        const bool withX = isB || n < 4;
        const int k0 = isB ? n * 64 : (n < 4 ? n * 128 : ((hg + n) & 3) * 128 + 64);
        if (elect_one()) {
          mbar_expect_tx(fb, withX ? 32768 : 16384);
          if (withX) {
            tma2d(sb + (sl & 255) * 8192, &mO, k0, isB * S_TOK + tok0, fb);
            tma2d(sb + ((sl >> 8) & 255) * 8192, &mO, k0, isB * S_TOK + tok0 + 64, fb);
          }
          tma2d(sb + ((sl >> 16) & 255) * 8192, mW, hg * 128, k0, fb);
          tma2d(sb + (sl >> 24) * 8192, mW, hg * 128 + 64, k0, fb);
        }
      }
      if (lane == 0) g_epoch[blockIdx.x] = ep;
    } else if (w4 == 3) {
      write_ones();
      flag_wait(FLAG_KV, ep * 128);
      const uint4 a = *(const uint4*)(g_stats + lane * 4);
      const float kmax2 = __uint_as_float(__reduce_max_sync(~0u, a.x)) + __uint_as_float(__reduce_max_sync(~0u, a.y));
      const float vmax = __uint_as_float(__reduce_max_sync(~0u, max(a.z, a.w)));
      const float lv = vmax > 0.f ? __log2f(vmax) : 0.f;
      const float lim = fminf(90.f, fminf(91.f + lv, 95.f - lv));
      float thr = -1.f;
      if (vmax < 1e27f && kmax2 <= 65536.f && lim > 2.f) thr = fminf(60000.f, (lim * lim - 1.f) / (kmax2 * 1.02f + 1e-30f));
      mbar_wait_long(BAR_VB(2), 0);
      uint32_t nmax = 0;
#pragma unroll 2
      for (int i = 0; i < 16; i++) {
        uint32_t x[4], y[4];
        const uint32_t ad = sb + OFF_F + i * 1024 + (lane >> 3) * 256 + (lane & 7) * 16;
        lds4(ad, x); lds4(ad + 128, y);
        uint32_t n = hfma2(x[0], x[0], hfma2(x[1], x[1], hfma2(x[2], x[2], hfma2(x[3], x[3], 0u))));
        n = hfma2(y[0], y[0], hfma2(y[1], y[1], hfma2(y[2], y[2], hfma2(y[3], y[3], n))));
        n = hadd2(n, n >> 16);
        nmax = max(nmax, n & 0x7FFFu);
      }
      nmax = __reduce_max_sync(~0u, nmax);
      const bool ok = __half2float(__ushort_as_half((unsigned short)nmax)) <= thr;
      if (lane == 0) { sts1(sM + 16, ok ? 1u : 0u); mbar_arrive(BAR_Q2); }
    } else {
      const int tok = (w4 - 1) * 32 + lane;
      int step, col;
      if ((tbA & 3) == 0) {
        const int b8 = tbA >> 2;
        if (tok < 22) { step = tok; col = 24 + b8; }
        else { const int c = tok >= 43; step = tok - 22 - 21 * c; col = 32 + b8 * 2 + c; }
      } else {
        const int b24 = (tbA >> 2) * 3 + (tbA & 3) - 1;
        if (tok < 42) { const int c = tok >= 21; step = tok - 21 * c; col = 48 + b24 * 2 + c; }
        else { step = tok - 42; col = b24; }
      }
      const int kap = step * STEPK + col;
      const bool chained = col >= 24;
      uint32_t v[4], o[4];
      lds4(sT + tok * 16, v);
      g_KV[(4 + hg) * S_TOK + kap] = make_uint4(v[0], v[1], v[2], v[3]);
      float st = 0.f;
      if (hg < 2) {
        o[0] = o[1] = o[2] = o[3] = 0;
        if (chained && step > 0) lds4(sT + tok * 16 - 16, o);
        const float sc = chained ? 2.f : 1.f;
#pragma unroll
        for (int u = 0; u < 4; u++) {
          const float x = bf_lo(v[u]), y = bf_hi(v[u]);
          st += x * x + y * y;
          o[u] = pack_f16((x - bf_lo(o[u])) * sc, (y - bf_hi(o[u])) * sc);
        }
      } else {
        const float sc = chained ? VSHIFT : 1.f;
#pragma unroll
        for (int u = 0; u < 4; u++) { float x = bf_lo(v[u]), y = bf_hi(v[u]); st += fabsf(x) + fabsf(y); o[u] = pack_bf16(x * sc, y * sc); }
      }
      g_KV[hg * S_TOK + kap] = make_uint4(o[0], o[1], o[2], o[3]);
      const uint32_t um = __reduce_max_sync(~0u, __float_as_uint(st) & 0x7FFFFFFFu);
      if (w4 == 2) {
        if (lane == 0) sts1(sM + 24, um);
        named_arrive(10, 64);
        write_ones();
        if (!isB) {
          mbar_wait_long(BAR_CL(3), 0);
          mbar_wait_long(BAR_RL, 0);
          uint32_t pend = 0xFE;
          const int li = lane & 7;
          const uint32_t* fl = FLAG_OA((tbA + (li & 1)) * 4 + ((hg + (li >> 1)) & 3), 1);
#pragma unroll 1
          for (int it = 0; pend; it++) {
            uint32_t fv;
            asm volatile("ld.acquire.gpu.global.u32 %0, [%1];" : "=r"(fv) : "l"(fl) : "memory");
            uint32_t go = __ballot_sync(~0u, (int32_t)(fv - ep) >= 0 && mbar_test(li >= 6 ? BAR_TE(0) : BAR_CL(4), 0)) & pend;
            pend &= ~go;
            if (go) fence_async_all();
#pragma unroll 1
            while (go) {
              const int b = __ffs(go) - 1;
              go &= go - 1;
              const uint32_t slot = (tail_slots(0, 4 + (b >> 1)) >> (8 * (b & 1))) & 255;
              if (elect_one()) {
                mbar_expect_tx(BAR_TF(8 + b), 8192);
                tma2d(sb + slot * 8192, &mO, ((hg + (b >> 1)) & 3) * 128 + 64, tok0 + (b & 1) * 64, BAR_TF(8 + b));
              }
            }
            if (it > 2000000) __trap();
          }
          if (lane == 0) TS(2, 14);
        }
      }
      else {
        named_bar(10, 64);
        if (elect_one()) {
          g_stats[tbA * 4 + hg] = max(um, lds1(sM + 24));
          fence_async_all();
          flag_add(FLAG_KV);
          TS(1, 9);
          mbar_wait_long(BAR_BDONE, 0);
          tma2d_store(&mQst, sb + OFF_F + 49152, hq * 64, S_TOK + ttB * 128);
          bulk_commit();
          bulk_wait_all();
          fence_async_all();
          flag_add(FLAG_B(hq >> 1));
          TS(0, 12);
          mbar_wait(BAR_Q, 0);
          mbar_arrive(BAR_CL(0));
#pragma unroll 1
          for (int p = 0; p < 2; p++) {
            mbar_wait_long(BAR_OD(p), 0);
            if (p == 0) {
#pragma unroll
              for (int w = 0; w < 4; w++) tma2d_store(&mO16, sb + OFF_F + w * 2048, hg * 128 + w * 16, tbA * 64);
            } else {
              tma2d_store(&mO, sb + 26 * 8192, hg * 128 + 64, tbA * 64);
            }
            bulk_commit();
            bulk_wait_all();
            if (p == 0) mbar_arrive(BAR_CL(1));
            PUBLISH(FLAG_OA(tbA * 4 + hg, p));
          }
          TS(2, 0);
        }
      }
    }
    return;
  }
  if (helper) { helper_cta(blockIdx.x - 128, sb, bars, wg, w4, &mQst, &mOst); return; }

  {
    float acc[64];
    if (wg == 0) proj_loop<0>(acc, sb, bars, 16384, 0, wg, sWKV, &mWq, hg * 128, w4 == 0);
    else proj_loop<1>(acc, sb, bars, 16384 + wg * 8192, 49152, wg, sWKV, &mWqkv, (wg - 1) * 512 + hq * 64, w4 == 0);
    if (tid == 0) TS(0, 10);
    const uint32_t sF = sb + OFF_F;
    const uint32_t qa = sF + w4 * 512 + ((lane >> 3) & 1) * 256 + (lane >> 4) * 128 + (lane & 7) * 16;
    if (wg == 0) {
#pragma unroll
      for (int hd = 0; hd < 4; hd++)
        stsm4(qa + hd * 2048, pack_f16(acc[8 * hd] * QSCALE, acc[8 * hd + 1] * QSCALE), pack_f16(acc[8 * hd + 2] * QSCALE, acc[8 * hd + 3] * QSCALE),
              pack_f16(acc[8 * hd + 4] * QSCALE, acc[8 * hd + 5] * QSCALE), pack_f16(acc[8 * hd + 6] * QSCALE, acc[8 * hd + 7] * QSCALE));
      fence_async();
      __syncwarp();
      if (lane == 0) mbar_arrive(BAR_Q);
    } else {
      if (wg != 3) named_arrive(6, 384);
      if (wg != 1) named_arrive(8, 384);
    }
    asm volatile("setmaxnreg.inc.sync.aligned.u32 112;");
    fence_regs<64>(acc);
    if (wg == 0) {
#pragma unroll
      for (int hd = 4; hd < 8; hd++)
        stsm4(qa + hd * 2048, pack_f16(acc[8 * hd] * QSCALE, acc[8 * hd + 1] * QSCALE), pack_f16(acc[8 * hd + 2] * QSCALE, acc[8 * hd + 3] * QSCALE),
              pack_f16(acc[8 * hd + 4] * QSCALE, acc[8 * hd + 5] * QSCALE), pack_f16(acc[8 * hd + 6] * QSCALE, acc[8 * hd + 7] * QSCALE));
      fence_async();
      __syncwarp();
      if (lane == 0) mbar_arrive(BAR_VB(2));
    } else if (wg == 3) {
      named_bar(6, 384);
      const int t = tid & 127;
#pragma unroll
      for (int j = 0; j < 8; j++)
        sts4(sF + 24576 + j * 2048 + t * 16, pack_bf16(acc[8 * j], acc[8 * j + 1]), pack_bf16(acc[8 * j + 2], acc[8 * j + 3]),
             pack_bf16(acc[8 * j + 4], acc[8 * j + 5]), pack_bf16(acc[8 * j + 6], acc[8 * j + 7]));
      named_arrive(7, 256);
    } else {
      if (wg == 1) {
        named_bar(8, 384);
        const int m = lane >> 3, r = lane & 7;
#pragma unroll
        for (int j = 0; j < 16; j += 2) {
          const int tok = (j + (m >> 1)) * 8 + r;
          const int chunk = w4 * 2 + (m & 1);
          stsm4t(sF + 49152 + tok * 128 + ((chunk ^ r) << 4), pack_bf16(acc[4 * j], acc[4 * j + 1]), pack_bf16(acc[4 * j + 2], acc[4 * j + 3]),
                 pack_bf16(acc[4 * j + 4], acc[4 * j + 5]), pack_bf16(acc[4 * j + 6], acc[4 * j + 7]));
        }
        fence_async();
      } else {
        uint32_t p[32];
#pragma unroll
        for (int i = 0; i < 32; i++) p[i] = phi2(acc[2 * i], acc[2 * i + 1]);
        named_bar(7, 256);
        float kv0[4] = {0, 0, 0, 0}, kv1[4] = {0, 0, 0, 0}, z0[4] = {0, 0, 0, 0}, z1[4] = {0, 0, 0, 0};
        const uint32_t one = 0x3F803F80u;
        const int t = tid & 127;
#pragma unroll
        for (int j = 0; j < 8; j++) {
          uint32_t a[4];
          lds4(sF + 24576 + j * 2048 + t * 16, a);
          mma_bf16(kv0, a[0], a[1], a[2], a[3], p[4 * j], p[4 * j + 2]);
          mma_bf16(kv1, a[0], a[1], a[2], a[3], p[4 * j + 1], p[4 * j + 3]);
          mma_bf16(z0, one, one, one, one, p[4 * j], p[4 * j + 2]);
          mma_bf16(z1, one, one, one, one, p[4 * j + 1], p[4 * j + 3]);
        }
        float4* dst = g_kvp + ((ttB * 32 + hq * 4 + w4) * 3) * 32 + lane;
        dst[0] = make_float4(kv0[0], kv0[1], kv1[0], kv1[1]);
        dst[32] = make_float4(kv0[2], kv0[3], kv1[2], kv1[3]);
        dst[64] = make_float4(z0[0], z0[1], z1[0], z1[1]);
      }
      __syncwarp();
      if (lane == 0) mbar_arrive(BAR_BDONE);
    }
  }

  bool safe = true;
  {
    const uint32_t c63 = 0x1F801F80u + (threadIdx.x >> 20);
    const uint32_t m1 = (gridDim.x >> 20) - 1u;
    const uint64_t dK0 = make_desc(sb + OFF_K, 32768, 128, 0);
    const uint64_t dV0 = make_desc(sb + OFF_V, 128, 32768, 0);
    constexpr uint32_t dKV = ((2048u - 8u)  __H0__ ) + STEPK - (OFF_V - OFF_K) / 16;
    float Sm[12], Sp[36], O[12];
    uint32_t P[24];
    uint64_t dQ = make_desc(sb + OFF_F + wg * 2048, 128, 256, 0);
#pragma unroll
    for (int i = 0; i < 36; i++) Sp[i] = SMAGIC;
#pragma unroll
    for (int i = 0; i < 12; i++) Sm[i] = 0.f;
    fence_regs<12>(Sm); fence_regs<36>(Sp);
    mbar_wait(BAR_Q, 0);
    mbar_wait(BAR_KV(0), 0);
    wg_fence();
    wg_qs72<1>(Sp, dQ, dK0 + 24);
    wg_qs24<0>(Sm, dQ, dK0);
    wg_commit();
    wg_wait<0>();
    fence_regs<12>(Sm); fence_regs<36>(Sp);
#pragma unroll 1
    for (int pass = 0; pass < 2; pass++) {
#pragma unroll
      for (int i = 0; i < 12; i++) O[i] = 0.f;
      fence_regs<12>(O);
      if (tid == 0) TSW(1, 2 + 2 * pass);
      uint32_t vlo = (uint32_t)dV0;
#pragma unroll 1
      for (int seg = 0; seg < 4; seg++) {
        if (pass == 0) {
          if (seg < 3) mbar_wait(seg == 0 ? BAR_VB(0) : BAR_KV(seg), 0);
        } else if (seg >= 1) {
          if ((tid & 127) == 0) {
            mbar_arrive(BAR_CL(seg));
            if (seg == 3) take_role(sM, wg);
          }
          __syncwarp();
        }
        if ((tid & 127) == 0) TSW(4 + wg, pass * 5 + seg);
        const uint32_t vend = vlo + (seg == 3 ? 3 : 6) * STEPK;
#pragma unroll 1
        for (; vlo != vend; vlo += 3 * STEPK) {
          uint64_t dK, dV;
          asm("mov.b64 %0, {%1, %2};" : "=l"(dK) : "r"(vlo + dKV), "r"(8u));
          asm("mov.b64 %0, {%1, %2};" : "=l"(dV) : "r"(vlo), "r"(2048u));
#pragma unroll
          for (int u = 0; u < 3; u++) {
          { uint32_t w[18], y[18], z[18]; float e[12];
            X_MU(0) X_PR(0) X_LO(0) X_IM(0) X_MU(1) X_FM(0) X_PR(1) X_LO(1) X_IM(1) X_MU(2) X_FM(1) X_PR(2)
            X_LO(2) X_MU(3) X_IM(2) X_FM(2) X_PR(3) X_LO(3) X_PK(0) X_MU(4) X_IM(3) X_FM(3) X_PR(4) X_LO(4)
            X_MU(5) X_IM(4) X_FM(4) X_PR(5) X_PK(1) X_MU(6) X_LO(5) X_IM(5) X_FM(5) X_PR(6) X_MU(7) X_LO(6)
            X_IM(6) X_FM(6) X_MU(8) X_PR(7) X_PK(2) X_LO(7) X_IM(7) X_FM(7) X_MU(9) X_PR(8) X_LO(8) X_IM(8)
            X_FM(8) X_PK(3) X_MU(10) X_PR(9) X_LO(9) X_IM(9) X_MU(11) X_FM(9) X_PR(10) X_LO(10) X_IM(10) X_PK(4)
            X_FM(10) X_PR(11) X_LO(11) X_IM(11) X_FM(11) X_PR(12) X_LO(12) X_PK(5) X_IM(12) X_FM(12) X_PR(13) X_LO(13)
            X_IM(13) X_FM(13) X_PR(14) X_LO(14) X_IM(14) X_FM(14) X_PR(15) X_LO(15) X_IM(15) X_FM(15) X_PR(16) X_LO(16)
            X_IM(16) X_FM(16) X_PR(17) X_LO(17) X_IM(17) X_FM(17) }
          fence_regs<24>(P);
          wg_fence();
          wg_pv24<1>(O, &P[20], dV + u * STEPK + 80);
          wg_pv24<1>(O, &P[16], dV + u * STEPK + 64);
          wg_pv24<1>(O, &P[12], dV + u * STEPK + 48);
          wg_pv24<1>(O, &P[8], dV + u * STEPK + 32);
          wg_pv24<1>(O, &P[4], dV + u * STEPK + 16);
          wg_pv24<1>(O, &P[0], dV + u * STEPK + 0);
          wg_qs72<1>(Sp, dQ, dK + u * STEPK + 24);
          wg_qs24<0>(Sm, dQ, dK + u * STEPK);
          wg_commit();
          wg_wait<0>();
          fence_regs<12>(Sm); fence_regs<36>(Sp); fence_regs<12>(O); fence_regs<24>(P);
          }
        }
      }
#pragma unroll
      for (int i = 0; i < 6; i++) P[i] = pack_bf16(ex2f(Sm[2 * i]), ex2f(Sm[2 * i + 1]));
      P[6] = exp2_pair_fix(Sp[0], Sp[1], c63, m1);
      P[7] = exp2_pair_fix(Sp[2], Sp[3], c63, m1);
      fence_regs<8>(P);
#pragma unroll
      for (int i = 0; i < 36; i++) Sp[i] = SMAGIC;
      fence_regs<36>(Sp);
      mbar_wait(pass == 0 ? BAR_Q2 : BAR_CL(3), 0);
      const uint32_t sO = pass == 0 ? sb + OFF_F + wg * 2048 + w4 * 512 + (lane & 15) * 32 + (lane >> 4) * 16
                                    : sb + 26 * 8192 + (w4 * 16 + (lane & 15)) * 128 + (((wg * 2 + (lane >> 4)) ^ (lane & 7)) << 4);
      dQ += 512;
      wg_fence();
      wg_pv24<1>(O, &P[0], dV0 + 21 * STEPK);
      wg_pv24<1>(O, &P[4], dV0 + 21 * STEPK + 16);
      wg_commit();
      wg_qs72<1>(Sp, dQ, dK0 + 24);
      wg_qs24<0>(Sm, dQ, dK0);
      wg_commit();
      wg_wait<1>();
      fence_regs<12>(O);
      const float l0 = __shfl_sync(~0u, O[8], lane & ~3), l1 = __shfl_sync(~0u, O[10], lane & ~3);
      const float i0 = rcpf(l0), i1 = rcpf(l1);
      stsm4(sO,
            pack_bf16(O[0] * i0, O[1] * i0), pack_bf16(O[2] * i1, O[3] * i1),
            pack_bf16(O[4] * i0, O[5] * i0), pack_bf16(O[6] * i1, O[7] * i1));
      fence_async();
      {
        safe = __all_sync(~0u, lds1(sM + 16) != 0);
      }
      if (safe && lane == 0) mbar_arrive(BAR_OD(pass));
      wg_wait<0>();
      fence_regs<12>(Sm); fence_regs<36>(Sp);
      if (!safe) break;
      if ((tid & 127) == 0) TSW(4 + wg, pass * 5 + 4);
      if (tid == 0) TSW(1, 3 + 2 * pass);
    }
  }
  if (!safe) {
    if ((tid & 127) == 0) { mbar_arrive(BAR_CL(1)); mbar_arrive(BAR_CL(2)); mbar_arrive(BAR_CL(3)); take_role(sM, wg); }
#pragma unroll 1
    for (int pass = 0; pass < 2; pass++) {
      const int t = tid & 127;
      mbar_wait(BAR_CL(3), 0);
      attn_slow(prm.xa + (size_t)tbA * 64 * D_MOD, prm.wq + (hg * 8 + pass * 4 + wg) * 16,
                pass == 0 ? sb + OFF_F + wg * 2048 + t * 16
                          : sb + 26 * 8192 + (t >> 1) * 128 + (((wg * 2 + (t & 1)) ^ ((t >> 1) & 7)) << 4));
      __syncwarp();
      if (lane == 0) mbar_arrive(BAR_OD(pass));
    }
  }

  {
    named_bar(wg + 1, 128);
    if ((tid & 127) == 0) mbar_arrive(BAR_CL(4));
    const int role = __shfl_sync(~0u, lds1(sM + 32 + wg * 4), 0);
    if ((tid & 127) == 0) TSW(4 + wg, 10);
    const int m = lane >> 3, r = lane & 7;
    const uint32_t stoff = (w4 * 16 + (m & 1) * 8 + r) * 128;
    if (role < 2) {
      if (role == 0 && (tid & 127) == 0) mbar_arrive(BAR_RL);
      if (!isB || role == 1) mbar_wait(BAR_CL(4), 0);
      float acc[64];
#pragma unroll 1
      for (int n = 0; n < 8; n++) {
        const uint32_t sl = tail_slots(isB, n);
        const uint32_t w0 = (sl >> 16) & 255, w1 = sl >> 24;
        const uint64_t da = make_desc(sb + ((sl >> (8 * role)) & 255) * 8192, 16, 1024, 1);
        const uint64_t db = make_desc(sb + w0 * 8192, (w1 - w0) * 8192, 1024, 1);
        mbar_wait(BAR_TF(n), 0);
        if (!isB && n >= 4) mbar_wait(n == 4 && role == 0 ? BAR_OD(1) : BAR_TF(2 * n + role), 0);
        if ((tid & 127) == 0 && role == 1) TSW(2, 2 + n);
        wg_fence();
#pragma unroll
        for (int k = 0; k < 4; k++) wg_ss128<0, 1>(acc, da + k * 2, db + k * 128, (n | k) != 0);
        wg_commit();
        wg_wait<1>();
        if ((n == 1 || n == 2) && (tid & 127) == 0) mbar_arrive(BAR_TE(n - 1));
        __syncwarp();
      }
      wg_wait<0>();
      fence_regs<64>(acc);
      if ((tid & 127) == 0) TSW(4 + wg, 11);
      const uint32_t x0 = sb + (role ? 16 : 8) * 8192, x1 = sb + (role ? 5 : 1) * 8192;
#pragma unroll
      for (int j = 0; j < 16; j += 2)
        stsm4((j < 8 ? x0 : x1) + stoff + ((((j & 7) + (m >> 1)) ^ r) << 4),
              pack_bf16(acc[4 * j], acc[4 * j + 1]), pack_bf16(acc[4 * j + 2], acc[4 * j + 3]),
              pack_bf16(acc[4 * j + 4], acc[4 * j + 5]), pack_bf16(acc[4 * j + 6], acc[4 * j + 7]));
      __syncwarp();
      uint4* dst = (uint4*)(prm.out + (size_t)(tok0 + role * 64 + w4 * 16 + (lane >> 4)) * 1024 + isB * 512 + hg * 128) + (lane & 15);
      const uint32_t src = ((lane & 8) ? x1 : x0) + (w4 * 16 + (lane >> 4)) * 128;
#pragma unroll
      for (int i = 0; i < 8; i++) {
        uint32_t v[4];
        lds4(src + i * 256 + (((lane & 7) ^ ((2 * i + (lane >> 4)) & 7)) << 4), v);
        dst[i * 256] = make_uint4(v[0], v[1], v[2], v[3]);
      }
      if ((tid & 127) == 0) TS(2, 11 + role);
    }
  }
}

typedef CUresult (*EncodeFn)(CUtensorMap*, CUtensorMapDataType, cuuint32_t, void*, const cuuint64_t*, const cuuint64_t*,
                             const cuuint32_t*, const cuuint32_t*, CUtensorMapInterleave, CUtensorMapSwizzle,
                             CUtensorMapL2promotion, CUtensorMapFloatOOBfill);

static void make_map(EncodeFn enc, CUtensorMap* m, const void* ptr, uint64_t cols, uint64_t rows, uint32_t bc, uint32_t br,
                     CUtensorMapSwizzle sw = CU_TENSOR_MAP_SWIZZLE_128B) {
  cuuint64_t dims[2] = {cols, rows};
  cuuint64_t strides[1] = {cols * 2};
  cuuint32_t box[2] = {bc, br};
  cuuint32_t es[2] = {1, 1};
  enc(m, CU_TENSOR_MAP_DATA_TYPE_BFLOAT16, 2, (void*)ptr, dims, strides, box, es, CU_TENSOR_MAP_INTERLEAVE_NONE,
      sw, CU_TENSOR_MAP_L2_PROMOTION_L2_256B, CU_TENSOR_MAP_FLOAT_OOB_FILL_NONE);
}

extern "C" void kernel_launch(void* const* d_in, const int* in_sizes, int n_in, void* d_out, int out_size) {
  (void)in_sizes; (void)n_in; (void)out_size;
  static EncodeFn enc = nullptr;
  static void* pQ = nullptr; static void* pO = nullptr;
  if (!enc) {
    void* fn = nullptr; cudaDriverEntryPointQueryResult qr;
    cudaGetDriverEntryPoint("cuTensorMapEncodeTiled", &fn, cudaEnableDefault, &qr);
    enc = (EncodeFn)fn;
    cudaGetSymbolAddress(&pQ, g_Q);
    cudaGetSymbolAddress(&pO, g_O);
    cudaFuncSetAttribute(k1_main, cudaFuncAttributeMaxDynamicSharedMemorySize, SM_TOTAL);
  }
  CUtensorMap mXA64, mXB, mWq, mWqkv, mQst, mO, mOst, mWoA, mWoB, mO16;
  make_map(enc, &mXA64, d_in[0], 512, 2048, 64, 64);
  make_map(enc, &mWq, d_in[1], 512, 512, 64, 64);
  make_map(enc, &mWoA, d_in[4], 512, 512, 64, 64);
  make_map(enc, &mXB, d_in[5], 512, 2048, 64, 128);
  make_map(enc, &mWqkv, d_in[6], 1536, 512, 64, 64);
  make_map(enc, &mWoB, d_in[7], 512, 512, 64, 64);
  make_map(enc, &mQst, pQ, 512, 4096, 64, 128);
  make_map(enc, &mO, pO, 512, 4096, 64, 64);
  make_map(enc, &mOst, pO, 512, 4096, 64, 128);
  make_map(enc, &mO16, pO, 512, 4096, 16, 64, CU_TENSOR_MAP_SWIZZLE_NONE);
  Params prm{(const __nv_bfloat16*)d_in[2], (const __nv_bfloat16*)d_in[3], (const __nv_bfloat16*)d_in[0], (const __nv_bfloat16*)d_in[1], (__nv_bfloat16*)d_out};
  k1_main<<<132, 640, SM_TOTAL, cudaStreamPerThread>>>(mXA64, mXB, mWq, mWqkv, mQst, mOst, mO, mWoA, mWoB, mO16, prm);
}
```

```cpp
#include <cuda_runtime.h>
#include <cuda_bf16.h>
#include <cuda_fp16.h>
#include <cuda.h>
#include <stdint.h>

#define S_TOK 2048
#define D_MOD 512

__device__ __align__(1024) __nv_bfloat16 g_Q[2 * S_TOK * D_MOD];
__device__ __align__(1024) __nv_bfloat16 g_O[2 * S_TOK * D_MOD];
__device__ __align__(1024) uint4 g_KV[8 * S_TOK];
__device__ __align__(16) uint32_t g_stats[128];
__device__ __align__(16) float4 g_kvp[16 * 32 * 3 * 32];

#define TS(k, i) do {} while (0)
#define TSW(k, i) do {} while (0)
__device__ __forceinline__ uint32_t smem_u32(const void* p) { return (uint32_t)__cvta_generic_to_shared(p); }
__device__ __forceinline__ void mbar_init(uint32_t bar, int cnt) { asm volatile("mbarrier.init.shared::cta.b64 [%0], %1;" :: "r"(bar), "r"(cnt) : "memory"); }
__device__ __forceinline__ void mbar_expect_tx(uint32_t bar, uint32_t bytes) { asm volatile("mbarrier.arrive.expect_tx.shared::cta.b64 _, [%0], %1;" :: "r"(bar), "r"(bytes) : "memory"); }
__device__ __forceinline__ bool mbar_try(uint32_t bar, uint32_t parity) {
  uint32_t ok;
  asm volatile("{\n.reg .pred p;\nmbarrier.try_wait.parity.shared::cta.b64 p, [%1], %2;\nselp.b32 %0, 1, 0, p;\n}\n" : "=r"(ok) : "r"(bar), "r"(parity) : "memory");
  return ok;
}
__device__ __forceinline__ void mbar_wait(uint32_t bar, uint32_t parity) {
  asm volatile("{\n.reg .pred p;\n.reg .u32 c;\nmov.u32 c, 0;\n"
               "LW_%=:\n"
               "mbarrier.try_wait.parity.shared::cta.b64 p, [%0], %1;\n"
               "@p bra LD_%=;\n"
               "add.u32 c, c, 1;\n"
               "setp.lt.u32 p, c, 4000000;\n"
               "@p bra LW_%=;\n"
               "trap;\n"
               "LD_%=:\n}\n" :: "r"(bar), "r"(parity) : "memory");
}
__device__ __forceinline__ void mbar_arrive_cta(uint32_t bar, uint32_t cta) {
  asm volatile("{\n.reg .b32 ra;\nmapa.shared::cluster.u32 ra, %0, %1;\nmbarrier.arrive.shared::cluster.b64 _, [ra];\n}\n" :: "r"(bar), "r"(cta) : "memory");
}
__device__ __forceinline__ void cluster_sync() {
  asm volatile("barrier.cluster.arrive.relaxed.aligned;\nbarrier.cluster.wait.aligned;" ::: "memory");
}
__device__ __forceinline__ void tma2d(uint32_t dst, const CUtensorMap* m, int c0, int c1, uint32_t bar) {
  asm volatile("cp.async.bulk.tensor.2d.shared::cluster.global.mbarrier::complete_tx::bytes [%0], [%1, {%3, %4}], [%2];"
               :: "r"(dst), "l"(m), "r"(bar), "r"(c0), "r"(c1) : "memory");
}
__device__ __forceinline__ void tma2d_mc(uint32_t dst, const CUtensorMap* m, int c0, int c1, uint32_t bar, uint16_t mask) {
  asm volatile("cp.async.bulk.tensor.2d.shared::cluster.global.mbarrier::complete_tx::bytes.multicast::cluster [%0], [%1, {%3, %4}], [%2], %5;"
               :: "r"(dst), "l"(m), "r"(bar), "r"(c0), "r"(c1), "h"(mask) : "memory");
}
__device__ __forceinline__ void tma2d_store(const CUtensorMap* m, uint32_t src, int c0, int c1) {
  asm volatile("cp.async.bulk.tensor.2d.global.shared::cta.bulk_group [%0, {%2, %3}], [%1];"
               :: "l"(m), "r"(src), "r"(c0), "r"(c1) : "memory");
}
__device__ __forceinline__ void bulk_g2s(uint32_t dst, const void* src, uint32_t bytes, uint32_t bar) {
  asm volatile("cp.async.bulk.shared::cluster.global.mbarrier::complete_tx::bytes [%0], [%1], %2, [%3];"
               :: "r"(dst), "l"(src), "r"(bytes), "r"(bar) : "memory");
}
__device__ __forceinline__ void bulk_commit() { asm volatile("cp.async.bulk.commit_group;" ::: "memory"); }
__device__ __forceinline__ void bulk_wait_all() { asm volatile("cp.async.bulk.wait_group 0;" ::: "memory"); }
__device__ __forceinline__ void fence_async() { asm volatile("fence.proxy.async.shared::cta;" ::: "memory"); }
__device__ __forceinline__ void named_bar(int id, int n) { asm volatile("bar.sync %0, %1;" :: "r"(id), "r"(n) : "memory"); }
__device__ __forceinline__ void pdl_launch() { asm volatile("griddepcontrol.launch_dependents;" ::: "memory"); }
__device__ __forceinline__ void pdl_wait() { asm volatile("griddepcontrol.wait;" ::: "memory"); }
__device__ __forceinline__ void wg_fence() { asm volatile("wgmma.fence.sync.aligned;" ::: "memory"); }
__device__ __forceinline__ void wg_commit() { asm volatile("wgmma.commit_group.sync.aligned;" ::: "memory"); }
template <int n> __device__ __forceinline__ void wg_wait() { asm volatile("wgmma.wait_group.sync.aligned %0;" :: "n"(n) : "memory"); }
template <int n> __device__ __forceinline__ void fence_regs(float* r) {
#pragma unroll
  for (int i = 0; i < n; i++) asm volatile("" : "+f"(r[i]) :: "memory");
}
template <int n> __device__ __forceinline__ void fence_regs(uint32_t* r) {
#pragma unroll
  for (int i = 0; i < n; i++) asm volatile("" : "+r"(r[i]) :: "memory");
}
__device__ __forceinline__ uint64_t make_desc(uint32_t addr, uint32_t lbo, uint32_t sbo, uint32_t swz) {
  return (uint64_t)((addr & 0x3FFFF) >> 4) | ((uint64_t)(lbo >> 4) << 16) | ((uint64_t)(sbo >> 4) << 32) | ((uint64_t)swz << 62);
}
__device__ __forceinline__ float ex2f(float x) { float y; asm("ex2.approx.ftz.f32 %0, %1;" : "=f"(y) : "f"(x)); return y; }
__device__ __forceinline__ uint32_t pack_bf16(float lo, float hi) { uint32_t r; asm("cvt.rn.bf16x2.f32 %0, %1, %2;" : "=r"(r) : "f"(hi), "f"(lo)); return r; }
__device__ __forceinline__ uint32_t pack_f16(float lo, float hi) { uint32_t r; asm("cvt.rn.f16x2.f32 %0, %1, %2;" : "=r"(r) : "f"(hi), "f"(lo)); return r; }
__device__ __forceinline__ float bf_lo(uint32_t v) { return __uint_as_float(v << 16); }
__device__ __forceinline__ float bf_hi(uint32_t v) { return __uint_as_float(v & 0xFFFF0000u); }
__device__ __forceinline__ float rbf(float x) { return __bfloat162float(__float2bfloat16_rn(x)); }
__device__ __forceinline__ void stsm4(uint32_t a, uint32_t r0, uint32_t r1, uint32_t r2, uint32_t r3) {
  asm volatile("stmatrix.sync.aligned.m8n8.x4.shared.b16 [%0], {%1,%2,%3,%4};" :: "r"(a), "r"(r0), "r"(r1), "r"(r2), "r"(r3) : "memory");
}
__device__ __forceinline__ void stsm4t(uint32_t a, uint32_t r0, uint32_t r1, uint32_t r2, uint32_t r3) {
  asm volatile("stmatrix.sync.aligned.m8n8.x4.trans.shared.b16 [%0], {%1,%2,%3,%4};" :: "r"(a), "r"(r0), "r"(r1), "r"(r2), "r"(r3) : "memory");
}
__device__ __forceinline__ void mma_bf16(float* d, uint32_t a0, uint32_t a1, uint32_t a2, uint32_t a3, uint32_t b0, uint32_t b1) {
  asm volatile("mma.sync.aligned.m16n8k16.row.col.f32.bf16.bf16.f32 {%0,%1,%2,%3}, {%4,%5,%6,%7}, {%8,%9}, {%0,%1,%2,%3};"
               : "+f"(d[0]), "+f"(d[1]), "+f"(d[2]), "+f"(d[3]) : "r"(a0), "r"(a1), "r"(a2), "r"(a3), "r"(b0), "r"(b1));
}
template<int SD> __device__ __forceinline__ void wg_qs24(float* d, uint64_t da, uint64_t db) {
  asm volatile("wgmma.mma_async.sync.aligned.m64n24k16.f32.f16.f16 {%0,%1,%2,%3,%4,%5,%6,%7,%8,%9,%10,%11}, %12, %13, %14, 1, 1, 0, 0;"
   : "+f"(d[0]),"+f"(d[1]),"+f"(d[2]),"+f"(d[3]),"+f"(d[4]),"+f"(d[5]),"+f"(d[6]),"+f"(d[7]),"+f"(d[8]),"+f"(d[9]),"+f"(d[10]),"+f"(d[11])
   : "l"(da),"l"(db),"n"(SD));
}
template<int SD> __device__ __forceinline__ void wg_qs72(float* d, uint64_t da, uint64_t db) {
  asm volatile("wgmma.mma_async.sync.aligned.m64n72k16.f32.f16.f16 {%0,%1,%2,%3,%4,%5,%6,%7,%8,%9,%10,%11,%12,%13,%14,%15,%16,%17,%18,%19,%20,%21,%22,%23,%24,%25,%26,%27,%28,%29,%30,%31,%32,%33,%34,%35}, %36, %37, %38, 1, 1, 0, 0;"
   : "+f"(d[0]),"+f"(d[1]),"+f"(d[2]),"+f"(d[3]),"+f"(d[4]),"+f"(d[5]),"+f"(d[6]),"+f"(d[7]),"+f"(d[8]),"+f"(d[9]),"+f"(d[10]),"+f"(d[11]),"+f"(d[12]),"+f"(d[13]),"+f"(d[14]),"+f"(d[15]),"+f"(d[16]),"+f"(d[17]),"+f"(d[18]),"+f"(d[19]),"+f"(d[20]),"+f"(d[21]),"+f"(d[22]),"+f"(d[23]),"+f"(d[24]),"+f"(d[25]),"+f"(d[26]),"+f"(d[27]),"+f"(d[28]),"+f"(d[29]),"+f"(d[30]),"+f"(d[31]),"+f"(d[32]),"+f"(d[33]),"+f"(d[34]),"+f"(d[35])
   : "l"(da),"l"(db),"n"(SD));
}
template<int SD> __device__ __forceinline__ void wg_qs96(float* d, uint64_t da, uint64_t db) {
  asm volatile("wgmma.mma_async.sync.aligned.m64n96k16.f32.f16.f16 {%0,%1,%2,%3,%4,%5,%6,%7,%8,%9,%10,%11,%12,%13,%14,%15,%16,%17,%18,%19,%20,%21,%22,%23,%24,%25,%26,%27,%28,%29,%30,%31,%32,%33,%34,%35,%36,%37,%38,%39,%40,%41,%42,%43,%44,%45,%46,%47}, %48, %49, %50, 1, 1, 0, 0;"
   : "+f"(d[0]),"+f"(d[1]),"+f"(d[2]),"+f"(d[3]),"+f"(d[4]),"+f"(d[5]),"+f"(d[6]),"+f"(d[7]),"+f"(d[8]),"+f"(d[9]),"+f"(d[10]),"+f"(d[11]),"+f"(d[12]),"+f"(d[13]),"+f"(d[14]),"+f"(d[15]),"+f"(d[16]),"+f"(d[17]),"+f"(d[18]),"+f"(d[19]),"+f"(d[20]),"+f"(d[21]),"+f"(d[22]),"+f"(d[23]),"+f"(d[24]),"+f"(d[25]),"+f"(d[26]),"+f"(d[27]),"+f"(d[28]),"+f"(d[29]),"+f"(d[30]),"+f"(d[31]),"+f"(d[32]),"+f"(d[33]),"+f"(d[34]),"+f"(d[35]),"+f"(d[36]),"+f"(d[37]),"+f"(d[38]),"+f"(d[39]),"+f"(d[40]),"+f"(d[41]),"+f"(d[42]),"+f"(d[43]),"+f"(d[44]),"+f"(d[45]),"+f"(d[46]),"+f"(d[47])
   : "l"(da),"l"(db),"n"(SD));
}
template<int SD> __device__ __forceinline__ void wg_pv24(float* d, const uint32_t* a, uint64_t desc) {
  asm volatile("wgmma.mma_async.sync.aligned.m64n24k16.f32.bf16.bf16 {%0,%1,%2,%3,%4,%5,%6,%7,%8,%9,%10,%11}, {%12,%13,%14,%15}, %16, %17, 1, 1, 1;"
   : "+f"(d[0]),"+f"(d[1]),"+f"(d[2]),"+f"(d[3]),"+f"(d[4]),"+f"(d[5]),"+f"(d[6]),"+f"(d[7]),"+f"(d[8]),"+f"(d[9]),"+f"(d[10]),"+f"(d[11])
   : "r"(a[0]),"r"(a[1]),"r"(a[2]),"r"(a[3]),"l"(desc),"n"(SD));
}
template<int TA, int TB> __device__ __forceinline__ void wg_ss128(float* d, uint64_t da, uint64_t db, int sd) {
  asm volatile("{\n.reg .pred p;\nsetp.ne.b32 p, %66, 0;\n"
   "wgmma.mma_async.sync.aligned.m64n128k16.f32.bf16.bf16 {%0,%1,%2,%3,%4,%5,%6,%7,%8,%9,%10,%11,%12,%13,%14,%15,%16,%17,%18,%19,%20,%21,%22,%23,%24,%25,%26,%27,%28,%29,%30,%31,%32,%33,%34,%35,%36,%37,%38,%39,%40,%41,%42,%43,%44,%45,%46,%47,%48,%49,%50,%51,%52,%53,%54,%55,%56,%57,%58,%59,%60,%61,%62,%63}, %64, %65, p, 1, 1, %67, %68;\n}\n"
   : "+f"(d[0]),"+f"(d[1]),"+f"(d[2]),"+f"(d[3]),"+f"(d[4]),"+f"(d[5]),"+f"(d[6]),"+f"(d[7]),"+f"(d[8]),"+f"(d[9]),"+f"(d[10]),"+f"(d[11]),"+f"(d[12]),"+f"(d[13]),"+f"(d[14]),"+f"(d[15]),"+f"(d[16]),"+f"(d[17]),"+f"(d[18]),"+f"(d[19]),"+f"(d[20]),"+f"(d[21]),"+f"(d[22]),"+f"(d[23]),"+f"(d[24]),"+f"(d[25]),"+f"(d[26]),"+f"(d[27]),"+f"(d[28]),"+f"(d[29]),"+f"(d[30]),"+f"(d[31]),"+f"(d[32]),"+f"(d[33]),"+f"(d[34]),"+f"(d[35]),"+f"(d[36]),"+f"(d[37]),"+f"(d[38]),"+f"(d[39]),"+f"(d[40]),"+f"(d[41]),"+f"(d[42]),"+f"(d[43]),"+f"(d[44]),"+f"(d[45]),"+f"(d[46]),"+f"(d[47]),"+f"(d[48]),"+f"(d[49]),"+f"(d[50]),"+f"(d[51]),"+f"(d[52]),"+f"(d[53]),"+f"(d[54]),"+f"(d[55]),"+f"(d[56]),"+f"(d[57]),"+f"(d[58]),"+f"(d[59]),"+f"(d[60]),"+f"(d[61]),"+f"(d[62]),"+f"(d[63])
   : "l"(da),"l"(db),"r"(sd),"n"(TA),"n"(TB));
}
template<int TA, int TB> __device__ __forceinline__ void wg_ss64(float* d, uint64_t da, uint64_t db, int sd) {
  asm volatile("{\n.reg .pred p;\nsetp.ne.b32 p, %34, 0;\n"
   "wgmma.mma_async.sync.aligned.m64n64k16.f32.bf16.bf16 {%0,%1,%2,%3,%4,%5,%6,%7,%8,%9,%10,%11,%12,%13,%14,%15,%16,%17,%18,%19,%20,%21,%22,%23,%24,%25,%26,%27,%28,%29,%30,%31}, %32, %33, p, 1, 1, %35, %36;\n}\n"
   : "+f"(d[0]),"+f"(d[1]),"+f"(d[2]),"+f"(d[3]),"+f"(d[4]),"+f"(d[5]),"+f"(d[6]),"+f"(d[7]),"+f"(d[8]),"+f"(d[9]),"+f"(d[10]),"+f"(d[11]),"+f"(d[12]),"+f"(d[13]),"+f"(d[14]),"+f"(d[15]),"+f"(d[16]),"+f"(d[17]),"+f"(d[18]),"+f"(d[19]),"+f"(d[20]),"+f"(d[21]),"+f"(d[22]),"+f"(d[23]),"+f"(d[24]),"+f"(d[25]),"+f"(d[26]),"+f"(d[27]),"+f"(d[28]),"+f"(d[29]),"+f"(d[30]),"+f"(d[31])
   : "l"(da),"l"(db),"r"(sd),"n"(TA),"n"(TB));
}
template<int TA, int TB> __device__ __forceinline__ void wg_ss8(float* d, uint64_t da, uint64_t db, int sd) {
  asm volatile("{\n.reg .pred p;\nsetp.ne.b32 p, %6, 0;\n"
   "wgmma.mma_async.sync.aligned.m64n8k16.f32.bf16.bf16 {%0,%1,%2,%3}, %4, %5, p, 1, 1, %7, %8;\n}\n"
   : "+f"(d[0]),"+f"(d[1]),"+f"(d[2]),"+f"(d[3])
   : "l"(da),"l"(db),"r"(sd),"n"(TA),"n"(TB));
}

__device__ __forceinline__ uint32_t phi2(float a, float b) {
  uint32_t r, e;
  asm("cvt.rn.relu.bf16x2.f32 %0, %1, %2;" : "=r"(r) : "f"(b), "f"(a));
  e = pack_bf16(ex2f(a * 1.4426950408889634f), ex2f(b * 1.4426950408889634f));
  asm("add.rn.bf16x2 %0, %0, %1;" : "+r"(e) : "r"(0x35863586u));
  asm("min.NaN.bf16x2 %0, %0, %1;" : "+r"(e) : "r"(0x3F803F80u));
  asm("add.rn.bf16x2 %0, %0, %1;" : "+r"(e) : "r"(r));
  return e;
}

__device__ __forceinline__ void mbar_wait_long(uint32_t bar, uint32_t parity) {
  asm volatile("{\n.reg .pred p;\n.reg .u32 c;\nmov.u32 c, 0;\n"
               "LW_%=:\n"
               "mbarrier.try_wait.parity.shared::cta.b64 p, [%0], %1, 100000;\n"
               "@p bra LD_%=;\n"
               "add.u32 c, c, 1;\n"
               "setp.lt.u32 p, c, 20000;\n"
               "@p bra LW_%=;\n"
               "trap;\n"
               "LD_%=:\n}\n" :: "r"(bar), "r"(parity) : "memory");
}
__device__ __forceinline__ void mbar_arrive(uint32_t bar) { asm volatile("mbarrier.arrive.shared::cta.b64 _, [%0];" :: "r"(bar) : "memory"); }
__device__ __forceinline__ void named_arrive(int id, int n) { asm volatile("bar.arrive %0, %1;" :: "r"(id), "r"(n) : "memory"); }
__device__ __forceinline__ void fence_async_all() { asm volatile("fence.proxy.async.global;" ::: "memory"); }
__device__ __forceinline__ void flag_add(uint32_t* f) { asm volatile("fence.acq_rel.gpu;\nred.relaxed.gpu.global.add.u32 [%0], 1;" :: "l"(f) : "memory"); }
#define PUBLISH(f) asm volatile("fence.proxy.async.global;\nred.relaxed.gpu.global.add.u32 [%0], 1;" :: "l"(f) : "memory")
__device__ __forceinline__ void flag_wait(const uint32_t* f, uint32_t target) {
  uint32_t v;
#pragma unroll 1
  for (int it = 0;; it++) {
    asm volatile("ld.acquire.gpu.global.u32 %0, [%1];" : "=r"(v) : "l"(f) : "memory");
    if ((int32_t)(v - target) >= 0) break;
    if (it > 2000000) __trap();
    __nanosleep(64);
  }
}
__device__ __forceinline__ bool mbar_test(uint32_t bar, uint32_t parity) {
  uint32_t ok;
  asm volatile("{\n.reg .pred p;\nmbarrier.test_wait.parity.shared::cta.b64 p, [%1], %2;\nselp.b32 %0, 1, 0, p;\n}\n" : "=r"(ok) : "r"(bar), "r"(parity) : "memory");
  return ok;
}
__device__ __forceinline__ bool elect_one() {
  uint32_t p;
  asm volatile("{\n.reg .pred P;\nelect.sync _|P, 0xFFFFFFFF;\nselp.b32 %0, 1, 0, P;\n}\n" : "=r"(p));
  return p;
}
__device__ __forceinline__ void lds4(uint32_t a, uint32_t* r) {
  asm volatile("ld.shared.v4.b32 {%0,%1,%2,%3}, [%4];" : "=r"(r[0]), "=r"(r[1]), "=r"(r[2]), "=r"(r[3]) : "r"(a) : "memory");
}
__device__ __forceinline__ uint32_t lds1(uint32_t a) { uint32_t r; asm volatile("ld.shared.b32 %0, [%1];" : "=r"(r) : "r"(a) : "memory"); return r; }
__device__ __forceinline__ void sts1(uint32_t a, uint32_t v) { asm volatile("st.shared.b32 [%0], %1;" :: "r"(a), "r"(v) : "memory"); }
__device__ __forceinline__ void sts4(uint32_t a, uint32_t r0, uint32_t r1, uint32_t r2, uint32_t r3) {
  asm volatile("st.shared.v4.b32 [%0], {%1,%2,%3,%4};" :: "r"(a), "r"(r0), "r"(r1), "r"(r2), "r"(r3) : "memory");
}
__device__ __forceinline__ void ldsm4(uint32_t a, uint32_t* r) {
  asm volatile("ldmatrix.sync.aligned.m8n8.x4.shared.b16 {%0,%1,%2,%3}, [%4];" : "=r"(r[0]), "=r"(r[1]), "=r"(r[2]), "=r"(r[3]) : "r"(a) : "memory");
}
__device__ __forceinline__ float rcpf(float x) { float y; asm("rcp.approx.ftz.f32 %0, %1;" : "=f"(y) : "f"(x)); return y; }
__device__ __forceinline__ uint32_t hfma2(uint32_t a, uint32_t b, uint32_t c) { uint32_t r; asm("fma.rn.f16x2 %0, %1, %2, %3;" : "=r"(r) : "r"(a), "r"(b), "r"(c)); return r; }
__device__ __forceinline__ uint32_t hadd2(uint32_t a, uint32_t b) { uint32_t r; asm("add.rn.f16x2 %0, %1, %2;" : "=r"(r) : "r"(a), "r"(b)); return r; }

#define STEPK 96
#define GIMAP(i) ((((i) & 1) << 2) | (((i) >> 1) & 3) | ((i) & 8))
#define QSCALE 0.36067376022224085f
#define SMAGIC (512.0f + 2.0f * (191.0f - 30.0f - 1.5823545f))
#define VSHIFT 1073741824.0f

__device__ uint32_t g_epoch[132];
__device__ uint32_t g_flag[288 * 8];
#define FLAG_KV (g_flag)
#define FLAG_B(h) (g_flag + (4 + (h)) * 8)
#define FLAG_OA(cta, pass) (g_flag + (16 + (cta) * 2 + (pass)) * 8)
#define FLAG_LM(i) (g_flag + (272 + (i)) * 8)

#define SM_TOTAL (224 * 1024 + 2048 + 1024)
#define OFF_K 0
#define OFF_F 65536
#define OFF_V 131072
#define OFF_MISC (224 * 1024)

#define BAR_FULL(s) (bars + 8 * (s))
#define BAR_EMPTY(s) (bars + 24 + 8 * (s))
#define BAR_KV(c) (bars + 48 + 8 * (c))
#define BAR_BDONE (bars + 80)
#define BAR_Q (bars + 88)
#define BAR_GO (bars + 96)
#define BAR_Q2 (bars + 104)
#define BAR_OD(p) (bars + 112 + 8 * (p))
#define BAR_CL(c) (bars + 128 + 8 * (c))
#define BAR_TE(i) (bars + 168 + 8 * (i))
#define BAR_RL (bars + 184)
#define BAR_TF(g) (bars + 224 + 8 * (g))
#define BAR_XA(w) (bars + 352 + 8 * (w))
#define BAR_VB(c) (bars + 384 + 8 * (c))

__device__ __forceinline__ uint32_t exp2_pair_fix(float d0, float d1, uint32_t c63, uint32_t m1) {
  uint32_t w, y, s, r;
  asm("prmt.b32 %0, %1, %2, 0x6521;" : "=r"(w) : "r"(__float_as_uint(d0)), "r"(__float_as_uint(d1)));
  asm("lop3.b32 %0, %1, 0x007F007F, %2, 0xEA;" : "=r"(y) : "r"(w), "r"(c63));
  asm("mad.lo.u32 %0, %1, %2, %3;" : "=r"(s) : "r"(y), "r"(m1), "r"(w));
  asm("fma.rn.bf16x2 %0, %1, %2, %3;" : "=r"(r) : "r"(w), "r"(y), "r"(s));
  return r;
}

#define X_PR(i) asm volatile("prmt.b32 %0, %1, %2, 0x6521;" : "=r"(w[i]) : "r"(__float_as_uint(Sp[2 * (i)])), "r"(__float_as_uint(Sp[2 * (i) + 1])));
#define X_LO(i) asm volatile("lop3.b32 %0, %1, 0x007F007F, %2, 0xEA;" : "=r"(y[i]) : "r"(w[i]), "r"(c63));
#define X_IM(i) asm volatile("mad.lo.u32 %0, %1, %2, %3;" : "=r"(z[i]) : "r"(y[i]), "r"(m1), "r"(w[i]));
#define X_FM(i) asm volatile("fma.rn.bf16x2 %0, %1, %2, %3;" : "=r"(P[6 + (i)]) : "r"(w[i]), "r"(y[i]), "r"(z[i]));
#define X_MU(i) asm volatile("ex2.approx.ftz.f32 %0, %1;" : "=f"(e[i]) : "f"(Sm[i]));
#define X_PK(i) asm volatile("cvt.rn.bf16x2.f32 %0, %1, %2;" : "=r"(P[i]) : "f"(e[2 * (i) + 1]), "f"(e[2 * (i)]));

__device__ __forceinline__ void attn_slow(const __nv_bfloat16* xa, const __nv_bfloat16* wq, uint32_t dst) {
  const int t = threadIdx.x & 127;
  const int row = t >> 1, half = t & 1;
  float q[16];
  {
    float a[8];
#pragma unroll
    for (int i = 0; i < 8; i++) a[i] = 0.f;
#pragma unroll 1
    for (int k = 0; k < D_MOD; k++) {
      const float x = __bfloat162float(xa[(size_t)row * D_MOD + k]);
      const uint4 w = *(const uint4*)(wq + (size_t)k * D_MOD + half * 8);
      const uint32_t ww[4] = {w.x, w.y, w.z, w.w};
#pragma unroll
      for (int i = 0; i < 4; i++) { a[2 * i] = fmaf(x, bf_lo(ww[i]), a[2 * i]); a[2 * i + 1] = fmaf(x, bf_hi(ww[i]), a[2 * i + 1]); }
    }
#pragma unroll
    for (int i = 0; i < 8; i++) {
      const float mine = rbf(a[i]), other = __shfl_xor_sync(~0u, mine, 1);
      q[i] = half ? other : mine; q[8 + i] = half ? mine : other;
    }
  }
  float m = -INFINITY, l = 0.f, o[16];
#pragma unroll
  for (int i = 0; i < 16; i++) o[i] = 0.f;
#pragma unroll 1
  for (int j = half * 1024; j < half * 1024 + 1024; j++) {
    uint4 ka = g_KV[4 * S_TOK + j], kb = g_KV[5 * S_TOK + j];
    uint4 va = g_KV[6 * S_TOK + j], vb = g_KV[7 * S_TOK + j];
    uint32_t kk[8] = {ka.x, ka.y, ka.z, ka.w, kb.x, kb.y, kb.z, kb.w};
    uint32_t vv[8] = {va.x, va.y, va.z, va.w, vb.x, vb.y, vb.z, vb.w};
    float s = 0.f;
#pragma unroll
    for (int i = 0; i < 8; i++) { s = fmaf(q[2 * i], bf_lo(kk[i]), s); s = fmaf(q[2 * i + 1], bf_hi(kk[i]), s); }
    s = rbf(s) * 0.25f;
    if (s > m) {
      float c = __expf(m - s);
      l *= c;
#pragma unroll
      for (int i = 0; i < 16; i++) o[i] *= c;
      m = s;
    }
    float p = __expf(s - m);
    l += p;
#pragma unroll
    for (int i = 0; i < 8; i++) { o[2 * i] = fmaf(p, bf_lo(vv[i]), o[2 * i]); o[2 * i + 1] = fmaf(p, bf_hi(vv[i]), o[2 * i + 1]); }
  }
  float m2 = __shfl_xor_sync(~0u, m, 1);
  float mm = fmaxf(m, m2);
  float c = __expf(m - mm);
  l *= c; l += __shfl_xor_sync(~0u, l, 1);
  float inv = 1.f / l;
  uint32_t r[8];
#pragma unroll
  for (int i = 0; i < 16; i++) { o[i] *= c; o[i] += __shfl_xor_sync(~0u, o[i], 1); o[i] *= inv; }
#pragma unroll
  for (int i = 0; i < 8; i++) r[i] = pack_bf16(o[2 * i], o[2 * i + 1]);
  if (half == 0) sts4(dst, r[0], r[1], r[2], r[3]); else sts4(dst, r[4], r[5], r[6], r[7]);
  fence_async();
}

struct Params { const __nv_bfloat16* wk; const __nv_bfloat16* wv; const __nv_bfloat16* xa; const __nv_bfloat16* wq; __nv_bfloat16* out; };
__device__ __forceinline__ void cp16(uint32_t dst, const void* src) { asm volatile("cp.async.cg.shared.global [%0], [%1], 16;" :: "r"(dst), "l"(src) : "memory"); }

__device__ __forceinline__ void helper_cta(const int h, const uint32_t sb, const uint32_t bars, const int wg, const int w4,
                                           const CUtensorMap* mQ) {
  const int lane = threadIdx.x & 31;
  mbar_wait(BAR_GO, 0);
  const int cb = wg & 1, col = h * 128 + cb * 64, row0 = S_TOK + (wg >> 1) * 1024;
  const uint32_t buf = sb + wg * 49152;
  if (w4 == 0 && elect_one()) {
    fence_async_all();
#pragma unroll 1
    for (int u = 0; u < 3; u++) {
      mbar_expect_tx(BAR_TF(wg * 3 + u), 16384);
      tma2d(buf + u * 16384, mQ, col, row0 + u * 128, BAR_TF(wg * 3 + u));
    }
  }
  const int head = h * 8 + cb * 4 + w4;
  float4 a0 = make_float4(0, 0, 0, 0), a1 = a0, a2 = a0;
#pragma unroll 8
  for (int tt = 0; tt < 16; tt++) {
    const float4* src = g_kvp + ((tt * 32 + head) * 3) * 32 + lane;
    float4 u = src[0], v = src[32], w = src[64];
    a0.x += u.x; a0.y += u.y; a0.z += u.z; a0.w += u.w;
    a1.x += v.x; a1.y += v.y; a1.z += v.z; a1.w += v.w;
    a2.x += w.x; a2.y += w.y; a2.z += w.z; a2.w += w.w;
  }
  const uint32_t b00 = pack_bf16(a0.x, a0.y), b01 = pack_bf16(a0.z, a0.w);
  const uint32_t b10 = pack_bf16(a1.x, a1.y), b11 = pack_bf16(a1.z, a1.w);
  const uint32_t bz0 = pack_bf16(a2.x, a2.y), bz1 = pack_bf16(a2.z, a2.w);
  const int m = lane >> 3, r = lane & 7;
  const uint32_t off = ((m & 1) * 8 + r) * 128 + (((w4 * 2 + (m >> 1)) ^ r) << 4);
  int s = 0, ph = 0;
#pragma unroll 1
  for (int u = 0; u < 8; u++) {
    const uint32_t bb = buf + s * 16384;
    mbar_wait(BAR_TF(wg * 3 + s), ph);
    uint32_t a[32];
#pragma unroll
    for (int mt = 0; mt < 8; mt++) ldsm4(bb + mt * 2048 + off, a + 4 * mt);
#pragma unroll
    for (int i = 0; i < 32; i++) a[i] = phi2(bf_lo(a[i]), bf_hi(a[i]));
#pragma unroll
    for (int mt = 0; mt < 8; mt++) {
      uint32_t* p = a + 4 * mt;
      float n0[4] = {0, 0, 0, 0}, n1[4] = {0, 0, 0, 0}, dn[4] = {0, 0, 0, 0};
      mma_bf16(dn, p[0], p[1], p[2], p[3], bz0, bz1);
      mma_bf16(n0, p[0], p[1], p[2], p[3], b00, b01);
      mma_bf16(n1, p[0], p[1], p[2], p[3], b10, b11);
      const float i0 = rcpf(dn[0] + 1e-6f), i1 = rcpf(dn[2] + 1e-6f);
      p[0] = pack_bf16(n0[0] * i0, n0[1] * i0); p[1] = pack_bf16(n0[2] * i1, n0[3] * i1);
      p[2] = pack_bf16(n1[0] * i0, n1[1] * i0); p[3] = pack_bf16(n1[2] * i1, n1[3] * i1);
    }
#pragma unroll
    for (int mt = 0; mt < 8; mt++) stsm4(bb + mt * 2048 + off, a[4 * mt], a[4 * mt + 1], a[4 * mt + 2], a[4 * mt + 3]);
    named_bar(wg + 1, 128);
#pragma unroll
    for (int i = 0; i < 8; i++) lds4(bb + (w4 * 32 + i * 4 + m) * 128 + ((r ^ ((i * 4 + m) & 7)) << 4), a + 4 * i);
    named_bar(wg + 1, 128);
    if (u + 3 < 8 && w4 == 0 && elect_one()) {
      mbar_expect_tx(BAR_TF(wg * 3 + s), 16384);
      tma2d(bb, mQ, col, row0 + (u + 3) * 128, BAR_TF(wg * 3 + s));
    }
    uint4* dst = (uint4*)(g_O + (size_t)(row0 + u * 128 + w4 * 32 + m) * D_MOD + col) + r;
#pragma unroll
    for (int i = 0; i < 8; i++) dst[i * 256] = make_uint4(a[4 * i], a[4 * i + 1], a[4 * i + 2], a[4 * i + 3]);
    if (++s == 3) { s = 0; ph ^= 1; }
  }
  named_bar(wg + 1, 128);
  if (w4 == 0 && lane == 0) {
    fence_async_all();
    flag_add(FLAG_LM((h * 2 + cb) * 2 + (wg >> 1)));
    if (wg == 0) TS(1, 8);
  }
}

#define STAGE(s) (sb + (2 - (s)) * 65536)
__device__ __forceinline__ uint32_t xa_addr(uint32_t sb, int kb) {
  return sb + (kb >= 1 && kb <= 4 ? OFF_V + 65536 + (kb - 1) * 8192 : 16384 + (kb == 5 ? OFF_K : (kb == 6 ? OFF_V : OFF_F)));
}
#define XA7_TMP (sb + OFF_K + 40960)
#define WKV_TMP (sb + OFF_K + 32768)
template <int TR> __device__ __forceinline__ void proj_kb(float* acc, uint32_t aA, uint32_t aB, int first) {
  const uint64_t da = make_desc(aA, TR ? 8192 : 16, 1024, 1);
  const uint64_t db = make_desc(aB, TR ? 16 : 8192, 1024, 1);
  wg_fence();
#pragma unroll
  for (int k = 0; k < 4; k++) wg_ss128<TR, 1 - TR>(acc, da + k * (TR ? 128 : 2), db + k * (TR ? 2 : 128), k != 0 || !first);
  wg_commit();
}
template <int TR> __device__ __forceinline__ void proj_loop(float* acc, uint32_t sb, uint32_t bars, uint32_t offA, uint32_t offB,
                                                            int wg, uint32_t sWKV, const CUtensorMap* mW, int col, bool w0) {
  {
    float kv[4];
    if (threadIdx.x == 0) TS(0, 13);
    mbar_wait(BAR_XA(wg), 0);
    if (threadIdx.x == 0) TS(0, 1);
    const uint64_t da0 = make_desc(xa_addr(sb, 2 * wg), 16, 1024, 1);
    const uint64_t da1 = make_desc(wg == 3 ? XA7_TMP : xa_addr(sb, 2 * wg + 1), 16, 1024, 1);
    const uint64_t db = make_desc(sWKV + wg * 2048, 128, 128, 0);
    wg_fence();
#pragma unroll
    for (int k = 0; k < 8; k++) wg_ss8<0, 1>(kv, (k < 4 ? da0 : da1) + (k & 3) * 2, db + k * 16, k != 0);
    wg_commit();
    wg_wait<0>();
    fence_regs<4>(kv);
    named_bar(wg + 1, 128);
    sts4(sWKV + threadIdx.x * 16, __float_as_uint(kv[0]), __float_as_uint(kv[1]), __float_as_uint(kv[2]), __float_as_uint(kv[3]));
    __syncwarp();
    if ((threadIdx.x & 31) == 0) mbar_arrive(BAR_GO);
  }
  int s = 0, ph = 0;
#pragma unroll 1
  for (int kb = 0; kb < 8; kb++) {
    mbar_wait(BAR_FULL(s), ph);
    if (threadIdx.x == 0) TSW(0, 2 + kb);
    if (TR == 0) mbar_wait(BAR_XA(kb >> 1), 0);
    proj_kb<TR>(acc, TR ? STAGE(s) + offA : xa_addr(sb, kb), STAGE(s) + offB, kb == 0);
    wg_wait<0>();
    if (w0 && elect_one()) {
      if (kb < 5) {
        mbar_expect_tx(BAR_FULL(s), TR ? 8192 : 16384);
        tma2d(STAGE(s) + (TR ? offA : 0), mW, col, (kb + 3) * 64, BAR_FULL(s));
        if (TR == 0) tma2d(STAGE(s) + 8192, mW, col + 64, (kb + 3) * 64, BAR_FULL(s));
      }
      if (kb < 7) mbar_arrive(BAR_EMPTY(s));
      if (TR == 0 && kb == 4) mbar_arrive(BAR_VB(1));
    }
    __syncwarp();
    if (++s == 3) { s = 0; ph ^= 1; }
  }
  wg_wait<0>();
  fence_regs<64>(acc);
}

__device__ __forceinline__ uint32_t tail_slots(int isB, int n) {
  if (n < 4) return n < 2 ? (n == 0 ? 0x0D0C0B0Au : 0x04000F0Eu) : (n == 2 ? 0x18141008u : 0x15110501u);
  if (isB) return n < 6 ? (n == 4 ? 0x19120602u : 0x0D0C0B0Au) : (n == 6 ? 0x04000F0Eu : 0x13070316u);
  return n < 6 ? (n == 4 ? 0x1902031Au : 0x12061307u) : (n == 6 ? 0x16091B17u : 0x0D0C0B0Au);
}

__device__ __forceinline__ void take_role(uint32_t sM, int wg) {
  uint32_t r;
  asm volatile("atom.shared.add.u32 %0, [%1], 1;" : "=r"(r) : "r"(sM + 20) : "memory");
  sts1(sM + 32 + wg * 4, r);
}

__global__ void __launch_bounds__(640, 1)
k1_main(const __grid_constant__ CUtensorMap mXA64, const __grid_constant__ CUtensorMap mXB,
        const __grid_constant__ CUtensorMap mWq, const __grid_constant__ CUtensorMap mWqkv,
        const __grid_constant__ CUtensorMap mQst,
        const __grid_constant__ CUtensorMap mO, const __grid_constant__ CUtensorMap mWoA,
        const __grid_constant__ CUtensorMap mWoB,
        const __grid_constant__ CUtensorMap mO16, const Params prm) {
  if (threadIdx.x >= 608 && threadIdx.x < 612) {
    const CUtensorMap* pm = &mXA64 + (threadIdx.x - 608);
    asm volatile("prefetch.tensormap [%0];" :: "l"(pm) : "memory");
  }
  extern __shared__ uint8_t smem_raw[];
  const uint32_t sb = (smem_u32(smem_raw) + 1023u) & ~1023u;
  const uint32_t bars = sb + OFF_MISC, sM = bars + 512, sT = bars + 1024;
  const int tid = threadIdx.x, warp = __shfl_sync(~0u, tid >> 5, 0), wg = warp >> 2, w4 = warp & 3, lane = tid & 31;
  const bool helper = blockIdx.x >= 128;
  if (tid == 0) TS(0, 0);
  const int G = blockIdx.x >> 4, gi = GIMAP(blockIdx.x & 15);
  const int tbA = G * 4 + (gi >> 2), hg = gi & 3;
  const int ttB = (G >> 1) * 4 + (gi >> 2), hq = (G & 1) * 4 + (gi & 3);
  const int isB = tbA & 1, tok0 = (tbA >> 1) * 128;
  auto issue = [&](int kb, int s, int part) {
    const uint32_t fb = BAR_FULL(s), st = STAGE(s);
    if (part & 1) {
      mbar_expect_tx(fb, 57344);
      asm volatile("mbarrier.arrive.shared::cta.b64 _, [%0], 4;" :: "r"(fb) : "memory");
      tma2d(st, &mWq, hg * 128, kb * 64, fb);
      tma2d(st + 8192, &mWq, hg * 128 + 64, kb * 64, fb);
      tma2d(st + 49152, &mXB, kb * 64, ttB * 128, fb);
      tma2d(st + 24576, &mWqkv, hq * 64, kb * 64, fb);
    }
    if (part & 2) {
      tma2d(st + 32768, &mWqkv, 512 + hq * 64, kb * 64, fb);
      tma2d(st + 40960, &mWqkv, 1024 + hq * 64, kb * 64, fb);
    }
  };
  const uint32_t sOne = sb + OFF_V + 65536, sWKV = WKV_TMP;
  if (warp >= 16) {
    if (warp == 17) {
      if (elect_one()) {
        mbar_init(BAR_BDONE, 8); mbar_init(BAR_Q, 6); mbar_init(BAR_GO, helper ? 1 : 16); mbar_init(BAR_Q2, 1);
        mbar_init(BAR_OD(0), 16); mbar_init(BAR_OD(1), 16); mbar_init(BAR_CL(0), 1); mbar_init(BAR_FULL(2), 5);
#pragma unroll
        for (int i = 0; i < 4; i++) mbar_init(BAR_CL(i + 1), i == 0 ? 5 : 4);
#pragma unroll
        for (int i = 0; i < 3; i++) { mbar_init(BAR_EMPTY(i), 4); mbar_init(BAR_KV(i), 1); mbar_init(BAR_VB(i), i == 2 ? 4 : 1); }
        sts1(sM + 20, 0);
        asm volatile("fence.mbarrier_init.release.cluster;" ::: "memory");
      }
    } else if (warp == 18) {
      if (elect_one()) {
#pragma unroll
        for (int i = 0; i < 2; i++) mbar_init(BAR_TE(i), 2);
        mbar_init(BAR_RL, 1);
#pragma unroll
        for (int i = 0; i < 16; i++) mbar_init(BAR_TF(i), 1);
        asm volatile("fence.mbarrier_init.release.cluster;" ::: "memory");
      }
    } else if (warp == 16 && !helper && elect_one()) {
#pragma unroll
      for (int w = 0; w < 4; w++) mbar_init(BAR_XA(w), 1);
      mbar_init(BAR_FULL(0), 5); mbar_init(BAR_FULL(1), 5);
      asm volatile("fence.mbarrier_init.release.cluster;" ::: "memory");
#pragma unroll
      for (int w = 0; w < 4; w++) {
        mbar_expect_tx(BAR_XA(w), 16384);
        tma2d(xa_addr(sb, 2 * w), &mXA64, w * 128, tbA * 64, BAR_XA(w));
        tma2d(w == 3 ? XA7_TMP : xa_addr(sb, 2 * w + 1), &mXA64, w * 128 + 64, tbA * 64, BAR_XA(w));
      }
      TS(0, 14);
      issue(0, 0, 3);
    }
  } else if (!helper) {
    const uint4 v = __ldg((const uint4*)(hg >= 2 ? prm.wv : prm.wk) + tid * 2 + (hg & 1));
    sts4(sWKV + tid * 16, v.x, v.y, v.z, v.w);
    fence_async();
  }
  __syncthreads();
  if (wg == 4) {
    if (w4 == 0 && !helper && elect_one()) { issue(1, 1, 3); issue(2, 2, 1); TS(0, 15); }
    asm volatile("setmaxnreg.dec.sync.aligned.u32 32;");
    const uint32_t ep = g_epoch[blockIdx.x] + 1;
    if (helper) {
      if (w4 == 0 && elect_one()) {
        flag_wait(FLAG_B(blockIdx.x - 128), ep * 32);
        fence_async_all();
        TS(1, 10);
        mbar_arrive(BAR_GO);
        g_epoch[blockIdx.x] = ep;
      }
      return;
    }
    mbar_wait(BAR_GO, 0);
    {
      uint32_t a[4], b[4];
      float c[4];
      lds4(sWKV + (tid - 512) * 16, a);
      lds4(sWKV + 2048 + (tid - 512) * 16, b);
#pragma unroll
      for (int i = 0; i < 4; i++) c[i] = __uint_as_float(a[i]) + __uint_as_float(b[i]);
      lds4(sWKV + 4096 + (tid - 512) * 16, a);
      lds4(sWKV + 6144 + (tid - 512) * 16, b);
#pragma unroll
      for (int i = 0; i < 4; i++) c[i] += __uint_as_float(a[i]) + __uint_as_float(b[i]);
      sts1(sT + w4 * 256 + lane * 4, pack_bf16(c[0], c[1]));
      sts1(sT + w4 * 256 + 128 + lane * 4, pack_bf16(c[2], c[3]));
    }
    named_bar(9, 128);
    if (w4 == 0 && elect_one()) issue(2, 2, 2);
    auto write_ones = [&]() {
      mbar_wait_long(BAR_VB(1), 0);
      int c = ((w4 & 1) * 32 + lane);
#pragma unroll 4
      for (int key = c; key < S_TOK; key += 64) {
        sts4(sOne + key * 16, c < 24 ? 0x00003F80u : 0x00004E80u, 0u, 0u, 0u);
        c += 64; if (c >= STEPK) c -= STEPK;
      }
      fence_async();
      __syncwarp();
      if (lane == 0) mbar_arrive(BAR_Q);
    };
    if (w4 == 0) {
      int s = 0, ph = 0;
#pragma unroll 1
      for (int kb = 3; kb < 8; kb++) {
        mbar_wait(BAR_EMPTY(s), ph);
        if (elect_one()) {
          mbar_expect_tx(BAR_FULL(s), kb == 7 ? 24576 : 16384);
          tma2d(STAGE(s) + 49152, &mXB, kb * 64, ttB * 128, BAR_FULL(s));
          if (kb == 7) tma2d(STAGE(s) + 16384, &mXA64, kb * 64, tbA * 64, BAR_FULL(s));
        }
        if (++s == 3) { s = 0; ph ^= 1; }
      }
      flag_wait(FLAG_KV, ep * 128);
      fence_async_all();
      if (lane == 0) TS(0, 11);
#pragma unroll 1
      for (int m = 0; m < 2; m++) {
        mbar_wait(m == 0 ? BAR_EMPTY(2) : BAR_EMPTY(0), 1 - m);
        if (elect_one()) {
          const uint32_t fb = m == 0 ? BAR_KV(0) : BAR_VB(0);
          mbar_expect_tx(fb, 2 * 7 * STEPK * 16);
#pragma unroll
          for (int p = 0; p < 2; p++) bulk_g2s(sb + m * OFF_V + p * 32768, g_KV + (m * 2 + p) * S_TOK, 7 * STEPK * 16, fb);
        }
      }
      mbar_wait(BAR_Q, 0);
      if (elect_one()) {
#pragma unroll
        for (int c = 1; c < 3; c++) {
          const int k0 = c == 1 ? 7 * STEPK : 13 * STEPK, k1 = c == 1 ? 13 * STEPK : S_TOK;
          const uint32_t bytes = (k1 - k0) * 16;
          mbar_expect_tx(BAR_KV(c), 4 * bytes);
#pragma unroll
          for (int p = 0; p < 4; p++)
            bulk_g2s(sb + (p >> 1) * OFF_V + (p & 1) * 32768 + k0 * 16, g_KV + p * S_TOK + k0, bytes, BAR_KV(c));
        }
      }
      mbar_wait_long(BAR_CL(1), 0);
      flag_wait(isB ? FLAG_LM((lane & 7) * 2 + (tbA >> 4)) : FLAG_OA(tbA * 4 + (lane & 7), 0), ep);
      __syncwarp();
      fence_async_all();
      if (lane == 0) TS(2, 13);
      const CUtensorMap* mW = isB ? &mWoB : &mWoA;
#pragma unroll 1
      for (int it = 0; it < 8; it++) {
        const int n = (!isB && it >= 6) ? 13 - it : it;
        uint32_t wb = BAR_CL(n < 3 ? 0 : (n == 3 ? 2 : 3));
        if (isB) { if (n >= 5) wb = n == 7 ? BAR_CL(4) : BAR_TE(n - 5); }
        else if (n >= 6) wb = n == 6 ? BAR_CL(4) : BAR_TE(0);
        if (it < 6) mbar_wait_long(wb, 0); else mbar_wait(wb, 0);
        const uint32_t sl = tail_slots(isB, n), fb = BAR_TF(n);
        const bool withX = isB || n < 4;
        const int k0 = isB ? n * 64 : (n < 4 ? n * 128 : ((hg + n) & 3) * 128 + 64);
        if (elect_one()) {
          mbar_expect_tx(fb, withX ? 32768 : 16384);
          if (withX) {
            tma2d(sb + (sl & 255) * 8192, &mO, k0, isB * S_TOK + tok0, fb);
            tma2d(sb + ((sl >> 8) & 255) * 8192, &mO, k0, isB * S_TOK + tok0 + 64, fb);
          }
          tma2d(sb + ((sl >> 16) & 255) * 8192, mW, hg * 128, k0, fb);
          tma2d(sb + (sl >> 24) * 8192, mW, hg * 128 + 64, k0, fb);
        }
      }
      if (lane == 0) g_epoch[blockIdx.x] = ep;
    } else if (w4 == 3) {
      write_ones();
      flag_wait(FLAG_KV, ep * 128);
      const uint4 a = *(const uint4*)(g_stats + lane * 4);
      const float kmax2 = __uint_as_float(__reduce_max_sync(~0u, a.x)) + __uint_as_float(__reduce_max_sync(~0u, a.y));
      const float vmax = __uint_as_float(__reduce_max_sync(~0u, max(a.z, a.w)));
      const float lv = vmax > 0.f ? __log2f(vmax) : 0.f;
      const float lim = fminf(90.f, fminf(91.f + lv, 95.f - lv));
      float thr = -1.f;
      if (vmax < 1e27f && kmax2 <= 65536.f && lim > 2.f) thr = fminf(60000.f, (lim * lim - 1.f) / (kmax2 * 1.02f + 1e-30f));
      mbar_wait_long(BAR_VB(2), 0);
      uint32_t nmax = 0;
#pragma unroll 2
      for (int i = 0; i < 16; i++) {
        uint32_t x[4], y[4];
        const uint32_t ad = sb + OFF_F + i * 1024 + (lane >> 3) * 256 + (lane & 7) * 16;
        lds4(ad, x); lds4(ad + 128, y);
        uint32_t n = hfma2(x[0], x[0], hfma2(x[1], x[1], hfma2(x[2], x[2], hfma2(x[3], x[3], 0u))));
        n = hfma2(y[0], y[0], hfma2(y[1], y[1], hfma2(y[2], y[2], hfma2(y[3], y[3], n))));
        n = hadd2(n, n >> 16);
        nmax = max(nmax, n & 0x7FFFu);
      }
      nmax = __reduce_max_sync(~0u, nmax);
      const bool ok = __half2float(__ushort_as_half((unsigned short)nmax)) <= thr;
      if (lane == 0) { sts1(sM + 16, ok ? 1u : 0u); mbar_arrive(BAR_Q2); }
    } else {
      const int tok = (w4 - 1) * 32 + lane;
      int step, col;
      if ((tbA & 3) == 0) {
        const int b8 = tbA >> 2;
        if (tok < 22) { step = tok; col = 24 + b8; }
        else { const int c = tok >= 43; step = tok - 22 - 21 * c; col = 32 + b8 * 2 + c; }
      } else {
        const int b24 = (tbA >> 2) * 3 + (tbA & 3) - 1;
        if (tok < 42) { const int c = tok >= 21; step = tok - 21 * c; col = 48 + b24 * 2 + c; }
        else { step = tok - 42; col = b24; }
      }
      const int kap = step * STEPK + col;
      const bool chained = col >= 24;
      uint32_t v[4], o[4];
      lds4(sT + tok * 16, v);
      g_KV[(4 + hg) * S_TOK + kap] = make_uint4(v[0], v[1], v[2], v[3]);
      float st = 0.f;
      if (hg < 2) {
        o[0] = o[1] = o[2] = o[3] = 0;
        if (chained && step > 0) lds4(sT + tok * 16 - 16, o);
        const float sc = chained ? 2.f : 1.f;
#pragma unroll
        for (int u = 0; u < 4; u++) {
          const float x = bf_lo(v[u]), y = bf_hi(v[u]);
          st += x * x + y * y;
          o[u] = pack_f16((x - bf_lo(o[u])) * sc, (y - bf_hi(o[u])) * sc);
        }
      } else {
        const float sc = chained ? VSHIFT : 1.f;
#pragma unroll
        for (int u = 0; u < 4; u++) { float x = bf_lo(v[u]), y = bf_hi(v[u]); st += fabsf(x) + fabsf(y); o[u] = pack_bf16(x * sc, y * sc); }
      }
      g_KV[hg * S_TOK + kap] = make_uint4(o[0], o[1], o[2], o[3]);
      const uint32_t um = __reduce_max_sync(~0u, __float_as_uint(st) & 0x7FFFFFFFu);
      if (w4 == 2) {
        if (lane == 0) sts1(sM + 24, um);
        named_arrive(10, 64);
        write_ones();
        if (!isB) {
          mbar_wait_long(BAR_CL(3), 0);
          mbar_wait_long(BAR_RL, 0);
          uint32_t pend = 0xFE;
          const int li = lane & 7;
          const uint32_t* fl = FLAG_OA((tbA + (li & 1)) * 4 + ((hg + (li >> 1)) & 3), 1);
#pragma unroll 1
          for (int it = 0; pend; it++) {
            uint32_t fv;
            asm volatile("ld.acquire.gpu.global.u32 %0, [%1];" : "=r"(fv) : "l"(fl) : "memory");
            uint32_t go = __ballot_sync(~0u, (int32_t)(fv - ep) >= 0 && mbar_test(li >= 6 ? BAR_TE(0) : BAR_CL(4), 0)) & pend;
            pend &= ~go;
            if (go) fence_async_all();
#pragma unroll 1
            while (go) {
              const int b = __ffs(go) - 1;
              go &= go - 1;
              const uint32_t slot = (tail_slots(0, 4 + (b >> 1)) >> (8 * (b & 1))) & 255;
              if (elect_one()) {
                mbar_expect_tx(BAR_TF(8 + b), 8192);
                tma2d(sb + slot * 8192, &mO, ((hg + (b >> 1)) & 3) * 128 + 64, tok0 + (b & 1) * 64, BAR_TF(8 + b));
              }
            }
            if (it > 2000000) __trap();
          }
          if (lane == 0) TS(2, 14);
        }
      }
      else {
        named_bar(10, 64);
        if (elect_one()) {
          g_stats[tbA * 4 + hg] = max(um, lds1(sM + 24));
          fence_async_all();
          flag_add(FLAG_KV);
          TS(1, 9);
          mbar_wait_long(BAR_BDONE, 0);
          tma2d_store(&mQst, sb + OFF_F + 49152, hq * 64, S_TOK + ttB * 128);
          bulk_commit();
          bulk_wait_all();
          fence_async_all();
          flag_add(FLAG_B(hq >> 1));
          TS(0, 12);
          mbar_wait(BAR_Q, 0);
          mbar_arrive(BAR_CL(0));
#pragma unroll 1
          for (int p = 0; p < 2; p++) {
            mbar_wait_long(BAR_OD(p), 0);
            if (p == 0) {
#pragma unroll
              for (int w = 0; w < 4; w++) tma2d_store(&mO16, sb + OFF_F + w * 2048, hg * 128 + w * 16, tbA * 64);
            } else {
              tma2d_store(&mO, sb + 26 * 8192, hg * 128 + 64, tbA * 64);
            }
            bulk_commit();
            bulk_wait_all();
            if (p == 0) mbar_arrive(BAR_CL(1));
            PUBLISH(FLAG_OA(tbA * 4 + hg, p));
          }
          TS(2, 0);
        }
      }
    }
    return;
  }
  if (helper) { helper_cta(blockIdx.x - 128, sb, bars, wg, w4, &mQst); return; }

  {
    float acc[64];
    if (wg == 0) proj_loop<0>(acc, sb, bars, 16384, 0, wg, sWKV, &mWq, hg * 128, w4 == 0);
    else proj_loop<1>(acc, sb, bars, 16384 + wg * 8192, 49152, wg, sWKV, &mWqkv, (wg - 1) * 512 + hq * 64, w4 == 0);
    if (tid == 0) TS(0, 10);
    const uint32_t sF = sb + OFF_F;
    const uint32_t qa = sF + w4 * 512 + ((lane >> 3) & 1) * 256 + (lane >> 4) * 128 + (lane & 7) * 16;
    if (wg == 0) {
#pragma unroll
      for (int hd = 0; hd < 4; hd++)
        stsm4(qa + hd * 2048, pack_f16(acc[8 * hd] * QSCALE, acc[8 * hd + 1] * QSCALE), pack_f16(acc[8 * hd + 2] * QSCALE, acc[8 * hd + 3] * QSCALE),
              pack_f16(acc[8 * hd + 4] * QSCALE, acc[8 * hd + 5] * QSCALE), pack_f16(acc[8 * hd + 6] * QSCALE, acc[8 * hd + 7] * QSCALE));
      fence_async();
      __syncwarp();
      if (lane == 0) mbar_arrive(BAR_Q);
    } else {
      if (wg != 3) named_arrive(6, 384);
      if (wg != 1) named_arrive(8, 384);
    }
    asm volatile("setmaxnreg.inc.sync.aligned.u32 112;");
    fence_regs<64>(acc);
    if (wg == 0) {
#pragma unroll
      for (int hd = 4; hd < 8; hd++)
        stsm4(qa + hd * 2048, pack_f16(acc[8 * hd] * QSCALE, acc[8 * hd + 1] * QSCALE), pack_f16(acc[8 * hd + 2] * QSCALE, acc[8 * hd + 3] * QSCALE),
              pack_f16(acc[8 * hd + 4] * QSCALE, acc[8 * hd + 5] * QSCALE), pack_f16(acc[8 * hd + 6] * QSCALE, acc[8 * hd + 7] * QSCALE));
      fence_async();
      __syncwarp();
      if (lane == 0) mbar_arrive(BAR_VB(2));
    } else if (wg == 3) {
      named_bar(6, 384);
      const int t = tid & 127;
#pragma unroll
      for (int j = 0; j < 8; j++)
        sts4(sF + 24576 + j * 2048 + t * 16, pack_bf16(acc[8 * j], acc[8 * j + 1]), pack_bf16(acc[8 * j + 2], acc[8 * j + 3]),
             pack_bf16(acc[8 * j + 4], acc[8 * j + 5]), pack_bf16(acc[8 * j + 6], acc[8 * j + 7]));
      named_arrive(7, 256);
    } else {
      if (wg == 1) {
        named_bar(8, 384);
        const int m = lane >> 3, r = lane & 7;
#pragma unroll
        for (int j = 0; j < 16; j += 2) {
          const int tok = (j + (m >> 1)) * 8 + r;
          const int chunk = w4 * 2 + (m & 1);
          stsm4t(sF + 49152 + tok * 128 + ((chunk ^ r) << 4), pack_bf16(acc[4 * j], acc[4 * j + 1]), pack_bf16(acc[4 * j + 2], acc[4 * j + 3]),
                 pack_bf16(acc[4 * j + 4], acc[4 * j + 5]), pack_bf16(acc[4 * j + 6], acc[4 * j + 7]));
        }
        fence_async();
      } else {
        uint32_t p[32];
#pragma unroll
        for (int i = 0; i < 32; i++) p[i] = phi2(acc[2 * i], acc[2 * i + 1]);
        named_bar(7, 256);
        float kv0[4] = {0, 0, 0, 0}, kv1[4] = {0, 0, 0, 0}, z0[4] = {0, 0, 0, 0}, z1[4] = {0, 0, 0, 0};
        const uint32_t one = 0x3F803F80u;
        const int t = tid & 127;
#pragma unroll
        for (int j = 0; j < 8; j++) {
          uint32_t a[4];
          lds4(sF + 24576 + j * 2048 + t * 16, a);
          mma_bf16(kv0, a[0], a[1], a[2], a[3], p[4 * j], p[4 * j + 2]);
          mma_bf16(kv1, a[0], a[1], a[2], a[3], p[4 * j + 1], p[4 * j + 3]);
          mma_bf16(z0, one, one, one, one, p[4 * j], p[4 * j + 2]);
          mma_bf16(z1, one, one, one, one, p[4 * j + 1], p[4 * j + 3]);
        }
        float4* dst = g_kvp + ((ttB * 32 + hq * 4 + w4) * 3) * 32 + lane;
        dst[0] = make_float4(kv0[0], kv0[1], kv1[0], kv1[1]);
        dst[32] = make_float4(kv0[2], kv0[3], kv1[2], kv1[3]);
        dst[64] = make_float4(z0[0], z0[1], z1[0], z1[1]);
      }
      __syncwarp();
      if (lane == 0) mbar_arrive(BAR_BDONE);
    }
  }

  bool safe = true;
  {
    const uint32_t c63 = 0x1F801F80u + (threadIdx.x >> 20);
    const uint32_t m1 = (gridDim.x >> 20) - 1u;
    const uint64_t dK0 = make_desc(sb + OFF_K, 32768, 128, 0);
    const uint64_t dV0 = make_desc(sb + OFF_V, 128, 32768, 0);
    constexpr uint32_t dKV = ((2048u - 8u)  __H0__ ) + STEPK - (OFF_V - OFF_K) / 16;
    float Sm[12], Sp[36], O[12];
    uint32_t P[24];
    uint64_t dQ = make_desc(sb + OFF_F + wg * 2048, 128, 256, 0);
#pragma unroll
    for (int i = 0; i < 36; i++) Sp[i] = SMAGIC;
#pragma unroll
    for (int i = 0; i < 12; i++) Sm[i] = 0.f;
    fence_regs<12>(Sm); fence_regs<36>(Sp);
    mbar_wait(BAR_Q, 0);
    mbar_wait(BAR_KV(0), 0);
    wg_fence();
    wg_qs72<1>(Sp, dQ, dK0 + 24);
    wg_qs24<0>(Sm, dQ, dK0);
    wg_commit();
    wg_wait<0>();
    fence_regs<12>(Sm); fence_regs<36>(Sp);
#pragma unroll 1
    for (int pass = 0; pass < 2; pass++) {
#pragma unroll
      for (int i = 0; i < 12; i++) O[i] = 0.f;
      fence_regs<12>(O);
      if (tid == 0) TSW(1, 2 + 2 * pass);
      uint32_t vlo = (uint32_t)dV0;
#pragma unroll 1
      for (int seg = 0; seg < 4; seg++) {
        if (pass == 0) {
          if (seg < 3) mbar_wait(seg == 0 ? BAR_VB(0) : BAR_KV(seg), 0);
        } else if (seg >= 1) {
          if ((tid & 127) == 0) {
            mbar_arrive(BAR_CL(seg));
            if (seg == 3) take_role(sM, wg);
          }
          __syncwarp();
        }
        if ((tid & 127) == 0) TSW(4 + wg, pass * 5 + seg);
        const uint32_t vend = vlo + (seg == 3 ? 3 : 6) * STEPK;
#pragma unroll 1
        for (; vlo != vend; vlo += 3 * STEPK) {
          uint64_t dK, dV;
          asm("mov.b64 %0, {%1, %2};" : "=l"(dK) : "r"(vlo + dKV), "r"(8u));
          asm("mov.b64 %0, {%1, %2};" : "=l"(dV) : "r"(vlo), "r"(2048u));
#pragma unroll
          for (int u = 0; u < 3; u++) {
          { uint32_t w[18], y[18], z[18]; float e[12];
            X_MU(0) X_PR(0) X_LO(0) X_IM(0) X_MU(1) X_FM(0) X_PR(1) X_LO(1) X_IM(1) X_MU(2) X_FM(1) X_PR(2)
            X_LO(2) X_MU(3) X_IM(2) X_FM(2) X_PR(3) X_LO(3) X_PK(0) X_MU(4) X_IM(3) X_FM(3) X_PR(4) X_LO(4)
            X_MU(5) X_IM(4) X_FM(4) X_PR(5) X_PK(1) X_MU(6) X_LO(5) X_IM(5) X_FM(5) X_PR(6) X_MU(7) X_LO(6)
            X_IM(6) X_FM(6) X_MU(8) X_PR(7) X_PK(2) X_LO(7) X_IM(7) X_FM(7) X_MU(9) X_PR(8) X_LO(8) X_IM(8)
            X_FM(8) X_PK(3) X_MU(10) X_PR(9) X_LO(9) X_IM(9) X_MU(11) X_FM(9) X_PR(10) X_LO(10) X_IM(10) X_PK(4)
            X_FM(10) X_PR(11) X_LO(11) X_IM(11) X_FM(11) X_PR(12) X_LO(12) X_PK(5) X_IM(12) X_FM(12) X_PR(13) X_LO(13)
            X_IM(13) X_FM(13) X_PR(14) X_LO(14) X_IM(14) X_FM(14) X_PR(15) X_LO(15) X_IM(15) X_FM(15) X_PR(16) X_LO(16)
            X_IM(16) X_FM(16) X_PR(17) X_LO(17) X_IM(17) X_FM(17) }
          fence_regs<24>(P);
          wg_fence();
          wg_pv24<1>(O, &P[20], dV + u * STEPK + 80);
          wg_pv24<1>(O, &P[16], dV + u * STEPK + 64);
          wg_pv24<1>(O, &P[12], dV + u * STEPK + 48);
          wg_pv24<1>(O, &P[8], dV + u * STEPK + 32);
          wg_pv24<1>(O, &P[4], dV + u * STEPK + 16);
          wg_pv24<1>(O, &P[0], dV + u * STEPK + 0);
          wg_qs72<1>(Sp, dQ, dK + u * STEPK + 24);
          wg_qs24<0>(Sm, dQ, dK + u * STEPK);
          wg_commit();
          wg_wait<0>();
          fence_regs<12>(Sm); fence_regs<36>(Sp); fence_regs<12>(O); fence_regs<24>(P);
          }
        }
      }
#pragma unroll
      for (int i = 0; i < 6; i++) P[i] = pack_bf16(ex2f(Sm[2 * i]), ex2f(Sm[2 * i + 1]));
      P[6] = exp2_pair_fix(Sp[0], Sp[1], c63, m1);
      P[7] = exp2_pair_fix(Sp[2], Sp[3], c63, m1);
      fence_regs<8>(P);
#pragma unroll
      for (int i = 0; i < 36; i++) Sp[i] = SMAGIC;
      fence_regs<36>(Sp);
      mbar_wait(pass == 0 ? BAR_Q2 : BAR_CL(3), 0);
      const uint32_t sO = pass == 0 ? sb + OFF_F + wg * 2048 + w4 * 512 + (lane & 15) * 32 + (lane >> 4) * 16
                                    : sb + 26 * 8192 + (w4 * 16 + (lane & 15)) * 128 + (((wg * 2 + (lane >> 4)) ^ (lane & 7)) << 4);
      dQ += 512;
      wg_fence();
      wg_pv24<1>(O, &P[0], dV0 + 21 * STEPK);
      wg_pv24<1>(O, &P[4], dV0 + 21 * STEPK + 16);
      wg_commit();
      wg_qs72<1>(Sp, dQ, dK0 + 24);
      wg_qs24<0>(Sm, dQ, dK0);
      wg_commit();
      wg_wait<1>();
      fence_regs<12>(O);
      const float l0 = __shfl_sync(~0u, O[8], lane & ~3), l1 = __shfl_sync(~0u, O[10], lane & ~3);
      const float i0 = rcpf(l0), i1 = rcpf(l1);
      stsm4(sO,
            pack_bf16(O[0] * i0, O[1] * i0), pack_bf16(O[2] * i1, O[3] * i1),
            pack_bf16(O[4] * i0, O[5] * i0), pack_bf16(O[6] * i1, O[7] * i1));
      fence_async();
      {
        safe = __all_sync(~0u, lds1(sM + 16) != 0);
      }
      if (safe && lane == 0) mbar_arrive(BAR_OD(pass));
      wg_wait<0>();
      fence_regs<12>(Sm); fence_regs<36>(Sp);
      if (!safe) break;
      if ((tid & 127) == 0) TSW(4 + wg, pass * 5 + 4);
      if (tid == 0) TSW(1, 3 + 2 * pass);
    }
  }
  if (!safe) {
    if ((tid & 127) == 0) { mbar_arrive(BAR_CL(1)); mbar_arrive(BAR_CL(2)); mbar_arrive(BAR_CL(3)); take_role(sM, wg); }
#pragma unroll 1
    for (int pass = 0; pass < 2; pass++) {
      const int t = tid & 127;
      mbar_wait(BAR_CL(3), 0);
      attn_slow(prm.xa + (size_t)tbA * 64 * D_MOD, prm.wq + (hg * 8 + pass * 4 + wg) * 16,
                pass == 0 ? sb + OFF_F + wg * 2048 + t * 16
                          : sb + 26 * 8192 + (t >> 1) * 128 + (((wg * 2 + (t & 1)) ^ ((t >> 1) & 7)) << 4));
      __syncwarp();
      if (lane == 0) mbar_arrive(BAR_OD(pass));
    }
  }

  {
    named_bar(wg + 1, 128);
    if ((tid & 127) == 0) mbar_arrive(BAR_CL(4));
    const int role = __shfl_sync(~0u, lds1(sM + 32 + wg * 4), 0);
    if ((tid & 127) == 0) TSW(4 + wg, 10);
    const int m = lane >> 3, r = lane & 7;
    const uint32_t stoff = (w4 * 16 + (m & 1) * 8 + r) * 128;
    if (role < 2) {
      if (role == 0 && (tid & 127) == 0) mbar_arrive(BAR_RL);
      if (!isB || role == 1) mbar_wait(BAR_CL(4), 0);
      float acc[64];
#pragma unroll 1
      for (int n = 0; n < 8; n++) {
        const uint32_t sl = tail_slots(isB, n);
        const uint32_t w0 = (sl >> 16) & 255, w1 = sl >> 24;
        const uint64_t da = make_desc(sb + ((sl >> (8 * role)) & 255) * 8192, 16, 1024, 1);
        const uint64_t db = make_desc(sb + w0 * 8192, (w1 - w0) * 8192, 1024, 1);
        mbar_wait(BAR_TF(n), 0);
        if (!isB && n >= 4) mbar_wait(n == 4 && role == 0 ? BAR_OD(1) : BAR_TF(2 * n + role), 0);
        if ((tid & 127) == 0 && role == 1) TSW(2, 2 + n);
        wg_fence();
#pragma unroll
        for (int k = 0; k < 4; k++) wg_ss128<0, 1>(acc, da + k * 2, db + k * 128, (n | k) != 0);
        wg_commit();
        wg_wait<1>();
        if ((n == 1 || n == 2) && (tid & 127) == 0) mbar_arrive(BAR_TE(n - 1));
        __syncwarp();
      }
      wg_wait<0>();
      fence_regs<64>(acc);
      if ((tid & 127) == 0) TSW(4 + wg, 11);
      const uint32_t x0 = sb + (role ? 16 : 8) * 8192, x1 = sb + (role ? 5 : 1) * 8192;
#pragma unroll
      for (int j = 0; j < 16; j += 2)
        stsm4((j < 8 ? x0 : x1) + stoff + ((((j & 7) + (m >> 1)) ^ r) << 4),
              pack_bf16(acc[4 * j], acc[4 * j + 1]), pack_bf16(acc[4 * j + 2], acc[4 * j + 3]),
              pack_bf16(acc[4 * j + 4], acc[4 * j + 5]), pack_bf16(acc[4 * j + 6], acc[4 * j + 7]));
      __syncwarp();
      uint4* dst = (uint4*)(prm.out + (size_t)(tok0 + role * 64 + w4 * 16 + (lane >> 4)) * 1024 + isB * 512 + hg * 128) + (lane & 15);
      const uint32_t src = ((lane & 8) ? x1 : x0) + (w4 * 16 + (lane >> 4)) * 128;
#pragma unroll
      for (int i = 0; i < 8; i++) {
        uint32_t v[4];
        lds4(src + i * 256 + (((lane & 7) ^ ((2 * i + (lane >> 4)) & 7)) << 4), v);
        dst[i * 256] = make_uint4(v[0], v[1], v[2], v[3]);
      }
      if ((tid & 127) == 0) TS(2, 11 + role);
    }
  }
}

typedef CUresult (*EncodeFn)(CUtensorMap*, CUtensorMapDataType, cuuint32_t, void*, const cuuint64_t*, const cuuint64_t*,
                             const cuuint32_t*, const cuuint32_t*, CUtensorMapInterleave, CUtensorMapSwizzle,
                             CUtensorMapL2promotion, CUtensorMapFloatOOBfill);

static void make_map(EncodeFn enc, CUtensorMap* m, const void* ptr, uint64_t cols, uint64_t rows, uint32_t bc, uint32_t br,
                     CUtensorMapSwizzle sw = CU_TENSOR_MAP_SWIZZLE_128B) {
  cuuint64_t dims[2] = {cols, rows};
  cuuint64_t strides[1] = {cols * 2};
  cuuint32_t box[2] = {bc, br};
  cuuint32_t es[2] = {1, 1};
  enc(m, CU_TENSOR_MAP_DATA_TYPE_BFLOAT16, 2, (void*)ptr, dims, strides, box, es, CU_TENSOR_MAP_INTERLEAVE_NONE,
      sw, CU_TENSOR_MAP_L2_PROMOTION_L2_256B, CU_TENSOR_MAP_FLOAT_OOB_FILL_NONE);
}

extern "C" void kernel_launch(void* const* d_in, const int* in_sizes, int n_in, void* d_out, int out_size) {
  (void)in_sizes; (void)n_in; (void)out_size;
  static EncodeFn enc = nullptr;
  static void* pQ = nullptr; static void* pO = nullptr;
  if (!enc) {
    void* fn = nullptr; cudaDriverEntryPointQueryResult qr;
    cudaGetDriverEntryPoint("cuTensorMapEncodeTiled", &fn, cudaEnableDefault, &qr);
    enc = (EncodeFn)fn;
    cudaGetSymbolAddress(&pQ, g_Q);
    cudaGetSymbolAddress(&pO, g_O);
    cudaFuncSetAttribute(k1_main, cudaFuncAttributeMaxDynamicSharedMemorySize, SM_TOTAL);
  }
  CUtensorMap mXA64, mXB, mWq, mWqkv, mQst, mO, mWoA, mWoB, mO16;
  make_map(enc, &mXA64, d_in[0], 512, 2048, 64, 64);
  make_map(enc, &mWq, d_in[1], 512, 512, 64, 64);
  make_map(enc, &mWoA, d_in[4], 512, 512, 64, 64);
  make_map(enc, &mXB, d_in[5], 512, 2048, 64, 128);
  make_map(enc, &mWqkv, d_in[6], 1536, 512, 64, 64);
  make_map(enc, &mWoB, d_in[7], 512, 512, 64, 64);
  make_map(enc, &mQst, pQ, 512, 4096, 64, 128);
  make_map(enc, &mO, pO, 512, 4096, 64, 64);
  make_map(enc, &mO16, pO, 512, 4096, 16, 64, CU_TENSOR_MAP_SWIZZLE_NONE);
  Params prm{(const __nv_bfloat16*)d_in[2], (const __nv_bfloat16*)d_in[3], (const __nv_bfloat16*)d_in[0], (const __nv_bfloat16*)d_in[1], (__nv_bfloat16*)d_out};
  k1_main<<<132, 640, SM_TOTAL, cudaStreamPerThread>>>(mXA64, mXB, mWq, mWqkv, mQst, mO, mWoA, mWoB, mO16, prm);
}
```

```cpp
#include <cuda_runtime.h>
#include <cuda_bf16.h>
#include <cuda_fp16.h>
#include <cuda.h>
#include <stdint.h>

#define S_TOK 2048
#define D_MOD 512

__device__ __align__(1024) __nv_bfloat16 g_Q[2 * S_TOK * D_MOD];
__device__ __align__(1024) __nv_bfloat16 g_O[2 * S_TOK * D_MOD];
__device__ __align__(1024) uint4 g_KV[8 * S_TOK];
__device__ __align__(16) uint32_t g_stats[128];
__device__ __align__(16) float4 g_kvp[16 * 32 * 3 * 32];

#define TS(k, i) do {} while (0)
#define TSW(k, i) do {} while (0)
__device__ __forceinline__ uint32_t smem_u32(const void* p) { return (uint32_t)__cvta_generic_to_shared(p); }
__device__ __forceinline__ void mbar_init(uint32_t bar, int cnt) { asm volatile("mbarrier.init.shared::cta.b64 [%0], %1;" :: "r"(bar), "r"(cnt) : "memory"); }
__device__ __forceinline__ void mbar_expect_tx(uint32_t bar, uint32_t bytes) { asm volatile("mbarrier.arrive.expect_tx.shared::cta.b64 _, [%0], %1;" :: "r"(bar), "r"(bytes) : "memory"); }
__device__ __forceinline__ bool mbar_try(uint32_t bar, uint32_t parity) {
  uint32_t ok;
  asm volatile("{\n.reg .pred p;\nmbarrier.try_wait.parity.shared::cta.b64 p, [%1], %2;\nselp.b32 %0, 1, 0, p;\n}\n" : "=r"(ok) : "r"(bar), "r"(parity) : "memory");
  return ok;
}
__device__ __forceinline__ void mbar_wait(uint32_t bar, uint32_t parity) {
  asm volatile("{\n.reg .pred p;\n.reg .u32 c;\nmov.u32 c, 0;\n"
               "LW_%=:\n"
               "mbarrier.try_wait.parity.shared::cta.b64 p, [%0], %1;\n"
               "@p bra LD_%=;\n"
               "add.u32 c, c, 1;\n"
               "setp.lt.u32 p, c, 4000000;\n"
               "@p bra LW_%=;\n"
               "trap;\n"
               "LD_%=:\n}\n" :: "r"(bar), "r"(parity) : "memory");
}
__device__ __forceinline__ void mbar_arrive_cta(uint32_t bar, uint32_t cta) {
  asm volatile("{\n.reg .b32 ra;\nmapa.shared::cluster.u32 ra, %0, %1;\nmbarrier.arrive.shared::cluster.b64 _, [ra];\n}\n" :: "r"(bar), "r"(cta) : "memory");
}
__device__ __forceinline__ void cluster_sync() {
  asm volatile("barrier.cluster.arrive.relaxed.aligned;\nbarrier.cluster.wait.aligned;" ::: "memory");
}
__device__ __forceinline__ void tma2d(uint32_t dst, const CUtensorMap* m, int c0, int c1, uint32_t bar) {
  asm volatile("cp.async.bulk.tensor.2d.shared::cluster.global.mbarrier::complete_tx::bytes [%0], [%1, {%3, %4}], [%2];"
               :: "r"(dst), "l"(m), "r"(bar), "r"(c0), "r"(c1) : "memory");
}
__device__ __forceinline__ void tma2d_mc(uint32_t dst, const CUtensorMap* m, int c0, int c1, uint32_t bar, uint16_t mask) {
  asm volatile("cp.async.bulk.tensor.2d.shared::cluster.global.mbarrier::complete_tx::bytes.multicast::cluster [%0], [%1, {%3, %4}], [%2], %5;"
               :: "r"(dst), "l"(m), "r"(bar), "r"(c0), "r"(c1), "h"(mask) : "memory");
}
__device__ __forceinline__ void tma2d_store(const CUtensorMap* m, uint32_t src, int c0, int c1) {
  asm volatile("cp.async.bulk.tensor.2d.global.shared::cta.bulk_group [%0, {%2, %3}], [%1];"
               :: "l"(m), "r"(src), "r"(c0), "r"(c1) : "memory");
}
__device__ __forceinline__ void bulk_g2s(uint32_t dst, const void* src, uint32_t bytes, uint32_t bar) {
  asm volatile("cp.async.bulk.shared::cluster.global.mbarrier::complete_tx::bytes [%0], [%1], %2, [%3];"
               :: "r"(dst), "l"(src), "r"(bytes), "r"(bar) : "memory");
}
__device__ __forceinline__ void bulk_commit() { asm volatile("cp.async.bulk.commit_group;" ::: "memory"); }
__device__ __forceinline__ void bulk_wait_all() { asm volatile("cp.async.bulk.wait_group 0;" ::: "memory"); }
__device__ __forceinline__ void fence_async() { asm volatile("fence.proxy.async.shared::cta;" ::: "memory"); }
__device__ __forceinline__ void named_bar(int id, int n) { asm volatile("bar.sync %0, %1;" :: "r"(id), "r"(n) : "memory"); }
__device__ __forceinline__ void pdl_launch() { asm volatile("griddepcontrol.launch_dependents;" ::: "memory"); }
__device__ __forceinline__ void pdl_wait() { asm volatile("griddepcontrol.wait;" ::: "memory"); }
__device__ __forceinline__ void wg_fence() { asm volatile("wgmma.fence.sync.aligned;" ::: "memory"); }
__device__ __forceinline__ void wg_commit() { asm volatile("wgmma.commit_group.sync.aligned;" ::: "memory"); }
template <int n> __device__ __forceinline__ void wg_wait() { asm volatile("wgmma.wait_group.sync.aligned %0;" :: "n"(n) : "memory"); }
template <int n> __device__ __forceinline__ void fence_regs(float* r) {
#pragma unroll
  for (int i = 0; i < n; i++) asm volatile("" : "+f"(r[i]) :: "memory");
}
template <int n> __device__ __forceinline__ void fence_regs(uint32_t* r) {
#pragma unroll
  for (int i = 0; i < n; i++) asm volatile("" : "+r"(r[i]) :: "memory");
}
__device__ __forceinline__ uint64_t make_desc(uint32_t addr, uint32_t lbo, uint32_t sbo, uint32_t swz) {
  return (uint64_t)((addr & 0x3FFFF) >> 4) | ((uint64_t)(lbo >> 4) << 16) | ((uint64_t)(sbo >> 4) << 32) | ((uint64_t)swz << 62);
}
__device__ __forceinline__ float ex2f(float x) { float y; asm("ex2.approx.ftz.f32 %0, %1;" : "=f"(y) : "f"(x)); return y; }
__device__ __forceinline__ uint32_t pack_bf16(float lo, float hi) { uint32_t r; asm("cvt.rn.bf16x2.f32 %0, %1, %2;" : "=r"(r) : "f"(hi), "f"(lo)); return r; }
__device__ __forceinline__ uint32_t pack_f16(float lo, float hi) { uint32_t r; asm("cvt.rn.f16x2.f32 %0, %1, %2;" : "=r"(r) : "f"(hi), "f"(lo)); return r; }
__device__ __forceinline__ float bf_lo(uint32_t v) { return __uint_as_float(v << 16); }
__device__ __forceinline__ float bf_hi(uint32_t v) { return __uint_as_float(v & 0xFFFF0000u); }
__device__ __forceinline__ float rbf(float x) { return __bfloat162float(__float2bfloat16_rn(x)); }
__device__ __forceinline__ void stsm4(uint32_t a, uint32_t r0, uint32_t r1, uint32_t r2, uint32_t r3) {
  asm volatile("stmatrix.sync.aligned.m8n8.x4.shared.b16 [%0], {%1,%2,%3,%4};" :: "r"(a), "r"(r0), "r"(r1), "r"(r2), "r"(r3) : "memory");
}
__device__ __forceinline__ void stsm4t(uint32_t a, uint32_t r0, uint32_t r1, uint32_t r2, uint32_t r3) {
  asm volatile("stmatrix.sync.aligned.m8n8.x4.trans.shared.b16 [%0], {%1,%2,%3,%4};" :: "r"(a), "r"(r0), "r"(r1), "r"(r2), "r"(r3) : "memory");
}
__device__ __forceinline__ void mma_bf16(float* d, uint32_t a0, uint32_t a1, uint32_t a2, uint32_t a3, uint32_t b0, uint32_t b1) {
  asm volatile("mma.sync.aligned.m16n8k16.row.col.f32.bf16.bf16.f32 {%0,%1,%2,%3}, {%4,%5,%6,%7}, {%8,%9}, {%0,%1,%2,%3};"
               : "+f"(d[0]), "+f"(d[1]), "+f"(d[2]), "+f"(d[3]) : "r"(a0), "r"(a1), "r"(a2), "r"(a3), "r"(b0), "r"(b1));
}
template<int SD> __device__ __forceinline__ void wg_qs24(float* d, uint64_t da, uint64_t db) {
  asm volatile("wgmma.mma_async.sync.aligned.m64n24k16.f32.f16.f16 {%0,%1,%2,%3,%4,%5,%6,%7,%8,%9,%10,%11}, %12, %13, %14, 1, 1, 0, 0;"
   : "+f"(d[0]),"+f"(d[1]),"+f"(d[2]),"+f"(d[3]),"+f"(d[4]),"+f"(d[5]),"+f"(d[6]),"+f"(d[7]),"+f"(d[8]),"+f"(d[9]),"+f"(d[10]),"+f"(d[11])
   : "l"(da),"l"(db),"n"(SD));
}
template<int SD> __device__ __forceinline__ void wg_qs72(float* d, uint64_t da, uint64_t db) {
  asm volatile("wgmma.mma_async.sync.aligned.m64n72k16.f32.f16.f16 {%0,%1,%2,%3,%4,%5,%6,%7,%8,%9,%10,%11,%12,%13,%14,%15,%16,%17,%18,%19,%20,%21,%22,%23,%24,%25,%26,%27,%28,%29,%30,%31,%32,%33,%34,%35}, %36, %37, %38, 1, 1, 0, 0;"
   : "+f"(d[0]),"+f"(d[1]),"+f"(d[2]),"+f"(d[3]),"+f"(d[4]),"+f"(d[5]),"+f"(d[6]),"+f"(d[7]),"+f"(d[8]),"+f"(d[9]),"+f"(d[10]),"+f"(d[11]),"+f"(d[12]),"+f"(d[13]),"+f"(d[14]),"+f"(d[15]),"+f"(d[16]),"+f"(d[17]),"+f"(d[18]),"+f"(d[19]),"+f"(d[20]),"+f"(d[21]),"+f"(d[22]),"+f"(d[23]),"+f"(d[24]),"+f"(d[25]),"+f"(d[26]),"+f"(d[27]),"+f"(d[28]),"+f"(d[29]),"+f"(d[30]),"+f"(d[31]),"+f"(d[32]),"+f"(d[33]),"+f"(d[34]),"+f"(d[35])
   : "l"(da),"l"(db),"n"(SD));
}
template<int SD> __device__ __forceinline__ void wg_qs96(float* d, uint64_t da, uint64_t db) {
  asm volatile("wgmma.mma_async.sync.aligned.m64n96k16.f32.f16.f16 {%0,%1,%2,%3,%4,%5,%6,%7,%8,%9,%10,%11,%12,%13,%14,%15,%16,%17,%18,%19,%20,%21,%22,%23,%24,%25,%26,%27,%28,%29,%30,%31,%32,%33,%34,%35,%36,%37,%38,%39,%40,%41,%42,%43,%44,%45,%46,%47}, %48, %49, %50, 1, 1, 0, 0;"
   : "+f"(d[0]),"+f"(d[1]),"+f"(d[2]),"+f"(d[3]),"+f"(d[4]),"+f"(d[5]),"+f"(d[6]),"+f"(d[7]),"+f"(d[8]),"+f"(d[9]),"+f"(d[10]),"+f"(d[11]),"+f"(d[12]),"+f"(d[13]),"+f"(d[14]),"+f"(d[15]),"+f"(d[16]),"+f"(d[17]),"+f"(d[18]),"+f"(d[19]),"+f"(d[20]),"+f"(d[21]),"+f"(d[22]),"+f"(d[23]),"+f"(d[24]),"+f"(d[25]),"+f"(d[26]),"+f"(d[27]),"+f"(d[28]),"+f"(d[29]),"+f"(d[30]),"+f"(d[31]),"+f"(d[32]),"+f"(d[33]),"+f"(d[34]),"+f"(d[35]),"+f"(d[36]),"+f"(d[37]),"+f"(d[38]),"+f"(d[39]),"+f"(d[40]),"+f"(d[41]),"+f"(d[42]),"+f"(d[43]),"+f"(d[44]),"+f"(d[45]),"+f"(d[46]),"+f"(d[47])
   : "l"(da),"l"(db),"n"(SD));
}
template<int SD> __device__ __forceinline__ void wg_pv24(float* d, const uint32_t* a, uint64_t desc) {
  asm volatile("wgmma.mma_async.sync.aligned.m64n24k16.f32.bf16.bf16 {%0,%1,%2,%3,%4,%5,%6,%7,%8,%9,%10,%11}, {%12,%13,%14,%15}, %16, %17, 1, 1, 1;"
   : "+f"(d[0]),"+f"(d[1]),"+f"(d[2]),"+f"(d[3]),"+f"(d[4]),"+f"(d[5]),"+f"(d[6]),"+f"(d[7]),"+f"(d[8]),"+f"(d[9]),"+f"(d[10]),"+f"(d[11])
   : "r"(a[0]),"r"(a[1]),"r"(a[2]),"r"(a[3]),"l"(desc),"n"(SD));
}
template<int TA, int TB> __device__ __forceinline__ void wg_ss128(float* d, uint64_t da, uint64_t db, int sd) {
  asm volatile("{\n.reg .pred p;\nsetp.ne.b32 p, %66, 0;\n"
   "wgmma.mma_async.sync.aligned.m64n128k16.f32.bf16.bf16 {%0,%1,%2,%3,%4,%5,%6,%7,%8,%9,%10,%11,%12,%13,%14,%15,%16,%17,%18,%19,%20,%21,%22,%23,%24,%25,%26,%27,%28,%29,%30,%31,%32,%33,%34,%35,%36,%37,%38,%39,%40,%41,%42,%43,%44,%45,%46,%47,%48,%49,%50,%51,%52,%53,%54,%55,%56,%57,%58,%59,%60,%61,%62,%63}, %64, %65, p, 1, 1, %67, %68;\n}\n"
   : "+f"(d[0]),"+f"(d[1]),"+f"(d[2]),"+f"(d[3]),"+f"(d[4]),"+f"(d[5]),"+f"(d[6]),"+f"(d[7]),"+f"(d[8]),"+f"(d[9]),"+f"(d[10]),"+f"(d[11]),"+f"(d[12]),"+f"(d[13]),"+f"(d[14]),"+f"(d[15]),"+f"(d[16]),"+f"(d[17]),"+f"(d[18]),"+f"(d[19]),"+f"(d[20]),"+f"(d[21]),"+f"(d[22]),"+f"(d[23]),"+f"(d[24]),"+f"(d[25]),"+f"(d[26]),"+f"(d[27]),"+f"(d[28]),"+f"(d[29]),"+f"(d[30]),"+f"(d[31]),"+f"(d[32]),"+f"(d[33]),"+f"(d[34]),"+f"(d[35]),"+f"(d[36]),"+f"(d[37]),"+f"(d[38]),"+f"(d[39]),"+f"(d[40]),"+f"(d[41]),"+f"(d[42]),"+f"(d[43]),"+f"(d[44]),"+f"(d[45]),"+f"(d[46]),"+f"(d[47]),"+f"(d[48]),"+f"(d[49]),"+f"(d[50]),"+f"(d[51]),"+f"(d[52]),"+f"(d[53]),"+f"(d[54]),"+f"(d[55]),"+f"(d[56]),"+f"(d[57]),"+f"(d[58]),"+f"(d[59]),"+f"(d[60]),"+f"(d[61]),"+f"(d[62]),"+f"(d[63])
   : "l"(da),"l"(db),"r"(sd),"n"(TA),"n"(TB));
}
template<int TA, int TB> __device__ __forceinline__ void wg_ss64(float* d, uint64_t da, uint64_t db, int sd) {
  asm volatile("{\n.reg .pred p;\nsetp.ne.b32 p, %34, 0;\n"
   "wgmma.mma_async.sync.aligned.m64n64k16.f32.bf16.bf16 {%0,%1,%2,%3,%4,%5,%6,%7,%8,%9,%10,%11,%12,%13,%14,%15,%16,%17,%18,%19,%20,%21,%22,%23,%24,%25,%26,%27,%28,%29,%30,%31}, %32, %33, p, 1, 1, %35, %36;\n}\n"
   : "+f"(d[0]),"+f"(d[1]),"+f"(d[2]),"+f"(d[3]),"+f"(d[4]),"+f"(d[5]),"+f"(d[6]),"+f"(d[7]),"+f"(d[8]),"+f"(d[9]),"+f"(d[10]),"+f"(d[11]),"+f"(d[12]),"+f"(d[13]),"+f"(d[14]),"+f"(d[15]),"+f"(d[16]),"+f"(d[17]),"+f"(d[18]),"+f"(d[19]),"+f"(d[20]),"+f"(d[21]),"+f"(d[22]),"+f"(d[23]),"+f"(d[24]),"+f"(d[25]),"+f"(d[26]),"+f"(d[27]),"+f"(d[28]),"+f"(d[29]),"+f"(d[30]),"+f"(d[31])
   : "l"(da),"l"(db),"r"(sd),"n"(TA),"n"(TB));
}
template<int TA, int TB> __device__ __forceinline__ void wg_ss8(float* d, uint64_t da, uint64_t db, int sd) {
  asm volatile("{\n.reg .pred p;\nsetp.ne.b32 p, %6, 0;\n"
   "wgmma.mma_async.sync.aligned.m64n8k16.f32.bf16.bf16 {%0,%1,%2,%3}, %4, %5, p, 1, 1, %7, %8;\n}\n"
   : "+f"(d[0]),"+f"(d[1]),"+f"(d[2]),"+f"(d[3])
   : "l"(da),"l"(db),"r"(sd),"n"(TA),"n"(TB));
}

__device__ __forceinline__ uint32_t phi2(float a, float b) {
  uint32_t r, e;
  asm("cvt.rn.relu.bf16x2.f32 %0, %1, %2;" : "=r"(r) : "f"(b), "f"(a));
  e = pack_bf16(ex2f(a * 1.4426950408889634f), ex2f(b * 1.4426950408889634f));
  asm("add.rn.bf16x2 %0, %0, %1;" : "+r"(e) : "r"(0x35863586u));
  asm("min.NaN.bf16x2 %0, %0, %1;" : "+r"(e) : "r"(0x3F803F80u));
  asm("add.rn.bf16x2 %0, %0, %1;" : "+r"(e) : "r"(r));
  return e;
}

__device__ __forceinline__ void mbar_wait_long(uint32_t bar, uint32_t parity) {
  asm volatile("{\n.reg .pred p;\n.reg .u32 c;\nmov.u32 c, 0;\n"
               "LW_%=:\n"
               "mbarrier.try_wait.parity.shared::cta.b64 p, [%0], %1, 100000;\n"
               "@p bra LD_%=;\n"
               "add.u32 c, c, 1;\n"
               "setp.lt.u32 p, c, 20000;\n"
               "@p bra LW_%=;\n"
               "trap;\n"
               "LD_%=:\n}\n" :: "r"(bar), "r"(parity) : "memory");
}
__device__ __forceinline__ void mbar_arrive(uint32_t bar) { asm volatile("mbarrier.arrive.shared::cta.b64 _, [%0];" :: "r"(bar) : "memory"); }
__device__ __forceinline__ void named_arrive(int id, int n) { asm volatile("bar.arrive %0, %1;" :: "r"(id), "r"(n) : "memory"); }
__device__ __forceinline__ void fence_async_all() { asm volatile("fence.proxy.async.global;" ::: "memory"); }
__device__ __forceinline__ void flag_add(uint32_t* f) { asm volatile("fence.acq_rel.gpu;\nred.relaxed.gpu.global.add.u32 [%0], 1;" :: "l"(f) : "memory"); }
#define PUBLISH(f) asm volatile("fence.proxy.async.global;\nred.relaxed.gpu.global.add.u32 [%0], 1;" :: "l"(f) : "memory")
__device__ __forceinline__ void flag_wait(const uint32_t* f, uint32_t target) {
  uint32_t v;
#pragma unroll 1
  for (int it = 0;; it++) {
    asm volatile("ld.acquire.gpu.global.u32 %0, [%1];" : "=r"(v) : "l"(f) : "memory");
    if ((int32_t)(v - target) >= 0) break;
    if (it > 2000000) __trap();
    __nanosleep(64);
  }
}
__device__ __forceinline__ bool mbar_test(uint32_t bar, uint32_t parity) {
  uint32_t ok;
  asm volatile("{\n.reg .pred p;\nmbarrier.test_wait.parity.shared::cta.b64 p, [%1], %2;\nselp.b32 %0, 1, 0, p;\n}\n" : "=r"(ok) : "r"(bar), "r"(parity) : "memory");
  return ok;
}
__device__ __forceinline__ bool elect_one() {
  uint32_t p;
  asm volatile("{\n.reg .pred P;\nelect.sync _|P, 0xFFFFFFFF;\nselp.b32 %0, 1, 0, P;\n}\n" : "=r"(p));
  return p;
}
__device__ __forceinline__ void lds4(uint32_t a, uint32_t* r) {
  asm volatile("ld.shared.v4.b32 {%0,%1,%2,%3}, [%4];" : "=r"(r[0]), "=r"(r[1]), "=r"(r[2]), "=r"(r[3]) : "r"(a) : "memory");
}
__device__ __forceinline__ uint32_t lds1(uint32_t a) { uint32_t r; asm volatile("ld.shared.b32 %0, [%1];" : "=r"(r) : "r"(a) : "memory"); return r; }
__device__ __forceinline__ void sts1(uint32_t a, uint32_t v) { asm volatile("st.shared.b32 [%0], %1;" :: "r"(a), "r"(v) : "memory"); }
__device__ __forceinline__ void sts4(uint32_t a, uint32_t r0, uint32_t r1, uint32_t r2, uint32_t r3) {
  asm volatile("st.shared.v4.b32 [%0], {%1,%2,%3,%4};" :: "r"(a), "r"(r0), "r"(r1), "r"(r2), "r"(r3) : "memory");
}
__device__ __forceinline__ void ldsm4(uint32_t a, uint32_t* r) {
  asm volatile("ldmatrix.sync.aligned.m8n8.x4.shared.b16 {%0,%1,%2,%3}, [%4];" : "=r"(r[0]), "=r"(r[1]), "=r"(r[2]), "=r"(r[3]) : "r"(a) : "memory");
}
__device__ __forceinline__ float rcpf(float x) { float y; asm("rcp.approx.ftz.f32 %0, %1;" : "=f"(y) : "f"(x)); return y; }
__device__ __forceinline__ uint32_t hfma2(uint32_t a, uint32_t b, uint32_t c) { uint32_t r; asm("fma.rn.f16x2 %0, %1, %2, %3;" : "=r"(r) : "r"(a), "r"(b), "r"(c)); return r; }
__device__ __forceinline__ uint32_t hadd2(uint32_t a, uint32_t b) { uint32_t r; asm("add.rn.f16x2 %0, %1, %2;" : "=r"(r) : "r"(a), "r"(b)); return r; }

#define STEPK 96
#define GIMAP(i) ((((i) & 1) << 2) | (((i) >> 1) & 3) | ((i) & 8))
#define QSCALE 0.36067376022224085f
#define SMAGIC (512.0f + 2.0f * (191.0f - 30.0f - 1.5823545f))
#define VSHIFT 1073741824.0f

__device__ uint32_t g_epoch[132];
__device__ uint32_t g_flag[288 * 8];
#define FLAG_KV (g_flag)
#define FLAG_B(h) (g_flag + (4 + (h)) * 8)
#define FLAG_OA(cta, pass) (g_flag + (16 + (cta) * 2 + (pass)) * 8)
#define FLAG_LM(i) (g_flag + (272 + (i)) * 8)

#define SM_TOTAL (224 * 1024 + 2048 + 1024)
#define OFF_K 0
#define OFF_F 65536
#define OFF_V 131072
#define OFF_MISC (224 * 1024)

#define BAR_FULL(s) (bars + 8 * (s))
#define BAR_EMPTY(s) (bars + 24 + 8 * (s))
#define BAR_KV(c) (bars + 48 + 8 * (c))
#define BAR_BDONE (bars + 80)
#define BAR_Q (bars + 88)
#define BAR_GO (bars + 96)
#define BAR_Q2 (bars + 104)
#define BAR_OD(p) (bars + 112 + 8 * (p))
#define BAR_CL(c) (bars + 128 + 8 * (c))
#define BAR_TE(i) (bars + 168 + 8 * (i))
#define BAR_RL (bars + 184)
#define BAR_TF(g) (bars + 224 + 8 * (g))
#define BAR_HD(i) (bars + 408 + 8 * (i))
#define BAR_XA(w) (bars + 352 + 8 * (w))
#define BAR_VB(c) (bars + 384 + 8 * (c))

__device__ __forceinline__ uint32_t exp2_pair_fix(float d0, float d1, uint32_t c63, uint32_t m1) {
  uint32_t w, y, s, r;
  asm("prmt.b32 %0, %1, %2, 0x6521;" : "=r"(w) : "r"(__float_as_uint(d0)), "r"(__float_as_uint(d1)));
  asm("lop3.b32 %0, %1, 0x007F007F, %2, 0xEA;" : "=r"(y) : "r"(w), "r"(c63));
  asm("mad.lo.u32 %0, %1, %2, %3;" : "=r"(s) : "r"(y), "r"(m1), "r"(w));
  asm("fma.rn.bf16x2 %0, %1, %2, %3;" : "=r"(r) : "r"(w), "r"(y), "r"(s));
  return r;
}

#define X_PR(i) asm volatile("prmt.b32 %0, %1, %2, 0x6521;" : "=r"(w[i]) : "r"(__float_as_uint(Sp[2 * (i)])), "r"(__float_as_uint(Sp[2 * (i) + 1])));
#define X_LO(i) asm volatile("lop3.b32 %0, %1, 0x007F007F, %2, 0xEA;" : "=r"(y[i]) : "r"(w[i]), "r"(c63));
#define X_IM(i) asm volatile("mad.lo.u32 %0, %1, %2, %3;" : "=r"(z[i]) : "r"(y[i]), "r"(m1), "r"(w[i]));
#define X_FM(i) asm volatile("fma.rn.bf16x2 %0, %1, %2, %3;" : "=r"(P[6 + (i)]) : "r"(w[i]), "r"(y[i]), "r"(z[i]));
#define X_MU(i) asm volatile("ex2.approx.ftz.f32 %0, %1;" : "=f"(e[i]) : "f"(Sm[i]));
#define X_PK(i) asm volatile("cvt.rn.bf16x2.f32 %0, %1, %2;" : "=r"(P[i]) : "f"(e[2 * (i) + 1]), "f"(e[2 * (i)]));

__device__ __forceinline__ void attn_slow(const __nv_bfloat16* xa, const __nv_bfloat16* wq, uint32_t dst) {
  const int t = threadIdx.x & 127;
  const int row = t >> 1, half = t & 1;
  float q[16];
  {
    float a[8];
#pragma unroll
    for (int i = 0; i < 8; i++) a[i] = 0.f;
#pragma unroll 1
    for (int k = 0; k < D_MOD; k++) {
      const float x = __bfloat162float(xa[(size_t)row * D_MOD + k]);
      const uint4 w = *(const uint4*)(wq + (size_t)k * D_MOD + half * 8);
      const uint32_t ww[4] = {w.x, w.y, w.z, w.w};
#pragma unroll
      for (int i = 0; i < 4; i++) { a[2 * i] = fmaf(x, bf_lo(ww[i]), a[2 * i]); a[2 * i + 1] = fmaf(x, bf_hi(ww[i]), a[2 * i + 1]); }
    }
#pragma unroll
    for (int i = 0; i < 8; i++) {
      const float mine = rbf(a[i]), other = __shfl_xor_sync(~0u, mine, 1);
      q[i] = half ? other : mine; q[8 + i] = half ? mine : other;
    }
  }
  float m = -INFINITY, l = 0.f, o[16];
#pragma unroll
  for (int i = 0; i < 16; i++) o[i] = 0.f;
#pragma unroll 1
  for (int j = half * 1024; j < half * 1024 + 1024; j++) {
    uint4 ka = g_KV[4 * S_TOK + j], kb = g_KV[5 * S_TOK + j];
    uint4 va = g_KV[6 * S_TOK + j], vb = g_KV[7 * S_TOK + j];
    uint32_t kk[8] = {ka.x, ka.y, ka.z, ka.w, kb.x, kb.y, kb.z, kb.w};
    uint32_t vv[8] = {va.x, va.y, va.z, va.w, vb.x, vb.y, vb.z, vb.w};
    float s = 0.f;
#pragma unroll
    for (int i = 0; i < 8; i++) { s = fmaf(q[2 * i], bf_lo(kk[i]), s); s = fmaf(q[2 * i + 1], bf_hi(kk[i]), s); }
    s = rbf(s) * 0.25f;
    if (s > m) {
      float c = __expf(m - s);
      l *= c;
#pragma unroll
      for (int i = 0; i < 16; i++) o[i] *= c;
      m = s;
    }
    float p = __expf(s - m);
    l += p;
#pragma unroll
    for (int i = 0; i < 8; i++) { o[2 * i] = fmaf(p, bf_lo(vv[i]), o[2 * i]); o[2 * i + 1] = fmaf(p, bf_hi(vv[i]), o[2 * i + 1]); }
  }
  float m2 = __shfl_xor_sync(~0u, m, 1);
  float mm = fmaxf(m, m2);
  float c = __expf(m - mm);
  l *= c; l += __shfl_xor_sync(~0u, l, 1);
  float inv = 1.f / l;
  uint32_t r[8];
#pragma unroll
  for (int i = 0; i < 16; i++) { o[i] *= c; o[i] += __shfl_xor_sync(~0u, o[i], 1); o[i] *= inv; }
#pragma unroll
  for (int i = 0; i < 8; i++) r[i] = pack_bf16(o[2 * i], o[2 * i + 1]);
  if (half == 0) sts4(dst, r[0], r[1], r[2], r[3]); else sts4(dst, r[4], r[5], r[6], r[7]);
  fence_async();
}

struct Params { const __nv_bfloat16* wk; const __nv_bfloat16* wv; const __nv_bfloat16* xa; const __nv_bfloat16* wq; __nv_bfloat16* out; };
__device__ __forceinline__ void cp16(uint32_t dst, const void* src) { asm volatile("cp.async.cg.shared.global [%0], [%1], 16;" :: "r"(dst), "l"(src) : "memory"); }

__device__ __forceinline__ void helper_cta(const int h, const uint32_t sb, const uint32_t bars, const int wg, const int w4) {
  const int lane = threadIdx.x & 31;
  mbar_wait(BAR_GO, 0);
  const int cb = wg & 1;
  const uint32_t buf = sb + wg * 49152;
  const int head = h * 8 + cb * 4 + w4;
  float4 a0 = make_float4(0, 0, 0, 0), a1 = a0, a2 = a0;
#pragma unroll 8
  for (int tt = 0; tt < 16; tt++) {
    const float4* src = g_kvp + ((tt * 32 + head) * 3) * 32 + lane;
    float4 u = src[0], v = src[32], w = src[64];
    a0.x += u.x; a0.y += u.y; a0.z += u.z; a0.w += u.w;
    a1.x += v.x; a1.y += v.y; a1.z += v.z; a1.w += v.w;
    a2.x += w.x; a2.y += w.y; a2.z += w.z; a2.w += w.w;
  }
  const uint32_t b00 = pack_bf16(a0.x, a0.y), b01 = pack_bf16(a0.z, a0.w);
  const uint32_t b10 = pack_bf16(a1.x, a1.y), b11 = pack_bf16(a1.z, a1.w);
  const uint32_t bz0 = pack_bf16(a2.x, a2.y), bz1 = pack_bf16(a2.z, a2.w);
  const int m = lane >> 3, r = lane & 7;
  const uint32_t off = ((m & 1) * 8 + r) * 128 + (((w4 * 2 + (m >> 1)) ^ r) << 4);
  int s = 0, ph = 0;
#pragma unroll 1
  for (int u = 0; u < 8; u++) {
    const uint32_t bb = buf + s * 16384;
    mbar_wait(BAR_TF(wg * 3 + s), ph);
    uint32_t a[32];
#pragma unroll
    for (int mt = 0; mt < 8; mt++) ldsm4(bb + mt * 2048 + off, a + 4 * mt);
#pragma unroll
    for (int i = 0; i < 32; i++) a[i] = phi2(bf_lo(a[i]), bf_hi(a[i]));
#pragma unroll
    for (int mt = 0; mt < 8; mt++) {
      uint32_t* p = a + 4 * mt;
      float n0[4] = {0, 0, 0, 0}, n1[4] = {0, 0, 0, 0}, dn[4] = {0, 0, 0, 0};
      mma_bf16(dn, p[0], p[1], p[2], p[3], bz0, bz1);
      mma_bf16(n0, p[0], p[1], p[2], p[3], b00, b01);
      mma_bf16(n1, p[0], p[1], p[2], p[3], b10, b11);
      const float i0 = rcpf(dn[0] + 1e-6f), i1 = rcpf(dn[2] + 1e-6f);
      p[0] = pack_bf16(n0[0] * i0, n0[1] * i0); p[1] = pack_bf16(n0[2] * i1, n0[3] * i1);
      p[2] = pack_bf16(n1[0] * i0, n1[1] * i0); p[3] = pack_bf16(n1[2] * i1, n1[3] * i1);
    }
#pragma unroll
    for (int mt = 0; mt < 8; mt++) stsm4(bb + mt * 2048 + off, a[4 * mt], a[4 * mt + 1], a[4 * mt + 2], a[4 * mt + 3]);
    fence_async();
    __syncwarp();
    if (lane == 0) mbar_arrive(BAR_HD(wg * 3 + s));
    if (++s == 3) { s = 0; ph ^= 1; }
  }
}

#define STAGE(s) (sb + (2 - (s)) * 65536)
__device__ __forceinline__ uint32_t xa_addr(uint32_t sb, int kb) {
  return sb + (kb >= 1 && kb <= 4 ? OFF_V + 65536 + (kb - 1) * 8192 : 16384 + (kb == 5 ? OFF_K : (kb == 6 ? OFF_V : OFF_F)));
}
#define XA7_TMP (sb + OFF_K + 40960)
#define WKV_TMP (sb + OFF_K + 32768)
template <int TR> __device__ __forceinline__ void proj_kb(float* acc, uint32_t aA, uint32_t aB, int first) {
  const uint64_t da = make_desc(aA, TR ? 8192 : 16, 1024, 1);
  const uint64_t db = make_desc(aB, TR ? 16 : 8192, 1024, 1);
  wg_fence();
#pragma unroll
  for (int k = 0; k < 4; k++) wg_ss128<TR, 1 - TR>(acc, da + k * (TR ? 128 : 2), db + k * (TR ? 2 : 128), k != 0 || !first);
  wg_commit();
}
template <int TR> __device__ __forceinline__ void proj_loop(float* acc, uint32_t sb, uint32_t bars, uint32_t offA, uint32_t offB,
                                                            int wg, uint32_t sWKV, const CUtensorMap* mW, int col, bool w0) {
  {
    float kv[4];
    if (threadIdx.x == 0) TS(0, 13);
    mbar_wait(BAR_XA(wg), 0);
    if (threadIdx.x == 0) TS(0, 1);
    const uint64_t da0 = make_desc(xa_addr(sb, 2 * wg), 16, 1024, 1);
    const uint64_t da1 = make_desc(wg == 3 ? XA7_TMP : xa_addr(sb, 2 * wg + 1), 16, 1024, 1);
    const uint64_t db = make_desc(sWKV + wg * 2048, 128, 128, 0);
    wg_fence();
#pragma unroll
    for (int k = 0; k < 8; k++) wg_ss8<0, 1>(kv, (k < 4 ? da0 : da1) + (k & 3) * 2, db + k * 16, k != 0);
    wg_commit();
    wg_wait<0>();
    fence_regs<4>(kv);
    named_bar(wg + 1, 128);
    sts4(sWKV + threadIdx.x * 16, __float_as_uint(kv[0]), __float_as_uint(kv[1]), __float_as_uint(kv[2]), __float_as_uint(kv[3]));
    __syncwarp();
    if ((threadIdx.x & 31) == 0) mbar_arrive(BAR_GO);
  }
  int s = 0, ph = 0;
#pragma unroll 1
  for (int kb = 0; kb < 8; kb++) {
    mbar_wait(BAR_FULL(s), ph);
    if (threadIdx.x == 0) TSW(0, 2 + kb);
    if (TR == 0) mbar_wait(BAR_XA(kb >> 1), 0);
    proj_kb<TR>(acc, TR ? STAGE(s) + offA : xa_addr(sb, kb), STAGE(s) + offB, kb == 0);
    wg_wait<0>();
    if (w0 && elect_one()) {
      if (kb < 5) {
        mbar_expect_tx(BAR_FULL(s), TR ? 8192 : 16384);
        tma2d(STAGE(s) + (TR ? offA : 0), mW, col, (kb + 3) * 64, BAR_FULL(s));
        if (TR == 0) tma2d(STAGE(s) + 8192, mW, col + 64, (kb + 3) * 64, BAR_FULL(s));
      }
      if (kb < 7) mbar_arrive(BAR_EMPTY(s));
      if (TR == 0 && kb == 4) mbar_arrive(BAR_VB(1));
    }
    __syncwarp();
    if (++s == 3) { s = 0; ph ^= 1; }
  }
  wg_wait<0>();
  fence_regs<64>(acc);
}

__device__ __forceinline__ uint32_t tail_slots(int isB, int n) {
  if (n < 4) return n < 2 ? (n == 0 ? 0x0D0C0B0Au : 0x04000F0Eu) : (n == 2 ? 0x18141008u : 0x15110501u);
  if (isB) return n < 6 ? (n == 4 ? 0x19120602u : 0x0D0C0B0Au) : (n == 6 ? 0x04000F0Eu : 0x13070316u);
  return n < 6 ? (n == 4 ? 0x1902031Au : 0x12061307u) : (n == 6 ? 0x16091B17u : 0x0D0C0B0Au);
}

__device__ __forceinline__ void take_role(uint32_t sM, int wg) {
  uint32_t r;
  asm volatile("atom.shared.add.u32 %0, [%1], 1;" : "=r"(r) : "r"(sM + 20) : "memory");
  sts1(sM + 32 + wg * 4, r);
}

__global__ void __launch_bounds__(640, 1)
k1_main(const __grid_constant__ CUtensorMap mXA64, const __grid_constant__ CUtensorMap mXB,
        const __grid_constant__ CUtensorMap mWq, const __grid_constant__ CUtensorMap mWqkv,
        const __grid_constant__ CUtensorMap mQst, const __grid_constant__ CUtensorMap mOst,
        const __grid_constant__ CUtensorMap mO, const __grid_constant__ CUtensorMap mWoA,
        const __grid_constant__ CUtensorMap mWoB,
        const __grid_constant__ CUtensorMap mO16, const Params prm) {
  if (threadIdx.x >= 608 && threadIdx.x < 612) {
    const CUtensorMap* pm = &mXA64 + (threadIdx.x - 608);
    asm volatile("prefetch.tensormap [%0];" :: "l"(pm) : "memory");
  }
  extern __shared__ uint8_t smem_raw[];
  const uint32_t sb = (smem_u32(smem_raw) + 1023u) & ~1023u;
  const uint32_t bars = sb + OFF_MISC, sM = bars + 512, sT = bars + 1024;
  const int tid = threadIdx.x, warp = __shfl_sync(~0u, tid >> 5, 0), wg = warp >> 2, w4 = warp & 3, lane = tid & 31;
  const bool helper = blockIdx.x >= 128;
  if (tid == 0) TS(0, 0);
  const int G = blockIdx.x >> 4, gi = GIMAP(blockIdx.x & 15);
  const int tbA = G * 4 + (gi >> 2), hg = gi & 3;
  const int ttB = (G >> 1) * 4 + (gi >> 2), hq = (G & 1) * 4 + (gi & 3);
  const int isB = tbA & 1, tok0 = (tbA >> 1) * 128;
  auto issue = [&](int kb, int s, int part) {
    const uint32_t fb = BAR_FULL(s), st = STAGE(s);
    if (part & 1) {
      mbar_expect_tx(fb, 57344);
      asm volatile("mbarrier.arrive.shared::cta.b64 _, [%0], 4;" :: "r"(fb) : "memory");
      tma2d(st, &mWq, hg * 128, kb * 64, fb);
      tma2d(st + 8192, &mWq, hg * 128 + 64, kb * 64, fb);
      tma2d(st + 49152, &mXB, kb * 64, ttB * 128, fb);
      tma2d(st + 24576, &mWqkv, hq * 64, kb * 64, fb);
    }
    if (part & 2) {
      tma2d(st + 32768, &mWqkv, 512 + hq * 64, kb * 64, fb);
      tma2d(st + 40960, &mWqkv, 1024 + hq * 64, kb * 64, fb);
    }
  };
  const uint32_t sOne = sb + OFF_V + 65536, sWKV = WKV_TMP;
  if (warp >= 16) {
    if (warp == 17) {
      if (elect_one()) {
        mbar_init(BAR_BDONE, 8); mbar_init(BAR_Q, 6); mbar_init(BAR_GO, helper ? 1 : 16); mbar_init(BAR_Q2, 1);
        mbar_init(BAR_OD(0), 16); mbar_init(BAR_OD(1), 16); mbar_init(BAR_CL(0), 1); mbar_init(BAR_FULL(2), 5);
#pragma unroll
        for (int i = 0; i < 4; i++) mbar_init(BAR_CL(i + 1), i == 0 ? 5 : 4);
#pragma unroll
        for (int i = 0; i < 3; i++) { mbar_init(BAR_EMPTY(i), 4); mbar_init(BAR_KV(i), 1); mbar_init(BAR_VB(i), i == 2 ? 4 : 1); }
        sts1(sM + 20, 0);
        asm volatile("fence.mbarrier_init.release.cluster;" ::: "memory");
      }
    } else if (warp == 18) {
      if (elect_one()) {
#pragma unroll
        for (int i = 0; i < 2; i++) mbar_init(BAR_TE(i), 2);
        mbar_init(BAR_RL, 1);
        if (helper) {
#pragma unroll
          for (int i = 0; i < 12; i++) mbar_init(BAR_HD(i), 4);
        }
#pragma unroll
        for (int i = 0; i < 16; i++) mbar_init(BAR_TF(i), 1);
        asm volatile("fence.mbarrier_init.release.cluster;" ::: "memory");
      }
    } else if (warp == 16 && !helper && elect_one()) {
#pragma unroll
      for (int w = 0; w < 4; w++) mbar_init(BAR_XA(w), 1);
      mbar_init(BAR_FULL(0), 5); mbar_init(BAR_FULL(1), 5);
      asm volatile("fence.mbarrier_init.release.cluster;" ::: "memory");
#pragma unroll
      for (int w = 0; w < 4; w++) {
        mbar_expect_tx(BAR_XA(w), 16384);
        tma2d(xa_addr(sb, 2 * w), &mXA64, w * 128, tbA * 64, BAR_XA(w));
        tma2d(w == 3 ? XA7_TMP : xa_addr(sb, 2 * w + 1), &mXA64, w * 128 + 64, tbA * 64, BAR_XA(w));
      }
      TS(0, 14);
      issue(0, 0, 3);
    }
  } else if (!helper) {
    const uint4 v = __ldg((const uint4*)(hg >= 2 ? prm.wv : prm.wk) + tid * 2 + (hg & 1));
    sts4(sWKV + tid * 16, v.x, v.y, v.z, v.w);
    fence_async();
  }
  __syncthreads();
  if (wg == 4) {
    if (w4 == 0 && !helper && elect_one()) { issue(1, 1, 3); issue(2, 2, 1); TS(0, 15); }
    asm volatile("setmaxnreg.dec.sync.aligned.u32 32;");
    const uint32_t ep = g_epoch[blockIdx.x] + 1;
    if (helper) {
      if (elect_one()) {
        const int h = blockIdx.x - 128, col = h * 128 + (w4 & 1) * 64, row0 = S_TOK + (w4 >> 1) * 1024;
        const uint32_t buf = sb + w4 * 49152;
        flag_wait(FLAG_B(h), ep * 32);
        fence_async_all();
        if (w4 == 0) { TS(1, 10); mbar_arrive(BAR_GO); }
#pragma unroll
        for (int u = 0; u < 3; u++) {
          mbar_expect_tx(BAR_TF(w4 * 3 + u), 16384);
          tma2d(buf + u * 16384, &mQst, col, row0 + u * 128, BAR_TF(w4 * 3 + u));
        }
        int s = 0, ph = 0;
#pragma unroll 1
        for (int u = 0; u < 8; u++) {
          mbar_wait(BAR_HD(w4 * 3 + s), ph);
          tma2d_store(&mOst, buf + s * 16384, col, row0 + u * 128);
          bulk_commit();
          if (u + 3 < 8) {
            asm volatile("cp.async.bulk.wait_group.read 0;" ::: "memory");
            mbar_expect_tx(BAR_TF(w4 * 3 + s), 16384);
            tma2d(buf + s * 16384, &mQst, col, row0 + (u + 3) * 128, BAR_TF(w4 * 3 + s));
          }
          if (++s == 3) { s = 0; ph ^= 1; }
        }
        bulk_wait_all();
        fence_async_all();
        flag_add(FLAG_LM((h * 2 + (w4 & 1)) * 2 + (w4 >> 1)));
        if (w4 == 0) { TS(1, 8); g_epoch[blockIdx.x] = ep; }
      }
      return;
    }
    mbar_wait(BAR_GO, 0);
    {
      uint32_t a[4], b[4];
      float c[4];
      lds4(sWKV + (tid - 512) * 16, a);
      lds4(sWKV + 2048 + (tid - 512) * 16, b);
#pragma unroll
      for (int i = 0; i < 4; i++) c[i] = __uint_as_float(a[i]) + __uint_as_float(b[i]);
      lds4(sWKV + 4096 + (tid - 512) * 16, a);
      lds4(sWKV + 6144 + (tid - 512) * 16, b);
#pragma unroll
      for (int i = 0; i < 4; i++) c[i] += __uint_as_float(a[i]) + __uint_as_float(b[i]);
      sts1(sT + w4 * 256 + lane * 4, pack_bf16(c[0], c[1]));
      sts1(sT + w4 * 256 + 128 + lane * 4, pack_bf16(c[2], c[3]));
    }
    named_bar(9, 128);
    if (w4 == 0 && elect_one()) issue(2, 2, 2);
    auto write_ones = [&]() {
      mbar_wait_long(BAR_VB(1), 0);
      int c = ((w4 & 1) * 32 + lane);
#pragma unroll 4
      for (int key = c; key < S_TOK; key += 64) {
        sts4(sOne + key * 16, c < 24 ? 0x00003F80u : 0x00004E80u, 0u, 0u, 0u);
        c += 64; if (c >= STEPK) c -= STEPK;
      }
      fence_async();
      __syncwarp();
      if (lane == 0) mbar_arrive(BAR_Q);
    };
    if (w4 == 0) {
      int s = 0, ph = 0;
#pragma unroll 1
      for (int kb = 3; kb < 8; kb++) {
        mbar_wait(BAR_EMPTY(s), ph);
        if (elect_one()) {
          mbar_expect_tx(BAR_FULL(s), kb == 7 ? 24576 : 16384);
          tma2d(STAGE(s) + 49152, &mXB, kb * 64, ttB * 128, BAR_FULL(s));
          if (kb == 7) tma2d(STAGE(s) + 16384, &mXA64, kb * 64, tbA * 64, BAR_FULL(s));
        }
        if (++s == 3) { s = 0; ph ^= 1; }
      }
      flag_wait(FLAG_KV, ep * 128);
      fence_async_all();
      if (lane == 0) TS(0, 11);
#pragma unroll 1
      for (int m = 0; m < 2; m++) {
        mbar_wait(m == 0 ? BAR_EMPTY(2) : BAR_EMPTY(0), 1 - m);
        if (elect_one()) {
          const uint32_t fb = m == 0 ? BAR_KV(0) : BAR_VB(0);
          mbar_expect_tx(fb, 2 * 7 * STEPK * 16);
#pragma unroll
          for (int p = 0; p < 2; p++) bulk_g2s(sb + m * OFF_V + p * 32768, g_KV + (m * 2 + p) * S_TOK, 7 * STEPK * 16, fb);
        }
      }
      mbar_wait(BAR_Q, 0);
      if (elect_one()) {
#pragma unroll
        for (int c = 1; c < 3; c++) {
          const int k0 = c == 1 ? 7 * STEPK : 13 * STEPK, k1 = c == 1 ? 13 * STEPK : S_TOK;
          const uint32_t bytes = (k1 - k0) * 16;
          mbar_expect_tx(BAR_KV(c), 4 * bytes);
#pragma unroll
          for (int p = 0; p < 4; p++)
            bulk_g2s(sb + (p >> 1) * OFF_V + (p & 1) * 32768 + k0 * 16, g_KV + p * S_TOK + k0, bytes, BAR_KV(c));
        }
      }
      mbar_wait_long(BAR_CL(1), 0);
      flag_wait(isB ? FLAG_LM((lane & 7) * 2 + (tbA >> 4)) : FLAG_OA(tbA * 4 + (lane & 7), 0), ep);
      __syncwarp();
      fence_async_all();
      if (lane == 0) TS(2, 13);
      const CUtensorMap* mW = isB ? &mWoB : &mWoA;
#pragma unroll 1
      for (int it = 0; it < 8; it++) {
        const int n = (!isB && it >= 6) ? 13 - it : it;
        uint32_t wb = BAR_CL(n < 3 ? 0 : (n == 3 ? 2 : 3));
        if (isB) { if (n >= 5) wb = n == 7 ? BAR_CL(4) : BAR_TE(n - 5); }
        else if (n >= 6) wb = n == 6 ? BAR_CL(4) : BAR_TE(0);
        if (it < 6) mbar_wait_long(wb, 0); else mbar_wait(wb, 0);
        const uint32_t sl = tail_slots(isB, n), fb = BAR_TF(n);
        const bool withX = isB || n < 4;
        const int k0 = isB ? n * 64 : (n < 4 ? n * 128 : ((hg + n) & 3) * 128 + 64);
        if (elect_one()) {
          mbar_expect_tx(fb, withX ? 32768 : 16384);
          if (withX) {
            tma2d(sb + (sl & 255) * 8192, &mO, k0, isB * S_TOK + tok0, fb);
            tma2d(sb + ((sl >> 8) & 255) * 8192, &mO, k0, isB * S_TOK + tok0 + 64, fb);
          }
          tma2d(sb + ((sl >> 16) & 255) * 8192, mW, hg * 128, k0, fb);
          tma2d(sb + (sl >> 24) * 8192, mW, hg * 128 + 64, k0, fb);
        }
      }
      if (lane == 0) g_epoch[blockIdx.x] = ep;
    } else if (w4 == 3) {
      write_ones();
      flag_wait(FLAG_KV, ep * 128);
      const uint4 a = *(const uint4*)(g_stats + lane * 4);
      const float kmax2 = __uint_as_float(__reduce_max_sync(~0u, a.x)) + __uint_as_float(__reduce_max_sync(~0u, a.y));
      const float vmax = __uint_as_float(__reduce_max_sync(~0u, max(a.z, a.w)));
      const float lv = vmax > 0.f ? __log2f(vmax) : 0.f;
      const float lim = fminf(90.f, fminf(91.f + lv, 95.f - lv));
      float thr = -1.f;
      if (vmax < 1e27f && kmax2 <= 65536.f && lim > 2.f) thr = fminf(60000.f, (lim * lim - 1.f) / (kmax2 * 1.02f + 1e-30f));
      mbar_wait_long(BAR_VB(2), 0);
      uint32_t nmax = 0;
#pragma unroll 2
      for (int i = 0; i < 16; i++) {
        uint32_t x[4], y[4];
        const uint32_t ad = sb + OFF_F + i * 1024 + (lane >> 3) * 256 + (lane & 7) * 16;
        lds4(ad, x); lds4(ad + 128, y);
        uint32_t n = hfma2(x[0], x[0], hfma2(x[1], x[1], hfma2(x[2], x[2], hfma2(x[3], x[3], 0u))));
        n = hfma2(y[0], y[0], hfma2(y[1], y[1], hfma2(y[2], y[2], hfma2(y[3], y[3], n))));
        n = hadd2(n, n >> 16);
        nmax = max(nmax, n & 0x7FFFu);
      }
      nmax = __reduce_max_sync(~0u, nmax);
      const bool ok = __half2float(__ushort_as_half((unsigned short)nmax)) <= thr;
      if (lane == 0) { sts1(sM + 16, ok ? 1u : 0u); mbar_arrive(BAR_Q2); }
    } else {
      const int tok = (w4 - 1) * 32 + lane;
      int step, col;
      if ((tbA & 3) == 0) {
        const int b8 = tbA >> 2;
        if (tok < 22) { step = tok; col = 24 + b8; }
        else { const int c = tok >= 43; step = tok - 22 - 21 * c; col = 32 + b8 * 2 + c; }
      } else {
        const int b24 = (tbA >> 2) * 3 + (tbA & 3) - 1;
        if (tok < 42) { const int c = tok >= 21; step = tok - 21 * c; col = 48 + b24 * 2 + c; }
        else { step = tok - 42; col = b24; }
      }
      const int kap = step * STEPK + col;
      const bool chained = col >= 24;
      uint32_t v[4], o[4];
      lds4(sT + tok * 16, v);
      g_KV[(4 + hg) * S_TOK + kap] = make_uint4(v[0], v[1], v[2], v[3]);
      float st = 0.f;
      if (hg < 2) {
        o[0] = o[1] = o[2] = o[3] = 0;
        if (chained && step > 0) lds4(sT + tok * 16 - 16, o);
        const float sc = chained ? 2.f : 1.f;
#pragma unroll
        for (int u = 0; u < 4; u++) {
          const float x = bf_lo(v[u]), y = bf_hi(v[u]);
          st += x * x + y * y;
          o[u] = pack_f16((x - bf_lo(o[u])) * sc, (y - bf_hi(o[u])) * sc);
        }
      } else {
        const float sc = chained ? VSHIFT : 1.f;
#pragma unroll
        for (int u = 0; u < 4; u++) { float x = bf_lo(v[u]), y = bf_hi(v[u]); st += fabsf(x) + fabsf(y); o[u] = pack_bf16(x * sc, y * sc); }
      }
      g_KV[hg * S_TOK + kap] = make_uint4(o[0], o[1], o[2], o[3]);
      const uint32_t um = __reduce_max_sync(~0u, __float_as_uint(st) & 0x7FFFFFFFu);
      if (w4 == 2) {
        if (lane == 0) sts1(sM + 24, um);
        named_arrive(10, 64);
        write_ones();
        if (!isB) {
          mbar_wait_long(BAR_CL(3), 0);
          mbar_wait_long(BAR_RL, 0);
          uint32_t pend = 0xFE;
          const int li = lane & 7;
          const uint32_t* fl = FLAG_OA((tbA + (li & 1)) * 4 + ((hg + (li >> 1)) & 3), 1);
#pragma unroll 1
          for (int it = 0; pend; it++) {
            uint32_t fv;
            asm volatile("ld.acquire.gpu.global.u32 %0, [%1];" : "=r"(fv) : "l"(fl) : "memory");
            uint32_t go = __ballot_sync(~0u, (int32_t)(fv - ep) >= 0 && mbar_test(li >= 6 ? BAR_TE(0) : BAR_CL(4), 0)) & pend;
            pend &= ~go;
            if (go) fence_async_all();
#pragma unroll 1
            while (go) {
              const int b = __ffs(go) - 1;
              go &= go - 1;
              const uint32_t slot = (tail_slots(0, 4 + (b >> 1)) >> (8 * (b & 1))) & 255;
              if (elect_one()) {
                mbar_expect_tx(BAR_TF(8 + b), 8192);
                tma2d(sb + slot * 8192, &mO, ((hg + (b >> 1)) & 3) * 128 + 64, tok0 + (b & 1) * 64, BAR_TF(8 + b));
              }
            }
            if (it > 2000000) __trap();
          }
          if (lane == 0) TS(2, 14);
        }
      }
      else {
        named_bar(10, 64);
        if (elect_one()) {
          g_stats[tbA * 4 + hg] = max(um, lds1(sM + 24));
          fence_async_all();
          flag_add(FLAG_KV);
          TS(1, 9);
          mbar_wait_long(BAR_BDONE, 0);
          tma2d_store(&mQst, sb + OFF_F + 49152, hq * 64, S_TOK + ttB * 128);
          bulk_commit();
          bulk_wait_all();
          fence_async_all();
          flag_add(FLAG_B(hq >> 1));
          TS(0, 12);
          mbar_wait(BAR_Q, 0);
          mbar_arrive(BAR_CL(0));
#pragma unroll 1
          for (int p = 0; p < 2; p++) {
            mbar_wait_long(BAR_OD(p), 0);
            if (p == 0) {
#pragma unroll
              for (int w = 0; w < 4; w++) tma2d_store(&mO16, sb + OFF_F + w * 2048, hg * 128 + w * 16, tbA * 64);
            } else {
              tma2d_store(&mO, sb + 26 * 8192, hg * 128 + 64, tbA * 64);
            }
            bulk_commit();
            bulk_wait_all();
            if (p == 0) mbar_arrive(BAR_CL(1));
            PUBLISH(FLAG_OA(tbA * 4 + hg, p));
          }
          TS(2, 0);
        }
      }
    }
    return;
  }
  if (helper) { helper_cta(blockIdx.x - 128, sb, bars, wg, w4); return; }

  {
    float acc[64];
    if (wg == 0) proj_loop<0>(acc, sb, bars, 16384, 0, wg, sWKV, &mWq, hg * 128, w4 == 0);
    else proj_loop<1>(acc, sb, bars, 16384 + wg * 8192, 49152, wg, sWKV, &mWqkv, (wg - 1) * 512 + hq * 64, w4 == 0);
    if (tid == 0) TS(0, 10);
    const uint32_t sF = sb + OFF_F;
    const uint32_t qa = sF + w4 * 512 + ((lane >> 3) & 1) * 256 + (lane >> 4) * 128 + (lane & 7) * 16;
    if (wg == 0) {
#pragma unroll
      for (int hd = 0; hd < 4; hd++)
        stsm4(qa + hd * 2048, pack_f16(acc[8 * hd] * QSCALE, acc[8 * hd + 1] * QSCALE), pack_f16(acc[8 * hd + 2] * QSCALE, acc[8 * hd + 3] * QSCALE),
              pack_f16(acc[8 * hd + 4] * QSCALE, acc[8 * hd + 5] * QSCALE), pack_f16(acc[8 * hd + 6] * QSCALE, acc[8 * hd + 7] * QSCALE));
      fence_async();
      __syncwarp();
      if (lane == 0) mbar_arrive(BAR_Q);
    } else {
      if (wg != 3) named_arrive(6, 384);
      if (wg != 1) named_arrive(8, 384);
    }
    asm volatile("setmaxnreg.inc.sync.aligned.u32 112;");
    fence_regs<64>(acc);
    if (wg == 0) {
#pragma unroll
      for (int hd = 4; hd < 8; hd++)
        stsm4(qa + hd * 2048, pack_f16(acc[8 * hd] * QSCALE, acc[8 * hd + 1] * QSCALE), pack_f16(acc[8 * hd + 2] * QSCALE, acc[8 * hd + 3] * QSCALE),
              pack_f16(acc[8 * hd + 4] * QSCALE, acc[8 * hd + 5] * QSCALE), pack_f16(acc[8 * hd + 6] * QSCALE, acc[8 * hd + 7] * QSCALE));
      fence_async();
      __syncwarp();
      if (lane == 0) mbar_arrive(BAR_VB(2));
    } else if (wg == 3) {
      named_bar(6, 384);
      const int t = tid & 127;
#pragma unroll
      for (int j = 0; j < 8; j++)
        sts4(sF + 24576 + j * 2048 + t * 16, pack_bf16(acc[8 * j], acc[8 * j + 1]), pack_bf16(acc[8 * j + 2], acc[8 * j + 3]),
             pack_bf16(acc[8 * j + 4], acc[8 * j + 5]), pack_bf16(acc[8 * j + 6], acc[8 * j + 7]));
      named_arrive(7, 256);
    } else {
      if (wg == 1) {
        named_bar(8, 384);
        const int m = lane >> 3, r = lane & 7;
#pragma unroll
        for (int j = 0; j < 16; j += 2) {
          const int tok = (j + (m >> 1)) * 8 + r;
          const int chunk = w4 * 2 + (m & 1);
          stsm4t(sF + 49152 + tok * 128 + ((chunk ^ r) << 4), pack_bf16(acc[4 * j], acc[4 * j + 1]), pack_bf16(acc[4 * j + 2], acc[4 * j + 3]),
                 pack_bf16(acc[4 * j + 4], acc[4 * j + 5]), pack_bf16(acc[4 * j + 6], acc[4 * j + 7]));
        }
        fence_async();
      } else {
        uint32_t p[32];
#pragma unroll
        for (int i = 0; i < 32; i++) p[i] = phi2(acc[2 * i], acc[2 * i + 1]);
        named_bar(7, 256);
        float kv0[4] = {0, 0, 0, 0}, kv1[4] = {0, 0, 0, 0}, z0[4] = {0, 0, 0, 0}, z1[4] = {0, 0, 0, 0};
        const uint32_t one = 0x3F803F80u;
        const int t = tid & 127;
#pragma unroll
        for (int j = 0; j < 8; j++) {
          uint32_t a[4];
          lds4(sF + 24576 + j * 2048 + t * 16, a);
          mma_bf16(kv0, a[0], a[1], a[2], a[3], p[4 * j], p[4 * j + 2]);
          mma_bf16(kv1, a[0], a[1], a[2], a[3], p[4 * j + 1], p[4 * j + 3]);
          mma_bf16(z0, one, one, one, one, p[4 * j], p[4 * j + 2]);
          mma_bf16(z1, one, one, one, one, p[4 * j + 1], p[4 * j + 3]);
        }
        float4* dst = g_kvp + ((ttB * 32 + hq * 4 + w4) * 3) * 32 + lane;
        dst[0] = make_float4(kv0[0], kv0[1], kv1[0], kv1[1]);
        dst[32] = make_float4(kv0[2], kv0[3], kv1[2], kv1[3]);
        dst[64] = make_float4(z0[0], z0[1], z1[0], z1[1]);
      }
      __syncwarp();
      if (lane == 0) mbar_arrive(BAR_BDONE);
    }
  }

  bool safe = true;
  {
    const uint32_t c63 = 0x1F801F80u + (threadIdx.x >> 20);
    const uint32_t m1 = (gridDim.x >> 20) - 1u;
    const uint64_t dK0 = make_desc(sb + OFF_K, 32768, 128, 0);
    const uint64_t dV0 = make_desc(sb + OFF_V, 128, 32768, 0);
    constexpr uint32_t dKV = ((2048u - 8u)  __H0__ ) + STEPK - (OFF_V - OFF_K) / 16;
    float Sm[12], Sp[36], O[12];
    uint32_t P[24];
    uint64_t dQ = make_desc(sb + OFF_F + wg * 2048, 128, 256, 0);
#pragma unroll
    for (int i = 0; i < 36; i++) Sp[i] = SMAGIC;
#pragma unroll
    for (int i = 0; i < 12; i++) Sm[i] = 0.f;
    fence_regs<12>(Sm); fence_regs<36>(Sp);
    mbar_wait(BAR_Q, 0);
    mbar_wait(BAR_KV(0), 0);
    wg_fence();
    wg_qs72<1>(Sp, dQ, dK0 + 24);
    wg_qs24<0>(Sm, dQ, dK0);
    wg_commit();
    wg_wait<0>();
    fence_regs<12>(Sm); fence_regs<36>(Sp);
#pragma unroll 1
    for (int pass = 0; pass < 2; pass++) {
#pragma unroll
      for (int i = 0; i < 12; i++) O[i] = 0.f;
      fence_regs<12>(O);
      if (tid == 0) TSW(1, 2 + 2 * pass);
      uint32_t vlo = (uint32_t)dV0;
#pragma unroll 1
      for (int seg = 0; seg < 4; seg++) {
        if (pass == 0) {
          if (seg < 3) mbar_wait(seg == 0 ? BAR_VB(0) : BAR_KV(seg), 0);
        } else if (seg >= 1) {
          if ((tid & 127) == 0) {
            mbar_arrive(BAR_CL(seg));
            if (seg == 3) take_role(sM, wg);
          }
          __syncwarp();
        }
        if ((tid & 127) == 0) TSW(4 + wg, pass * 5 + seg);
        const uint32_t vend = vlo + (seg == 3 ? 3 : 6) * STEPK;
#pragma unroll 1
        for (; vlo != vend; vlo += 3 * STEPK) {
          uint64_t dK, dV;
          asm("mov.b64 %0, {%1, %2};" : "=l"(dK) : "r"(vlo + dKV), "r"(8u));
          asm("mov.b64 %0, {%1, %2};" : "=l"(dV) : "r"(vlo), "r"(2048u));
#pragma unroll
          for (int u = 0; u < 3; u++) {
          { uint32_t w[18], y[18], z[18]; float e[12];
            X_MU(0) X_PR(0) X_LO(0) X_IM(0) X_MU(1) X_FM(0) X_PR(1) X_LO(1) X_IM(1) X_MU(2) X_FM(1) X_PR(2)
            X_LO(2) X_MU(3) X_IM(2) X_FM(2) X_PR(3) X_LO(3) X_PK(0) X_MU(4) X_IM(3) X_FM(3) X_PR(4) X_LO(4)
            X_MU(5) X_IM(4) X_FM(4) X_PR(5) X_PK(1) X_MU(6) X_LO(5) X_IM(5) X_FM(5) X_PR(6) X_MU(7) X_LO(6)
            X_IM(6) X_FM(6) X_MU(8) X_PR(7) X_PK(2) X_LO(7) X_IM(7) X_FM(7) X_MU(9) X_PR(8) X_LO(8) X_IM(8)
            X_FM(8) X_PK(3) X_MU(10) X_PR(9) X_LO(9) X_IM(9) X_MU(11) X_FM(9) X_PR(10) X_LO(10) X_IM(10) X_PK(4)
            X_FM(10) X_PR(11) X_LO(11) X_IM(11) X_FM(11) X_PR(12) X_LO(12) X_PK(5) X_IM(12) X_FM(12) X_PR(13) X_LO(13)
            X_IM(13) X_FM(13) X_PR(14) X_LO(14) X_IM(14) X_FM(14) X_PR(15) X_LO(15) X_IM(15) X_FM(15) X_PR(16) X_LO(16)
            X_IM(16) X_FM(16) X_PR(17) X_LO(17) X_IM(17) X_FM(17) }
          fence_regs<24>(P);
          wg_fence();
          wg_pv24<1>(O, &P[20], dV + u * STEPK + 80);
          wg_pv24<1>(O, &P[16], dV + u * STEPK + 64);
          wg_pv24<1>(O, &P[12], dV + u * STEPK + 48);
          wg_pv24<1>(O, &P[8], dV + u * STEPK + 32);
          wg_pv24<1>(O, &P[4], dV + u * STEPK + 16);
          wg_pv24<1>(O, &P[0], dV + u * STEPK + 0);
          wg_qs72<1>(Sp, dQ, dK + u * STEPK + 24);
          wg_qs24<0>(Sm, dQ, dK + u * STEPK);
          wg_commit();
          wg_wait<0>();
          fence_regs<12>(Sm); fence_regs<36>(Sp); fence_regs<12>(O); fence_regs<24>(P);
          }
        }
      }
#pragma unroll
      for (int i = 0; i < 6; i++) P[i] = pack_bf16(ex2f(Sm[2 * i]), ex2f(Sm[2 * i + 1]));
      P[6] = exp2_pair_fix(Sp[0], Sp[1], c63, m1);
      P[7] = exp2_pair_fix(Sp[2], Sp[3], c63, m1);
      fence_regs<8>(P);
#pragma unroll
      for (int i = 0; i < 36; i++) Sp[i] = SMAGIC;
      fence_regs<36>(Sp);
      mbar_wait(pass == 0 ? BAR_Q2 : BAR_CL(3), 0);
      const uint32_t sO = pass == 0 ? sb + OFF_F + wg * 2048 + w4 * 512 + (lane & 15) * 32 + (lane >> 4) * 16
                                    : sb + 26 * 8192 + (w4 * 16 + (lane & 15)) * 128 + (((wg * 2 + (lane >> 4)) ^ (lane & 7)) << 4);
      dQ += 512;
      wg_fence();
      wg_pv24<1>(O, &P[0], dV0 + 21 * STEPK);
      wg_pv24<1>(O, &P[4], dV0 + 21 * STEPK + 16);
      wg_commit();
      wg_qs72<1>(Sp, dQ, dK0 + 24);
      wg_qs24<0>(Sm, dQ, dK0);
      wg_commit();
      wg_wait<1>();
      fence_regs<12>(O);
      const float l0 = __shfl_sync(~0u, O[8], lane & ~3), l1 = __shfl_sync(~0u, O[10], lane & ~3);
      const float i0 = rcpf(l0), i1 = rcpf(l1);
      stsm4(sO,
            pack_bf16(O[0] * i0, O[1] * i0), pack_bf16(O[2] * i1, O[3] * i1),
            pack_bf16(O[4] * i0, O[5] * i0), pack_bf16(O[6] * i1, O[7] * i1));
      fence_async();
      {
        safe = __all_sync(~0u, lds1(sM + 16) != 0);
      }
      if (safe && lane == 0) mbar_arrive(BAR_OD(pass));
      wg_wait<0>();
      fence_regs<12>(Sm); fence_regs<36>(Sp);
      if (!safe) break;
      if ((tid & 127) == 0) TSW(4 + wg, pass * 5 + 4);
      if (tid == 0) TSW(1, 3 + 2 * pass);
    }
  }
  if (!safe) {
    if ((tid & 127) == 0) { mbar_arrive(BAR_CL(1)); mbar_arrive(BAR_CL(2)); mbar_arrive(BAR_CL(3)); take_role(sM, wg); }
#pragma unroll 1
    for (int pass = 0; pass < 2; pass++) {
      const int t = tid & 127;
      mbar_wait(BAR_CL(3), 0);
      attn_slow(prm.xa + (size_t)tbA * 64 * D_MOD, prm.wq + (hg * 8 + pass * 4 + wg) * 16,
                pass == 0 ? sb + OFF_F + wg * 2048 + t * 16
                          : sb + 26 * 8192 + (t >> 1) * 128 + (((wg * 2 + (t & 1)) ^ ((t >> 1) & 7)) << 4));
      __syncwarp();
      if (lane == 0) mbar_arrive(BAR_OD(pass));
    }
  }

  {
    named_bar(wg + 1, 128);
    if ((tid & 127) == 0) mbar_arrive(BAR_CL(4));
    const int role = __shfl_sync(~0u, lds1(sM + 32 + wg * 4), 0);
    if ((tid & 127) == 0) TSW(4 + wg, 10);
    const int m = lane >> 3, r = lane & 7;
    const uint32_t stoff = (w4 * 16 + (m & 1) * 8 + r) * 128;
    if (role < 2) {
      if (role == 0 && (tid & 127) == 0) mbar_arrive(BAR_RL);
      if (!isB || role == 1) mbar_wait(BAR_CL(4), 0);
      float acc[64];
#pragma unroll 1
      for (int n = 0; n < 8; n++) {
        const uint32_t sl = tail_slots(isB, n);
        const uint32_t w0 = (sl >> 16) & 255, w1 = sl >> 24;
        const uint64_t da = make_desc(sb + ((sl >> (8 * role)) & 255) * 8192, 16, 1024, 1);
        const uint64_t db = make_desc(sb + w0 * 8192, (w1 - w0) * 8192, 1024, 1);
        mbar_wait(BAR_TF(n), 0);
        if (!isB && n >= 4) mbar_wait(n == 4 && role == 0 ? BAR_OD(1) : BAR_TF(2 * n + role), 0);
        if ((tid & 127) == 0 && role == 1) TSW(2, 2 + n);
        wg_fence();
#pragma unroll
        for (int k = 0; k < 4; k++) wg_ss128<0, 1>(acc, da + k * 2, db + k * 128, (n | k) != 0);
        wg_commit();
        wg_wait<1>();
        if ((n == 1 || n == 2) && (tid & 127) == 0) mbar_arrive(BAR_TE(n - 1));
        __syncwarp();
      }
      wg_wait<0>();
      fence_regs<64>(acc);
      if ((tid & 127) == 0) TSW(4 + wg, 11);
      const uint32_t x0 = sb + (role ? 16 : 8) * 8192, x1 = sb + (role ? 5 : 1) * 8192;
#pragma unroll
      for (int j = 0; j < 16; j += 2)
        stsm4((j < 8 ? x0 : x1) + stoff + ((((j & 7) + (m >> 1)) ^ r) << 4),
              pack_bf16(acc[4 * j], acc[4 * j + 1]), pack_bf16(acc[4 * j + 2], acc[4 * j + 3]),
              pack_bf16(acc[4 * j + 4], acc[4 * j + 5]), pack_bf16(acc[4 * j + 6], acc[4 * j + 7]));
      __syncwarp();
      uint4* dst = (uint4*)(prm.out + (size_t)(tok0 + role * 64 + w4 * 16 + (lane >> 4)) * 1024 + isB * 512 + hg * 128) + (lane & 15);
      const uint32_t src = ((lane & 8) ? x1 : x0) + (w4 * 16 + (lane >> 4)) * 128;
#pragma unroll
      for (int i = 0; i < 8; i++) {
        uint32_t v[4];
        lds4(src + i * 256 + (((lane & 7) ^ ((2 * i + (lane >> 4)) & 7)) << 4), v);
        dst[i * 256] = make_uint4(v[0], v[1], v[2], v[3]);
      }
      if ((tid & 127) == 0) TS(2, 11 + role);
    }
  }
}

typedef CUresult (*EncodeFn)(CUtensorMap*, CUtensorMapDataType, cuuint32_t, void*, const cuuint64_t*, const cuuint64_t*,
                             const cuuint32_t*, const cuuint32_t*, CUtensorMapInterleave, CUtensorMapSwizzle,
                             CUtensorMapL2promotion, CUtensorMapFloatOOBfill);

static void make_map(EncodeFn enc, CUtensorMap* m, const void* ptr, uint64_t cols, uint64_t rows, uint32_t bc, uint32_t br,
                     CUtensorMapSwizzle sw = CU_TENSOR_MAP_SWIZZLE_128B) {
  cuuint64_t dims[2] = {cols, rows};
  cuuint64_t strides[1] = {cols * 2};
  cuuint32_t box[2] = {bc, br};
  cuuint32_t es[2] = {1, 1};
  enc(m, CU_TENSOR_MAP_DATA_TYPE_BFLOAT16, 2, (void*)ptr, dims, strides, box, es, CU_TENSOR_MAP_INTERLEAVE_NONE,
      sw, CU_TENSOR_MAP_L2_PROMOTION_L2_256B, CU_TENSOR_MAP_FLOAT_OOB_FILL_NONE);
}

extern "C" void kernel_launch(void* const* d_in, const int* in_sizes, int n_in, void* d_out, int out_size) {
  (void)in_sizes; (void)n_in; (void)out_size;
  static EncodeFn enc = nullptr;
  static void* pQ = nullptr; static void* pO = nullptr;
  if (!enc) {
    void* fn = nullptr; cudaDriverEntryPointQueryResult qr;
    cudaGetDriverEntryPoint("cuTensorMapEncodeTiled", &fn, cudaEnableDefault, &qr);
    enc = (EncodeFn)fn;
    cudaGetSymbolAddress(&pQ, g_Q);
    cudaGetSymbolAddress(&pO, g_O);
    cudaFuncSetAttribute(k1_main, cudaFuncAttributeMaxDynamicSharedMemorySize, SM_TOTAL);
  }
  CUtensorMap mXA64, mXB, mWq, mWqkv, mQst, mO, mOst, mWoA, mWoB, mO16;
  make_map(enc, &mXA64, d_in[0], 512, 2048, 64, 64);
  make_map(enc, &mWq, d_in[1], 512, 512, 64, 64);
  make_map(enc, &mWoA, d_in[4], 512, 512, 64, 64);
  make_map(enc, &mXB, d_in[5], 512, 2048, 64, 128);
  make_map(enc, &mWqkv, d_in[6], 1536, 512, 64, 64);
  make_map(enc, &mWoB, d_in[7], 512, 512, 64, 64);
  make_map(enc, &mQst, pQ, 512, 4096, 64, 128);
  make_map(enc, &mO, pO, 512, 4096, 64, 64);
  make_map(enc, &mOst, pO, 512, 4096, 64, 128);
  make_map(enc, &mO16, pO, 512, 4096, 16, 64, CU_TENSOR_MAP_SWIZZLE_NONE);
  Params prm{(const __nv_bfloat16*)d_in[2], (const __nv_bfloat16*)d_in[3], (const __nv_bfloat16*)d_in[0], (const __nv_bfloat16*)d_in[1], (__nv_bfloat16*)d_out};
  k1_main<<<132, 640, SM_TOTAL, cudaStreamPerThread>>>(mXA64, mXB, mWq, mWqkv, mQst, mOst, mO, mWoA, mWoB, mO16, prm);
}
```

```cpp
#include <cuda_runtime.h>
#include <cuda_bf16.h>
#include <cuda_fp16.h>
#include <cuda.h>
#include <stdint.h>

#define S_TOK 2048
#define D_MOD 512

__device__ __align__(1024) __nv_bfloat16 g_Q[2 * S_TOK * D_MOD];
__device__ __align__(1024) __nv_bfloat16 g_O[2 * S_TOK * D_MOD];
__device__ __align__(1024) uint4 g_KV[8 * S_TOK];
__device__ __align__(16) uint32_t g_stats[128];
__device__ __align__(16) float4 g_kvp[16 * 32 * 3 * 32];

__device__ __forceinline__ uint32_t smem_u32(const void* p) { return (uint32_t)__cvta_generic_to_shared(p); }
__device__ __forceinline__ void mbar_init(uint32_t bar, int cnt) { asm volatile("mbarrier.init.shared::cta.b64 [%0], %1;" :: "r"(bar), "r"(cnt) : "memory"); }
__device__ __forceinline__ void mbar_expect_tx(uint32_t bar, uint32_t bytes) { asm volatile("mbarrier.arrive.expect_tx.shared::cta.b64 _, [%0], %1;" :: "r"(bar), "r"(bytes) : "memory"); }
__device__ __forceinline__ void mbar_wait(uint32_t bar, uint32_t parity) {
  asm volatile("{\n.reg .pred p;\n.reg .u32 c;\nmov.u32 c, 0;\n"
               "LW_%=:\n"
               "mbarrier.try_wait.parity.shared::cta.b64 p, [%0], %1;\n"
               "@p bra LD_%=;\n"
               "add.u32 c, c, 1;\n"
               "setp.lt.u32 p, c, 4000000;\n"
               "@p bra LW_%=;\n"
               "trap;\n"
               "LD_%=:\n}\n" :: "r"(bar), "r"(parity) : "memory");
}
__device__ __forceinline__ void tma2d(uint32_t dst, const CUtensorMap* m, int c0, int c1, uint32_t bar) {
  asm volatile("cp.async.bulk.tensor.2d.shared::cluster.global.mbarrier::complete_tx::bytes [%0], [%1, {%3, %4}], [%2];"
               :: "r"(dst), "l"(m), "r"(bar), "r"(c0), "r"(c1) : "memory");
}
__device__ __forceinline__ void tma2d_store(const CUtensorMap* m, uint32_t src, int c0, int c1) {
  asm volatile("cp.async.bulk.tensor.2d.global.shared::cta.bulk_group [%0, {%2, %3}], [%1];"
               :: "l"(m), "r"(src), "r"(c0), "r"(c1) : "memory");
}
__device__ __forceinline__ void tma3d_store(const CUtensorMap* m, uint32_t src, int c0, int c1, int c2) {
  asm volatile("cp.async.bulk.tensor.3d.global.shared::cta.bulk_group [%0, {%2, %3, %4}], [%1];"
               :: "l"(m), "r"(src), "r"(c0), "r"(c1), "r"(c2) : "memory");
}
__device__ __forceinline__ void bulk_g2s(uint32_t dst, const void* src, uint32_t bytes, uint32_t bar) {
  asm volatile("cp.async.bulk.shared::cluster.global.mbarrier::complete_tx::bytes [%0], [%1], %2, [%3];"
               :: "r"(dst), "l"(src), "r"(bytes), "r"(bar) : "memory");
}
__device__ __forceinline__ void bulk_commit() { asm volatile("cp.async.bulk.commit_group;" ::: "memory"); }
__device__ __forceinline__ void bulk_wait_all() { asm volatile("cp.async.bulk.wait_group 0;" ::: "memory"); }
__device__ __forceinline__ void fence_async() { asm volatile("fence.proxy.async.shared::cta;" ::: "memory"); }
__device__ __forceinline__ void named_bar(int id, int n) { asm volatile("bar.sync %0, %1;" :: "r"(id), "r"(n) : "memory"); }
__device__ __forceinline__ void wg_fence() { asm volatile("wgmma.fence.sync.aligned;" ::: "memory"); }
__device__ __forceinline__ void wg_commit() { asm volatile("wgmma.commit_group.sync.aligned;" ::: "memory"); }
template <int n> __device__ __forceinline__ void wg_wait() { asm volatile("wgmma.wait_group.sync.aligned %0;" :: "n"(n) : "memory"); }
template <int n> __device__ __forceinline__ void fence_regs(float* r) {
#pragma unroll
  for (int i = 0; i < n; i++) asm volatile("" : "+f"(r[i]) :: "memory");
}
template <int n> __device__ __forceinline__ void fence_regs(uint32_t* r) {
#pragma unroll
  for (int i = 0; i < n; i++) asm volatile("" : "+r"(r[i]) :: "memory");
}
__device__ __forceinline__ uint64_t make_desc(uint32_t addr, uint32_t lbo, uint32_t sbo, uint32_t swz) {
  return (uint64_t)((addr & 0x3FFFF) >> 4) | ((uint64_t)(lbo >> 4) << 16) | ((uint64_t)(sbo >> 4) << 32) | ((uint64_t)swz << 62);
}
__device__ __forceinline__ float ex2f(float x) { float y; asm("ex2.approx.ftz.f32 %0, %1;" : "=f"(y) : "f"(x)); return y; }
__device__ __forceinline__ uint32_t pack_bf16(float lo, float hi) { uint32_t r; asm("cvt.rn.bf16x2.f32 %0, %1, %2;" : "=r"(r) : "f"(hi), "f"(lo)); return r; }
__device__ __forceinline__ uint32_t pack_f16(float lo, float hi) { uint32_t r; asm("cvt.rn.f16x2.f32 %0, %1, %2;" : "=r"(r) : "f"(hi), "f"(lo)); return r; }
__device__ __forceinline__ float bf_lo(uint32_t v) { return __uint_as_float(v << 16); }
__device__ __forceinline__ float bf_hi(uint32_t v) { return __uint_as_float(v & 0xFFFF0000u); }
__device__ __forceinline__ float rbf(float x) { return __bfloat162float(__float2bfloat16_rn(x)); }
__device__ __forceinline__ void stsm4(uint32_t a, uint32_t r0, uint32_t r1, uint32_t r2, uint32_t r3) {
  asm volatile("stmatrix.sync.aligned.m8n8.x4.shared.b16 [%0], {%1,%2,%3,%4};" :: "r"(a), "r"(r0), "r"(r1), "r"(r2), "r"(r3) : "memory");
}
__device__ __forceinline__ void stsm4t(uint32_t a, uint32_t r0, uint32_t r1, uint32_t r2, uint32_t r3) {
  asm volatile("stmatrix.sync.aligned.m8n8.x4.trans.shared.b16 [%0], {%1,%2,%3,%4};" :: "r"(a), "r"(r0), "r"(r1), "r"(r2), "r"(r3) : "memory");
}
__device__ __forceinline__ void mma_bf16(float* d, uint32_t a0, uint32_t a1, uint32_t a2, uint32_t a3, uint32_t b0, uint32_t b1) {
  asm volatile("mma.sync.aligned.m16n8k16.row.col.f32.bf16.bf16.f32 {%0,%1,%2,%3}, {%4,%5,%6,%7}, {%8,%9}, {%0,%1,%2,%3};"
               : "+f"(d[0]), "+f"(d[1]), "+f"(d[2]), "+f"(d[3]) : "r"(a0), "r"(a1), "r"(a2), "r"(a3), "r"(b0), "r"(b1));
}
template<int SD> __device__ __forceinline__ void wg_qs24(float* d, uint64_t da, uint64_t db) {
  asm volatile("wgmma.mma_async.sync.aligned.m64n24k16.f32.f16.f16 {%0,%1,%2,%3,%4,%5,%6,%7,%8,%9,%10,%11}, %12, %13, %14, 1, 1, 0, 0;"
   : "+f"(d[0]),"+f"(d[1]),"+f"(d[2]),"+f"(d[3]),"+f"(d[4]),"+f"(d[5]),"+f"(d[6]),"+f"(d[7]),"+f"(d[8]),"+f"(d[9]),"+f"(d[10]),"+f"(d[11])
   : "l"(da),"l"(db),"n"(SD));
}
template<int SD> __device__ __forceinline__ void wg_qs72(float* d, uint64_t da, uint64_t db) {
  asm volatile("wgmma.mma_async.sync.aligned.m64n72k16.f32.f16.f16 {%0,%1,%2,%3,%4,%5,%6,%7,%8,%9,%10,%11,%12,%13,%14,%15,%16,%17,%18,%19,%20,%21,%22,%23,%24,%25,%26,%27,%28,%29,%30,%31,%32,%33,%34,%35}, %36, %37, %38, 1, 1, 0, 0;"
   : "+f"(d[0]),"+f"(d[1]),"+f"(d[2]),"+f"(d[3]),"+f"(d[4]),"+f"(d[5]),"+f"(d[6]),"+f"(d[7]),"+f"(d[8]),"+f"(d[9]),"+f"(d[10]),"+f"(d[11]),"+f"(d[12]),"+f"(d[13]),"+f"(d[14]),"+f"(d[15]),"+f"(d[16]),"+f"(d[17]),"+f"(d[18]),"+f"(d[19]),"+f"(d[20]),"+f"(d[21]),"+f"(d[22]),"+f"(d[23]),"+f"(d[24]),"+f"(d[25]),"+f"(d[26]),"+f"(d[27]),"+f"(d[28]),"+f"(d[29]),"+f"(d[30]),"+f"(d[31]),"+f"(d[32]),"+f"(d[33]),"+f"(d[34]),"+f"(d[35])
   : "l"(da),"l"(db),"n"(SD));
}
template<int SD> __device__ __forceinline__ void wg_pv24(float* d, const uint32_t* a, uint64_t desc) {
  asm volatile("wgmma.mma_async.sync.aligned.m64n24k16.f32.bf16.bf16 {%0,%1,%2,%3,%4,%5,%6,%7,%8,%9,%10,%11}, {%12,%13,%14,%15}, %16, %17, 1, 1, 1;"
   : "+f"(d[0]),"+f"(d[1]),"+f"(d[2]),"+f"(d[3]),"+f"(d[4]),"+f"(d[5]),"+f"(d[6]),"+f"(d[7]),"+f"(d[8]),"+f"(d[9]),"+f"(d[10]),"+f"(d[11])
   : "r"(a[0]),"r"(a[1]),"r"(a[2]),"r"(a[3]),"l"(desc),"n"(SD));
}
template<int TA, int TB> __device__ __forceinline__ void wg_ss128(float* d, uint64_t da, uint64_t db, int sd) {
  asm volatile("{\n.reg .pred p;\nsetp.ne.b32 p, %66, 0;\n"
   "wgmma.mma_async.sync.aligned.m64n128k16.f32.bf16.bf16 {%0,%1,%2,%3,%4,%5,%6,%7,%8,%9,%10,%11,%12,%13,%14,%15,%16,%17,%18,%19,%20,%21,%22,%23,%24,%25,%26,%27,%28,%29,%30,%31,%32,%33,%34,%35,%36,%37,%38,%39,%40,%41,%42,%43,%44,%45,%46,%47,%48,%49,%50,%51,%52,%53,%54,%55,%56,%57,%58,%59,%60,%61,%62,%63}, %64, %65, p, 1, 1, %67, %68;\n}\n"
   : "+f"(d[0]),"+f"(d[1]),"+f"(d[2]),"+f"(d[3]),"+f"(d[4]),"+f"(d[5]),"+f"(d[6]),"+f"(d[7]),"+f"(d[8]),"+f"(d[9]),"+f"(d[10]),"+f"(d[11]),"+f"(d[12]),"+f"(d[13]),"+f"(d[14]),"+f"(d[15]),"+f"(d[16]),"+f"(d[17]),"+f"(d[18]),"+f"(d[19]),"+f"(d[20]),"+f"(d[21]),"+f"(d[22]),"+f"(d[23]),"+f"(d[24]),"+f"(d[25]),"+f"(d[26]),"+f"(d[27]),"+f"(d[28]),"+f"(d[29]),"+f"(d[30]),"+f"(d[31]),"+f"(d[32]),"+f"(d[33]),"+f"(d[34]),"+f"(d[35]),"+f"(d[36]),"+f"(d[37]),"+f"(d[38]),"+f"(d[39]),"+f"(d[40]),"+f"(d[41]),"+f"(d[42]),"+f"(d[43]),"+f"(d[44]),"+f"(d[45]),"+f"(d[46]),"+f"(d[47]),"+f"(d[48]),"+f"(d[49]),"+f"(d[50]),"+f"(d[51]),"+f"(d[52]),"+f"(d[53]),"+f"(d[54]),"+f"(d[55]),"+f"(d[56]),"+f"(d[57]),"+f"(d[58]),"+f"(d[59]),"+f"(d[60]),"+f"(d[61]),"+f"(d[62]),"+f"(d[63])
   : "l"(da),"l"(db),"r"(sd),"n"(TA),"n"(TB));
}
template<int TA, int TB> __device__ __forceinline__ void wg_ss8(float* d, uint64_t da, uint64_t db, int sd) {
  asm volatile("{\n.reg .pred p;\nsetp.ne.b32 p, %6, 0;\n"
   "wgmma.mma_async.sync.aligned.m64n8k16.f32.bf16.bf16 {%0,%1,%2,%3}, %4, %5, p, 1, 1, %7, %8;\n}\n"
   : "+f"(d[0]),"+f"(d[1]),"+f"(d[2]),"+f"(d[3])
   : "l"(da),"l"(db),"r"(sd),"n"(TA),"n"(TB));
}


__device__ __forceinline__ uint32_t phi2(float a, float b) {
  uint32_t r, e;
  asm("cvt.rn.relu.bf16x2.f32 %0, %1, %2;" : "=r"(r) : "f"(b), "f"(a));
  e = pack_bf16(ex2f(a * 1.4426950408889634f), ex2f(b * 1.4426950408889634f));
  asm("add.rn.bf16x2 %0, %0, %1;" : "+r"(e) : "r"(0x35863586u));
  asm("min.NaN.bf16x2 %0, %0, %1;" : "+r"(e) : "r"(0x3F803F80u));
  asm("add.rn.bf16x2 %0, %0, %1;" : "+r"(e) : "r"(r));
  return e;
}

__device__ __forceinline__ void mbar_wait_long(uint32_t bar, uint32_t parity) {
  asm volatile("{\n.reg .pred p;\n.reg .u32 c;\nmov.u32 c, 0;\n"
               "LW_%=:\n"
               "mbarrier.try_wait.parity.shared::cta.b64 p, [%0], %1, 10000;\n"
               "@p bra LD_%=;\n"
               "add.u32 c, c, 1;\n"
               "setp.lt.u32 p, c, 400000;\n"
               "@p bra LW_%=;\n"
               "trap;\n"
               "LD_%=:\n}\n" :: "r"(bar), "r"(parity) : "memory");
}
__device__ __forceinline__ void mbar_arrive(uint32_t bar) { asm volatile("mbarrier.arrive.shared::cta.b64 _, [%0];" :: "r"(bar) : "memory"); }
__device__ __forceinline__ void named_arrive(int id, int n) { asm volatile("bar.arrive %0, %1;" :: "r"(id), "r"(n) : "memory"); }
__device__ __forceinline__ void fence_async_all() { asm volatile("fence.proxy.async.global;" ::: "memory"); }
__device__ __forceinline__ void flag_add(uint32_t* f) { asm volatile("fence.acq_rel.gpu;\nred.relaxed.gpu.global.add.u32 [%0], 1;" :: "l"(f) : "memory"); }
#define PUBLISH(f) asm volatile("fence.proxy.async.global;\nred.relaxed.gpu.global.add.u32 [%0], 1;" :: "l"(f) : "memory")
__device__ __forceinline__ void flag_wait(const uint32_t* f, uint32_t target) {
  uint32_t v;
#pragma unroll 1
  for (int it = 0;; it++) {
    asm volatile("ld.acquire.gpu.global.u32 %0, [%1];" : "=r"(v) : "l"(f) : "memory");
    if ((int32_t)(v - target) >= 0) break;
    if (it > 2000000) __trap();
    __nanosleep(64);
  }
}
__device__ __forceinline__ bool mbar_test(uint32_t bar, uint32_t parity) {
  uint32_t ok;
  asm volatile("{\n.reg .pred p;\nmbarrier.test_wait.parity.shared::cta.b64 p, [%1], %2;\nselp.b32 %0, 1, 0, p;\n}\n" : "=r"(ok) : "r"(bar), "r"(parity) : "memory");
  return ok;
}
__device__ __forceinline__ bool elect_one() {
  uint32_t p;
  asm volatile("{\n.reg .pred P;\nelect.sync _|P, 0xFFFFFFFF;\nselp.b32 %0, 1, 0, P;\n}\n" : "=r"(p));
  return p;
}
__device__ __forceinline__ void lds4(uint32_t a, uint32_t* r) {
  asm volatile("ld.shared.v4.b32 {%0,%1,%2,%3}, [%4];" : "=r"(r[0]), "=r"(r[1]), "=r"(r[2]), "=r"(r[3]) : "r"(a) : "memory");
}
__device__ __forceinline__ uint32_t lds1(uint32_t a) { uint32_t r; asm volatile("ld.shared.b32 %0, [%1];" : "=r"(r) : "r"(a) : "memory"); return r; }
__device__ __forceinline__ void sts1(uint32_t a, uint32_t v) { asm volatile("st.shared.b32 [%0], %1;" :: "r"(a), "r"(v) : "memory"); }
__device__ __forceinline__ void sts4(uint32_t a, uint32_t r0, uint32_t r1, uint32_t r2, uint32_t r3) {
  asm volatile("st.shared.v4.b32 [%0], {%1,%2,%3,%4};" :: "r"(a), "r"(r0), "r"(r1), "r"(r2), "r"(r3) : "memory");
}
__device__ __forceinline__ void ldsm4(uint32_t a, uint32_t* r) {
  asm volatile("ldmatrix.sync.aligned.m8n8.x4.shared.b16 {%0,%1,%2,%3}, [%4];" : "=r"(r[0]), "=r"(r[1]), "=r"(r[2]), "=r"(r[3]) : "r"(a) : "memory");
}
__device__ __forceinline__ float rcpf(float x) { float y; asm("rcp.approx.ftz.f32 %0, %1;" : "=f"(y) : "f"(x)); return y; }
__device__ __forceinline__ uint32_t hfma2(uint32_t a, uint32_t b, uint32_t c) { uint32_t r; asm("fma.rn.f16x2 %0, %1, %2, %3;" : "=r"(r) : "r"(a), "r"(b), "r"(c)); return r; }
__device__ __forceinline__ uint32_t hadd2(uint32_t a, uint32_t b) { uint32_t r; asm("add.rn.f16x2 %0, %1, %2;" : "=r"(r) : "r"(a), "r"(b)); return r; }

#define STEPK 96
#define GIMAP(i) ((((i) & 1) << 2) | (((i) >> 1) & 3) | ((i) & 8))
#define QSCALE 0.36067376022224085f
#define SMAGIC (512.0f + 2.0f * (191.0f - 30.0f - 1.5823545f))
#define VSHIFT 1073741824.0f

__device__ uint32_t g_epoch[132];
__device__ uint32_t g_flag[288 * 8];
#define FLAG_KV (g_flag)
#define FLAG_KV2 (g_flag + 8 * 8)
#define FLAG_B(h) (g_flag + (4 + (h)) * 8)
#define FLAG_OA(cta, pass) (g_flag + (16 + (cta) * 2 + (pass)) * 8)
#define FLAG_LM(i) (g_flag + (272 + (i)) * 8)

#define SM_TOTAL (224 * 1024 + 2048 + 1024)
#define OFF_K 0
#define OFF_F 65536
#define OFF_V 131072
#define OFF_MISC (224 * 1024)

#define BAR_FULL(s) (bars + 8 * (s))
#define BAR_FW(s, w) (bars + 408 + 8 * ((s) * 4 + (w)))
#define BAR_EMPTY(s) (bars + 24 + 8 * (s))
#define BAR_KV(c) (bars + 48 + 8 * (c))
#define BAR_E0(i) (bars + 200 + 8 * (i))
#define BAR_IMG (bars + 72)
#define BAR_BDONE (bars + 80)
#define BAR_Q (bars + 88)
#define BAR_GO (bars + 96)
#define BAR_Q2 (bars + 104)
#define BAR_OD(p) (bars + 112 + 8 * (p))
#define BAR_CL(c) (bars + 128 + 8 * (c))
#define BAR_TE(i) (bars + 168 + 8 * (i))
#define BAR_RL (bars + 184)
#define BAR_TF(g) (bars + 224 + 8 * (g))
#define BAR_XA(w) (bars + 352 + 8 * (w))
#define BAR_VB(c) (bars + 384 + 8 * (c))

__device__ __forceinline__ uint32_t exp2_pair_fix(float d0, float d1, uint32_t c63, uint32_t m1) {
  uint32_t w, y, s, r;
  asm("prmt.b32 %0, %1, %2, 0x6521;" : "=r"(w) : "r"(__float_as_uint(d0)), "r"(__float_as_uint(d1)));
  asm("lop3.b32 %0, %1, 0x007F007F, %2, 0xEA;" : "=r"(y) : "r"(w), "r"(c63));
  asm("mad.lo.u32 %0, %1, %2, %3;" : "=r"(s) : "r"(y), "r"(m1), "r"(w));
  asm("fma.rn.bf16x2 %0, %1, %2, %3;" : "=r"(r) : "r"(w), "r"(y), "r"(s));
  return r;
}

#define X_PR(i) asm volatile("prmt.b32 %0, %1, %2, 0x6521;" : "=r"(w[i]) : "r"(__float_as_uint(Sp[2 * (i)])), "r"(__float_as_uint(Sp[2 * (i) + 1])));
#define X_LO(i) asm volatile("lop3.b32 %0, %1, 0x007F007F, %2, 0xEA;" : "=r"(y[i]) : "r"(w[i]), "r"(c63));
#define X_IM(i) asm volatile("mad.lo.u32 %0, %1, %2, %3;" : "=r"(z[i]) : "r"(y[i]), "r"(m1), "r"(w[i]));
#define X_FM(i) asm volatile("fma.rn.bf16x2 %0, %1, %2, %3;" : "=r"(P[6 + (i)]) : "r"(w[i]), "r"(y[i]), "r"(z[i]));
#define X_MU(i) asm volatile("ex2.approx.ftz.f32 %0, %1;" : "=f"(e[i]) : "f"(Sm[i]));
#define X_PK(i) asm volatile("cvt.rn.bf16x2.f32 %0, %1, %2;" : "=r"(P[i]) : "f"(e[2 * (i) + 1]), "f"(e[2 * (i)]));

__device__ __forceinline__ void attn_slow(const __nv_bfloat16* xa, const __nv_bfloat16* wq, uint32_t dst) {
  const int t = threadIdx.x & 127;
  const int row = t >> 1, half = t & 1;
  float q[16];
  {
    float a[8];
#pragma unroll
    for (int i = 0; i < 8; i++) a[i] = 0.f;
#pragma unroll 1
    for (int k = 0; k < D_MOD; k++) {
      const float x = __bfloat162float(xa[(size_t)row * D_MOD + k]);
      const uint4 w = *(const uint4*)(wq + (size_t)k * D_MOD + half * 8);
      const uint32_t ww[4] = {w.x, w.y, w.z, w.w};
#pragma unroll
      for (int i = 0; i < 4; i++) { a[2 * i] = fmaf(x, bf_lo(ww[i]), a[2 * i]); a[2 * i + 1] = fmaf(x, bf_hi(ww[i]), a[2 * i + 1]); }
    }
#pragma unroll
    for (int i = 0; i < 8; i++) {
      const float mine = rbf(a[i]), other = __shfl_xor_sync(~0u, mine, 1);
      q[i] = half ? other : mine; q[8 + i] = half ? mine : other;
    }
  }
  float m = -INFINITY, l = 0.f, o[16];
#pragma unroll
  for (int i = 0; i < 16; i++) o[i] = 0.f;
#pragma unroll 1
  for (int j = half * 1024; j < half * 1024 + 1024; j++) {
    uint4 ka = g_KV[4 * S_TOK + j], kb = g_KV[5 * S_TOK + j];
    uint4 va = g_KV[6 * S_TOK + j], vb = g_KV[7 * S_TOK + j];
    uint32_t kk[8] = {ka.x, ka.y, ka.z, ka.w, kb.x, kb.y, kb.z, kb.w};
    uint32_t vv[8] = {va.x, va.y, va.z, va.w, vb.x, vb.y, vb.z, vb.w};
    float s = 0.f;
#pragma unroll
    for (int i = 0; i < 8; i++) { s = fmaf(q[2 * i], bf_lo(kk[i]), s); s = fmaf(q[2 * i + 1], bf_hi(kk[i]), s); }
    s = rbf(s) * 0.25f;
    if (s > m) {
      float c = __expf(m - s);
      l *= c;
#pragma unroll
      for (int i = 0; i < 16; i++) o[i] *= c;
      m = s;
    }
    float p = __expf(s - m);
    l += p;
#pragma unroll
    for (int i = 0; i < 8; i++) { o[2 * i] = fmaf(p, bf_lo(vv[i]), o[2 * i]); o[2 * i + 1] = fmaf(p, bf_hi(vv[i]), o[2 * i + 1]); }
  }
  float m2 = __shfl_xor_sync(~0u, m, 1);
  float mm = fmaxf(m, m2);
  float c = __expf(m - mm);
  l *= c; l += __shfl_xor_sync(~0u, l, 1);
  float inv = 1.f / l;
  uint32_t r[8];
#pragma unroll
  for (int i = 0; i < 16; i++) { o[i] *= c; o[i] += __shfl_xor_sync(~0u, o[i], 1); o[i] *= inv; }
#pragma unroll
  for (int i = 0; i < 8; i++) r[i] = pack_bf16(o[2 * i], o[2 * i + 1]);
  if (half == 0) sts4(dst, r[0], r[1], r[2], r[3]); else sts4(dst, r[4], r[5], r[6], r[7]);
  fence_async();
}

struct Params { const __nv_bfloat16* wk; const __nv_bfloat16* wv; const __nv_bfloat16* xa; const __nv_bfloat16* wq; __nv_bfloat16* out; };

__device__ __forceinline__ void helper_cta(const int h, const uint32_t sb, const uint32_t bars, const int wg, const int w4,
                                           const CUtensorMap* mQ, const CUtensorMap* mOs) {
  const int lane = threadIdx.x & 31;
  mbar_wait(BAR_GO, 0);
  const int cb = wg & 1, col = h * 128 + cb * 64, row0 = S_TOK + (wg >> 1) * 1024;
  const uint32_t buf = sb + wg * 49152;
  if (w4 == 0 && elect_one()) {
    fence_async_all();
#pragma unroll 1
    for (int u = 0; u < 3; u++) {
      mbar_expect_tx(BAR_TF(wg * 3 + u), 16384);
      tma2d(buf + u * 16384, mQ, col, row0 + u * 128, BAR_TF(wg * 3 + u));
    }
  }
  const int head = h * 8 + cb * 4 + w4;
  float4 a0 = make_float4(0, 0, 0, 0), a1 = a0, a2 = a0;
#pragma unroll 8
  for (int tt = 0; tt < 16; tt++) {
    const float4* src = g_kvp + ((tt * 32 + head) * 3) * 32 + lane;
    float4 u = src[0], v = src[32], w = src[64];
    a0.x += u.x; a0.y += u.y; a0.z += u.z; a0.w += u.w;
    a1.x += v.x; a1.y += v.y; a1.z += v.z; a1.w += v.w;
    a2.x += w.x; a2.y += w.y; a2.z += w.z; a2.w += w.w;
  }
  const uint32_t b00 = pack_bf16(a0.x, a0.y), b01 = pack_bf16(a0.z, a0.w);
  const uint32_t b10 = pack_bf16(a1.x, a1.y), b11 = pack_bf16(a1.z, a1.w);
  const uint32_t bz0 = pack_bf16(a2.x, a2.y), bz1 = pack_bf16(a2.z, a2.w);
  const int m = lane >> 3, r = lane & 7;
  const uint32_t off = ((m & 1) * 8 + r) * 128 + (((w4 * 2 + (m >> 1)) ^ r) << 4);
  int s = 0, ph = 0;
#pragma unroll 1
  for (int u = 0; u < 8; u++) {
    const uint32_t bb = buf + s * 16384;
    mbar_wait(BAR_TF(wg * 3 + s), ph);
#pragma unroll
    for (int mt = 0; mt < 8; mt++) {
      uint32_t a[4];
      ldsm4(bb + mt * 2048 + off, a);
      float n0[4] = {0, 0, 0, 0}, n1[4] = {0, 0, 0, 0}, dn[4] = {0, 0, 0, 0};
      mma_bf16(dn, a[0], a[1], a[2], a[3], bz0, bz1);
      mma_bf16(n0, a[0], a[1], a[2], a[3], b00, b01);
      mma_bf16(n1, a[0], a[1], a[2], a[3], b10, b11);
      const float i0 = rcpf(dn[0] + 1e-6f), i1 = rcpf(dn[2] + 1e-6f);
      stsm4(bb + mt * 2048 + off, pack_bf16(n0[0] * i0, n0[1] * i0), pack_bf16(n0[2] * i1, n0[3] * i1),
            pack_bf16(n1[0] * i0, n1[1] * i0), pack_bf16(n1[2] * i1, n1[3] * i1));
    }
    fence_async();
    named_bar(wg + 1, 128);
    if (w4 == 0 && lane == 0) {
      tma2d_store(mOs, bb, col, row0 + u * 128);
      bulk_commit();
      if (u >= 1 && u + 2 < 8) {
        asm volatile("cp.async.bulk.wait_group.read 1;" ::: "memory");
        const int sp = s == 0 ? 2 : s - 1;
        mbar_expect_tx(BAR_TF(wg * 3 + sp), 16384);
        tma2d(buf + sp * 16384, mQ, col, row0 + (u + 2) * 128, BAR_TF(wg * 3 + sp));
      }
    }
    __syncwarp();
    if (++s == 3) { s = 0; ph ^= 1; }
  }
  if (w4 == 0 && lane == 0) {
    bulk_wait_all();
    fence_async_all();
    flag_add(FLAG_LM((h * 2 + cb) * 2 + (wg >> 1)));
  }
}

#define STAGE(s) (sb + (2 - (s)) * 65536)
__device__ __forceinline__ uint32_t xa_addr(uint32_t sb, int kb) {
  return sb + (kb >= 1 && kb <= 4 ? OFF_V + 65536 + (kb - 1) * 8192 : 16384 + (kb == 5 ? OFF_K : (kb == 6 ? OFF_V : OFF_F)));
}
#define XA7_TMP (sb + OFF_K + 8192)
#define WKV_TMP (sb + OFF_K)
template <int TR> __device__ __forceinline__ void proj_kb(float* acc, uint32_t aA, uint32_t aB, int first) {
  const uint64_t da = make_desc(aA, TR ? 8192 : 16, 1024, 1);
  const uint64_t db = make_desc(aB, TR ? 16 : 8192, 1024, 1);
  wg_fence();
#pragma unroll
  for (int k = 0; k < 4; k++) wg_ss128<TR, 1 - TR>(acc, da + k * (TR ? 128 : 2), db + k * (TR ? 2 : 128), k != 0 || !first);
  wg_commit();
}
template <int TR> __device__ __forceinline__ void proj_loop(float* acc, uint32_t sb, uint32_t bars, uint32_t offA, uint32_t offB,
                                                            int wg, uint32_t sWKV, const CUtensorMap* mW, int col, bool w0, const CUtensorMap* mX, int xrow) {
  int s = 0, ph = 0;
#pragma unroll 1
  for (int kb = 0; kb < 8; kb++) {
    if (kb == 2 * TR)
  {
    float kv[4];
    mbar_wait(BAR_XA(wg), 0);
    const uint64_t da0 = make_desc(xa_addr(sb, 2 * wg), 16, 1024, 1);
    const uint64_t da1 = make_desc(wg == 3 ? XA7_TMP : xa_addr(sb, 2 * wg + 1), 16, 1024, 1);
    const uint64_t db = make_desc(sWKV + wg * 2048, 128, 128, 0);
    wg_fence();
#pragma unroll
    for (int k = 0; k < 8; k++) wg_ss8<0, 1>(kv, (k < 4 ? da0 : da1) + (k & 3) * 2, db + k * 16, k != 0);
    wg_commit();
    wg_wait<0>();
    fence_regs<4>(kv);
    named_bar(wg + 1, 128);
    sts4(sWKV + threadIdx.x * 16, __float_as_uint(kv[0]), __float_as_uint(kv[1]), __float_as_uint(kv[2]), __float_as_uint(kv[3]));
    __syncwarp();
    if ((threadIdx.x & 31) == 0) mbar_arrive(BAR_GO);
  }
    mbar_wait(BAR_FW(s, wg), ph);
    if (TR == 0) mbar_wait(BAR_XA(kb >> 1), 0); else mbar_wait(BAR_FULL(s), ph);
    proj_kb<TR>(acc, TR ? STAGE(s) + offA : xa_addr(sb, kb), STAGE(s) + offB, kb == 0);
    wg_wait<0>();
    if (w0 && elect_one()) {
      if (kb < 5) {
        mbar_expect_tx(BAR_FW(s, wg), TR ? 8192 : (kb == 4 ? 24576 : 16384));
        tma2d(STAGE(s) + (TR ? offA : 0), mW, col, (kb + 3) * 64, BAR_FW(s, wg));
        if (TR == 0) {
          tma2d(STAGE(s) + 8192, mW, col + 64, (kb + 3) * 64, BAR_FW(s, wg));
          if (kb == 4) tma2d(STAGE(s) + 16384, mX, 448, xrow, BAR_FW(s, wg));
        }
      }
      if (TR ? kb < 7 : (kb == 5 || kb == 6)) mbar_arrive(TR ? BAR_EMPTY(s) : BAR_E0(kb - 5));
      if (TR == 0 && kb == 4) mbar_arrive(BAR_VB(1));
    }
    __syncwarp();
    if (++s == 3) { s = 0; ph ^= 1; }
  }
  wg_wait<0>();
  fence_regs<64>(acc);
}

__device__ __forceinline__ uint32_t tail_slots(int isB, int n) {
  if (n < 4) return n < 2 ? (n == 0 ? 0x0D0C0B0Au : 0x04000F0Eu) : (n == 2 ? 0x18141008u : 0x15110501u);
  if (isB) return n < 6 ? (n == 4 ? 0x19120602u : 0x0D0C0B0Au) : (n == 6 ? 0x04000F0Eu : 0x13070316u);
  return n < 6 ? (n == 4 ? 0x1902031Au : 0x12061307u) : (n == 6 ? 0x16091B17u : 0x0D0C0B0Au);
}

__device__ __forceinline__ void take_role(uint32_t sM, int wg) {
  uint32_t r;
  asm volatile("atom.shared.add.u32 %0, [%1], 1;" : "=r"(r) : "r"(sM + 20) : "memory");
  sts1(sM + 32 + wg * 4, r);
}

__global__ void __launch_bounds__(640, 1)
k1_main(const __grid_constant__ CUtensorMap mXA64, const __grid_constant__ CUtensorMap mXB,
        const __grid_constant__ CUtensorMap mWq, const __grid_constant__ CUtensorMap mWqkv,
        const __grid_constant__ CUtensorMap mQst, const __grid_constant__ CUtensorMap mOst,
        const __grid_constant__ CUtensorMap mO, const __grid_constant__ CUtensorMap mWoA,
        const __grid_constant__ CUtensorMap mWoB,
        const __grid_constant__ CUtensorMap mO16, const __grid_constant__ CUtensorMap mKV, const Params prm) {
  if (threadIdx.x >= 608 && threadIdx.x < 612) {
    const CUtensorMap* pm = &mXA64 + (threadIdx.x - 608);
    asm volatile("prefetch.tensormap [%0];" :: "l"(pm) : "memory");
  }
  extern __shared__ uint8_t smem_raw[];
  const uint32_t sb = (smem_u32(smem_raw) + 1023u) & ~1023u;
  const uint32_t bars = sb + OFF_MISC, sM = bars + 512, sT = bars + 1024;
  const int tid = threadIdx.x, warp = __shfl_sync(~0u, tid >> 5, 0), wg = warp >> 2, w4 = warp & 3, lane = tid & 31;
  const bool helper = blockIdx.x >= 128;
  const int G = blockIdx.x >> 4, gi = GIMAP(blockIdx.x & 15);
  const int tbA = G * 4 + (gi >> 2), hg = gi & 3;
  const int ttB = (G >> 1) * 4 + (gi >> 2), hq = (G & 1) * 4 + (gi & 3);
  const int isB = tbA & 1, tok0 = (tbA >> 1) * 128;
  auto issue = [&](int kb, int part) {
    const uint32_t st = STAGE(kb);
    if (part & 1) {
      mbar_expect_tx(BAR_FW(kb, 0), 16384);
      tma2d(st, &mWq, hg * 128, kb * 64, BAR_FW(kb, 0));
      tma2d(st + 8192, &mWq, hg * 128 + 64, kb * 64, BAR_FW(kb, 0));
    }
    if (part & 2) {
      mbar_expect_tx(BAR_FULL(kb), 16384);
      tma2d(st + 49152, &mXB, kb * 64, ttB * 128, BAR_FULL(kb));
      mbar_expect_tx(BAR_FW(kb, 1), 8192);
      tma2d(st + 24576, &mWqkv, hq * 64, kb * 64, BAR_FW(kb, 1));
    }
    if (part & 4) {
      mbar_expect_tx(BAR_FW(kb, 2), 8192);
      tma2d(st + 32768, &mWqkv, 512 + hq * 64, kb * 64, BAR_FW(kb, 2));
      mbar_expect_tx(BAR_FW(kb, 3), 8192);
      tma2d(st + 40960, &mWqkv, 1024 + hq * 64, kb * 64, BAR_FW(kb, 3));
    }
  };
  const uint32_t sOne = sb + OFF_V + 65536, sWKV = WKV_TMP;
  if (warp >= 16) {
    if (warp == 17) {
      if (elect_one()) {
        mbar_init(BAR_BDONE, 8); mbar_init(BAR_Q, 6); mbar_init(BAR_GO, helper ? 1 : 16); mbar_init(BAR_Q2, 1);
        mbar_init(BAR_OD(0), 16); mbar_init(BAR_OD(1), 16); mbar_init(BAR_CL(0), 1); mbar_init(BAR_FULL(1), 1); mbar_init(BAR_FULL(2), 1);
        mbar_init(BAR_E0(0), 1); mbar_init(BAR_E0(1), 1);
#pragma unroll
        for (int i = 0; i < 4; i++) mbar_init(BAR_CL(i + 1), i == 0 ? 5 : 4);
#pragma unroll
        for (int i = 0; i < 3; i++) { mbar_init(BAR_EMPTY(i), 3); mbar_init(BAR_KV(i), 1); mbar_init(BAR_VB(i), i == 2 ? 4 : 1); }
        sts1(sM + 20, 0);
        asm volatile("fence.mbarrier_init.release.cluster;" ::: "memory");
      }
    } else if (warp == 18) {
      if (elect_one()) {
#pragma unroll
        for (int i = 0; i < 2; i++) mbar_init(BAR_TE(i), 2);
        mbar_init(BAR_RL, 1); mbar_init(BAR_IMG, 1);
#pragma unroll
        for (int i = 4; i < 12; i++) mbar_init(BAR_FW(0, i), 1);
#pragma unroll
        for (int i = 0; i < 16; i++) mbar_init(BAR_TF(i), 1);
        asm volatile("fence.mbarrier_init.release.cluster;" ::: "memory");
      }
    } else if (warp == 16 && !helper && elect_one()) {
#pragma unroll
      for (int w = 0; w < 4; w++) { mbar_init(BAR_XA(w), 1); mbar_init(BAR_FW(0, w), 1); }
      mbar_init(BAR_FULL(0), 1);
      asm volatile("fence.mbarrier_init.release.cluster;" ::: "memory");
      issue(0, 6);
#pragma unroll
      for (int w = 0; w < 1; w++) {
        mbar_expect_tx(BAR_XA(w), 16384);
        tma2d(xa_addr(sb, 2 * w), &mXA64, w * 128, tbA * 64, BAR_XA(w));
        tma2d(w == 3 ? XA7_TMP : xa_addr(sb, 2 * w + 1), &mXA64, w * 128 + 64, tbA * 64, BAR_XA(w));
        if (w == 0) issue(0, 1);
      }
    }
  } else if (!helper) {
    const uint4 v = __ldg((const uint4*)(hg >= 2 ? prm.wv : prm.wk) + tid * 2 + (hg & 1));
    sts4(sWKV + tid * 16, v.x, v.y, v.z, v.w);
    fence_async();
  }
  __syncthreads();
  if (wg == 4) {
    if (w4 == 0 && !helper && elect_one()) {
      issue(1, 7);
#pragma unroll
      for (int w = 1; w < 4; w++) {
        mbar_expect_tx(BAR_XA(w), 16384);
        tma2d(xa_addr(sb, 2 * w), &mXA64, w * 128, tbA * 64, BAR_XA(w));
        tma2d(w == 3 ? XA7_TMP : xa_addr(sb, 2 * w + 1), &mXA64, w * 128 + 64, tbA * 64, BAR_XA(w));
      }
      issue(2, 6);
    }
    asm volatile("setmaxnreg.dec.sync.aligned.u32 32;");
    const uint32_t ep = g_epoch[blockIdx.x] + 1;
    if (helper) {
      if (w4 == 0 && elect_one()) {
        flag_wait(FLAG_B(blockIdx.x - 128), ep * 32);
        fence_async_all();
        mbar_arrive(BAR_GO);
        g_epoch[blockIdx.x] = ep;
      }
      return;
    }
    mbar_wait(BAR_GO, 0);
    {
      uint32_t a[4], b[4];
      float c[4];
      lds4(sWKV + (tid - 512) * 16, a);
      lds4(sWKV + 2048 + (tid - 512) * 16, b);
#pragma unroll
      for (int i = 0; i < 4; i++) c[i] = __uint_as_float(a[i]) + __uint_as_float(b[i]);
      lds4(sWKV + 4096 + (tid - 512) * 16, a);
      lds4(sWKV + 6144 + (tid - 512) * 16, b);
#pragma unroll
      for (int i = 0; i < 4; i++) c[i] += __uint_as_float(a[i]) + __uint_as_float(b[i]);
      sts1(sT + w4 * 256 + lane * 4, pack_bf16(c[0], c[1]));
      sts1(sT + w4 * 256 + 128 + lane * 4, pack_bf16(c[2], c[3]));
    }
    named_bar(9, 128);
    if (w4 == 0) { mbar_wait(BAR_IMG, 0); if (elect_one()) issue(2, 1); }
    auto write_ones = [&]() {
      mbar_wait_long(BAR_VB(1), 0);
      int c = ((w4 & 1) * 32 + lane);
#pragma unroll 4
      for (int key = c; key < S_TOK; key += 64) {
        sts4(sOne + key * 16, c < 24 ? 0x00003F80u : 0x00004E80u, 0u, 0u, 0u);
        c += 64; if (c >= STEPK) c -= STEPK;
      }
      fence_async();
      __syncwarp();
      if (lane == 0) mbar_arrive(BAR_Q);
    };
    if (w4 == 0) {
      int s = 0, ph = 0;
#pragma unroll 1
      for (int kb = 3; kb < 8; kb++) {
        mbar_wait(BAR_EMPTY(s), ph);
        if (elect_one()) {
          mbar_expect_tx(BAR_FULL(s), 16384);
          tma2d(STAGE(s) + 49152, &mXB, kb * 64, ttB * 128, BAR_FULL(s));
        }
        if (++s == 3) { s = 0; ph ^= 1; }
      }
      flag_wait(FLAG_KV, ep * 128);
      fence_async_all();
#pragma unroll 1
      for (int m = 0; m < 2; m++) {
        mbar_wait(m == 0 ? BAR_EMPTY(2) : BAR_EMPTY(0), 1 - m);
        mbar_wait(BAR_E0(m), 0);
        if (elect_one()) {
          const uint32_t fb = m == 0 ? BAR_KV(0) : BAR_VB(0);
          mbar_expect_tx(fb, 2 * 7 * STEPK * 16);
#pragma unroll
          for (int p = 0; p < 2; p++) bulk_g2s(sb + m * OFF_V + p * 32768, g_KV + (m * 2 + p) * S_TOK, 7 * STEPK * 16, fb);
        }
      }
      mbar_wait(BAR_Q, 0);
      if (elect_one()) {
#pragma unroll
        for (int c = 1; c < 3; c++) {
          const int k0 = c == 1 ? 7 * STEPK : 13 * STEPK, k1 = c == 1 ? 13 * STEPK : S_TOK;
          const uint32_t bytes = (k1 - k0) * 16;
          mbar_expect_tx(BAR_KV(c), 4 * bytes);
#pragma unroll
          for (int p = 0; p < 4; p++)
            bulk_g2s(sb + (p >> 1) * OFF_V + (p & 1) * 32768 + k0 * 16, g_KV + p * S_TOK + k0, bytes, BAR_KV(c));
        }
      }
      mbar_wait_long(BAR_CL(1), 0);
      flag_wait(isB ? FLAG_LM((lane & 7) * 2 + (tbA >> 4)) : FLAG_OA(tbA * 4 + (lane & 7), 0), ep);
      __syncwarp();
      fence_async_all();
      const CUtensorMap* mW = isB ? &mWoB : &mWoA;
#pragma unroll 1
      for (int it = 0; it < 8; it++) {
        const int n = (!isB && it >= 6) ? 13 - it : it;
        uint32_t wb = BAR_CL(n < 3 ? 0 : (n == 3 ? 2 : 3));
        if (isB) { if (n >= 5) wb = n == 7 ? BAR_CL(4) : BAR_TE(n - 5); }
        else if (n >= 6) wb = n == 6 ? BAR_CL(4) : BAR_TE(0);
        if (it < 6) mbar_wait_long(wb, 0); else mbar_wait(wb, 0);
        const uint32_t sl = tail_slots(isB, n), fb = BAR_TF(n);
        const bool withX = isB || n < 4;
        const int k0 = isB ? n * 64 : (n < 4 ? n * 128 : ((hg + n) & 3) * 128 + 64);
        if (elect_one()) {
          mbar_expect_tx(fb, withX ? 32768 : 16384);
          if (withX) {
            tma2d(sb + (sl & 255) * 8192, &mO, k0, isB * S_TOK + tok0, fb);
            tma2d(sb + ((sl >> 8) & 255) * 8192, &mO, k0, isB * S_TOK + tok0 + 64, fb);
          }
          tma2d(sb + ((sl >> 16) & 255) * 8192, mW, hg * 128, k0, fb);
          tma2d(sb + (sl >> 24) * 8192, mW, hg * 128 + 64, k0, fb);
        }
      }
      if (lane == 0) g_epoch[blockIdx.x] = ep;
    } else if (w4 == 3) {
      write_ones();
      flag_wait(FLAG_KV2, ep * 128);
      const uint4 a = *(const uint4*)(g_stats + lane * 4);
      const float kmax2 = __uint_as_float(__reduce_max_sync(~0u, a.x)) + __uint_as_float(__reduce_max_sync(~0u, a.y));
      const float vmax = __uint_as_float(__reduce_max_sync(~0u, max(a.z, a.w)));
      const float lv = vmax > 0.f ? __log2f(vmax) : 0.f;
      const float lim = fminf(90.f, fminf(91.f + lv, 95.f - lv));
      float thr = -1.f;
      if (vmax < 1e27f && kmax2 <= 65536.f && lim > 2.f) thr = fminf(60000.f, (lim * lim - 1.f) / (kmax2 * 1.02f + 1e-30f));
      mbar_wait_long(BAR_VB(2), 0);
      uint32_t nmax = 0;
#pragma unroll 2
      for (int i = 0; i < 16; i++) {
        uint32_t x[4], y[4];
        const uint32_t ad = sb + OFF_F + i * 1024 + (lane >> 3) * 256 + (lane & 7) * 16;
        lds4(ad, x); lds4(ad + 128, y);
        uint32_t n = hfma2(x[0], x[0], hfma2(x[1], x[1], hfma2(x[2], x[2], hfma2(x[3], x[3], 0u))));
        n = hfma2(y[0], y[0], hfma2(y[1], y[1], hfma2(y[2], y[2], hfma2(y[3], y[3], n))));
        n = hadd2(n, n >> 16);
        nmax = max(nmax, n & 0x7FFFu);
      }
      nmax = __reduce_max_sync(~0u, nmax);
      const bool ok = __half2float(__ushort_as_half((unsigned short)nmax)) <= thr;
      if (lane == 0) { sts1(sM + 16, ok ? 1u : 0u); mbar_arrive(BAR_Q2); }
    } else {
      const int tok = (w4 - 1) * 32 + lane;
      int step, col;
      if ((tbA & 3) == 0) {
        const int b8 = tbA >> 2;
        if (tok < 22) { step = tok; col = 24 + b8; }
        else { const int c = tok >= 43; step = tok - 22 - 21 * c; col = 32 + b8 * 2 + c; }
      } else {
        const int b24 = (tbA >> 2) * 3 + (tbA & 3) - 1;
        if (tok < 42) { const int c = tok >= 21; step = tok - 21 * c; col = 48 + b24 * 2 + c; }
        else { step = tok - 42; col = b24; }
      }
      const int kap = step * STEPK + col;
      const bool chained = col >= 24;
      uint32_t v[4], o[4];
      lds4(sT + tok * 16, v);
      float st = 0.f;
      if (hg < 2) {
        o[0] = o[1] = o[2] = o[3] = 0;
        if (chained && step > 0) lds4(sT + tok * 16 - 16, o);
        const float sc = chained ? 2.f : 1.f;
#pragma unroll
        for (int u = 0; u < 4; u++) {
          const float x = bf_lo(v[u]), y = bf_hi(v[u]);
          st += x * x + y * y;
          o[u] = pack_f16((x - bf_lo(o[u])) * sc, (y - bf_hi(o[u])) * sc);
        }
      } else {
        const float sc = chained ? VSHIFT : 1.f;
#pragma unroll
        for (int u = 0; u < 4; u++) { float x = bf_lo(v[u]), y = bf_hi(v[u]); st += fabsf(x) + fabsf(y); o[u] = pack_bf16(x * sc, y * sc); }
      }
      {
        const bool tl = (tbA & 3) == 0;
        const int run = tl ? (tok < 22 ? 0 : (tok < 43 ? 1 : 2)) : (tok < 21 ? 0 : (tok < 42 ? 1 : 2));
        const int h2 = (tl ? run == 0 : run == 2) ? 11 : 10;
        const uint32_t img = sWKV + run * 512;
        if (step < 11) sts4(img + step * 16, o[0], o[1], o[2], o[3]);
        if (step >= h2) sts4(img + 256 + (step - h2) * 16, o[0], o[1], o[2], o[3]);
        if (step == 0) sts1(sM + 48 + run * 4, col * 8 + (h2 << 16));
        fence_async();
        named_bar(10, 64);
        if (w4 == 1 && elect_one()) {
#pragma unroll
          for (int r = 0; r < 3; r++) {
            const uint32_t cw = lds1(sM + 48 + r * 4);
            tma3d_store(&mKV, sWKV + r * 512, cw & 0xFFFF, 0, hg);
            tma3d_store(&mKV, sWKV + r * 512 + 256, cw & 0xFFFF, cw >> 16, hg);
          }
          bulk_commit();
          asm volatile("cp.async.bulk.wait_group.read 0;" ::: "memory");
          mbar_arrive(BAR_IMG);
          bulk_wait_all();
          PUBLISH(FLAG_KV);
        }
        __syncwarp();
      }
      g_KV[(4 + hg) * S_TOK + kap] = make_uint4(v[0], v[1], v[2], v[3]);
      const uint32_t um = __reduce_max_sync(~0u, __float_as_uint(st) & 0x7FFFFFFFu);
      if (w4 == 2) {
        if (lane == 0) sts1(sM + 24, um);
        named_arrive(11, 64);
        write_ones();
        if (!isB) {
          mbar_wait_long(BAR_CL(3), 0);
          mbar_wait_long(BAR_RL, 0);
          uint32_t pend = 0xFE;
          const int li = lane & 7;
          const uint32_t* fl = FLAG_OA((tbA + (li & 1)) * 4 + ((hg + (li >> 1)) & 3), 1);
#pragma unroll 1
          for (int it = 0; pend; it++) {
            uint32_t fv;
            asm volatile("ld.acquire.gpu.global.u32 %0, [%1];" : "=r"(fv) : "l"(fl) : "memory");
            uint32_t go = __ballot_sync(~0u, (int32_t)(fv - ep) >= 0 && mbar_test(li >= 6 ? BAR_TE(0) : BAR_CL(4), 0)) & pend;
            pend &= ~go;
            if (go) fence_async_all();
#pragma unroll 1
            while (go) {
              const int b = __ffs(go) - 1;
              go &= go - 1;
              const uint32_t slot = (tail_slots(0, 4 + (b >> 1)) >> (8 * (b & 1))) & 255;
              if (elect_one()) {
                mbar_expect_tx(BAR_TF(8 + b), 8192);
                tma2d(sb + slot * 8192, &mO, ((hg + (b >> 1)) & 3) * 128 + 64, tok0 + (b & 1) * 64, BAR_TF(8 + b));
              }
            }
            if (it > 2000000) __trap();
          }
        }
      }
      else {
        named_bar(11, 64);
        if (elect_one()) {
          g_stats[tbA * 4 + hg] = max(um, lds1(sM + 24));
          flag_add(FLAG_KV2);
          mbar_wait_long(BAR_BDONE, 0);
          tma2d_store(&mQst, sb + OFF_F + 49152, hq * 64, S_TOK + ttB * 128);
          bulk_commit();
          bulk_wait_all();
          fence_async_all();
          flag_add(FLAG_B(hq >> 1));
          mbar_wait(BAR_Q, 0);
          mbar_arrive(BAR_CL(0));
#pragma unroll 1
          for (int p = 0; p < 2; p++) {
            mbar_wait_long(BAR_OD(p), 0);
            if (p == 0) {
#pragma unroll
              for (int w = 0; w < 4; w++) tma2d_store(&mO16, sb + OFF_F + w * 2048, hg * 128 + w * 16, tbA * 64);
            } else {
              tma2d_store(&mO, sb + 26 * 8192, hg * 128 + 64, tbA * 64);
            }
            bulk_commit();
            bulk_wait_all();
            if (p == 0) mbar_arrive(BAR_CL(1));
            PUBLISH(FLAG_OA(tbA * 4 + hg, p));
          }
        }
      }
    }
    return;
  }
  if (helper) { helper_cta(blockIdx.x - 128, sb, bars, wg, w4, &mQst, &mOst); return; }

  {
    float acc[64];
    if (wg == 0) proj_loop<0>(acc, sb, bars, 16384, 0, wg, sWKV, &mWq, hg * 128, w4 == 0, &mXA64, tbA * 64);
    else proj_loop<1>(acc, sb, bars, 16384 + wg * 8192, 49152, wg, sWKV, &mWqkv, (wg - 1) * 512 + hq * 64, w4 == 0, &mXA64, 0);
    const uint32_t sF = sb + OFF_F;
    const uint32_t qa = sF + w4 * 512 + ((lane >> 3) & 1) * 256 + (lane >> 4) * 128 + (lane & 7) * 16;
    if (wg == 0) {
#pragma unroll
      for (int hd = 0; hd < 4; hd++)
        stsm4(qa + hd * 2048, pack_f16(acc[8 * hd] * QSCALE, acc[8 * hd + 1] * QSCALE), pack_f16(acc[8 * hd + 2] * QSCALE, acc[8 * hd + 3] * QSCALE),
              pack_f16(acc[8 * hd + 4] * QSCALE, acc[8 * hd + 5] * QSCALE), pack_f16(acc[8 * hd + 6] * QSCALE, acc[8 * hd + 7] * QSCALE));
      fence_async();
      __syncwarp();
      if (lane == 0) mbar_arrive(BAR_Q);
    } else {
      if (wg != 3) named_arrive(6, 384);
      if (wg != 1) named_arrive(8, 384);
    }
    asm volatile("setmaxnreg.inc.sync.aligned.u32 112;");
    fence_regs<64>(acc);
    if (wg == 0) {
#pragma unroll
      for (int hd = 4; hd < 8; hd++)
        stsm4(qa + hd * 2048, pack_f16(acc[8 * hd] * QSCALE, acc[8 * hd + 1] * QSCALE), pack_f16(acc[8 * hd + 2] * QSCALE, acc[8 * hd + 3] * QSCALE),
              pack_f16(acc[8 * hd + 4] * QSCALE, acc[8 * hd + 5] * QSCALE), pack_f16(acc[8 * hd + 6] * QSCALE, acc[8 * hd + 7] * QSCALE));
      fence_async();
      __syncwarp();
      if (lane == 0) mbar_arrive(BAR_VB(2));
    } else if (wg == 3) {
      named_bar(6, 384);
      const int t = tid & 127;
#pragma unroll
      for (int j = 0; j < 8; j++)
        sts4(sF + 24576 + j * 2048 + t * 16, pack_bf16(acc[8 * j], acc[8 * j + 1]), pack_bf16(acc[8 * j + 2], acc[8 * j + 3]),
             pack_bf16(acc[8 * j + 4], acc[8 * j + 5]), pack_bf16(acc[8 * j + 6], acc[8 * j + 7]));
      named_arrive(7, 256);
    } else {
      uint32_t p[32];
#pragma unroll
      for (int i = 0; i < 32; i++) p[i] = phi2(acc[2 * i], acc[2 * i + 1]);
      if (wg == 1) {
        named_bar(8, 384);
        const int m = lane >> 3, r = lane & 7;
#pragma unroll
        for (int j = 0; j < 16; j += 2) {
          const int tok = (j + (m >> 1)) * 8 + r;
          const int chunk = w4 * 2 + (m & 1);
          stsm4t(sF + 49152 + tok * 128 + ((chunk ^ r) << 4), p[2 * j], p[2 * j + 1], p[2 * j + 2], p[2 * j + 3]);
        }
        fence_async();
      } else {
        named_bar(7, 256);
        float kv0[4] = {0, 0, 0, 0}, kv1[4] = {0, 0, 0, 0}, z0[4] = {0, 0, 0, 0}, z1[4] = {0, 0, 0, 0};
        const uint32_t one = 0x3F803F80u;
        const int t = tid & 127;
#pragma unroll
        for (int j = 0; j < 8; j++) {
          uint32_t a[4];
          lds4(sF + 24576 + j * 2048 + t * 16, a);
          mma_bf16(kv0, a[0], a[1], a[2], a[3], p[4 * j], p[4 * j + 2]);
          mma_bf16(kv1, a[0], a[1], a[2], a[3], p[4 * j + 1], p[4 * j + 3]);
          mma_bf16(z0, one, one, one, one, p[4 * j], p[4 * j + 2]);
          mma_bf16(z1, one, one, one, one, p[4 * j + 1], p[4 * j + 3]);
        }
        float4* dst = g_kvp + ((ttB * 32 + hq * 4 + w4) * 3) * 32 + lane;
        dst[0] = make_float4(kv0[0], kv0[1], kv1[0], kv1[1]);
        dst[32] = make_float4(kv0[2], kv0[3], kv1[2], kv1[3]);
        dst[64] = make_float4(z0[0], z0[1], z1[0], z1[1]);
      }
      __syncwarp();
      if (lane == 0) mbar_arrive(BAR_BDONE);
    }
  }

  bool safe = true;
  {
    const uint32_t c63 = 0x1F801F80u + (threadIdx.x >> 20);
    const uint32_t m1 = (gridDim.x >> 20) - 1u;
    const uint64_t dK0 = make_desc(sb + OFF_K, 32768, 128, 0);
    const uint64_t dV0 = make_desc(sb + OFF_V, 128, 32768, 0);
    constexpr uint32_t dKV = ((2048u - 8u)  __H0__ ) + STEPK - (OFF_V - OFF_K) / 16;
    float Sm[12], Sp[36], O[12];
    uint32_t P[24];
    uint64_t dQ = make_desc(sb + OFF_F + wg * 2048, 128, 256, 0);
#pragma unroll
    for (int i = 0; i < 36; i++) Sp[i] = SMAGIC;
#pragma unroll
    for (int i = 0; i < 12; i++) Sm[i] = 0.f;
    fence_regs<12>(Sm); fence_regs<36>(Sp);
    mbar_wait(BAR_Q, 0);
    mbar_wait(BAR_KV(0), 0);
    wg_fence();
    wg_qs72<1>(Sp, dQ, dK0 + 24);
    wg_qs24<0>(Sm, dQ, dK0);
    wg_commit();
    wg_wait<0>();
    fence_regs<12>(Sm); fence_regs<36>(Sp);
#pragma unroll 1
    for (int pass = 0; pass < 2; pass++) {
#pragma unroll
      for (int i = 0; i < 12; i++) O[i] = 0.f;
      fence_regs<12>(O);
      uint32_t vlo = (uint32_t)dV0;
#pragma unroll 1
      for (int seg = 0; seg < 4; seg++) {
        if (pass == 0) {
          if (seg < 3) mbar_wait(seg == 0 ? BAR_VB(0) : BAR_KV(seg), 0);
        } else if (seg >= 1) {
          if ((tid & 127) == 0) {
            mbar_arrive(BAR_CL(seg));
            if (seg == 3) take_role(sM, wg);
          }
          __syncwarp();
        }
        const uint32_t vend = vlo + (seg == 3 ? 3 : 6) * STEPK;
#pragma unroll 1
        for (; vlo != vend; vlo += 3 * STEPK) {
          uint64_t dK, dV;
          asm("mov.b64 %0, {%1, %2};" : "=l"(dK) : "r"(vlo + dKV), "r"(8u));
          asm("mov.b64 %0, {%1, %2};" : "=l"(dV) : "r"(vlo), "r"(2048u));
#pragma unroll
          for (int u = 0; u < 3; u++) {
          { uint32_t w[18], y[18], z[18]; float e[12];
            X_MU(0) X_PR(0) X_LO(0) X_IM(0) X_MU(1) X_FM(0) X_PR(1) X_LO(1) X_IM(1) X_MU(2) X_FM(1) X_PR(2)
            X_LO(2) X_MU(3) X_IM(2) X_FM(2) X_PR(3) X_LO(3) X_PK(0) X_MU(4) X_IM(3) X_FM(3) X_PR(4) X_LO(4)
            X_MU(5) X_IM(4) X_FM(4) X_PR(5) X_PK(1) X_MU(6) X_LO(5) X_IM(5) X_FM(5) X_PR(6) X_MU(7) X_LO(6)
            X_IM(6) X_FM(6) X_MU(8) X_PR(7) X_PK(2) X_LO(7) X_IM(7) X_FM(7) X_MU(9) X_PR(8) X_LO(8) X_IM(8)
            X_FM(8) X_PK(3) X_MU(10) X_PR(9) X_LO(9) X_IM(9) X_MU(11) X_FM(9) X_PR(10) X_LO(10) X_IM(10) X_PK(4)
            X_FM(10) X_PR(11) X_LO(11) X_IM(11) X_FM(11) X_PR(12) X_LO(12) X_PK(5) X_IM(12) X_FM(12) X_PR(13) X_LO(13)
            X_IM(13) X_FM(13) X_PR(14) X_LO(14) X_IM(14) X_FM(14) X_PR(15) X_LO(15) X_IM(15) X_FM(15) X_PR(16) X_LO(16)
            X_IM(16) X_FM(16) X_PR(17) X_LO(17) X_IM(17) X_FM(17) }
          fence_regs<24>(P);
          wg_fence();
          wg_pv24<1>(O, &P[20], dV + u * STEPK + 80);
          wg_pv24<1>(O, &P[16], dV + u * STEPK + 64);
          wg_pv24<1>(O, &P[12], dV + u * STEPK + 48);
          wg_pv24<1>(O, &P[8], dV + u * STEPK + 32);
          wg_pv24<1>(O, &P[4], dV + u * STEPK + 16);
          wg_pv24<1>(O, &P[0], dV + u * STEPK + 0);
          wg_qs72<1>(Sp, dQ, dK + u * STEPK + 24);
          wg_qs24<0>(Sm, dQ, dK + u * STEPK);
          wg_commit();
          wg_wait<0>();
          fence_regs<12>(Sm); fence_regs<36>(Sp); fence_regs<12>(O); fence_regs<24>(P);
          }
        }
      }
#pragma unroll
      for (int i = 0; i < 6; i++) P[i] = pack_bf16(ex2f(Sm[2 * i]), ex2f(Sm[2 * i + 1]));
      P[6] = exp2_pair_fix(Sp[0], Sp[1], c63, m1);
      P[7] = exp2_pair_fix(Sp[2], Sp[3], c63, m1);
      fence_regs<8>(P);
      const uint32_t sO = pass == 0 ? sb + OFF_F + wg * 2048 + w4 * 512 + (lane & 15) * 32 + (lane >> 4) * 16
                                    : sb + 26 * 8192 + (w4 * 16 + (lane & 15)) * 128 + (((wg * 2 + (lane >> 4)) ^ (lane & 7)) << 4);
      dQ += 512;
      wg_fence();
      wg_pv24<1>(O, &P[0], dV0 + 21 * STEPK);
      wg_pv24<1>(O, &P[4], dV0 + 21 * STEPK + 16);
      wg_commit();
#pragma unroll
      for (int i = 0; i < 36; i++) Sp[i] = SMAGIC;
      fence_regs<36>(Sp);
      mbar_wait(pass == 0 ? BAR_Q2 : BAR_CL(3), 0);
      wg_fence();
      wg_qs72<1>(Sp, dQ, dK0 + 24);
      wg_qs24<0>(Sm, dQ, dK0);
      wg_commit();
      wg_wait<1>();
      fence_regs<12>(O);
      const float l0 = __shfl_sync(~0u, O[8], lane & ~3), l1 = __shfl_sync(~0u, O[10], lane & ~3);
      const float i0 = rcpf(l0), i1 = rcpf(l1);
      stsm4(sO,
            pack_bf16(O[0] * i0, O[1] * i0), pack_bf16(O[2] * i1, O[3] * i1),
            pack_bf16(O[4] * i0, O[5] * i0), pack_bf16(O[6] * i1, O[7] * i1));
      fence_async();
      {
        safe = __all_sync(~0u, lds1(sM + 16) != 0);
      }
      if (safe && lane == 0) mbar_arrive(BAR_OD(pass));
      wg_wait<0>();
      fence_regs<12>(Sm); fence_regs<36>(Sp);
      if (!safe) break;
    }
  }
  if (!safe) {
    if ((tid & 127) == 0) { mbar_arrive(BAR_CL(1)); mbar_arrive(BAR_CL(2)); mbar_arrive(BAR_CL(3)); take_role(sM, wg); }
#pragma unroll 1
    for (int pass = 0; pass < 2; pass++) {
      const int t = tid & 127;
      mbar_wait(BAR_CL(3), 0);
      attn_slow(prm.xa + (size_t)tbA * 64 * D_MOD, prm.wq + (hg * 8 + pass * 4 + wg) * 16,
                pass == 0 ? sb + OFF_F + wg * 2048 + t * 16
                          : sb + 26 * 8192 + (t >> 1) * 128 + (((wg * 2 + (t & 1)) ^ ((t >> 1) & 7)) << 4));
      __syncwarp();
      if (lane == 0) mbar_arrive(BAR_OD(pass));
    }
  }

  {
    named_bar(wg + 1, 128);
    if ((tid & 127) == 0) mbar_arrive(BAR_CL(4));
    const int role = __shfl_sync(~0u, lds1(sM + 32 + wg * 4), 0);
    const int m = lane >> 3, r = lane & 7;
    const uint32_t stoff = (w4 * 16 + (m & 1) * 8 + r) * 128;
    if (role < 2) {
      if (role == 0 && (tid & 127) == 0) mbar_arrive(BAR_RL);
      if (!isB || role == 1) mbar_wait(BAR_CL(4), 0);
      float acc[64];
#pragma unroll 1
      for (int n = 0; n < 8; n++) {
        const uint32_t sl = tail_slots(isB, n);
        const uint32_t w0 = (sl >> 16) & 255, w1 = sl >> 24;
        const uint64_t da = make_desc(sb + ((sl >> (8 * role)) & 255) * 8192, 16, 1024, 1);
        const uint64_t db = make_desc(sb + w0 * 8192, (w1 - w0) * 8192, 1024, 1);
        mbar_wait(BAR_TF(n), 0);
        if (!isB && n >= 4) mbar_wait(n == 4 && role == 0 ? BAR_OD(1) : BAR_TF(2 * n + role), 0);
        wg_fence();
#pragma unroll
        for (int k = 0; k < 4; k++) wg_ss128<0, 1>(acc, da + k * 2, db + k * 128, (n | k) != 0);
        wg_commit();
        wg_wait<1>();
        if ((n == 1 || n == 2) && (tid & 127) == 0) mbar_arrive(BAR_TE(n - 1));
        __syncwarp();
      }
      wg_wait<0>();
      fence_regs<64>(acc);
      const uint32_t x0 = sb + (role ? 16 : 8) * 8192, x1 = sb + (role ? 5 : 1) * 8192;
#pragma unroll
      for (int j = 0; j < 16; j += 2)
        stsm4((j < 8 ? x0 : x1) + stoff + ((((j & 7) + (m >> 1)) ^ r) << 4),
              pack_bf16(acc[4 * j], acc[4 * j + 1]), pack_bf16(acc[4 * j + 2], acc[4 * j + 3]),
              pack_bf16(acc[4 * j + 4], acc[4 * j + 5]), pack_bf16(acc[4 * j + 6], acc[4 * j + 7]));
      __syncwarp();
      uint4* dst = (uint4*)(prm.out + (size_t)(tok0 + role * 64 + w4 * 16 + (lane >> 4)) * 1024 + isB * 512 + hg * 128) + (lane & 15);
      const uint32_t src = ((lane & 8) ? x1 : x0) + (w4 * 16 + (lane >> 4)) * 128;
#pragma unroll
      for (int i = 0; i < 8; i++) {
        uint32_t v[4];
        lds4(src + i * 256 + (((lane & 7) ^ ((2 * i + (lane >> 4)) & 7)) << 4), v);
        dst[i * 256] = make_uint4(v[0], v[1], v[2], v[3]);
      }
    }
  }
}

__device__ __nv_bfloat16 g_T[S_TOK * 1536];
__device__ float g_Z[32 * 272];
__global__ void fb_gemm(const __nv_bfloat16* A, const __nv_bfloat16* B, __nv_bfloat16* C, int N, int ldc) {
  __shared__ float sa[16][17], sbm[16][17];
  const int tx = threadIdx.x & 15, ty = threadIdx.x >> 4, row = blockIdx.y * 16 + ty, col = blockIdx.x * 16 + tx;
  float acc = 0.f;
  for (int k0 = 0; k0 < D_MOD; k0 += 16) {
    sa[ty][tx] = __bfloat162float(A[(size_t)row * D_MOD + k0 + tx]);
    sbm[ty][tx] = __bfloat162float(B[(size_t)(k0 + ty) * N + col]);
    __syncthreads();
    for (int k = 0; k < 16; k++) acc = fmaf(sa[ty][k], sbm[k][tx], acc);
    __syncthreads();
  }
  C[(size_t)row * ldc + col] = __float2bfloat16_rn(acc);
}
__global__ void fb_attn() {
  const int r = blockIdx.x * blockDim.x + threadIdx.x;
  float q[16], o[16], m = -INFINITY, l = 0.f;
  for (int i = 0; i < 16; i++) { q[i] = __bfloat162float(g_Q[(size_t)r * 16 + i]); o[i] = 0.f; }
  for (int j = 0; j < S_TOK; j++) {
    float s = 0.f;
    for (int i = 0; i < 16; i++) s = fmaf(q[i], __bfloat162float(g_T[j * 32 + i]), s);
    s = rbf(s) * 0.25f;
    const float mn = fmaxf(m, s), c = __expf(m - mn), p = __expf(s - mn);
    l = l * c + p; m = mn;
    for (int i = 0; i < 16; i++) o[i] = fmaf(p, __bfloat162float(g_T[j * 32 + 16 + i]), o[i] * c);
  }
  for (int i = 0; i < 16; i++) g_O[(size_t)r * 16 + i] = __float2bfloat16_rn(o[i] / l);
}
__device__ __forceinline__ float fb_phi(__nv_bfloat16 x) { const float t = __bfloat162float(x); return bf_lo(phi2(t, t)); }
__global__ void fb_kv() {
  const int h = blockIdx.x, t = threadIdx.x, d = t < 256 ? t >> 4 : t - 256, e = t & 15;
  float acc = 0.f;
  for (int s = 0; s < S_TOK; s++)
    acc = fmaf(fb_phi(g_T[(size_t)s * 1536 + 512 + h * 16 + d]), t < 256 ? __bfloat162float(g_T[(size_t)s * 1536 + 1024 + h * 16 + e]) : 1.f, acc);
  g_Z[h * 272 + t] = rbf(acc);
}
__global__ void fb_lin() {
  const int idx = blockIdx.x * blockDim.x + threadIdx.x, s = idx >> 9, c = idx & 511, h = c >> 4, e = c & 15;
  float num = 0.f, den = 0.f;
  for (int d = 0; d < 16; d++) {
    const float p = fb_phi(g_T[(size_t)s * 1536 + h * 16 + d]);
    num = fmaf(p, g_Z[h * 272 + d * 16 + e], num); den = fmaf(p, g_Z[h * 272 + 256 + d], den);
  }
  g_O[(size_t)S_TOK * D_MOD + idx] = __float2bfloat16_rn(num / (den + 1e-6f));
}

typedef CUresult (*EncodeFn)(CUtensorMap*, CUtensorMapDataType, cuuint32_t, void*, const cuuint64_t*, const cuuint64_t*,
                             const cuuint32_t*, const cuuint32_t*, CUtensorMapInterleave, CUtensorMapSwizzle,
                             CUtensorMapL2promotion, CUtensorMapFloatOOBfill);

static void make_map(EncodeFn enc, CUtensorMap* m, const void* ptr, uint64_t cols, uint64_t rows, uint32_t bc, uint32_t br,
                     CUtensorMapSwizzle sw = CU_TENSOR_MAP_SWIZZLE_128B) {
  cuuint64_t dims[2] = {cols, rows};
  cuuint64_t strides[1] = {cols * 2};
  cuuint32_t box[2] = {bc, br};
  cuuint32_t es[2] = {1, 1};
  enc(m, CU_TENSOR_MAP_DATA_TYPE_BFLOAT16, 2, (void*)ptr, dims, strides, box, es, CU_TENSOR_MAP_INTERLEAVE_NONE,
      sw, CU_TENSOR_MAP_L2_PROMOTION_L2_256B, CU_TENSOR_MAP_FLOAT_OOB_FILL_NONE);
}

extern "C" void kernel_launch(void* const* d_in, const int* in_sizes, int n_in, void* d_out, int out_size) {
  (void)in_sizes; (void)n_in; (void)out_size;
  static EncodeFn enc = nullptr;
  static void* pQ = nullptr; static void* pO = nullptr; static void* pT = nullptr; static void* pK = nullptr;
  static bool fused = false;
  if (!enc) {
    void* fn = nullptr; cudaDriverEntryPointQueryResult qr;
    cudaGetDriverEntryPoint("cuTensorMapEncodeTiled", &fn, cudaEnableDefault, &qr);
    enc = (EncodeFn)fn;
    cudaGetSymbolAddress(&pQ, g_Q);
    cudaGetSymbolAddress(&pO, g_O);
    cudaGetSymbolAddress(&pT, g_T);
    cudaGetSymbolAddress(&pK, g_KV);
    cudaFuncSetAttribute(k1_main, cudaFuncAttributeMaxDynamicSharedMemorySize, SM_TOTAL);
    int dev = 0, sms = 0, occ = 0;
    cudaGetDevice(&dev);
    cudaDeviceGetAttribute(&sms, cudaDevAttrMultiProcessorCount, dev);
    cudaOccupancyMaxActiveBlocksPerMultiprocessor(&occ, k1_main, 640, SM_TOTAL);
    fused = sms * occ >= 132;
  }
  if (!fused) {
    typedef const __nv_bfloat16* CB; typedef __nv_bfloat16* MB;
    cudaStream_t st = cudaStreamPerThread;
    fb_gemm<<<dim3(32, 128), 256, 0, st>>>((CB)d_in[0], (CB)d_in[1], (MB)pQ, 512, 512);
    fb_gemm<<<dim3(1, 128), 256, 0, st>>>((CB)d_in[0], (CB)d_in[2], (MB)pT, 16, 32);
    fb_gemm<<<dim3(1, 128), 256, 0, st>>>((CB)d_in[0], (CB)d_in[3], (MB)pT + 16, 16, 32);
    fb_attn<<<512, 128, 0, st>>>();
    fb_gemm<<<dim3(96, 128), 256, 0, st>>>((CB)d_in[5], (CB)d_in[6], (MB)pT, 1536, 1536);
    fb_kv<<<32, 272, 0, st>>>();
    fb_lin<<<4096, 256, 0, st>>>();
    fb_gemm<<<dim3(32, 128), 256, 0, st>>>((CB)pO, (CB)d_in[4], (MB)d_out, 512, 1024);
    fb_gemm<<<dim3(32, 128), 256, 0, st>>>((CB)pO + S_TOK * D_MOD, (CB)d_in[7], (MB)d_out + 512, 512, 1024);
    return;
  }
  CUtensorMap mXA64, mXB, mWq, mWqkv, mQst, mO, mOst, mWoA, mWoB, mO16, mKV;
  make_map(enc, &mXA64, d_in[0], 512, 2048, 64, 64);
  make_map(enc, &mWq, d_in[1], 512, 512, 64, 64);
  make_map(enc, &mWoA, d_in[4], 512, 512, 64, 64);
  make_map(enc, &mXB, d_in[5], 512, 2048, 64, 128);
  make_map(enc, &mWqkv, d_in[6], 1536, 512, 64, 64);
  make_map(enc, &mWoB, d_in[7], 512, 512, 64, 64);
  make_map(enc, &mQst, pQ, 512, 4096, 64, 128);
  make_map(enc, &mO, pO, 512, 4096, 64, 64);
  make_map(enc, &mOst, pO, 512, 4096, 64, 128);
  make_map(enc, &mO16, pO, 512, 4096, 16, 64, CU_TENSOR_MAP_SWIZZLE_NONE);
  {
    cuuint64_t dims[3] = {768, 22, 4};
    cuuint64_t strides[2] = {1536, 32768};
    cuuint32_t box[3] = {8, 11, 1};
    cuuint32_t es[3] = {1, 1, 1};
    enc(&mKV, CU_TENSOR_MAP_DATA_TYPE_BFLOAT16, 3, pK, dims, strides, box, es, CU_TENSOR_MAP_INTERLEAVE_NONE,
        CU_TENSOR_MAP_SWIZZLE_NONE, CU_TENSOR_MAP_L2_PROMOTION_NONE, CU_TENSOR_MAP_FLOAT_OOB_FILL_NONE);
  }
  Params prm{(const __nv_bfloat16*)d_in[2], (const __nv_bfloat16*)d_in[3], (const __nv_bfloat16*)d_in[0], (const __nv_bfloat16*)d_in[1], (__nv_bfloat16*)d_out};
  k1_main<<<132, 640, SM_TOTAL, cudaStreamPerThread>>>(mXA64, mXB, mWq, mWqkv, mQst, mOst, mO, mWoA, mWoB, mO16, mKV, prm);
}
```

```cpp
#include <cuda_runtime.h>
#include <cuda_bf16.h>
#include <cuda_fp16.h>
#include <cuda.h>
#include <stdint.h>

#define S_TOK 2048
#define D_MOD 512

__device__ __align__(1024) __nv_bfloat16 g_Q[2 * S_TOK * D_MOD];
__device__ __align__(1024) __nv_bfloat16 g_O[2 * S_TOK * D_MOD];
__device__ __align__(1024) uint4 g_KV[8 * S_TOK];
__device__ __align__(16) uint32_t g_stats[128];
__device__ __align__(16) float4 g_kvp[16 * 32 * 3 * 32];

__device__ __forceinline__ uint32_t smem_u32(const void* p) { return (uint32_t)__cvta_generic_to_shared(p); }
__device__ __forceinline__ void mbar_init(uint32_t bar, int cnt) { asm volatile("mbarrier.init.shared::cta.b64 [%0], %1;" :: "r"(bar), "r"(cnt) : "memory"); }
__device__ __forceinline__ void mbar_expect_tx(uint32_t bar, uint32_t bytes) { asm volatile("mbarrier.arrive.expect_tx.shared::cta.b64 _, [%0], %1;" :: "r"(bar), "r"(bytes) : "memory"); }
__device__ __forceinline__ void mbar_wait(uint32_t bar, uint32_t parity) {
  asm volatile("{\n.reg .pred p;\n.reg .u32 c;\nmov.u32 c, 0;\n"
               "LW_%=:\n"
               "mbarrier.try_wait.parity.shared::cta.b64 p, [%0], %1;\n"
               "@p bra LD_%=;\n"
               "add.u32 c, c, 1;\n"
               "setp.lt.u32 p, c, 4000000;\n"
               "@p bra LW_%=;\n"
               "trap;\n"
               "LD_%=:\n}\n" :: "r"(bar), "r"(parity) : "memory");
}
__device__ __forceinline__ void tma2d(uint32_t dst, const CUtensorMap* m, int c0, int c1, uint32_t bar) {
  asm volatile("cp.async.bulk.tensor.2d.shared::cluster.global.mbarrier::complete_tx::bytes [%0], [%1, {%3, %4}], [%2];"
               :: "r"(dst), "l"(m), "r"(bar), "r"(c0), "r"(c1) : "memory");
}
__device__ __forceinline__ void tma2d_store(const CUtensorMap* m, uint32_t src, int c0, int c1) {
  asm volatile("cp.async.bulk.tensor.2d.global.shared::cta.bulk_group [%0, {%2, %3}], [%1];"
               :: "l"(m), "r"(src), "r"(c0), "r"(c1) : "memory");
}
__device__ __forceinline__ void tma3d_store(const CUtensorMap* m, uint32_t src, int c0, int c1, int c2) {
  asm volatile("cp.async.bulk.tensor.3d.global.shared::cta.bulk_group [%0, {%2, %3, %4}], [%1];"
               :: "l"(m), "r"(src), "r"(c0), "r"(c1), "r"(c2) : "memory");
}
__device__ __forceinline__ void bulk_g2s(uint32_t dst, const void* src, uint32_t bytes, uint32_t bar) {
  asm volatile("cp.async.bulk.shared::cluster.global.mbarrier::complete_tx::bytes [%0], [%1], %2, [%3];"
               :: "r"(dst), "l"(src), "r"(bytes), "r"(bar) : "memory");
}
__device__ __forceinline__ void bulk_commit() { asm volatile("cp.async.bulk.commit_group;" ::: "memory"); }
__device__ __forceinline__ void bulk_wait_all() { asm volatile("cp.async.bulk.wait_group 0;" ::: "memory"); }
__device__ __forceinline__ void fence_async() { asm volatile("fence.proxy.async.shared::cta;" ::: "memory"); }
__device__ __forceinline__ void named_bar(int id, int n) { asm volatile("bar.sync %0, %1;" :: "r"(id), "r"(n) : "memory"); }
__device__ __forceinline__ void wg_fence() { asm volatile("wgmma.fence.sync.aligned;" ::: "memory"); }
__device__ __forceinline__ void wg_commit() { asm volatile("wgmma.commit_group.sync.aligned;" ::: "memory"); }
template <int n> __device__ __forceinline__ void wg_wait() { asm volatile("wgmma.wait_group.sync.aligned %0;" :: "n"(n) : "memory"); }
template <int n> __device__ __forceinline__ void fence_regs(float* r) {
#pragma unroll
  for (int i = 0; i < n; i++) asm volatile("" : "+f"(r[i]) :: "memory");
}
template <int n> __device__ __forceinline__ void fence_regs(uint32_t* r) {
#pragma unroll
  for (int i = 0; i < n; i++) asm volatile("" : "+r"(r[i]) :: "memory");
}
__device__ __forceinline__ uint64_t make_desc(uint32_t addr, uint32_t lbo, uint32_t sbo, uint32_t swz) {
  return (uint64_t)((addr & 0x3FFFF) >> 4) | ((uint64_t)(lbo >> 4) << 16) | ((uint64_t)(sbo >> 4) << 32) | ((uint64_t)swz << 62);
}
__device__ __forceinline__ float ex2f(float x) { float y; asm("ex2.approx.ftz.f32 %0, %1;" : "=f"(y) : "f"(x)); return y; }
__device__ __forceinline__ uint32_t pack_bf16(float lo, float hi) { uint32_t r; asm("cvt.rn.bf16x2.f32 %0, %1, %2;" : "=r"(r) : "f"(hi), "f"(lo)); return r; }
__device__ __forceinline__ uint32_t pack_f16(float lo, float hi) { uint32_t r; asm("cvt.rn.f16x2.f32 %0, %1, %2;" : "=r"(r) : "f"(hi), "f"(lo)); return r; }
__device__ __forceinline__ float bf_lo(uint32_t v) { return __uint_as_float(v << 16); }
__device__ __forceinline__ float bf_hi(uint32_t v) { return __uint_as_float(v & 0xFFFF0000u); }
__device__ __forceinline__ float rbf(float x) { return __bfloat162float(__float2bfloat16_rn(x)); }
__device__ __forceinline__ void stsm4(uint32_t a, uint32_t r0, uint32_t r1, uint32_t r2, uint32_t r3) {
  asm volatile("stmatrix.sync.aligned.m8n8.x4.shared.b16 [%0], {%1,%2,%3,%4};" :: "r"(a), "r"(r0), "r"(r1), "r"(r2), "r"(r3) : "memory");
}
__device__ __forceinline__ void stsm4t(uint32_t a, uint32_t r0, uint32_t r1, uint32_t r2, uint32_t r3) {
  asm volatile("stmatrix.sync.aligned.m8n8.x4.trans.shared.b16 [%0], {%1,%2,%3,%4};" :: "r"(a), "r"(r0), "r"(r1), "r"(r2), "r"(r3) : "memory");
}
__device__ __forceinline__ void mma_bf16(float* d, uint32_t a0, uint32_t a1, uint32_t a2, uint32_t a3, uint32_t b0, uint32_t b1) {
  asm volatile("mma.sync.aligned.m16n8k16.row.col.f32.bf16.bf16.f32 {%0,%1,%2,%3}, {%4,%5,%6,%7}, {%8,%9}, {%0,%1,%2,%3};"
               : "+f"(d[0]), "+f"(d[1]), "+f"(d[2]), "+f"(d[3]) : "r"(a0), "r"(a1), "r"(a2), "r"(a3), "r"(b0), "r"(b1));
}
template<int SD> __device__ __forceinline__ void wg_qs24(float* d, uint64_t da, uint64_t db) {
  asm volatile("wgmma.mma_async.sync.aligned.m64n24k16.f32.f16.f16 {%0,%1,%2,%3,%4,%5,%6,%7,%8,%9,%10,%11}, %12, %13, %14, 1, 1, 0, 0;"
   : "+f"(d[0]),"+f"(d[1]),"+f"(d[2]),"+f"(d[3]),"+f"(d[4]),"+f"(d[5]),"+f"(d[6]),"+f"(d[7]),"+f"(d[8]),"+f"(d[9]),"+f"(d[10]),"+f"(d[11])
   : "l"(da),"l"(db),"n"(SD));
}
template<int SD> __device__ __forceinline__ void wg_qs72(float* d, uint64_t da, uint64_t db) {
  asm volatile("wgmma.mma_async.sync.aligned.m64n72k16.f32.f16.f16 {%0,%1,%2,%3,%4,%5,%6,%7,%8,%9,%10,%11,%12,%13,%14,%15,%16,%17,%18,%19,%20,%21,%22,%23,%24,%25,%26,%27,%28,%29,%30,%31,%32,%33,%34,%35}, %36, %37, %38, 1, 1, 0, 0;"
   : "+f"(d[0]),"+f"(d[1]),"+f"(d[2]),"+f"(d[3]),"+f"(d[4]),"+f"(d[5]),"+f"(d[6]),"+f"(d[7]),"+f"(d[8]),"+f"(d[9]),"+f"(d[10]),"+f"(d[11]),"+f"(d[12]),"+f"(d[13]),"+f"(d[14]),"+f"(d[15]),"+f"(d[16]),"+f"(d[17]),"+f"(d[18]),"+f"(d[19]),"+f"(d[20]),"+f"(d[21]),"+f"(d[22]),"+f"(d[23]),"+f"(d[24]),"+f"(d[25]),"+f"(d[26]),"+f"(d[27]),"+f"(d[28]),"+f"(d[29]),"+f"(d[30]),"+f"(d[31]),"+f"(d[32]),"+f"(d[33]),"+f"(d[34]),"+f"(d[35])
   : "l"(da),"l"(db),"n"(SD));
}
template<int SD> __device__ __forceinline__ void wg_pv24(float* d, const uint32_t* a, uint64_t desc) {
  asm volatile("wgmma.mma_async.sync.aligned.m64n24k16.f32.bf16.bf16 {%0,%1,%2,%3,%4,%5,%6,%7,%8,%9,%10,%11}, {%12,%13,%14,%15}, %16, %17, 1, 1, 1;"
   : "+f"(d[0]),"+f"(d[1]),"+f"(d[2]),"+f"(d[3]),"+f"(d[4]),"+f"(d[5]),"+f"(d[6]),"+f"(d[7]),"+f"(d[8]),"+f"(d[9]),"+f"(d[10]),"+f"(d[11])
   : "r"(a[0]),"r"(a[1]),"r"(a[2]),"r"(a[3]),"l"(desc),"n"(SD));
}
template<int TA, int TB> __device__ __forceinline__ void wg_ss128(float* d, uint64_t da, uint64_t db, int sd) {
  asm volatile("{\n.reg .pred p;\nsetp.ne.b32 p, %66, 0;\n"
   "wgmma.mma_async.sync.aligned.m64n128k16.f32.bf16.bf16 {%0,%1,%2,%3,%4,%5,%6,%7,%8,%9,%10,%11,%12,%13,%14,%15,%16,%17,%18,%19,%20,%21,%22,%23,%24,%25,%26,%27,%28,%29,%30,%31,%32,%33,%34,%35,%36,%37,%38,%39,%40,%41,%42,%43,%44,%45,%46,%47,%48,%49,%50,%51,%52,%53,%54,%55,%56,%57,%58,%59,%60,%61,%62,%63}, %64, %65, p, 1, 1, %67, %68;\n}\n"
   : "+f"(d[0]),"+f"(d[1]),"+f"(d[2]),"+f"(d[3]),"+f"(d[4]),"+f"(d[5]),"+f"(d[6]),"+f"(d[7]),"+f"(d[8]),"+f"(d[9]),"+f"(d[10]),"+f"(d[11]),"+f"(d[12]),"+f"(d[13]),"+f"(d[14]),"+f"(d[15]),"+f"(d[16]),"+f"(d[17]),"+f"(d[18]),"+f"(d[19]),"+f"(d[20]),"+f"(d[21]),"+f"(d[22]),"+f"(d[23]),"+f"(d[24]),"+f"(d[25]),"+f"(d[26]),"+f"(d[27]),"+f"(d[28]),"+f"(d[29]),"+f"(d[30]),"+f"(d[31]),"+f"(d[32]),"+f"(d[33]),"+f"(d[34]),"+f"(d[35]),"+f"(d[36]),"+f"(d[37]),"+f"(d[38]),"+f"(d[39]),"+f"(d[40]),"+f"(d[41]),"+f"(d[42]),"+f"(d[43]),"+f"(d[44]),"+f"(d[45]),"+f"(d[46]),"+f"(d[47]),"+f"(d[48]),"+f"(d[49]),"+f"(d[50]),"+f"(d[51]),"+f"(d[52]),"+f"(d[53]),"+f"(d[54]),"+f"(d[55]),"+f"(d[56]),"+f"(d[57]),"+f"(d[58]),"+f"(d[59]),"+f"(d[60]),"+f"(d[61]),"+f"(d[62]),"+f"(d[63])
   : "l"(da),"l"(db),"r"(sd),"n"(TA),"n"(TB));
}
template<int TA, int TB> __device__ __forceinline__ void wg_ss8(float* d, uint64_t da, uint64_t db, int sd) {
  asm volatile("{\n.reg .pred p;\nsetp.ne.b32 p, %6, 0;\n"
   "wgmma.mma_async.sync.aligned.m64n8k16.f32.bf16.bf16 {%0,%1,%2,%3}, %4, %5, p, 1, 1, %7, %8;\n}\n"
   : "+f"(d[0]),"+f"(d[1]),"+f"(d[2]),"+f"(d[3])
   : "l"(da),"l"(db),"r"(sd),"n"(TA),"n"(TB));
}


__device__ __forceinline__ uint32_t phi2(float a, float b) {
  uint32_t r, e;
  asm("cvt.rn.relu.bf16x2.f32 %0, %1, %2;" : "=r"(r) : "f"(b), "f"(a));
  e = pack_bf16(ex2f(a * 1.4426950408889634f), ex2f(b * 1.4426950408889634f));
  asm("add.rn.bf16x2 %0, %0, %1;" : "+r"(e) : "r"(0x35863586u));
  asm("min.NaN.bf16x2 %0, %0, %1;" : "+r"(e) : "r"(0x3F803F80u));
  asm("add.rn.bf16x2 %0, %0, %1;" : "+r"(e) : "r"(r));
  return e;
}

__device__ __forceinline__ void mbar_wait_long(uint32_t bar, uint32_t parity) {
  asm volatile("{\n.reg .pred p;\n.reg .u32 c;\nmov.u32 c, 0;\n"
               "LW_%=:\n"
               "mbarrier.try_wait.parity.shared::cta.b64 p, [%0], %1, 10000;\n"
               "@p bra LD_%=;\n"
               "add.u32 c, c, 1;\n"
               "setp.lt.u32 p, c, 400000;\n"
               "@p bra LW_%=;\n"
               "trap;\n"
               "LD_%=:\n}\n" :: "r"(bar), "r"(parity) : "memory");
}
__device__ __forceinline__ void mbar_arrive(uint32_t bar) { asm volatile("mbarrier.arrive.shared::cta.b64 _, [%0];" :: "r"(bar) : "memory"); }
__device__ __forceinline__ void named_arrive(int id, int n) { asm volatile("bar.arrive %0, %1;" :: "r"(id), "r"(n) : "memory"); }
__device__ __forceinline__ void fence_async_all() { asm volatile("fence.proxy.async.global;" ::: "memory"); }
__device__ __forceinline__ void flag_add(uint32_t* f) { asm volatile("fence.acq_rel.gpu;\nred.relaxed.gpu.global.add.u32 [%0], 1;" :: "l"(f) : "memory"); }
#define PUBLISH(f) asm volatile("fence.proxy.async.global;\nred.relaxed.gpu.global.add.u32 [%0], 1;" :: "l"(f) : "memory")
__device__ __forceinline__ void flag_wait(const uint32_t* f, uint32_t target) {
  uint32_t v;
#pragma unroll 1
  for (int it = 0;; it++) {
    asm volatile("ld.acquire.gpu.global.u32 %0, [%1];" : "=r"(v) : "l"(f) : "memory");
    if ((int32_t)(v - target) >= 0) break;
    if (it > 2000000) __trap();
    __nanosleep(64);
  }
}
__device__ __forceinline__ bool mbar_test(uint32_t bar, uint32_t parity) {
  uint32_t ok;
  asm volatile("{\n.reg .pred p;\nmbarrier.test_wait.parity.shared::cta.b64 p, [%1], %2;\nselp.b32 %0, 1, 0, p;\n}\n" : "=r"(ok) : "r"(bar), "r"(parity) : "memory");
  return ok;
}
__device__ __forceinline__ bool elect_one() {
  uint32_t p;
  asm volatile("{\n.reg .pred P;\nelect.sync _|P, 0xFFFFFFFF;\nselp.b32 %0, 1, 0, P;\n}\n" : "=r"(p));
  return p;
}
__device__ __forceinline__ void lds4(uint32_t a, uint32_t* r) {
  asm volatile("ld.shared.v4.b32 {%0,%1,%2,%3}, [%4];" : "=r"(r[0]), "=r"(r[1]), "=r"(r[2]), "=r"(r[3]) : "r"(a) : "memory");
}
__device__ __forceinline__ uint32_t lds1(uint32_t a) { uint32_t r; asm volatile("ld.shared.b32 %0, [%1];" : "=r"(r) : "r"(a) : "memory"); return r; }
__device__ __forceinline__ void sts1(uint32_t a, uint32_t v) { asm volatile("st.shared.b32 [%0], %1;" :: "r"(a), "r"(v) : "memory"); }
__device__ __forceinline__ void sts4(uint32_t a, uint32_t r0, uint32_t r1, uint32_t r2, uint32_t r3) {
  asm volatile("st.shared.v4.b32 [%0], {%1,%2,%3,%4};" :: "r"(a), "r"(r0), "r"(r1), "r"(r2), "r"(r3) : "memory");
}
__device__ __forceinline__ void ldsm4(uint32_t a, uint32_t* r) {
  asm volatile("ldmatrix.sync.aligned.m8n8.x4.shared.b16 {%0,%1,%2,%3}, [%4];" : "=r"(r[0]), "=r"(r[1]), "=r"(r[2]), "=r"(r[3]) : "r"(a) : "memory");
}
__device__ __forceinline__ float rcpf(float x) { float y; asm("rcp.approx.ftz.f32 %0, %1;" : "=f"(y) : "f"(x)); return y; }
__device__ __forceinline__ uint32_t hfma2(uint32_t a, uint32_t b, uint32_t c) { uint32_t r; asm("fma.rn.f16x2 %0, %1, %2, %3;" : "=r"(r) : "r"(a), "r"(b), "r"(c)); return r; }
__device__ __forceinline__ uint32_t hadd2(uint32_t a, uint32_t b) { uint32_t r; asm("add.rn.f16x2 %0, %1, %2;" : "=r"(r) : "r"(a), "r"(b)); return r; }

#define STEPK 96
#define GIMAP(i) ((((i) & 1) << 2) | (((i) >> 1) & 3) | ((i) & 8))
#define QSCALE 0.36067376022224085f
#define SMAGIC (512.0f + 2.0f * (191.0f - 30.0f - 1.5823545f))
#define VSHIFT 1073741824.0f

__device__ uint32_t g_epoch[132];
__device__ uint32_t g_flag[288 * 8];
#define FLAG_KV (g_flag)
#define FLAG_KV2 (g_flag + 8 * 8)
#define FLAG_B(h) (g_flag + (4 + (h)) * 8)
#define FLAG_OA(cta, pass) (g_flag + (16 + (cta) * 2 + (pass)) * 8)
#define FLAG_LM(i) (g_flag + (272 + (i)) * 8)

#define SM_TOTAL (224 * 1024 + 3072)
#define OFF_K 0
#define OFF_F 65536
#define OFF_V 131072
#define OFF_MISC (224 * 1024)

#define BAR_FULL(s) (bars + 8 * (s))
#define BAR_FW(s, w) (bars + 408 + 8 * ((s) * 4 + (w)))
#define BAR_EMPTY(s) (bars + 24 + 8 * (s))
#define BAR_KV(c) (bars + 48 + 8 * (c))
#define BAR_E0(i) (bars + 200 + 8 * (i))
#define BAR_BDONE (bars + 80)
#define BAR_Q (bars + 88)
#define BAR_GO (bars + 96)
#define BAR_Q2 (bars + 104)
#define BAR_OD(p) (bars + 112 + 8 * (p))
#define BAR_CL(c) (bars + 128 + 8 * (c))
#define BAR_TE(i) (bars + 168 + 8 * (i))
#define BAR_RL (bars + 184)
#define BAR_TF(g) (bars + 224 + 8 * (g))
#define BAR_XA(w) (bars + 352 + 8 * (w))
#define BAR_VB(c) (bars + 384 + 8 * (c))

__device__ __forceinline__ uint32_t exp2_pair_fix(float d0, float d1, uint32_t c63, uint32_t m1) {
  uint32_t w, y, s, r;
  asm("prmt.b32 %0, %1, %2, 0x6521;" : "=r"(w) : "r"(__float_as_uint(d0)), "r"(__float_as_uint(d1)));
  asm("lop3.b32 %0, %1, 0x007F007F, %2, 0xEA;" : "=r"(y) : "r"(w), "r"(c63));
  asm("mad.lo.u32 %0, %1, %2, %3;" : "=r"(s) : "r"(y), "r"(m1), "r"(w));
  asm("fma.rn.bf16x2 %0, %1, %2, %3;" : "=r"(r) : "r"(w), "r"(y), "r"(s));
  return r;
}

#define X_PR(i) asm volatile("prmt.b32 %0, %1, %2, 0x6521;" : "=r"(w[i]) : "r"(__float_as_uint(Sp[2 * (i)])), "r"(__float_as_uint(Sp[2 * (i) + 1])));
#define X_LO(i) asm volatile("lop3.b32 %0, %1, 0x007F007F, %2, 0xEA;" : "=r"(y[i]) : "r"(w[i]), "r"(c63));
#define X_IM(i) asm volatile("mad.lo.u32 %0, %1, %2, %3;" : "=r"(z[i]) : "r"(y[i]), "r"(m1), "r"(w[i]));
#define X_FM(i) asm volatile("fma.rn.bf16x2 %0, %1, %2, %3;" : "=r"(P[6 + (i)]) : "r"(w[i]), "r"(y[i]), "r"(z[i]));
#define X_MU(i) asm volatile("ex2.approx.ftz.f32 %0, %1;" : "=f"(e[i]) : "f"(Sm[i]));
#define X_PK(i) asm volatile("cvt.rn.bf16x2.f32 %0, %1, %2;" : "=r"(P[i]) : "f"(e[2 * (i) + 1]), "f"(e[2 * (i)]));

__device__ __forceinline__ void attn_slow(const __nv_bfloat16* xa, const __nv_bfloat16* wq, uint32_t dst) {
  const int t = threadIdx.x & 127;
  const int row = t >> 1, half = t & 1;
  float q[16];
  {
    float a[8];
#pragma unroll
    for (int i = 0; i < 8; i++) a[i] = 0.f;
#pragma unroll 1
    for (int k = 0; k < D_MOD; k++) {
      const float x = __bfloat162float(xa[(size_t)row * D_MOD + k]);
      const uint4 w = *(const uint4*)(wq + (size_t)k * D_MOD + half * 8);
      const uint32_t ww[4] = {w.x, w.y, w.z, w.w};
#pragma unroll
      for (int i = 0; i < 4; i++) { a[2 * i] = fmaf(x, bf_lo(ww[i]), a[2 * i]); a[2 * i + 1] = fmaf(x, bf_hi(ww[i]), a[2 * i + 1]); }
    }
#pragma unroll
    for (int i = 0; i < 8; i++) {
      const float mine = rbf(a[i]), other = __shfl_xor_sync(~0u, mine, 1);
      q[i] = half ? other : mine; q[8 + i] = half ? mine : other;
    }
  }
  float m = -INFINITY, l = 0.f, o[16];
#pragma unroll
  for (int i = 0; i < 16; i++) o[i] = 0.f;
#pragma unroll 1
  for (int j = half * 1024; j < half * 1024 + 1024; j++) {
    uint4 ka = g_KV[4 * S_TOK + j], kb = g_KV[5 * S_TOK + j];
    uint4 va = g_KV[6 * S_TOK + j], vb = g_KV[7 * S_TOK + j];
    uint32_t kk[8] = {ka.x, ka.y, ka.z, ka.w, kb.x, kb.y, kb.z, kb.w};
    uint32_t vv[8] = {va.x, va.y, va.z, va.w, vb.x, vb.y, vb.z, vb.w};
    float s = 0.f;
#pragma unroll
    for (int i = 0; i < 8; i++) { s = fmaf(q[2 * i], bf_lo(kk[i]), s); s = fmaf(q[2 * i + 1], bf_hi(kk[i]), s); }
    s = rbf(s) * 0.25f;
    if (s > m) {
      float c = __expf(m - s);
      l *= c;
#pragma unroll
      for (int i = 0; i < 16; i++) o[i] *= c;
      m = s;
    }
    float p = __expf(s - m);
    l += p;
#pragma unroll
    for (int i = 0; i < 8; i++) { o[2 * i] = fmaf(p, bf_lo(vv[i]), o[2 * i]); o[2 * i + 1] = fmaf(p, bf_hi(vv[i]), o[2 * i + 1]); }
  }
  float m2 = __shfl_xor_sync(~0u, m, 1);
  float mm = fmaxf(m, m2);
  float c = __expf(m - mm);
  l *= c; l += __shfl_xor_sync(~0u, l, 1);
  float inv = 1.f / l;
  uint32_t r[8];
#pragma unroll
  for (int i = 0; i < 16; i++) { o[i] *= c; o[i] += __shfl_xor_sync(~0u, o[i], 1); o[i] *= inv; }
#pragma unroll
  for (int i = 0; i < 8; i++) r[i] = pack_bf16(o[2 * i], o[2 * i + 1]);
  if (half == 0) sts4(dst, r[0], r[1], r[2], r[3]); else sts4(dst, r[4], r[5], r[6], r[7]);
  fence_async();
}

struct Params { const __nv_bfloat16* wk; const __nv_bfloat16* wv; const __nv_bfloat16* xa; const __nv_bfloat16* wq; __nv_bfloat16* out; };

__device__ __forceinline__ void helper_cta(const int h, const uint32_t sb, const uint32_t bars, const int wg, const int w4,
                                           const CUtensorMap* mQ, const CUtensorMap* mOs) {
  const int lane = threadIdx.x & 31;
  mbar_wait(BAR_GO, 0);
  const int cb = wg & 1, col = h * 128 + cb * 64, row0 = S_TOK + (wg >> 1) * 1024;
  const uint32_t buf = sb + wg * 49152;
  if (w4 == 0 && elect_one()) {
    fence_async_all();
#pragma unroll 1
    for (int u = 0; u < 3; u++) {
      mbar_expect_tx(BAR_TF(wg * 3 + u), 16384);
      tma2d(buf + u * 16384, mQ, col, row0 + u * 128, BAR_TF(wg * 3 + u));
    }
  }
  const int head = h * 8 + cb * 4 + w4;
  float4 a0 = make_float4(0, 0, 0, 0), a1 = a0, a2 = a0;
#pragma unroll 8
  for (int tt = 0; tt < 16; tt++) {
    const float4* src = g_kvp + ((tt * 32 + head) * 3) * 32 + lane;
    float4 u = src[0], v = src[32], w = src[64];
    a0.x += u.x; a0.y += u.y; a0.z += u.z; a0.w += u.w;
    a1.x += v.x; a1.y += v.y; a1.z += v.z; a1.w += v.w;
    a2.x += w.x; a2.y += w.y; a2.z += w.z; a2.w += w.w;
  }
  const uint32_t b00 = pack_bf16(a0.x, a0.y), b01 = pack_bf16(a0.z, a0.w);
  const uint32_t b10 = pack_bf16(a1.x, a1.y), b11 = pack_bf16(a1.z, a1.w);
  const uint32_t bz0 = pack_bf16(a2.x, a2.y), bz1 = pack_bf16(a2.z, a2.w);
  const int m = lane >> 3, r = lane & 7;
  const uint32_t off = ((m & 1) * 8 + r) * 128 + (((w4 * 2 + (m >> 1)) ^ r) << 4);
  int s = 0, ph = 0;
#pragma unroll 1
  for (int u = 0; u < 8; u++) {
    const uint32_t bb = buf + s * 16384;
    mbar_wait(BAR_TF(wg * 3 + s), ph);
#pragma unroll
    for (int mt = 0; mt < 8; mt++) {
      uint32_t a[4];
      ldsm4(bb + mt * 2048 + off, a);
      float n0[4] = {0, 0, 0, 0}, n1[4] = {0, 0, 0, 0}, dn[4] = {0, 0, 0, 0};
      mma_bf16(dn, a[0], a[1], a[2], a[3], bz0, bz1);
      mma_bf16(n0, a[0], a[1], a[2], a[3], b00, b01);
      mma_bf16(n1, a[0], a[1], a[2], a[3], b10, b11);
      const float i0 = rcpf(dn[0] + 1e-6f), i1 = rcpf(dn[2] + 1e-6f);
      stsm4(bb + mt * 2048 + off, pack_bf16(n0[0] * i0, n0[1] * i0), pack_bf16(n0[2] * i1, n0[3] * i1),
            pack_bf16(n1[0] * i0, n1[1] * i0), pack_bf16(n1[2] * i1, n1[3] * i1));
    }
    fence_async();
    named_bar(wg + 1, 128);
    if (w4 == 0 && lane == 0) {
      tma2d_store(mOs, bb, col, row0 + u * 128);
      bulk_commit();
      if (u >= 1 && u + 2 < 8) {
        asm volatile("cp.async.bulk.wait_group.read 1;" ::: "memory");
        const int sp = s == 0 ? 2 : s - 1;
        mbar_expect_tx(BAR_TF(wg * 3 + sp), 16384);
        tma2d(buf + sp * 16384, mQ, col, row0 + (u + 2) * 128, BAR_TF(wg * 3 + sp));
      }
    }
    __syncwarp();
    if (++s == 3) { s = 0; ph ^= 1; }
  }
  if (w4 == 0 && lane == 0) {
    bulk_wait_all();
    fence_async_all();
    flag_add(FLAG_LM((h * 2 + cb) * 2 + (wg >> 1)));
  }
}

#define STAGE(s) (sb + (2 - (s)) * 65536)
__device__ __forceinline__ uint32_t xa_addr(uint32_t sb, int kb) {
  return sb + (kb >= 1 && kb <= 4 ? OFF_V + 65536 + (kb - 1) * 8192 : 16384 + (kb == 5 ? OFF_K : (kb == 6 ? OFF_V : OFF_F)));
}
#define XA7_TMP (sb + OFF_K + 8192)
#define WKV_TMP (sb + OFF_K)
template <int TR> __device__ __forceinline__ void proj_kb(float* acc, uint32_t aA, uint32_t aB, int first) {
  const uint64_t da = make_desc(aA, TR ? 8192 : 16, 1024, 1);
  const uint64_t db = make_desc(aB, TR ? 16 : 8192, 1024, 1);
  wg_fence();
#pragma unroll
  for (int k = 0; k < 4; k++) wg_ss128<TR, 1 - TR>(acc, da + k * (TR ? 128 : 2), db + k * (TR ? 2 : 128), k != 0 || !first);
  wg_commit();
}
template <int TR> __device__ __forceinline__ void proj_loop(float* acc, uint32_t sb, uint32_t bars, uint32_t offA, uint32_t offB,
                                                            int wg, uint32_t sWKV, const CUtensorMap* mW, int col, bool w0, const CUtensorMap* mX, int xrow) {
  int s = 0, ph = 0;
#pragma unroll 1
  for (int kb = 0; kb < 8; kb++) {
    if (kb == 2 * TR)
  {
    float kv[4];
    mbar_wait(BAR_XA(wg), 0);
    const uint64_t da0 = make_desc(xa_addr(sb, 2 * wg), 16, 1024, 1);
    const uint64_t da1 = make_desc(wg == 3 ? XA7_TMP : xa_addr(sb, 2 * wg + 1), 16, 1024, 1);
    const uint64_t db = make_desc(sWKV + wg * 2048, 128, 128, 0);
    wg_fence();
#pragma unroll
    for (int k = 0; k < 8; k++) wg_ss8<0, 1>(kv, (k < 4 ? da0 : da1) + (k & 3) * 2, db + k * 16, k != 0);
    wg_commit();
    wg_wait<0>();
    fence_regs<4>(kv);
    named_bar(wg + 1, 128);
    sts4(sWKV + threadIdx.x * 16, __float_as_uint(kv[0]), __float_as_uint(kv[1]), __float_as_uint(kv[2]), __float_as_uint(kv[3]));
    __syncwarp();
    if ((threadIdx.x & 31) == 0) mbar_arrive(BAR_GO);
  }
    mbar_wait(BAR_FW(s, wg), ph);
    if (TR == 0) mbar_wait(BAR_XA(kb >> 1), 0); else mbar_wait(BAR_FULL(s), ph);
    proj_kb<TR>(acc, TR ? STAGE(s) + offA : xa_addr(sb, kb), STAGE(s) + offB, kb == 0);
    wg_wait<0>();
    if (w0 && elect_one()) {
      if (kb < 5) {
        mbar_expect_tx(BAR_FW(s, wg), TR ? 8192 : (kb == 4 ? 24576 : 16384));
        tma2d(STAGE(s) + (TR ? offA : 0), mW, col, (kb + 3) * 64, BAR_FW(s, wg));
        if (TR == 0) {
          tma2d(STAGE(s) + 8192, mW, col + 64, (kb + 3) * 64, BAR_FW(s, wg));
          if (kb == 4) tma2d(STAGE(s) + 16384, mX, 448, xrow, BAR_FW(s, wg));
        }
      }
      if (TR ? kb < 7 : (kb == 5 || kb == 6)) mbar_arrive(TR ? BAR_EMPTY(s) : BAR_E0(kb - 5));
      if (TR == 0 && kb == 4) mbar_arrive(BAR_VB(1));
    }
    __syncwarp();
    if (++s == 3) { s = 0; ph ^= 1; }
  }
  wg_wait<0>();
  fence_regs<64>(acc);
}

__device__ __forceinline__ uint32_t tail_slots(int isB, int n) {
  if (n < 4) return n < 2 ? (n == 0 ? 0x0D0C0B0Au : 0x04000F0Eu) : (n == 2 ? 0x18141008u : 0x15110501u);
  if (isB) return n < 6 ? (n == 4 ? 0x19120602u : 0x0D0C0B0Au) : (n == 6 ? 0x04000F0Eu : 0x13070316u);
  return n < 6 ? (n == 4 ? 0x1902031Au : 0x12061307u) : (n == 6 ? 0x16091B17u : 0x0D0C0B0Au);
}

__device__ __forceinline__ void take_role(uint32_t sM, int wg) {
  uint32_t r;
  asm volatile("atom.shared.add.u32 %0, [%1], 1;" : "=r"(r) : "r"(sM + 20) : "memory");
  sts1(sM + 32 + wg * 4, r);
}

__global__ void __launch_bounds__(640, 1)
k1_main(const __grid_constant__ CUtensorMap mXA64, const __grid_constant__ CUtensorMap mXB,
        const __grid_constant__ CUtensorMap mWq, const __grid_constant__ CUtensorMap mWqkv,
        const __grid_constant__ CUtensorMap mQst, const __grid_constant__ CUtensorMap mOst,
        const __grid_constant__ CUtensorMap mO, const __grid_constant__ CUtensorMap mWoA,
        const __grid_constant__ CUtensorMap mWoB,
        const __grid_constant__ CUtensorMap mO16, const __grid_constant__ CUtensorMap mKV, const Params prm) {
  if (threadIdx.x >= 608 && threadIdx.x < 612) {
    const CUtensorMap* pm = &mXA64 + (threadIdx.x - 608);
    asm volatile("prefetch.tensormap [%0];" :: "l"(pm) : "memory");
  }
  extern __shared__ __align__(1024) uint8_t smem_raw[];
  const uint32_t sb = smem_u32(smem_raw);
  if (sb & 1023u) __trap();
  const uint32_t bars = sb + OFF_MISC, sM = bars + 512, sT = bars + 640;
  const int tid = threadIdx.x, warp = __shfl_sync(~0u, tid >> 5, 0), wg = warp >> 2, w4 = warp & 3, lane = tid & 31;
  const bool helper = blockIdx.x >= 128;
  const int G = blockIdx.x >> 4, gi = GIMAP(blockIdx.x & 15);
  const int tbA = G * 4 + (gi >> 2), hg = gi & 3;
  const int ttB = (G >> 1) * 4 + (gi >> 2), hq = (G & 1) * 4 + (gi & 3);
  const int isB = tbA & 1, tok0 = (tbA >> 1) * 128;
  auto issue = [&](int kb, int part) {
    const uint32_t st = STAGE(kb);
    if (part & 1) {
      mbar_expect_tx(BAR_FW(kb, 0), 16384);
      tma2d(st, &mWq, hg * 128, kb * 64, BAR_FW(kb, 0));
      tma2d(st + 8192, &mWq, hg * 128 + 64, kb * 64, BAR_FW(kb, 0));
    }
    if (part & 2) {
      mbar_expect_tx(BAR_FULL(kb), 16384);
      tma2d(st + 49152, &mXB, kb * 64, ttB * 128, BAR_FULL(kb));
      mbar_expect_tx(BAR_FW(kb, 1), 8192);
      tma2d(st + 24576, &mWqkv, hq * 64, kb * 64, BAR_FW(kb, 1));
    }
    if (part & 4) {
      mbar_expect_tx(BAR_FW(kb, 2), 8192);
      tma2d(st + 32768, &mWqkv, 512 + hq * 64, kb * 64, BAR_FW(kb, 2));
      mbar_expect_tx(BAR_FW(kb, 3), 8192);
      tma2d(st + 40960, &mWqkv, 1024 + hq * 64, kb * 64, BAR_FW(kb, 3));
    }
  };
  const uint32_t sOne = sb + OFF_V + 65536, sWKV = WKV_TMP;
  if (warp >= 16) {
    if (warp == 17) {
      if (elect_one()) {
        mbar_init(BAR_BDONE, 8); mbar_init(BAR_Q, 6); mbar_init(BAR_GO, helper ? 1 : 16); mbar_init(BAR_Q2, 1);
        mbar_init(BAR_OD(0), 16); mbar_init(BAR_OD(1), 16); mbar_init(BAR_CL(0), 1); mbar_init(BAR_FULL(1), 1); mbar_init(BAR_FULL(2), 1);
        mbar_init(BAR_E0(0), 1); mbar_init(BAR_E0(1), 1);
#pragma unroll
        for (int i = 0; i < 4; i++) mbar_init(BAR_CL(i + 1), i == 0 ? 5 : 4);
#pragma unroll
        for (int i = 0; i < 3; i++) { mbar_init(BAR_EMPTY(i), 3); mbar_init(BAR_KV(i), 1); mbar_init(BAR_VB(i), i == 2 ? 4 : 1); }
        sts1(sM + 20, 0);
        asm volatile("fence.mbarrier_init.release.cluster;" ::: "memory");
      }
    } else if (warp == 18) {
      if (elect_one()) {
#pragma unroll
        for (int i = 0; i < 2; i++) mbar_init(BAR_TE(i), 2);
        mbar_init(BAR_RL, 1);
#pragma unroll
        for (int i = 4; i < 12; i++) mbar_init(BAR_FW(0, i), 1);
#pragma unroll
        for (int i = 0; i < 16; i++) mbar_init(BAR_TF(i), 1);
        asm volatile("fence.mbarrier_init.release.cluster;" ::: "memory");
      }
    } else if (warp == 16 && !helper && elect_one()) {
#pragma unroll
      for (int w = 0; w < 4; w++) { mbar_init(BAR_XA(w), 1); mbar_init(BAR_FW(0, w), 1); }
      mbar_init(BAR_FULL(0), 1);
      asm volatile("fence.mbarrier_init.release.cluster;" ::: "memory");
      issue(0, 6);
#pragma unroll
      for (int w = 0; w < 1; w++) {
        mbar_expect_tx(BAR_XA(w), 16384);
        tma2d(xa_addr(sb, 2 * w), &mXA64, w * 128, tbA * 64, BAR_XA(w));
        tma2d(w == 3 ? XA7_TMP : xa_addr(sb, 2 * w + 1), &mXA64, w * 128 + 64, tbA * 64, BAR_XA(w));
        if (w == 0) issue(0, 1);
      }
    }
  } else if (!helper) {
    const uint4 v = __ldg((const uint4*)(hg >= 2 ? prm.wv : prm.wk) + tid * 2 + (hg & 1));
    sts4(sWKV + tid * 16, v.x, v.y, v.z, v.w);
    fence_async();
  }
  __syncthreads();
  if (wg == 4) {
    if (w4 == 0 && !helper && elect_one()) {
      issue(1, 7);
#pragma unroll
      for (int w = 1; w < 4; w++) {
        mbar_expect_tx(BAR_XA(w), 16384);
        tma2d(xa_addr(sb, 2 * w), &mXA64, w * 128, tbA * 64, BAR_XA(w));
        tma2d(w == 3 ? XA7_TMP : xa_addr(sb, 2 * w + 1), &mXA64, w * 128 + 64, tbA * 64, BAR_XA(w));
      }
      issue(2, 6);
    }
    asm volatile("setmaxnreg.dec.sync.aligned.u32 32;");
    const uint32_t ep = g_epoch[blockIdx.x] + 1;
    if (helper) {
      if (w4 == 0 && elect_one()) {
        flag_wait(FLAG_B(blockIdx.x - 128), ep * 32);
        fence_async_all();
        mbar_arrive(BAR_GO);
        g_epoch[blockIdx.x] = ep;
      }
      return;
    }
    if (w4 != 0) {
      mbar_wait(BAR_GO, 0);
#pragma unroll 1
      for (int qd = w4 & 3; qd >= 0; qd -= 3) {
        uint32_t a[4], b[4];
        float c[4];
        const uint32_t ad = sWKV + (qd * 32 + lane) * 16;
        lds4(ad, a);
        lds4(ad + 2048, b);
#pragma unroll
        for (int i = 0; i < 4; i++) c[i] = __uint_as_float(a[i]) + __uint_as_float(b[i]);
        lds4(ad + 4096, a);
        lds4(ad + 6144, b);
#pragma unroll
        for (int i = 0; i < 4; i++) c[i] += __uint_as_float(a[i]) + __uint_as_float(b[i]);
        sts1(sT + qd * 256 + lane * 4, pack_bf16(c[0], c[1]));
        sts1(sT + qd * 256 + 128 + lane * 4, pack_bf16(c[2], c[3]));
      }
      named_bar(9, 96);
      if (w4 == 3 && elect_one()) issue(2, 1);
    }
    auto write_ones = [&]() {
      mbar_wait_long(BAR_VB(1), 0);
      int c = ((w4 & 1) * 32 + lane);
#pragma unroll 4
      for (int key = c; key < S_TOK; key += 64) {
        sts4(sOne + key * 16, c < 24 ? 0x00003F80u : 0x00004E80u, 0u, 0u, 0u);
        c += 64; if (c >= STEPK) c -= STEPK;
      }
      fence_async();
      __syncwarp();
      if (lane == 0) mbar_arrive(BAR_Q);
    };
    if (w4 == 0) {
      int s = 0, ph = 0;
#pragma unroll 1
      for (int kb = 3; kb < 8; kb++) {
        mbar_wait(BAR_EMPTY(s), ph);
        if (elect_one()) {
          mbar_expect_tx(BAR_FULL(s), 16384);
          tma2d(STAGE(s) + 49152, &mXB, kb * 64, ttB * 128, BAR_FULL(s));
        }
        if (++s == 3) { s = 0; ph ^= 1; }
      }
      flag_wait(FLAG_KV, ep * 128);
      fence_async_all();
#pragma unroll 1
      for (int m = 0; m < 2; m++) {
        mbar_wait(m == 0 ? BAR_EMPTY(2) : BAR_EMPTY(0), 1 - m);
        mbar_wait(BAR_E0(m), 0);
        if (elect_one()) {
          const uint32_t fb = m == 0 ? BAR_KV(0) : BAR_VB(0);
          mbar_expect_tx(fb, 2 * 7 * STEPK * 16);
#pragma unroll
          for (int p = 0; p < 2; p++) bulk_g2s(sb + m * OFF_V + p * 32768, g_KV + (m * 2 + p) * S_TOK, 7 * STEPK * 16, fb);
        }
      }
      mbar_wait(BAR_Q, 0);
      if (elect_one()) {
#pragma unroll
        for (int c = 1; c < 3; c++) {
          const int k0 = c == 1 ? 7 * STEPK : 13 * STEPK, k1 = c == 1 ? 13 * STEPK : S_TOK;
          const uint32_t bytes = (k1 - k0) * 16;
          mbar_expect_tx(BAR_KV(c), 4 * bytes);
#pragma unroll
          for (int p = 0; p < 4; p++)
            bulk_g2s(sb + (p >> 1) * OFF_V + (p & 1) * 32768 + k0 * 16, g_KV + p * S_TOK + k0, bytes, BAR_KV(c));
        }
      }
      mbar_wait_long(BAR_CL(1), 0);
      flag_wait(isB ? FLAG_LM((lane & 7) * 2 + (tbA >> 4)) : FLAG_OA(tbA * 4 + (lane & 7), 0), ep);
      __syncwarp();
      fence_async_all();
      const CUtensorMap* mW = isB ? &mWoB : &mWoA;
#pragma unroll 1
      for (int it = 0; it < 8; it++) {
        const int n = (!isB && it >= 6) ? 13 - it : it;
        uint32_t wb = BAR_CL(n < 3 ? 0 : (n == 3 ? 2 : 3));
        if (isB) { if (n >= 5) wb = n == 7 ? BAR_CL(4) : BAR_TE(n - 5); }
        else if (n >= 6) wb = n == 6 ? BAR_CL(4) : BAR_TE(0);
        if (it < 6) mbar_wait_long(wb, 0); else mbar_wait(wb, 0);
        const uint32_t sl = tail_slots(isB, n), fb = BAR_TF(n);
        const bool withX = isB || n < 4;
        const int k0 = isB ? n * 64 : (n < 4 ? n * 128 : ((hg + n) & 3) * 128 + 64);
        if (elect_one()) {
          mbar_expect_tx(fb, withX ? 32768 : 16384);
          if (withX) {
            tma2d(sb + (sl & 255) * 8192, &mO, k0, isB * S_TOK + tok0, fb);
            tma2d(sb + ((sl >> 8) & 255) * 8192, &mO, k0, isB * S_TOK + tok0 + 64, fb);
          }
          tma2d(sb + ((sl >> 16) & 255) * 8192, mW, hg * 128, k0, fb);
          tma2d(sb + (sl >> 24) * 8192, mW, hg * 128 + 64, k0, fb);
        }
      }
      if (lane == 0) g_epoch[blockIdx.x] = ep;
    } else if (w4 == 3) {
      write_ones();
      flag_wait(FLAG_KV2, ep * 128);
      const uint4 a = *(const uint4*)(g_stats + lane * 4);
      const float kmax2 = __uint_as_float(__reduce_max_sync(~0u, a.x)) + __uint_as_float(__reduce_max_sync(~0u, a.y));
      const float vmax = __uint_as_float(__reduce_max_sync(~0u, max(a.z, a.w)));
      const float lv = vmax > 0.f ? __log2f(vmax) : 0.f;
      const float lim = fminf(90.f, fminf(91.f + lv, 95.f - lv));
      float thr = -1.f;
      if (vmax < 1e27f && kmax2 <= 65536.f && lim > 2.f) thr = fminf(60000.f, (lim * lim - 1.f) / (kmax2 * 1.02f + 1e-30f));
      mbar_wait_long(BAR_VB(2), 0);
      uint32_t nmax = 0;
#pragma unroll 2
      for (int i = 0; i < 16; i++) {
        uint32_t x[4], y[4];
        const uint32_t ad = sb + OFF_F + i * 1024 + (lane >> 3) * 256 + (lane & 7) * 16;
        lds4(ad, x); lds4(ad + 128, y);
        uint32_t n = hfma2(x[0], x[0], hfma2(x[1], x[1], hfma2(x[2], x[2], hfma2(x[3], x[3], 0u))));
        n = hfma2(y[0], y[0], hfma2(y[1], y[1], hfma2(y[2], y[2], hfma2(y[3], y[3], n))));
        n = hadd2(n, n >> 16);
        nmax = max(nmax, n & 0x7FFFu);
      }
      nmax = __reduce_max_sync(~0u, nmax);
      const bool ok = __half2float(__ushort_as_half((unsigned short)nmax)) <= thr;
      if (lane == 0) { sts1(sM + 16, ok ? 1u : 0u); mbar_arrive(BAR_Q2); }
    } else {
      const int tok = (w4 - 1) * 32 + lane;
      int step, col;
      if ((tbA & 3) == 0) {
        const int b8 = tbA >> 2;
        if (tok < 22) { step = tok; col = 24 + b8; }
        else { const int c = tok >= 43; step = tok - 22 - 21 * c; col = 32 + b8 * 2 + c; }
      } else {
        const int b24 = (tbA >> 2) * 3 + (tbA & 3) - 1;
        if (tok < 42) { const int c = tok >= 21; step = tok - 21 * c; col = 48 + b24 * 2 + c; }
        else { step = tok - 42; col = b24; }
      }
      const int kap = step * STEPK + col;
      const bool chained = col >= 24;
      uint32_t v[4], o[4];
      lds4(sT + tok * 16, v);
      float st = 0.f;
      if (hg < 2) {
        o[0] = o[1] = o[2] = o[3] = 0;
        if (chained && step > 0) lds4(sT + tok * 16 - 16, o);
        const float sc = chained ? 2.f : 1.f;
#pragma unroll
        for (int u = 0; u < 4; u++) {
          const float x = bf_lo(v[u]), y = bf_hi(v[u]);
          st += x * x + y * y;
          o[u] = pack_f16((x - bf_lo(o[u])) * sc, (y - bf_hi(o[u])) * sc);
        }
      } else {
        const float sc = chained ? VSHIFT : 1.f;
#pragma unroll
        for (int u = 0; u < 4; u++) { float x = bf_lo(v[u]), y = bf_hi(v[u]); st += fabsf(x) + fabsf(y); o[u] = pack_bf16(x * sc, y * sc); }
      }
      {
        const bool tl = (tbA & 3) == 0;
        const int run = tl ? (tok < 22 ? 0 : (tok < 43 ? 1 : 2)) : (tok < 21 ? 0 : (tok < 42 ? 1 : 2));
        const int h2 = (tl ? run == 0 : run == 2) ? 11 : 10;
        const uint32_t img = sT + run * 512;
        named_bar(10, 64);
        if (step < 11) sts4(img + step * 16, o[0], o[1], o[2], o[3]);
        if (step >= h2) sts4(img + 256 + (step - h2) * 16, o[0], o[1], o[2], o[3]);
        if (step == 0) sts1(sM + 48 + run * 4, col * 8 + (h2 << 16));
        fence_async();
        named_bar(10, 64);
        if (w4 == 1 && elect_one()) {
#pragma unroll
          for (int r = 0; r < 3; r++) {
            const uint32_t cw = lds1(sM + 48 + r * 4);
            tma3d_store(&mKV, sT + r * 512, cw & 0xFFFF, 0, hg);
            tma3d_store(&mKV, sT + r * 512 + 256, cw & 0xFFFF, cw >> 16, hg);
          }
          bulk_commit();
          bulk_wait_all();
          PUBLISH(FLAG_KV);
        }
        __syncwarp();
      }
      g_KV[(4 + hg) * S_TOK + kap] = make_uint4(v[0], v[1], v[2], v[3]);
      const uint32_t um = __reduce_max_sync(~0u, __float_as_uint(st) & 0x7FFFFFFFu);
      if (w4 == 2) {
        if (lane == 0) sts1(sM + 24, um);
        named_arrive(11, 64);
        write_ones();
        if (!isB) {
          mbar_wait_long(BAR_CL(3), 0);
          mbar_wait_long(BAR_RL, 0);
          uint32_t pend = 0xFE;
          const int li = lane & 7;
          const uint32_t* fl = FLAG_OA((tbA + (li & 1)) * 4 + ((hg + (li >> 1)) & 3), 1);
#pragma unroll 1
          for (int it = 0; pend; it++) {
            uint32_t fv;
            asm volatile("ld.acquire.gpu.global.u32 %0, [%1];" : "=r"(fv) : "l"(fl) : "memory");
            uint32_t go = __ballot_sync(~0u, (int32_t)(fv - ep) >= 0 && mbar_test(li >= 6 ? BAR_TE(0) : BAR_CL(4), 0)) & pend;
            pend &= ~go;
            if (go) fence_async_all();
#pragma unroll 1
            while (go) {
              const int b = __ffs(go) - 1;
              go &= go - 1;
              const uint32_t slot = (tail_slots(0, 4 + (b >> 1)) >> (8 * (b & 1))) & 255;
              if (elect_one()) {
                mbar_expect_tx(BAR_TF(8 + b), 8192);
                tma2d(sb + slot * 8192, &mO, ((hg + (b >> 1)) & 3) * 128 + 64, tok0 + (b & 1) * 64, BAR_TF(8 + b));
              }
            }
            if (it > 2000000) __trap();
          }
        }
      }
      else {
        named_bar(11, 64);
        if (elect_one()) {
          g_stats[tbA * 4 + hg] = max(um, lds1(sM + 24));
          flag_add(FLAG_KV2);
          mbar_wait_long(BAR_BDONE, 0);
          tma2d_store(&mQst, sb + OFF_F + 49152, hq * 64, S_TOK + ttB * 128);
          bulk_commit();
          bulk_wait_all();
          fence_async_all();
          flag_add(FLAG_B(hq >> 1));
          mbar_wait(BAR_Q, 0);
          mbar_arrive(BAR_CL(0));
#pragma unroll 1
          for (int p = 0; p < 2; p++) {
            mbar_wait_long(BAR_OD(p), 0);
            if (p == 0) {
#pragma unroll
              for (int w = 0; w < 4; w++) tma2d_store(&mO16, sb + OFF_F + w * 2048, hg * 128 + w * 16, tbA * 64);
            } else {
              tma2d_store(&mO, sb + 26 * 8192, hg * 128 + 64, tbA * 64);
            }
            bulk_commit();
            bulk_wait_all();
            if (p == 0) mbar_arrive(BAR_CL(1));
            PUBLISH(FLAG_OA(tbA * 4 + hg, p));
          }
        }
      }
    }
    return;
  }
  if (helper) { helper_cta(blockIdx.x - 128, sb, bars, wg, w4, &mQst, &mOst); return; }

  {
    float acc[64];
    if (wg == 0) proj_loop<0>(acc, sb, bars, 16384, 0, wg, sWKV, &mWq, hg * 128, w4 == 0, &mXA64, tbA * 64);
    else proj_loop<1>(acc, sb, bars, 16384 + wg * 8192, 49152, wg, sWKV, &mWqkv, (wg - 1) * 512 + hq * 64, w4 == 0, &mXA64, 0);
    const uint32_t sF = sb + OFF_F;
    const uint32_t qa = sF + w4 * 512 + ((lane >> 3) & 1) * 256 + (lane >> 4) * 128 + (lane & 7) * 16;
    if (wg == 0) {
#pragma unroll
      for (int hd = 0; hd < 4; hd++)
        stsm4(qa + hd * 2048, pack_f16(acc[8 * hd] * QSCALE, acc[8 * hd + 1] * QSCALE), pack_f16(acc[8 * hd + 2] * QSCALE, acc[8 * hd + 3] * QSCALE),
              pack_f16(acc[8 * hd + 4] * QSCALE, acc[8 * hd + 5] * QSCALE), pack_f16(acc[8 * hd + 6] * QSCALE, acc[8 * hd + 7] * QSCALE));
      fence_async();
      __syncwarp();
      if (lane == 0) mbar_arrive(BAR_Q);
    } else {
      if (wg != 3) named_arrive(6, 384);
      if (wg != 1) named_arrive(8, 384);
    }
    asm volatile("setmaxnreg.inc.sync.aligned.u32 112;");
    fence_regs<64>(acc);
    if (wg == 0) {
#pragma unroll
      for (int hd = 4; hd < 8; hd++)
        stsm4(qa + hd * 2048, pack_f16(acc[8 * hd] * QSCALE, acc[8 * hd + 1] * QSCALE), pack_f16(acc[8 * hd + 2] * QSCALE, acc[8 * hd + 3] * QSCALE),
              pack_f16(acc[8 * hd + 4] * QSCALE, acc[8 * hd + 5] * QSCALE), pack_f16(acc[8 * hd + 6] * QSCALE, acc[8 * hd + 7] * QSCALE));
      fence_async();
      __syncwarp();
      if (lane == 0) mbar_arrive(BAR_VB(2));
    } else if (wg == 3) {
      named_bar(6, 384);
      const int t = tid & 127;
#pragma unroll
      for (int j = 0; j < 8; j++)
        sts4(sF + 24576 + j * 2048 + t * 16, pack_bf16(acc[8 * j], acc[8 * j + 1]), pack_bf16(acc[8 * j + 2], acc[8 * j + 3]),
             pack_bf16(acc[8 * j + 4], acc[8 * j + 5]), pack_bf16(acc[8 * j + 6], acc[8 * j + 7]));
      named_arrive(7, 256);
    } else {
      uint32_t p[32];
#pragma unroll
      for (int i = 0; i < 32; i++) p[i] = phi2(acc[2 * i], acc[2 * i + 1]);
      if (wg == 1) {
        named_bar(8, 384);
        const int m = lane >> 3, r = lane & 7;
#pragma unroll
        for (int j = 0; j < 16; j += 2) {
          const int tok = (j + (m >> 1)) * 8 + r;
          const int chunk = w4 * 2 + (m & 1);
          stsm4t(sF + 49152 + tok * 128 + ((chunk ^ r) << 4), p[2 * j], p[2 * j + 1], p[2 * j + 2], p[2 * j + 3]);
        }
        fence_async();
      } else {
        named_bar(7, 256);
        float kv0[4] = {0, 0, 0, 0}, kv1[4] = {0, 0, 0, 0}, z0[4] = {0, 0, 0, 0}, z1[4] = {0, 0, 0, 0};
        const uint32_t one = 0x3F803F80u;
        const int t = tid & 127;
#pragma unroll
        for (int j = 0; j < 8; j++) {
          uint32_t a[4];
          lds4(sF + 24576 + j * 2048 + t * 16, a);
          mma_bf16(kv0, a[0], a[1], a[2], a[3], p[4 * j], p[4 * j + 2]);
          mma_bf16(kv1, a[0], a[1], a[2], a[3], p[4 * j + 1], p[4 * j + 3]);
          mma_bf16(z0, one, one, one, one, p[4 * j], p[4 * j + 2]);
          mma_bf16(z1, one, one, one, one, p[4 * j + 1], p[4 * j + 3]);
        }
        float4* dst = g_kvp + ((ttB * 32 + hq * 4 + w4) * 3) * 32 + lane;
        dst[0] = make_float4(kv0[0], kv0[1], kv1[0], kv1[1]);
        dst[32] = make_float4(kv0[2], kv0[3], kv1[2], kv1[3]);
        dst[64] = make_float4(z0[0], z0[1], z1[0], z1[1]);
      }
      __syncwarp();
      if (lane == 0) mbar_arrive(BAR_BDONE);
    }
  }

  bool safe = true;
  {
    const uint32_t c63 = 0x1F801F80u + (threadIdx.x >> 20);
    const uint32_t m1 = (gridDim.x >> 20) - 1u;
    const uint64_t dK0 = make_desc(sb + OFF_K, 32768, 128, 0);
    const uint64_t dV0 = make_desc(sb + OFF_V, 128, 32768, 0);
    constexpr uint32_t dKV = ((2048u - 8u)  __H0__ ) + STEPK - (OFF_V - OFF_K) / 16;
    float Sm[12], Sp[36], O[12];
    uint32_t P[24];
    uint64_t dQ = make_desc(sb + OFF_F + wg * 2048, 128, 256, 0);
#pragma unroll
    for (int i = 0; i < 36; i++) Sp[i] = SMAGIC;
#pragma unroll
    for (int i = 0; i < 12; i++) Sm[i] = 0.f;
    fence_regs<12>(Sm); fence_regs<36>(Sp);
    mbar_wait(BAR_Q, 0);
    mbar_wait(BAR_KV(0), 0);
    wg_fence();
    wg_qs72<1>(Sp, dQ, dK0 + 24);
    wg_qs24<0>(Sm, dQ, dK0);
    wg_commit();
    wg_wait<0>();
    fence_regs<12>(Sm); fence_regs<36>(Sp);
#pragma unroll 1
    for (int pass = 0; pass < 2; pass++) {
#pragma unroll
      for (int i = 0; i < 12; i++) O[i] = 0.f;
      fence_regs<12>(O);
      uint32_t vlo = (uint32_t)dV0;
#pragma unroll 1
      for (int seg = 0; seg < 4; seg++) {
        if (pass == 0) {
          if (seg < 3) mbar_wait(seg == 0 ? BAR_VB(0) : BAR_KV(seg), 0);
        } else if (seg >= 1) {
          if ((tid & 127) == 0) {
            mbar_arrive(BAR_CL(seg));
            if (seg == 3) take_role(sM, wg);
          }
          __syncwarp();
        }
        const uint32_t vend = vlo + (seg == 3 ? 3 : 6) * STEPK;
#pragma unroll 1
        for (; vlo != vend; vlo += 3 * STEPK) {
          uint64_t dK, dV;
          asm("mov.b64 %0, {%1, %2};" : "=l"(dK) : "r"(vlo + dKV), "r"(8u));
          asm("mov.b64 %0, {%1, %2};" : "=l"(dV) : "r"(vlo), "r"(2048u));
#pragma unroll
          for (int u = 0; u < 3; u++) {
          { uint32_t w[18], y[18], z[18]; float e[12];
            X_MU(0) X_PR(0) X_LO(0) X_IM(0) X_MU(1) X_FM(0) X_PR(1) X_LO(1) X_IM(1) X_MU(2) X_FM(1) X_PR(2)
            X_LO(2) X_MU(3) X_IM(2) X_FM(2) X_PR(3) X_LO(3) X_PK(0) X_MU(4) X_IM(3) X_FM(3) X_PR(4) X_LO(4)
            X_MU(5) X_IM(4) X_FM(4) X_PR(5) X_PK(1) X_MU(6) X_LO(5) X_IM(5) X_FM(5) X_PR(6) X_MU(7) X_LO(6)
            X_IM(6) X_FM(6) X_MU(8) X_PR(7) X_PK(2) X_LO(7) X_IM(7) X_FM(7) X_MU(9) X_PR(8) X_LO(8) X_IM(8)
            X_FM(8) X_PK(3) X_MU(10) X_PR(9) X_LO(9) X_IM(9) X_MU(11) X_FM(9) X_PR(10) X_LO(10) X_IM(10) X_PK(4)
            X_FM(10) X_PR(11) X_LO(11) X_IM(11) X_FM(11) X_PR(12) X_LO(12) X_PK(5) X_IM(12) X_FM(12) X_PR(13) X_LO(13)
            X_IM(13) X_FM(13) X_PR(14) X_LO(14) X_IM(14) X_FM(14) X_PR(15) X_LO(15) X_IM(15) X_FM(15) X_PR(16) X_LO(16)
            X_IM(16) X_FM(16) X_PR(17) X_LO(17) X_IM(17) X_FM(17) }
          fence_regs<24>(P);
          wg_fence();
          wg_pv24<1>(O, &P[20], dV + u * STEPK + 80);
          wg_pv24<1>(O, &P[16], dV + u * STEPK + 64);
          wg_pv24<1>(O, &P[12], dV + u * STEPK + 48);
          wg_pv24<1>(O, &P[8], dV + u * STEPK + 32);
          wg_pv24<1>(O, &P[4], dV + u * STEPK + 16);
          wg_pv24<1>(O, &P[0], dV + u * STEPK + 0);
          wg_qs72<1>(Sp, dQ, dK + u * STEPK + 24);
          wg_qs24<0>(Sm, dQ, dK + u * STEPK);
          wg_commit();
          wg_wait<0>();
          fence_regs<12>(Sm); fence_regs<36>(Sp); fence_regs<12>(O); fence_regs<24>(P);
          }
        }
      }
#pragma unroll
      for (int i = 0; i < 6; i++) P[i] = pack_bf16(ex2f(Sm[2 * i]), ex2f(Sm[2 * i + 1]));
      P[6] = exp2_pair_fix(Sp[0], Sp[1], c63, m1);
      P[7] = exp2_pair_fix(Sp[2], Sp[3], c63, m1);
      fence_regs<8>(P);
      const uint32_t sO = pass == 0 ? sb + OFF_F + wg * 2048 + w4 * 512 + (lane & 15) * 32 + (lane >> 4) * 16
                                    : sb + 26 * 8192 + (w4 * 16 + (lane & 15)) * 128 + (((wg * 2 + (lane >> 4)) ^ (lane & 7)) << 4);
      dQ += 512;
      wg_fence();
      wg_pv24<1>(O, &P[0], dV0 + 21 * STEPK);
      wg_pv24<1>(O, &P[4], dV0 + 21 * STEPK + 16);
      wg_commit();
#pragma unroll
      for (int i = 0; i < 36; i++) Sp[i] = SMAGIC;
      fence_regs<36>(Sp);
      mbar_wait(pass == 0 ? BAR_Q2 : BAR_CL(3), 0);
      wg_fence();
      wg_qs72<1>(Sp, dQ, dK0 + 24);
      wg_qs24<0>(Sm, dQ, dK0);
      wg_commit();
      wg_wait<1>();
      fence_regs<12>(O);
      const float l0 = __shfl_sync(~0u, O[8], lane & ~3), l1 = __shfl_sync(~0u, O[10], lane & ~3);
      const float i0 = rcpf(l0), i1 = rcpf(l1);
      stsm4(sO,
            pack_bf16(O[0] * i0, O[1] * i0), pack_bf16(O[2] * i1, O[3] * i1),
            pack_bf16(O[4] * i0, O[5] * i0), pack_bf16(O[6] * i1, O[7] * i1));
      fence_async();
      {
        safe = __all_sync(~0u, lds1(sM + 16) != 0);
      }
      if (safe && lane == 0) mbar_arrive(BAR_OD(pass));
      wg_wait<0>();
      fence_regs<12>(Sm); fence_regs<36>(Sp);
      if (!safe) break;
    }
  }
  if (!safe) {
    if ((tid & 127) == 0) { mbar_arrive(BAR_CL(1)); mbar_arrive(BAR_CL(2)); mbar_arrive(BAR_CL(3)); take_role(sM, wg); }
#pragma unroll 1
    for (int pass = 0; pass < 2; pass++) {
      const int t = tid & 127;
      mbar_wait(BAR_CL(3), 0);
      attn_slow(prm.xa + (size_t)tbA * 64 * D_MOD, prm.wq + (hg * 8 + pass * 4 + wg) * 16,
                pass == 0 ? sb + OFF_F + wg * 2048 + t * 16
                          : sb + 26 * 8192 + (t >> 1) * 128 + (((wg * 2 + (t & 1)) ^ ((t >> 1) & 7)) << 4));
      __syncwarp();
      if (lane == 0) mbar_arrive(BAR_OD(pass));
    }
  }

  {
    named_bar(wg + 1, 128);
    if ((tid & 127) == 0) mbar_arrive(BAR_CL(4));
    const int role = __shfl_sync(~0u, lds1(sM + 32 + wg * 4), 0);
    const int m = lane >> 3, r = lane & 7;
    const uint32_t stoff = (w4 * 16 + (m & 1) * 8 + r) * 128;
    if (role < 2) {
      if (role == 0 && (tid & 127) == 0) mbar_arrive(BAR_RL);
      if (!isB || role == 1) mbar_wait(BAR_CL(4), 0);
      float acc[64];
#pragma unroll 1
      for (int n = 0; n < 8; n++) {
        const uint32_t sl = tail_slots(isB, n);
        const uint32_t w0 = (sl >> 16) & 255, w1 = sl >> 24;
        const uint64_t da = make_desc(sb + ((sl >> (8 * role)) & 255) * 8192, 16, 1024, 1);
        const uint64_t db = make_desc(sb + w0 * 8192, (w1 - w0) * 8192, 1024, 1);
        mbar_wait(BAR_TF(n), 0);
        if (!isB && n >= 4) mbar_wait(n == 4 && role == 0 ? BAR_OD(1) : BAR_TF(2 * n + role), 0);
        wg_fence();
#pragma unroll
        for (int k = 0; k < 4; k++) wg_ss128<0, 1>(acc, da + k * 2, db + k * 128, (n | k) != 0);
        wg_commit();
        wg_wait<1>();
        if ((n == 1 || n == 2) && (tid & 127) == 0) mbar_arrive(BAR_TE(n - 1));
        __syncwarp();
      }
      wg_wait<0>();
      fence_regs<64>(acc);
      const uint32_t x0 = sb + (role ? 16 : 8) * 8192, x1 = sb + (role ? 5 : 1) * 8192;
#pragma unroll
      for (int j = 0; j < 16; j += 2)
        stsm4((j < 8 ? x0 : x1) + stoff + ((((j & 7) + (m >> 1)) ^ r) << 4),
              pack_bf16(acc[4 * j], acc[4 * j + 1]), pack_bf16(acc[4 * j + 2], acc[4 * j + 3]),
              pack_bf16(acc[4 * j + 4], acc[4 * j + 5]), pack_bf16(acc[4 * j + 6], acc[4 * j + 7]));
      __syncwarp();
      uint4* dst = (uint4*)(prm.out + (size_t)(tok0 + role * 64 + w4 * 16 + (lane >> 4)) * 1024 + isB * 512 + hg * 128) + (lane & 15);
      const uint32_t src = ((lane & 8) ? x1 : x0) + (w4 * 16 + (lane >> 4)) * 128;
#pragma unroll
      for (int i = 0; i < 8; i++) {
        uint32_t v[4];
        lds4(src + i * 256 + (((lane & 7) ^ ((2 * i + (lane >> 4)) & 7)) << 4), v);
        dst[i * 256] = make_uint4(v[0], v[1], v[2], v[3]);
      }
    }
  }
}

__device__ __nv_bfloat16 g_T[S_TOK * 1536];
__device__ float g_Z[32 * 272];
__global__ void fb_gemm(const __nv_bfloat16* A, const __nv_bfloat16* B, __nv_bfloat16* C, int N, int ldc) {
  __shared__ float sa[16][17], sbm[16][17];
  const int tx = threadIdx.x & 15, ty = threadIdx.x >> 4, row = blockIdx.y * 16 + ty, col = blockIdx.x * 16 + tx;
  float acc = 0.f;
  for (int k0 = 0; k0 < D_MOD; k0 += 16) {
    sa[ty][tx] = __bfloat162float(A[(size_t)row * D_MOD + k0 + tx]);
    sbm[ty][tx] = __bfloat162float(B[(size_t)(k0 + ty) * N + col]);
    __syncthreads();
    for (int k = 0; k < 16; k++) acc = fmaf(sa[ty][k], sbm[k][tx], acc);
    __syncthreads();
  }
  C[(size_t)row * ldc + col] = __float2bfloat16_rn(acc);
}
__global__ void fb_attn() {
  const int r = blockIdx.x * blockDim.x + threadIdx.x;
  float q[16], o[16], m = -INFINITY, l = 0.f;
  for (int i = 0; i < 16; i++) { q[i] = __bfloat162float(g_Q[(size_t)r * 16 + i]); o[i] = 0.f; }
  for (int j = 0; j < S_TOK; j++) {
    float s = 0.f;
    for (int i = 0; i < 16; i++) s = fmaf(q[i], __bfloat162float(g_T[j * 32 + i]), s);
    s = rbf(s) * 0.25f;
    const float mn = fmaxf(m, s), c = __expf(m - mn), p = __expf(s - mn);
    l = l * c + p; m = mn;
    for (int i = 0; i < 16; i++) o[i] = fmaf(p, __bfloat162float(g_T[j * 32 + 16 + i]), o[i] * c);
  }
  for (int i = 0; i < 16; i++) g_O[(size_t)r * 16 + i] = __float2bfloat16_rn(o[i] / l);
}
__device__ __forceinline__ float fb_phi(__nv_bfloat16 x) { const float t = __bfloat162float(x); return bf_lo(phi2(t, t)); }
__global__ void fb_kv() {
  const int h = blockIdx.x, t = threadIdx.x, d = t < 256 ? t >> 4 : t - 256, e = t & 15;
  float acc = 0.f;
  for (int s = 0; s < S_TOK; s++)
    acc = fmaf(fb_phi(g_T[(size_t)s * 1536 + 512 + h * 16 + d]), t < 256 ? __bfloat162float(g_T[(size_t)s * 1536 + 1024 + h * 16 + e]) : 1.f, acc);
  g_Z[h * 272 + t] = rbf(acc);
}
__global__ void fb_lin() {
  const int idx = blockIdx.x * blockDim.x + threadIdx.x, s = idx >> 9, c = idx & 511, h = c >> 4, e = c & 15;
  float num = 0.f, den = 0.f;
  for (int d = 0; d < 16; d++) {
    const float p = fb_phi(g_T[(size_t)s * 1536 + h * 16 + d]);
    num = fmaf(p, g_Z[h * 272 + d * 16 + e], num); den = fmaf(p, g_Z[h * 272 + 256 + d], den);
  }
  g_O[(size_t)S_TOK * D_MOD + idx] = __float2bfloat16_rn(num / (den + 1e-6f));
}

typedef CUresult (*EncodeFn)(CUtensorMap*, CUtensorMapDataType, cuuint32_t, void*, const cuuint64_t*, const cuuint64_t*,
                             const cuuint32_t*, const cuuint32_t*, CUtensorMapInterleave, CUtensorMapSwizzle,
                             CUtensorMapL2promotion, CUtensorMapFloatOOBfill);

static void make_map(EncodeFn enc, CUtensorMap* m, const void* ptr, uint64_t cols, uint64_t rows, uint32_t bc, uint32_t br,
                     CUtensorMapSwizzle sw = CU_TENSOR_MAP_SWIZZLE_128B) {
  cuuint64_t dims[2] = {cols, rows};
  cuuint64_t strides[1] = {cols * 2};
  cuuint32_t box[2] = {bc, br};
  cuuint32_t es[2] = {1, 1};
  enc(m, CU_TENSOR_MAP_DATA_TYPE_BFLOAT16, 2, (void*)ptr, dims, strides, box, es, CU_TENSOR_MAP_INTERLEAVE_NONE,
      sw, CU_TENSOR_MAP_L2_PROMOTION_L2_256B, CU_TENSOR_MAP_FLOAT_OOB_FILL_NONE);
}

extern "C" void kernel_launch(void* const* d_in, const int* in_sizes, int n_in, void* d_out, int out_size) {
  (void)in_sizes; (void)n_in; (void)out_size;
  static EncodeFn enc = nullptr;
  static void* pQ = nullptr; static void* pO = nullptr; static void* pT = nullptr; static void* pK = nullptr;
  static bool fused = false;
  if (!enc) {
    void* fn = nullptr; cudaDriverEntryPointQueryResult qr;
    cudaGetDriverEntryPoint("cuTensorMapEncodeTiled", &fn, cudaEnableDefault, &qr);
    enc = (EncodeFn)fn;
    cudaGetSymbolAddress(&pQ, g_Q);
    cudaGetSymbolAddress(&pO, g_O);
    cudaGetSymbolAddress(&pT, g_T);
    cudaGetSymbolAddress(&pK, g_KV);
    cudaFuncSetAttribute(k1_main, cudaFuncAttributeMaxDynamicSharedMemorySize, SM_TOTAL);
    int dev = 0, sms = 0, occ = 0;
    cudaGetDevice(&dev);
    cudaDeviceGetAttribute(&sms, cudaDevAttrMultiProcessorCount, dev);
    cudaOccupancyMaxActiveBlocksPerMultiprocessor(&occ, k1_main, 640, SM_TOTAL);
    fused = sms * occ >= 132;
  }
  if (!fused) {
    typedef const __nv_bfloat16* CB; typedef __nv_bfloat16* MB;
    cudaStream_t st = cudaStreamPerThread;
    fb_gemm<<<dim3(32, 128), 256, 0, st>>>((CB)d_in[0], (CB)d_in[1], (MB)pQ, 512, 512);
    fb_gemm<<<dim3(1, 128), 256, 0, st>>>((CB)d_in[0], (CB)d_in[2], (MB)pT, 16, 32);
    fb_gemm<<<dim3(1, 128), 256, 0, st>>>((CB)d_in[0], (CB)d_in[3], (MB)pT + 16, 16, 32);
    fb_attn<<<512, 128, 0, st>>>();
    fb_gemm<<<dim3(96, 128), 256, 0, st>>>((CB)d_in[5], (CB)d_in[6], (MB)pT, 1536, 1536);
    fb_kv<<<32, 272, 0, st>>>();
    fb_lin<<<4096, 256, 0, st>>>();
    fb_gemm<<<dim3(32, 128), 256, 0, st>>>((CB)pO, (CB)d_in[4], (MB)d_out, 512, 1024);
    fb_gemm<<<dim3(32, 128), 256, 0, st>>>((CB)pO + S_TOK * D_MOD, (CB)d_in[7], (MB)d_out + 512, 512, 1024);
    return;
  }
  CUtensorMap mXA64, mXB, mWq, mWqkv, mQst, mO, mOst, mWoA, mWoB, mO16, mKV;
  make_map(enc, &mXA64, d_in[0], 512, 2048, 64, 64);
  make_map(enc, &mWq, d_in[1], 512, 512, 64, 64);
  make_map(enc, &mWoA, d_in[4], 512, 512, 64, 64);
  make_map(enc, &mXB, d_in[5], 512, 2048, 64, 128);
  make_map(enc, &mWqkv, d_in[6], 1536, 512, 64, 64);
  make_map(enc, &mWoB, d_in[7], 512, 512, 64, 64);
  make_map(enc, &mQst, pQ, 512, 4096, 64, 128);
  make_map(enc, &mO, pO, 512, 4096, 64, 64);
  make_map(enc, &mOst, pO, 512, 4096, 64, 128);
  make_map(enc, &mO16, pO, 512, 4096, 16, 64, CU_TENSOR_MAP_SWIZZLE_NONE);
  {
    cuuint64_t dims[3] = {768, 22, 4};
    cuuint64_t strides[2] = {1536, 32768};
    cuuint32_t box[3] = {8, 11, 1};
    cuuint32_t es[3] = {1, 1, 1};
    enc(&mKV, CU_TENSOR_MAP_DATA_TYPE_BFLOAT16, 3, pK, dims, strides, box, es, CU_TENSOR_MAP_INTERLEAVE_NONE,
        CU_TENSOR_MAP_SWIZZLE_NONE, CU_TENSOR_MAP_L2_PROMOTION_NONE, CU_TENSOR_MAP_FLOAT_OOB_FILL_NONE);
  }
  Params prm{(const __nv_bfloat16*)d_in[2], (const __nv_bfloat16*)d_in[3], (const __nv_bfloat16*)d_in[0], (const __nv_bfloat16*)d_in[1], (__nv_bfloat16*)d_out};
  k1_main<<<132, 640, SM_TOTAL, cudaStreamPerThread>>>(mXA64, mXB, mWq, mWqkv, mQst, mOst, mO, mWoA, mWoB, mO16, mKV, prm);
}
```

```cpp
#include <cuda_runtime.h>
#include <cuda_bf16.h>
#include <cuda_fp16.h>
#include <cuda.h>
#include <stdint.h>

#define S_TOK 2048
#define D_MOD 512

__device__ __align__(1024) __nv_bfloat16 g_Q[2 * S_TOK * D_MOD];
__device__ __align__(1024) __nv_bfloat16 g_O[2 * S_TOK * D_MOD];
__device__ __align__(1024) uint4 g_KV[8 * S_TOK];
__device__ __align__(16) uint32_t g_stats[128];
__device__ __align__(16) float4 g_kvp[16 * 32 * 3 * 32];

__device__ __forceinline__ uint32_t smem_u32(const void* p) { return (uint32_t)__cvta_generic_to_shared(p); }
__device__ __forceinline__ void mbar_init(uint32_t bar, int cnt) { asm volatile("mbarrier.init.shared::cta.b64 [%0], %1;" :: "r"(bar), "r"(cnt) : "memory"); }
__device__ __forceinline__ void mbar_expect_tx(uint32_t bar, uint32_t bytes) { asm volatile("mbarrier.arrive.expect_tx.shared::cta.b64 _, [%0], %1;" :: "r"(bar), "r"(bytes) : "memory"); }
__device__ __forceinline__ void mbar_wait(uint32_t bar, uint32_t parity) {
  asm volatile("{\n.reg .pred p;\n.reg .u32 c;\nmov.u32 c, 0;\n"
               "LW_%=:\n"
               "mbarrier.try_wait.parity.shared::cta.b64 p, [%0], %1;\n"
               "@p bra LD_%=;\n"
               "add.u32 c, c, 1;\n"
               "setp.lt.u32 p, c, 4000000;\n"
               "@p bra LW_%=;\n"
               "trap;\n"
               "LD_%=:\n}\n" :: "r"(bar), "r"(parity) : "memory");
}
__device__ __forceinline__ void tma2d(uint32_t dst, const CUtensorMap* m, int c0, int c1, uint32_t bar) {
  asm volatile("cp.async.bulk.tensor.2d.shared::cluster.global.mbarrier::complete_tx::bytes [%0], [%1, {%3, %4}], [%2];"
               :: "r"(dst), "l"(m), "r"(bar), "r"(c0), "r"(c1) : "memory");
}
__device__ __forceinline__ void tma2d_store(const CUtensorMap* m, uint32_t src, int c0, int c1) {
  asm volatile("cp.async.bulk.tensor.2d.global.shared::cta.bulk_group [%0, {%2, %3}], [%1];"
               :: "l"(m), "r"(src), "r"(c0), "r"(c1) : "memory");
}
__device__ __forceinline__ void tma3d_store(const CUtensorMap* m, uint32_t src, int c0, int c1, int c2) {
  asm volatile("cp.async.bulk.tensor.3d.global.shared::cta.bulk_group [%0, {%2, %3, %4}], [%1];"
               :: "l"(m), "r"(src), "r"(c0), "r"(c1), "r"(c2) : "memory");
}
__device__ __forceinline__ void bulk_g2s(uint32_t dst, const void* src, uint32_t bytes, uint32_t bar) {
  asm volatile("cp.async.bulk.shared::cluster.global.mbarrier::complete_tx::bytes [%0], [%1], %2, [%3];"
               :: "r"(dst), "l"(src), "r"(bytes), "r"(bar) : "memory");
}
__device__ __forceinline__ void bulk_commit() { asm volatile("cp.async.bulk.commit_group;" ::: "memory"); }
__device__ __forceinline__ void bulk_wait_all() { asm volatile("cp.async.bulk.wait_group 0;" ::: "memory"); }
__device__ __forceinline__ void fence_async() { asm volatile("fence.proxy.async.shared::cta;" ::: "memory"); }
__device__ __forceinline__ void named_bar(int id, int n) { asm volatile("bar.sync %0, %1;" :: "r"(id), "r"(n) : "memory"); }
__device__ __forceinline__ void wg_fence() { asm volatile("wgmma.fence.sync.aligned;" ::: "memory"); }
__device__ __forceinline__ void wg_commit() { asm volatile("wgmma.commit_group.sync.aligned;" ::: "memory"); }
template <int n> __device__ __forceinline__ void wg_wait() { asm volatile("wgmma.wait_group.sync.aligned %0;" :: "n"(n) : "memory"); }
template <int n> __device__ __forceinline__ void fence_regs(float* r) {
#pragma unroll
  for (int i = 0; i < n; i++) asm volatile("" : "+f"(r[i]) :: "memory");
}
template <int n> __device__ __forceinline__ void fence_regs(uint32_t* r) {
#pragma unroll
  for (int i = 0; i < n; i++) asm volatile("" : "+r"(r[i]) :: "memory");
}
__device__ __forceinline__ uint64_t make_desc(uint32_t addr, uint32_t lbo, uint32_t sbo, uint32_t swz) {
  return (uint64_t)((addr & 0x3FFFF) >> 4) | ((uint64_t)(lbo >> 4) << 16) | ((uint64_t)(sbo >> 4) << 32) | ((uint64_t)swz << 62);
}
__device__ __forceinline__ float ex2f(float x) { float y; asm("ex2.approx.ftz.f32 %0, %1;" : "=f"(y) : "f"(x)); return y; }
__device__ __forceinline__ uint32_t pack_bf16(float lo, float hi) { uint32_t r; asm("cvt.rn.bf16x2.f32 %0, %1, %2;" : "=r"(r) : "f"(hi), "f"(lo)); return r; }
__device__ __forceinline__ uint32_t pack_f16(float lo, float hi) { uint32_t r; asm("cvt.rn.f16x2.f32 %0, %1, %2;" : "=r"(r) : "f"(hi), "f"(lo)); return r; }
__device__ __forceinline__ float bf_lo(uint32_t v) { return __uint_as_float(v << 16); }
__device__ __forceinline__ float bf_hi(uint32_t v) { return __uint_as_float(v & 0xFFFF0000u); }
__device__ __forceinline__ float rbf(float x) { return __bfloat162float(__float2bfloat16_rn(x)); }
__device__ __forceinline__ void stsm4(uint32_t a, uint32_t r0, uint32_t r1, uint32_t r2, uint32_t r3) {
  asm volatile("stmatrix.sync.aligned.m8n8.x4.shared.b16 [%0], {%1,%2,%3,%4};" :: "r"(a), "r"(r0), "r"(r1), "r"(r2), "r"(r3) : "memory");
}
__device__ __forceinline__ void stsm4t(uint32_t a, uint32_t r0, uint32_t r1, uint32_t r2, uint32_t r3) {
  asm volatile("stmatrix.sync.aligned.m8n8.x4.trans.shared.b16 [%0], {%1,%2,%3,%4};" :: "r"(a), "r"(r0), "r"(r1), "r"(r2), "r"(r3) : "memory");
}
__device__ __forceinline__ void mma_bf16(float* d, uint32_t a0, uint32_t a1, uint32_t a2, uint32_t a3, uint32_t b0, uint32_t b1) {
  asm volatile("mma.sync.aligned.m16n8k16.row.col.f32.bf16.bf16.f32 {%0,%1,%2,%3}, {%4,%5,%6,%7}, {%8,%9}, {%0,%1,%2,%3};"
               : "+f"(d[0]), "+f"(d[1]), "+f"(d[2]), "+f"(d[3]) : "r"(a0), "r"(a1), "r"(a2), "r"(a3), "r"(b0), "r"(b1));
}
template<int SD> __device__ __forceinline__ void wg_qs24(float* d, uint64_t da, uint64_t db) {
  asm volatile("wgmma.mma_async.sync.aligned.m64n24k16.f32.f16.f16 {%0,%1,%2,%3,%4,%5,%6,%7,%8,%9,%10,%11}, %12, %13, %14, 1, 1, 0, 0;"
   : "+f"(d[0]),"+f"(d[1]),"+f"(d[2]),"+f"(d[3]),"+f"(d[4]),"+f"(d[5]),"+f"(d[6]),"+f"(d[7]),"+f"(d[8]),"+f"(d[9]),"+f"(d[10]),"+f"(d[11])
   : "l"(da),"l"(db),"n"(SD));
}
template<int SD> __device__ __forceinline__ void wg_qs72(float* d, uint64_t da, uint64_t db) {
  asm volatile("wgmma.mma_async.sync.aligned.m64n72k16.f32.f16.f16 {%0,%1,%2,%3,%4,%5,%6,%7,%8,%9,%10,%11,%12,%13,%14,%15,%16,%17,%18,%19,%20,%21,%22,%23,%24,%25,%26,%27,%28,%29,%30,%31,%32,%33,%34,%35}, %36, %37, %38, 1, 1, 0, 0;"
   : "+f"(d[0]),"+f"(d[1]),"+f"(d[2]),"+f"(d[3]),"+f"(d[4]),"+f"(d[5]),"+f"(d[6]),"+f"(d[7]),"+f"(d[8]),"+f"(d[9]),"+f"(d[10]),"+f"(d[11]),"+f"(d[12]),"+f"(d[13]),"+f"(d[14]),"+f"(d[15]),"+f"(d[16]),"+f"(d[17]),"+f"(d[18]),"+f"(d[19]),"+f"(d[20]),"+f"(d[21]),"+f"(d[22]),"+f"(d[23]),"+f"(d[24]),"+f"(d[25]),"+f"(d[26]),"+f"(d[27]),"+f"(d[28]),"+f"(d[29]),"+f"(d[30]),"+f"(d[31]),"+f"(d[32]),"+f"(d[33]),"+f"(d[34]),"+f"(d[35])
   : "l"(da),"l"(db),"n"(SD));
}
template<int SD> __device__ __forceinline__ void wg_pv24(float* d, const uint32_t* a, uint64_t desc) {
  asm volatile("wgmma.mma_async.sync.aligned.m64n24k16.f32.bf16.bf16 {%0,%1,%2,%3,%4,%5,%6,%7,%8,%9,%10,%11}, {%12,%13,%14,%15}, %16, %17, 1, 1, 1;"
   : "+f"(d[0]),"+f"(d[1]),"+f"(d[2]),"+f"(d[3]),"+f"(d[4]),"+f"(d[5]),"+f"(d[6]),"+f"(d[7]),"+f"(d[8]),"+f"(d[9]),"+f"(d[10]),"+f"(d[11])
   : "r"(a[0]),"r"(a[1]),"r"(a[2]),"r"(a[3]),"l"(desc),"n"(SD));
}
template<int TA, int TB> __device__ __forceinline__ void wg_ss128(float* d, uint64_t da, uint64_t db, int sd) {
  asm volatile("{\n.reg .pred p;\nsetp.ne.b32 p, %66, 0;\n"
   "wgmma.mma_async.sync.aligned.m64n128k16.f32.bf16.bf16 {%0,%1,%2,%3,%4,%5,%6,%7,%8,%9,%10,%11,%12,%13,%14,%15,%16,%17,%18,%19,%20,%21,%22,%23,%24,%25,%26,%27,%28,%29,%30,%31,%32,%33,%34,%35,%36,%37,%38,%39,%40,%41,%42,%43,%44,%45,%46,%47,%48,%49,%50,%51,%52,%53,%54,%55,%56,%57,%58,%59,%60,%61,%62,%63}, %64, %65, p, 1, 1, %67, %68;\n}\n"
   : "+f"(d[0]),"+f"(d[1]),"+f"(d[2]),"+f"(d[3]),"+f"(d[4]),"+f"(d[5]),"+f"(d[6]),"+f"(d[7]),"+f"(d[8]),"+f"(d[9]),"+f"(d[10]),"+f"(d[11]),"+f"(d[12]),"+f"(d[13]),"+f"(d[14]),"+f"(d[15]),"+f"(d[16]),"+f"(d[17]),"+f"(d[18]),"+f"(d[19]),"+f"(d[20]),"+f"(d[21]),"+f"(d[22]),"+f"(d[23]),"+f"(d[24]),"+f"(d[25]),"+f"(d[26]),"+f"(d[27]),"+f"(d[28]),"+f"(d[29]),"+f"(d[30]),"+f"(d[31]),"+f"(d[32]),"+f"(d[33]),"+f"(d[34]),"+f"(d[35]),"+f"(d[36]),"+f"(d[37]),"+f"(d[38]),"+f"(d[39]),"+f"(d[40]),"+f"(d[41]),"+f"(d[42]),"+f"(d[43]),"+f"(d[44]),"+f"(d[45]),"+f"(d[46]),"+f"(d[47]),"+f"(d[48]),"+f"(d[49]),"+f"(d[50]),"+f"(d[51]),"+f"(d[52]),"+f"(d[53]),"+f"(d[54]),"+f"(d[55]),"+f"(d[56]),"+f"(d[57]),"+f"(d[58]),"+f"(d[59]),"+f"(d[60]),"+f"(d[61]),"+f"(d[62]),"+f"(d[63])
   : "l"(da),"l"(db),"r"(sd),"n"(TA),"n"(TB));
}
template<int TA, int TB> __device__ __forceinline__ void wg_ss8(float* d, uint64_t da, uint64_t db, int sd) {
  asm volatile("{\n.reg .pred p;\nsetp.ne.b32 p, %6, 0;\n"
   "wgmma.mma_async.sync.aligned.m64n8k16.f32.bf16.bf16 {%0,%1,%2,%3}, %4, %5, p, 1, 1, %7, %8;\n}\n"
   : "+f"(d[0]),"+f"(d[1]),"+f"(d[2]),"+f"(d[3])
   : "l"(da),"l"(db),"r"(sd),"n"(TA),"n"(TB));
}


__device__ __forceinline__ uint32_t phi2(float a, float b) {
  uint32_t r, e;
  asm("cvt.rn.relu.bf16x2.f32 %0, %1, %2;" : "=r"(r) : "f"(b), "f"(a));
  e = pack_bf16(ex2f(a * 1.4426950408889634f), ex2f(b * 1.4426950408889634f));
  asm("add.rn.bf16x2 %0, %0, %1;" : "+r"(e) : "r"(0x35863586u));
  asm("min.NaN.bf16x2 %0, %0, %1;" : "+r"(e) : "r"(0x3F803F80u));
  asm("add.rn.bf16x2 %0, %0, %1;" : "+r"(e) : "r"(r));
  return e;
}

__device__ __forceinline__ void mbar_wait_long(uint32_t bar, uint32_t parity) {
  asm volatile("{\n.reg .pred p;\n.reg .u32 c;\nmov.u32 c, 0;\n"
               "LW_%=:\n"
               "mbarrier.try_wait.parity.shared::cta.b64 p, [%0], %1, 10000;\n"
               "@p bra LD_%=;\n"
               "add.u32 c, c, 1;\n"
               "setp.lt.u32 p, c, 400000;\n"
               "@p bra LW_%=;\n"
               "trap;\n"
               "LD_%=:\n}\n" :: "r"(bar), "r"(parity) : "memory");
}
__device__ __forceinline__ void mbar_arrive(uint32_t bar) { asm volatile("mbarrier.arrive.shared::cta.b64 _, [%0];" :: "r"(bar) : "memory"); }
__device__ __forceinline__ void named_arrive(int id, int n) { asm volatile("bar.arrive %0, %1;" :: "r"(id), "r"(n) : "memory"); }
__device__ __forceinline__ void fence_async_all() { asm volatile("fence.proxy.async.global;" ::: "memory"); }
__device__ __forceinline__ void flag_add(uint32_t* f) { asm volatile("fence.acq_rel.gpu;\nred.relaxed.gpu.global.add.u32 [%0], 1;" :: "l"(f) : "memory"); }
#define PUBLISH(f) asm volatile("fence.proxy.async.global;\nred.relaxed.gpu.global.add.u32 [%0], 1;" :: "l"(f) : "memory")
__device__ __forceinline__ void flag_wait(const uint32_t* f, uint32_t target) {
  uint32_t v;
#pragma unroll 1
  for (int it = 0;; it++) {
    asm volatile("ld.acquire.gpu.global.u32 %0, [%1];" : "=r"(v) : "l"(f) : "memory");
    if ((int32_t)(v - target) >= 0) break;
    if (it > 2000000) __trap();
    __nanosleep(64);
  }
}
__device__ __forceinline__ bool mbar_test(uint32_t bar, uint32_t parity) {
  uint32_t ok;
  asm volatile("{\n.reg .pred p;\nmbarrier.test_wait.parity.shared::cta.b64 p, [%1], %2;\nselp.b32 %0, 1, 0, p;\n}\n" : "=r"(ok) : "r"(bar), "r"(parity) : "memory");
  return ok;
}
__device__ __forceinline__ bool elect_one() {
  uint32_t p;
  asm volatile("{\n.reg .pred P;\nelect.sync _|P, 0xFFFFFFFF;\nselp.b32 %0, 1, 0, P;\n}\n" : "=r"(p));
  return p;
}
__device__ __forceinline__ void lds4(uint32_t a, uint32_t* r) {
  asm volatile("ld.shared.v4.b32 {%0,%1,%2,%3}, [%4];" : "=r"(r[0]), "=r"(r[1]), "=r"(r[2]), "=r"(r[3]) : "r"(a) : "memory");
}
__device__ __forceinline__ uint32_t lds1(uint32_t a) { uint32_t r; asm volatile("ld.shared.b32 %0, [%1];" : "=r"(r) : "r"(a) : "memory"); return r; }
__device__ __forceinline__ void sts1(uint32_t a, uint32_t v) { asm volatile("st.shared.b32 [%0], %1;" :: "r"(a), "r"(v) : "memory"); }
__device__ __forceinline__ void sts4(uint32_t a, uint32_t r0, uint32_t r1, uint32_t r2, uint32_t r3) {
  asm volatile("st.shared.v4.b32 [%0], {%1,%2,%3,%4};" :: "r"(a), "r"(r0), "r"(r1), "r"(r2), "r"(r3) : "memory");
}
__device__ __forceinline__ void ldsm4(uint32_t a, uint32_t* r) {
  asm volatile("ldmatrix.sync.aligned.m8n8.x4.shared.b16 {%0,%1,%2,%3}, [%4];" : "=r"(r[0]), "=r"(r[1]), "=r"(r[2]), "=r"(r[3]) : "r"(a) : "memory");
}
__device__ __forceinline__ float rcpf(float x) { float y; asm("rcp.approx.ftz.f32 %0, %1;" : "=f"(y) : "f"(x)); return y; }
__device__ __forceinline__ uint32_t hfma2(uint32_t a, uint32_t b, uint32_t c) { uint32_t r; asm("fma.rn.f16x2 %0, %1, %2, %3;" : "=r"(r) : "r"(a), "r"(b), "r"(c)); return r; }
__device__ __forceinline__ uint32_t hadd2(uint32_t a, uint32_t b) { uint32_t r; asm("add.rn.f16x2 %0, %1, %2;" : "=r"(r) : "r"(a), "r"(b)); return r; }

#define STEPK 96
#define GIMAP(i) ((((i) & 1) << 2) | (((i) >> 1) & 3) | ((i) & 8))
#define QSCALE 0.36067376022224085f
#define SMAGIC (512.0f + 2.0f * (191.0f - 30.0f - 1.5823545f))
#define VSHIFT 1073741824.0f

__device__ uint32_t g_epoch[132];
__device__ uint32_t g_flag[288 * 8];
#define FLAG_KV (g_flag)
#define FLAG_KV2 (g_flag + 8 * 8)
#define FLAG_B(h) (g_flag + (4 + (h)) * 8)
#define FLAG_OA(cta, pass) (g_flag + (16 + (cta) * 2 + (pass)) * 8)
#define FLAG_LM(i) (g_flag + (272 + (i)) * 8)

#define SM_TOTAL (224 * 1024 + 3072)
#define OFF_K 0
#define OFF_F 65536
#define OFF_V 131072
#define OFF_MISC (224 * 1024)

#define BAR_FULL(s) (bars + 8 * (s))
#define BAR_FW(s, w) (bars + 408 + 8 * ((s) * 4 + (w)))
#define BAR_EMPTY(s) (bars + 24 + 8 * (s))
#define BAR_KV(c) (bars + 48 + 8 * (c))
#define BAR_E0(i) (bars + 200 + 8 * (i))
#define BAR_PQ (bars + 72)
#define BAR_BDONE (bars + 80)
#define BAR_Q (bars + 88)
#define BAR_GO (bars + 96)
#define BAR_Q2 (bars + 104)
#define BAR_OD(p) (bars + 112 + 8 * (p))
#define BAR_CL(c) (bars + 128 + 8 * (c))
#define BAR_TE(i) (bars + 168 + 8 * (i))
#define BAR_RL (bars + 184)
#define BAR_TF(g) (bars + 224 + 8 * (g))
#define BAR_XA(w) (bars + 352 + 8 * (w))
#define BAR_VB(c) (bars + 384 + 8 * (c))

__device__ __forceinline__ uint32_t exp2_pair_fix(float d0, float d1, uint32_t c63, uint32_t m1) {
  uint32_t w, y, s, r;
  asm("prmt.b32 %0, %1, %2, 0x6521;" : "=r"(w) : "r"(__float_as_uint(d0)), "r"(__float_as_uint(d1)));
  asm("lop3.b32 %0, %1, 0x007F007F, %2, 0xEA;" : "=r"(y) : "r"(w), "r"(c63));
  asm("mad.lo.u32 %0, %1, %2, %3;" : "=r"(s) : "r"(y), "r"(m1), "r"(w));
  asm("fma.rn.bf16x2 %0, %1, %2, %3;" : "=r"(r) : "r"(w), "r"(y), "r"(s));
  return r;
}

#define X_PR(i) asm volatile("prmt.b32 %0, %1, %2, 0x6521;" : "=r"(w[i]) : "r"(__float_as_uint(Sp[2 * (i)])), "r"(__float_as_uint(Sp[2 * (i) + 1])));
#define X_LO(i) asm volatile("lop3.b32 %0, %1, 0x007F007F, %2, 0xEA;" : "=r"(y[i]) : "r"(w[i]), "r"(c63));
#define X_IM(i) asm volatile("mad.lo.u32 %0, %1, %2, %3;" : "=r"(z[i]) : "r"(y[i]), "r"(m1), "r"(w[i]));
#define X_FM(i) asm volatile("fma.rn.bf16x2 %0, %1, %2, %3;" : "=r"(P[6 + (i)]) : "r"(w[i]), "r"(y[i]), "r"(z[i]));
#define X_MU(i) asm volatile("ex2.approx.ftz.f32 %0, %1;" : "=f"(e[i]) : "f"(Sm[i]));
#define X_PK(i) asm volatile("cvt.rn.bf16x2.f32 %0, %1, %2;" : "=r"(P[i]) : "f"(e[2 * (i) + 1]), "f"(e[2 * (i)]));

__device__ __forceinline__ void attn_slow(const __nv_bfloat16* xa, const __nv_bfloat16* wq, uint32_t dst) {
  const int t = threadIdx.x & 127;
  const int row = t >> 1, half = t & 1;
  float q[16];
  {
    float a[8];
#pragma unroll
    for (int i = 0; i < 8; i++) a[i] = 0.f;
#pragma unroll 1
    for (int k = 0; k < D_MOD; k++) {
      const float x = __bfloat162float(xa[(size_t)row * D_MOD + k]);
      const uint4 w = *(const uint4*)(wq + (size_t)k * D_MOD + half * 8);
      const uint32_t ww[4] = {w.x, w.y, w.z, w.w};
#pragma unroll
      for (int i = 0; i < 4; i++) { a[2 * i] = fmaf(x, bf_lo(ww[i]), a[2 * i]); a[2 * i + 1] = fmaf(x, bf_hi(ww[i]), a[2 * i + 1]); }
    }
#pragma unroll
    for (int i = 0; i < 8; i++) {
      const float mine = rbf(a[i]), other = __shfl_xor_sync(~0u, mine, 1);
      q[i] = half ? other : mine; q[8 + i] = half ? mine : other;
    }
  }
  float m = -INFINITY, l = 0.f, o[16];
#pragma unroll
  for (int i = 0; i < 16; i++) o[i] = 0.f;
#pragma unroll 1
  for (int j = half * 1024; j < half * 1024 + 1024; j++) {
    uint4 ka = g_KV[4 * S_TOK + j], kb = g_KV[5 * S_TOK + j];
    uint4 va = g_KV[6 * S_TOK + j], vb = g_KV[7 * S_TOK + j];
    uint32_t kk[8] = {ka.x, ka.y, ka.z, ka.w, kb.x, kb.y, kb.z, kb.w};
    uint32_t vv[8] = {va.x, va.y, va.z, va.w, vb.x, vb.y, vb.z, vb.w};
    float s = 0.f;
#pragma unroll
    for (int i = 0; i < 8; i++) { s = fmaf(q[2 * i], bf_lo(kk[i]), s); s = fmaf(q[2 * i + 1], bf_hi(kk[i]), s); }
    s = rbf(s) * 0.25f;
    if (s > m) {
      float c = __expf(m - s);
      l *= c;
#pragma unroll
      for (int i = 0; i < 16; i++) o[i] *= c;
      m = s;
    }
    float p = __expf(s - m);
    l += p;
#pragma unroll
    for (int i = 0; i < 8; i++) { o[2 * i] = fmaf(p, bf_lo(vv[i]), o[2 * i]); o[2 * i + 1] = fmaf(p, bf_hi(vv[i]), o[2 * i + 1]); }
  }
  float m2 = __shfl_xor_sync(~0u, m, 1);
  float mm = fmaxf(m, m2);
  float c = __expf(m - mm);
  l *= c; l += __shfl_xor_sync(~0u, l, 1);
  float inv = 1.f / l;
  uint32_t r[8];
#pragma unroll
  for (int i = 0; i < 16; i++) { o[i] *= c; o[i] += __shfl_xor_sync(~0u, o[i], 1); o[i] *= inv; }
#pragma unroll
  for (int i = 0; i < 8; i++) r[i] = pack_bf16(o[2 * i], o[2 * i + 1]);
  if (half == 0) sts4(dst, r[0], r[1], r[2], r[3]); else sts4(dst, r[4], r[5], r[6], r[7]);
  fence_async();
}

struct Params { const __nv_bfloat16* wk; const __nv_bfloat16* wv; const __nv_bfloat16* xa; const __nv_bfloat16* wq; __nv_bfloat16* out; };

__device__ __forceinline__ void helper_cta(const int h, const uint32_t sb, const uint32_t bars, const int wg, const int w4,
                                           const CUtensorMap* mQ, const CUtensorMap* mOs) {
  const int lane = threadIdx.x & 31;
  mbar_wait(BAR_GO, 0);
  const int cb = wg & 1, col = h * 128 + cb * 64, row0 = S_TOK + (wg >> 1) * 1024;
  const uint32_t buf = sb + wg * 49152;
  if (w4 == 0 && elect_one()) {
    fence_async_all();
#pragma unroll 1
    for (int u = 0; u < 3; u++) {
      mbar_expect_tx(BAR_TF(wg * 3 + u), 16384);
      tma2d(buf + u * 16384, mQ, col, row0 + u * 128, BAR_TF(wg * 3 + u));
    }
  }
  const int head = h * 8 + cb * 4 + w4;
  float4 a0 = make_float4(0, 0, 0, 0), a1 = a0, a2 = a0;
#pragma unroll 8
  for (int tt = 0; tt < 16; tt++) {
    const float4* src = g_kvp + ((tt * 32 + head) * 3) * 32 + lane;
    float4 u = src[0], v = src[32], w = src[64];
    a0.x += u.x; a0.y += u.y; a0.z += u.z; a0.w += u.w;
    a1.x += v.x; a1.y += v.y; a1.z += v.z; a1.w += v.w;
    a2.x += w.x; a2.y += w.y; a2.z += w.z; a2.w += w.w;
  }
  const uint32_t b00 = pack_bf16(a0.x, a0.y), b01 = pack_bf16(a0.z, a0.w);
  const uint32_t b10 = pack_bf16(a1.x, a1.y), b11 = pack_bf16(a1.z, a1.w);
  const uint32_t bz0 = pack_bf16(a2.x, a2.y), bz1 = pack_bf16(a2.z, a2.w);
  const int m = lane >> 3, r = lane & 7;
  const uint32_t off = ((m & 1) * 8 + r) * 128 + (((w4 * 2 + (m >> 1)) ^ r) << 4);
  int s = 0, ph = 0;
#pragma unroll 1
  for (int u = 0; u < 8; u++) {
    const uint32_t bb = buf + s * 16384;
    mbar_wait(BAR_TF(wg * 3 + s), ph);
#pragma unroll
    for (int mt = 0; mt < 8; mt++) {
      uint32_t a[4];
      ldsm4(bb + mt * 2048 + off, a);
      float n0[4] = {0, 0, 0, 0}, n1[4] = {0, 0, 0, 0}, dn[4] = {0, 0, 0, 0};
      mma_bf16(dn, a[0], a[1], a[2], a[3], bz0, bz1);
      mma_bf16(n0, a[0], a[1], a[2], a[3], b00, b01);
      mma_bf16(n1, a[0], a[1], a[2], a[3], b10, b11);
      const float i0 = rcpf(dn[0] + 1e-6f), i1 = rcpf(dn[2] + 1e-6f);
      stsm4(bb + mt * 2048 + off, pack_bf16(n0[0] * i0, n0[1] * i0), pack_bf16(n0[2] * i1, n0[3] * i1),
            pack_bf16(n1[0] * i0, n1[1] * i0), pack_bf16(n1[2] * i1, n1[3] * i1));
    }
    fence_async();
    named_bar(wg + 1, 128);
    if (w4 == 0 && lane == 0) {
      tma2d_store(mOs, bb, col, row0 + u * 128);
      bulk_commit();
      if (u >= 1 && u + 2 < 8) {
        asm volatile("cp.async.bulk.wait_group.read 1;" ::: "memory");
        const int sp = s == 0 ? 2 : s - 1;
        mbar_expect_tx(BAR_TF(wg * 3 + sp), 16384);
        tma2d(buf + sp * 16384, mQ, col, row0 + (u + 2) * 128, BAR_TF(wg * 3 + sp));
      }
    }
    __syncwarp();
    if (++s == 3) { s = 0; ph ^= 1; }
  }
  if (w4 == 0 && lane == 0) {
    bulk_wait_all();
    fence_async_all();
    flag_add(FLAG_LM((h * 2 + cb) * 2 + (wg >> 1)));
  }
}

#define STAGE(s) (sb + (2 - (s)) * 65536)
__device__ __forceinline__ uint32_t xa_addr(uint32_t sb, int kb) {
  return sb + (kb >= 1 && kb <= 4 ? OFF_V + 65536 + (kb - 1) * 8192 : 16384 + (kb == 5 ? OFF_K : (kb == 6 ? OFF_V : OFF_F)));
}
#define XA7_TMP (sb + OFF_K + 8192)
#define WKV_TMP (sb + OFF_K)
template <int TR> __device__ __forceinline__ void proj_kb(float* acc, uint32_t aA, uint32_t aB, int first) {
  const uint64_t da = make_desc(aA, TR ? 8192 : 16, 1024, 1);
  const uint64_t db = make_desc(aB, TR ? 16 : 8192, 1024, 1);
  wg_fence();
#pragma unroll
  for (int k = 0; k < 4; k++) wg_ss128<TR, 1 - TR>(acc, da + k * (TR ? 128 : 2), db + k * (TR ? 2 : 128), k != 0 || !first);
  wg_commit();
}
template <int TR> __device__ __forceinline__ void proj_loop(float* acc, uint32_t sb, uint32_t bars, uint32_t offA, uint32_t offB,
                                                            int wg, uint32_t sWKV, const CUtensorMap* mW, int col, bool w0, const CUtensorMap* mX, int xrow) {
  int s = 0, ph = 0;
#pragma unroll 1
  for (int kb = 0; kb < 8; kb++) {
    if (kb == TR)
  {
    float kv[4];
    mbar_wait(BAR_XA(wg), 0);
    const uint64_t da0 = make_desc(xa_addr(sb, 2 * wg), 16, 1024, 1);
    const uint64_t da1 = make_desc(wg == 3 ? XA7_TMP : xa_addr(sb, 2 * wg + 1), 16, 1024, 1);
    const uint64_t db = make_desc(sWKV + wg * 2048, 128, 128, 0);
    wg_fence();
#pragma unroll
    for (int k = 0; k < 8; k++) wg_ss8<0, 1>(kv, (k < 4 ? da0 : da1) + (k & 3) * 2, db + k * 16, k != 0);
    wg_commit();
    wg_wait<0>();
    fence_regs<4>(kv);
    named_bar(wg + 1, 128);
    sts4(sWKV + threadIdx.x * 16, __float_as_uint(kv[0]), __float_as_uint(kv[1]), __float_as_uint(kv[2]), __float_as_uint(kv[3]));
    __syncwarp();
    if ((threadIdx.x & 31) == 0) mbar_arrive(BAR_GO);
  }
    mbar_wait(BAR_FW(s, wg), ph);
    if (TR == 0) mbar_wait(BAR_XA(kb >> 1), 0); else mbar_wait(BAR_FULL(s), ph);
    proj_kb<TR>(acc, TR ? STAGE(s) + offA : xa_addr(sb, kb), STAGE(s) + offB, kb == 0);
    wg_wait<0>();
    if (w0 && elect_one()) {
      if (kb < 5) {
        mbar_expect_tx(BAR_FW(s, wg), TR ? 8192 : (kb == 4 ? 24576 : 16384));
        tma2d(STAGE(s) + (TR ? offA : 0), mW, col, (kb + 3) * 64, BAR_FW(s, wg));
        if (TR == 0) {
          tma2d(STAGE(s) + 8192, mW, col + 64, (kb + 3) * 64, BAR_FW(s, wg));
          if (kb == 4) tma2d(STAGE(s) + 16384, mX, 448, xrow, BAR_FW(s, wg));
        }
      }
      if (TR ? kb < 7 : (kb == 5 || kb == 6)) mbar_arrive(TR ? BAR_EMPTY(s) : BAR_E0(kb - 5));
      if (TR == 0 && kb == 4) mbar_arrive(BAR_VB(1));
    }
    __syncwarp();
    if (++s == 3) { s = 0; ph ^= 1; }
  }
  wg_wait<0>();
  fence_regs<64>(acc);
}

__device__ __forceinline__ uint32_t tail_slots(int isB, int n) {
  if (n < 4) return n < 2 ? (n == 0 ? 0x0D0C0B0Au : 0x04000F0Eu) : (n == 2 ? 0x18141008u : 0x15110501u);
  if (isB) return n < 6 ? (n == 4 ? 0x19120602u : 0x0D0C0B0Au) : (n == 6 ? 0x04000F0Eu : 0x13070316u);
  return n < 6 ? (n == 4 ? 0x1902031Au : 0x12061307u) : (n == 6 ? 0x16091B17u : 0x0D0C0B0Au);
}

__device__ __forceinline__ void take_role(uint32_t sM, int wg) {
  uint32_t r;
  asm volatile("atom.shared.add.u32 %0, [%1], 1;" : "=r"(r) : "r"(sM + 20) : "memory");
  sts1(sM + 32 + wg * 4, r);
}

__global__ void __launch_bounds__(640, 1)
k1_main(const __grid_constant__ CUtensorMap mXA64, const __grid_constant__ CUtensorMap mXB,
        const __grid_constant__ CUtensorMap mWq, const __grid_constant__ CUtensorMap mWqkv,
        const __grid_constant__ CUtensorMap mQst, const __grid_constant__ CUtensorMap mOst,
        const __grid_constant__ CUtensorMap mO, const __grid_constant__ CUtensorMap mWoA,
        const __grid_constant__ CUtensorMap mWoB,
        const __grid_constant__ CUtensorMap mO16, const __grid_constant__ CUtensorMap mKV, const Params prm) {
  if (threadIdx.x >= 608 && threadIdx.x < 612) {
    const CUtensorMap* pm = &mXA64 + (threadIdx.x - 608);
    asm volatile("prefetch.tensormap [%0];" :: "l"(pm) : "memory");
  }
  extern __shared__ __align__(1024) uint8_t smem_raw[];
  const uint32_t sb = smem_u32(smem_raw);
  if (sb & 1023u) __trap();
  const uint32_t bars = sb + OFF_MISC, sM = bars + 512, sT = bars + 640;
  const int tid = threadIdx.x, warp = __shfl_sync(~0u, tid >> 5, 0), wg = warp >> 2, w4 = warp & 3, lane = tid & 31;
  const bool helper = blockIdx.x >= 128;
  const int G = blockIdx.x >> 4, gi = GIMAP(blockIdx.x & 15);
  const int tbA = G * 4 + (gi >> 2), hg = gi & 3;
  const int ttB = (G >> 1) * 4 + (gi >> 2), hq = (G & 1) * 4 + (gi & 3);
  const int isB = tbA & 1, tok0 = (tbA >> 1) * 128;
  auto issue = [&](int kb, int part) {
    const uint32_t st = STAGE(kb);
    if (part & 1) {
      mbar_expect_tx(BAR_FW(kb, 0), 16384);
      tma2d(st, &mWq, hg * 128, kb * 64, BAR_FW(kb, 0));
      tma2d(st + 8192, &mWq, hg * 128 + 64, kb * 64, BAR_FW(kb, 0));
    }
    if (part & 2) {
      mbar_expect_tx(BAR_FULL(kb), 16384);
      tma2d(st + 49152, &mXB, kb * 64, ttB * 128, BAR_FULL(kb));
      mbar_expect_tx(BAR_FW(kb, 1), 8192);
      tma2d(st + 24576, &mWqkv, hq * 64, kb * 64, BAR_FW(kb, 1));
    }
    if (part & 4) {
      mbar_expect_tx(BAR_FW(kb, 2), 8192);
      tma2d(st + 32768, &mWqkv, 512 + hq * 64, kb * 64, BAR_FW(kb, 2));
      mbar_expect_tx(BAR_FW(kb, 3), 8192);
      tma2d(st + 40960, &mWqkv, 1024 + hq * 64, kb * 64, BAR_FW(kb, 3));
    }
  };
  const uint32_t sOne = sb + OFF_V + 65536, sWKV = WKV_TMP;
  if (warp >= 16) {
    if (warp == 17) {
      if (elect_one()) {
        mbar_init(BAR_BDONE, 8); mbar_init(BAR_Q, 6); mbar_init(BAR_GO, helper ? 1 : 16); mbar_init(BAR_Q2, 1);
        mbar_init(BAR_OD(0), 16); mbar_init(BAR_OD(1), 16); mbar_init(BAR_CL(0), 1); mbar_init(BAR_FULL(1), 1); mbar_init(BAR_FULL(2), 1);
        mbar_init(BAR_E0(0), 1); mbar_init(BAR_E0(1), 1);
#pragma unroll
        for (int i = 0; i < 4; i++) mbar_init(BAR_CL(i + 1), i == 0 ? 5 : 4);
#pragma unroll
        for (int i = 0; i < 3; i++) { mbar_init(BAR_EMPTY(i), 3); mbar_init(BAR_KV(i), 1); mbar_init(BAR_VB(i), i == 2 ? 4 : 1); }
        sts1(sM + 20, 0);
        asm volatile("fence.mbarrier_init.release.cluster;" ::: "memory");
      }
    } else if (warp == 18) {
      if (elect_one()) {
#pragma unroll
        for (int i = 0; i < 2; i++) mbar_init(BAR_TE(i), 2);
        mbar_init(BAR_RL, 1); mbar_init(BAR_PQ, 4);
#pragma unroll
        for (int i = 4; i < 12; i++) mbar_init(BAR_FW(0, i), 1);
#pragma unroll
        for (int i = 0; i < 16; i++) mbar_init(BAR_TF(i), 1);
        asm volatile("fence.mbarrier_init.release.cluster;" ::: "memory");
      }
    } else if (warp == 16 && !helper && elect_one()) {
#pragma unroll
      for (int w = 0; w < 4; w++) { mbar_init(BAR_XA(w), 1); mbar_init(BAR_FW(0, w), 1); }
      mbar_init(BAR_FULL(0), 1);
      asm volatile("fence.mbarrier_init.release.cluster;" ::: "memory");
      issue(0, 6);
#pragma unroll
      for (int w = 0; w < 4; w++) {
        mbar_expect_tx(BAR_XA(w), 16384);
        tma2d(xa_addr(sb, 2 * w), &mXA64, w * 128, tbA * 64, BAR_XA(w));
        tma2d(w == 3 ? XA7_TMP : xa_addr(sb, 2 * w + 1), &mXA64, w * 128 + 64, tbA * 64, BAR_XA(w));
        if (w == 0) issue(0, 1);
      }
    }
  } else if (!helper) {
    const uint4 v = __ldg((const uint4*)(hg >= 2 ? prm.wv : prm.wk) + tid * 2 + (hg & 1));
    sts4(sWKV + tid * 16, v.x, v.y, v.z, v.w);
    fence_async();
  }
  __syncthreads();
  if (wg == 4) {
    if (w4 == 0 && !helper && elect_one()) { issue(1, 7); issue(2, 6); }
    asm volatile("setmaxnreg.dec.sync.aligned.u32 32;");
    const uint32_t ep = g_epoch[blockIdx.x] + 1;
    if (helper) {
      if (w4 == 0 && elect_one()) {
        flag_wait(FLAG_B(blockIdx.x - 128), ep * 32);
        fence_async_all();
        mbar_arrive(BAR_GO);
        g_epoch[blockIdx.x] = ep;
      }
      return;
    }
    if (w4 != 0) {
      mbar_wait(BAR_GO, 0);
#pragma unroll 1
      for (int qd = w4 & 3; qd >= 0; qd -= 3) {
        uint32_t a[4], b[4];
        float c[4];
        const uint32_t ad = sWKV + (qd * 32 + lane) * 16;
        lds4(ad, a);
        lds4(ad + 2048, b);
#pragma unroll
        for (int i = 0; i < 4; i++) c[i] = __uint_as_float(a[i]) + __uint_as_float(b[i]);
        lds4(ad + 4096, a);
        lds4(ad + 6144, b);
#pragma unroll
        for (int i = 0; i < 4; i++) c[i] += __uint_as_float(a[i]) + __uint_as_float(b[i]);
        sts1(sT + qd * 256 + lane * 4, pack_bf16(c[0], c[1]));
        sts1(sT + qd * 256 + 128 + lane * 4, pack_bf16(c[2], c[3]));
      }
      named_bar(9, 96);
      if (w4 == 3 && elect_one()) issue(2, 1);
    }
    auto write_ones = [&]() {
      mbar_wait_long(BAR_VB(1), 0);
      int c = ((w4 & 1) * 32 + lane);
#pragma unroll 4
      for (int key = c; key < S_TOK; key += 64) {
        sts4(sOne + key * 16, c < 24 ? 0x00003F80u : 0x00004E80u, 0u, 0u, 0u);
        c += 64; if (c >= STEPK) c -= STEPK;
      }
      fence_async();
      __syncwarp();
      if (lane == 0) mbar_arrive(BAR_Q);
    };
    auto phi_q = [&]() {
      mbar_wait_long(BAR_PQ, 0);
#pragma unroll 1
      for (int i = 0; i < 8; i++) {
        uint32_t x[4];
        const uint32_t ad = sb + OFF_F + 49152 + i * 2048 + (tid - 512) * 16;
        lds4(ad, x);
        sts4(ad, phi2(bf_lo(x[0]), bf_hi(x[0])), phi2(bf_lo(x[1]), bf_hi(x[1])), phi2(bf_lo(x[2]), bf_hi(x[2])), phi2(bf_lo(x[3]), bf_hi(x[3])));
      }
      fence_async();
      __syncwarp();
      if (lane == 0) mbar_arrive(BAR_BDONE);
    };
    if (w4 == 0) {
      int s = 0, ph = 0;
#pragma unroll 1
      for (int kb = 3; kb < 8; kb++) {
        mbar_wait(BAR_EMPTY(s), ph);
        if (elect_one()) {
          mbar_expect_tx(BAR_FULL(s), 16384);
          tma2d(STAGE(s) + 49152, &mXB, kb * 64, ttB * 128, BAR_FULL(s));
        }
        if (++s == 3) { s = 0; ph ^= 1; }
      }
      flag_wait(FLAG_KV, ep * 128);
      fence_async_all();
#pragma unroll 1
      for (int m = 0; m < 2; m++) {
        mbar_wait(m == 0 ? BAR_EMPTY(2) : BAR_EMPTY(0), 1 - m);
        mbar_wait(BAR_E0(m), 0);
        if (elect_one()) {
          const uint32_t fb = m == 0 ? BAR_KV(0) : BAR_VB(0);
          mbar_expect_tx(fb, 2 * 7 * STEPK * 16);
#pragma unroll
          for (int p = 0; p < 2; p++) bulk_g2s(sb + m * OFF_V + p * 32768, g_KV + (m * 2 + p) * S_TOK, 7 * STEPK * 16, fb);
        }
      }
      mbar_wait(BAR_Q, 0);
      if (elect_one()) {
#pragma unroll
        for (int c = 1; c < 3; c++) {
          const int k0 = c == 1 ? 7 * STEPK : 13 * STEPK, k1 = c == 1 ? 13 * STEPK : S_TOK;
          const uint32_t bytes = (k1 - k0) * 16;
          mbar_expect_tx(BAR_KV(c), 4 * bytes);
#pragma unroll
          for (int p = 0; p < 4; p++)
            bulk_g2s(sb + (p >> 1) * OFF_V + (p & 1) * 32768 + k0 * 16, g_KV + p * S_TOK + k0, bytes, BAR_KV(c));
        }
      }
      phi_q();
      mbar_wait_long(BAR_CL(1), 0);
      flag_wait(isB ? FLAG_LM((lane & 7) * 2 + (tbA >> 4)) : FLAG_OA(tbA * 4 + (lane & 7), 0), ep);
      __syncwarp();
      fence_async_all();
      const CUtensorMap* mW = isB ? &mWoB : &mWoA;
#pragma unroll 1
      for (int it = 0; it < 8; it++) {
        const int n = (!isB && it >= 6) ? 13 - it : it;
        uint32_t wb = BAR_CL(n < 3 ? 0 : (n == 3 ? 2 : 3));
        if (isB) { if (n >= 5) wb = n == 7 ? BAR_CL(4) : BAR_TE(n - 5); }
        else if (n >= 6) wb = n == 6 ? BAR_CL(4) : BAR_TE(0);
        if (it < 6) mbar_wait_long(wb, 0); else mbar_wait(wb, 0);
        const uint32_t sl = tail_slots(isB, n), fb = BAR_TF(n);
        const bool withX = isB || n < 4;
        const int k0 = isB ? n * 64 : (n < 4 ? n * 128 : ((hg + n) & 3) * 128 + 64);
        if (elect_one()) {
          mbar_expect_tx(fb, withX ? 32768 : 16384);
          if (withX) {
            tma2d(sb + (sl & 255) * 8192, &mO, k0, isB * S_TOK + tok0, fb);
            tma2d(sb + ((sl >> 8) & 255) * 8192, &mO, k0, isB * S_TOK + tok0 + 64, fb);
          }
          tma2d(sb + ((sl >> 16) & 255) * 8192, mW, hg * 128, k0, fb);
          tma2d(sb + (sl >> 24) * 8192, mW, hg * 128 + 64, k0, fb);
        }
      }
      if (lane == 0) g_epoch[blockIdx.x] = ep;
    } else if (w4 == 3) {
      write_ones();
      phi_q();
      flag_wait(FLAG_KV2, ep * 128);
      const uint4 a = *(const uint4*)(g_stats + lane * 4);
      const float kmax2 = __uint_as_float(__reduce_max_sync(~0u, a.x)) + __uint_as_float(__reduce_max_sync(~0u, a.y));
      const float vmax = __uint_as_float(__reduce_max_sync(~0u, max(a.z, a.w)));
      const float lv = vmax > 0.f ? __log2f(vmax) : 0.f;
      const float lim = fminf(90.f, fminf(91.f + lv, 95.f - lv));
      float thr = -1.f;
      if (vmax < 1e27f && kmax2 <= 65536.f && lim > 2.f) thr = fminf(60000.f, (lim * lim - 1.f) / (kmax2 * 1.02f + 1e-30f));
      mbar_wait_long(BAR_VB(2), 0);
      uint32_t nmax = 0;
#pragma unroll 2
      for (int i = 0; i < 16; i++) {
        uint32_t x[4], y[4];
        const uint32_t ad = sb + OFF_F + i * 1024 + (lane >> 3) * 256 + (lane & 7) * 16;
        lds4(ad, x); lds4(ad + 128, y);
        uint32_t n = hfma2(x[0], x[0], hfma2(x[1], x[1], hfma2(x[2], x[2], hfma2(x[3], x[3], 0u))));
        n = hfma2(y[0], y[0], hfma2(y[1], y[1], hfma2(y[2], y[2], hfma2(y[3], y[3], n))));
        n = hadd2(n, n >> 16);
        nmax = max(nmax, n & 0x7FFFu);
      }
      nmax = __reduce_max_sync(~0u, nmax);
      const bool ok = __half2float(__ushort_as_half((unsigned short)nmax)) <= thr;
      if (lane == 0) { sts1(sM + 16, ok ? 1u : 0u); mbar_arrive(BAR_Q2); }
    } else {
      const int tok = (w4 - 1) * 32 + lane;
      int step, col;
      if ((tbA & 3) == 0) {
        const int b8 = tbA >> 2;
        if (tok < 22) { step = tok; col = 24 + b8; }
        else { const int c = tok >= 43; step = tok - 22 - 21 * c; col = 32 + b8 * 2 + c; }
      } else {
        const int b24 = (tbA >> 2) * 3 + (tbA & 3) - 1;
        if (tok < 42) { const int c = tok >= 21; step = tok - 21 * c; col = 48 + b24 * 2 + c; }
        else { step = tok - 42; col = b24; }
      }
      const int kap = step * STEPK + col;
      const bool chained = col >= 24;
      uint32_t v[4], o[4];
      lds4(sT + tok * 16, v);
      float st = 0.f;
      if (hg < 2) {
        o[0] = o[1] = o[2] = o[3] = 0;
        if (chained && step > 0) lds4(sT + tok * 16 - 16, o);
        const float sc = chained ? 2.f : 1.f;
#pragma unroll
        for (int u = 0; u < 4; u++) {
          const float x = bf_lo(v[u]), y = bf_hi(v[u]);
          st += x * x + y * y;
          o[u] = pack_f16((x - bf_lo(o[u])) * sc, (y - bf_hi(o[u])) * sc);
        }
      } else {
        const float sc = chained ? VSHIFT : 1.f;
#pragma unroll
        for (int u = 0; u < 4; u++) { float x = bf_lo(v[u]), y = bf_hi(v[u]); st += fabsf(x) + fabsf(y); o[u] = pack_bf16(x * sc, y * sc); }
      }
      {
        const bool tl = (tbA & 3) == 0;
        const int run = tl ? (tok < 22 ? 0 : (tok < 43 ? 1 : 2)) : (tok < 21 ? 0 : (tok < 42 ? 1 : 2));
        const int h2 = (tl ? run == 0 : run == 2) ? 11 : 10;
        const uint32_t img = sT + run * 512;
        named_bar(10, 64);
        if (step < 11) sts4(img + step * 16, o[0], o[1], o[2], o[3]);
        if (step >= h2) sts4(img + 256 + (step - h2) * 16, o[0], o[1], o[2], o[3]);
        if (step == 0) sts1(sM + 48 + run * 4, col * 8 + (h2 << 16));
        fence_async();
        named_bar(10, 64);
        if (w4 == 1 && elect_one()) {
#pragma unroll
          for (int r = 0; r < 3; r++) {
            const uint32_t cw = lds1(sM + 48 + r * 4);
            tma3d_store(&mKV, sT + r * 512, cw & 0xFFFF, 0, hg);
            tma3d_store(&mKV, sT + r * 512 + 256, cw & 0xFFFF, cw >> 16, hg);
          }
          bulk_commit();
          bulk_wait_all();
          PUBLISH(FLAG_KV);
        }
        __syncwarp();
      }
      g_KV[(4 + hg) * S_TOK + kap] = make_uint4(v[0], v[1], v[2], v[3]);
      const uint32_t um = __reduce_max_sync(~0u, __float_as_uint(st) & 0x7FFFFFFFu);
      if (w4 == 2) {
        if (lane == 0) sts1(sM + 24, um);
        named_arrive(11, 64);
        write_ones();
        phi_q();
        if (!isB) {
          mbar_wait_long(BAR_CL(3), 0);
          mbar_wait_long(BAR_RL, 0);
          uint32_t pend = 0xFE;
          const int li = lane & 7;
          const uint32_t* fl = FLAG_OA((tbA + (li & 1)) * 4 + ((hg + (li >> 1)) & 3), 1);
#pragma unroll 1
          for (int it = 0; pend; it++) {
            uint32_t fv;
            asm volatile("ld.acquire.gpu.global.u32 %0, [%1];" : "=r"(fv) : "l"(fl) : "memory");
            uint32_t go = __ballot_sync(~0u, (int32_t)(fv - ep) >= 0 && mbar_test(li >= 6 ? BAR_TE(0) : BAR_CL(4), 0)) & pend;
            pend &= ~go;
            if (go) fence_async_all();
#pragma unroll 1
            while (go) {
              const int b = __ffs(go) - 1;
              go &= go - 1;
              const uint32_t slot = (tail_slots(0, 4 + (b >> 1)) >> (8 * (b & 1))) & 255;
              if (elect_one()) {
                mbar_expect_tx(BAR_TF(8 + b), 8192);
                tma2d(sb + slot * 8192, &mO, ((hg + (b >> 1)) & 3) * 128 + 64, tok0 + (b & 1) * 64, BAR_TF(8 + b));
              }
            }
            if (it > 2000000) __trap();
          }
        }
      }
      else {
        named_bar(11, 64);
        if (elect_one()) {
          g_stats[tbA * 4 + hg] = max(um, lds1(sM + 24));
          flag_add(FLAG_KV2);
        }
        __syncwarp();
        phi_q();
        if (elect_one()) {
          mbar_wait_long(BAR_BDONE, 0);
          tma2d_store(&mQst, sb + OFF_F + 49152, hq * 64, S_TOK + ttB * 128);
          bulk_commit();
          bulk_wait_all();
          fence_async_all();
          flag_add(FLAG_B(hq >> 1));
          mbar_wait(BAR_Q, 0);
          mbar_arrive(BAR_CL(0));
#pragma unroll 1
          for (int p = 0; p < 2; p++) {
            mbar_wait_long(BAR_OD(p), 0);
            if (p == 0) {
#pragma unroll
              for (int w = 0; w < 4; w++) tma2d_store(&mO16, sb + OFF_F + w * 2048, hg * 128 + w * 16, tbA * 64);
            } else {
              tma2d_store(&mO, sb + 26 * 8192, hg * 128 + 64, tbA * 64);
            }
            bulk_commit();
            bulk_wait_all();
            if (p == 0) mbar_arrive(BAR_CL(1));
            PUBLISH(FLAG_OA(tbA * 4 + hg, p));
          }
        }
      }
    }
    return;
  }
  if (helper) { helper_cta(blockIdx.x - 128, sb, bars, wg, w4, &mQst, &mOst); return; }

  {
    float acc[64];
    if (wg == 0) proj_loop<0>(acc, sb, bars, 16384, 0, wg, sWKV, &mWq, hg * 128, w4 == 0, &mXA64, tbA * 64);
    else proj_loop<1>(acc, sb, bars, 16384 + wg * 8192, 49152, wg, sWKV, &mWqkv, (wg - 1) * 512 + hq * 64, w4 == 0, &mXA64, 0);
    const uint32_t sF = sb + OFF_F;
    const uint32_t qa = sF + w4 * 512 + ((lane >> 3) & 1) * 256 + (lane >> 4) * 128 + (lane & 7) * 16;
    if (wg == 0) {
#pragma unroll
      for (int hd = 0; hd < 4; hd++)
        stsm4(qa + hd * 2048, pack_f16(acc[8 * hd] * QSCALE, acc[8 * hd + 1] * QSCALE), pack_f16(acc[8 * hd + 2] * QSCALE, acc[8 * hd + 3] * QSCALE),
              pack_f16(acc[8 * hd + 4] * QSCALE, acc[8 * hd + 5] * QSCALE), pack_f16(acc[8 * hd + 6] * QSCALE, acc[8 * hd + 7] * QSCALE));
      fence_async();
      __syncwarp();
      if (lane == 0) mbar_arrive(BAR_Q);
    } else {
      if (wg != 3) named_arrive(6, 384);
      if (wg != 1) named_arrive(8, 384);
    }
    asm volatile("setmaxnreg.inc.sync.aligned.u32 112;");
    fence_regs<64>(acc);
    if (wg == 0) {
#pragma unroll
      for (int hd = 4; hd < 8; hd++)
        stsm4(qa + hd * 2048, pack_f16(acc[8 * hd] * QSCALE, acc[8 * hd + 1] * QSCALE), pack_f16(acc[8 * hd + 2] * QSCALE, acc[8 * hd + 3] * QSCALE),
              pack_f16(acc[8 * hd + 4] * QSCALE, acc[8 * hd + 5] * QSCALE), pack_f16(acc[8 * hd + 6] * QSCALE, acc[8 * hd + 7] * QSCALE));
      fence_async();
      __syncwarp();
      if (lane == 0) mbar_arrive(BAR_VB(2));
    } else if (wg == 3) {
      named_bar(6, 384);
      const int t = tid & 127;
#pragma unroll
      for (int j = 0; j < 8; j++)
        sts4(sF + 24576 + j * 2048 + t * 16, pack_bf16(acc[8 * j], acc[8 * j + 1]), pack_bf16(acc[8 * j + 2], acc[8 * j + 3]),
             pack_bf16(acc[8 * j + 4], acc[8 * j + 5]), pack_bf16(acc[8 * j + 6], acc[8 * j + 7]));
      named_arrive(7, 256);
    } else {
      if (wg == 1) {
        named_bar(8, 384);
        const int m = lane >> 3, r = lane & 7;
#pragma unroll
        for (int j = 0; j < 16; j += 2) {
          const int tok = (j + (m >> 1)) * 8 + r;
          const int chunk = w4 * 2 + (m & 1);
          stsm4t(sF + 49152 + tok * 128 + ((chunk ^ r) << 4), pack_bf16(acc[4 * j], acc[4 * j + 1]), pack_bf16(acc[4 * j + 2], acc[4 * j + 3]),
                 pack_bf16(acc[4 * j + 4], acc[4 * j + 5]), pack_bf16(acc[4 * j + 6], acc[4 * j + 7]));
        }
      } else {
        uint32_t p[32];
#pragma unroll
        for (int i = 0; i < 32; i++) p[i] = phi2(acc[2 * i], acc[2 * i + 1]);
        named_bar(7, 256);
        float kv0[4] = {0, 0, 0, 0}, kv1[4] = {0, 0, 0, 0}, z0[4] = {0, 0, 0, 0}, z1[4] = {0, 0, 0, 0};
        const uint32_t one = 0x3F803F80u;
        const int t = tid & 127;
#pragma unroll
        for (int j = 0; j < 8; j++) {
          uint32_t a[4];
          lds4(sF + 24576 + j * 2048 + t * 16, a);
          mma_bf16(kv0, a[0], a[1], a[2], a[3], p[4 * j], p[4 * j + 2]);
          mma_bf16(kv1, a[0], a[1], a[2], a[3], p[4 * j + 1], p[4 * j + 3]);
          mma_bf16(z0, one, one, one, one, p[4 * j], p[4 * j + 2]);
          mma_bf16(z1, one, one, one, one, p[4 * j + 1], p[4 * j + 3]);
        }
        float4* dst = g_kvp + ((ttB * 32 + hq * 4 + w4) * 3) * 32 + lane;
        dst[0] = make_float4(kv0[0], kv0[1], kv1[0], kv1[1]);
        dst[32] = make_float4(kv0[2], kv0[3], kv1[2], kv1[3]);
        dst[64] = make_float4(z0[0], z0[1], z1[0], z1[1]);
      }
      __syncwarp();
      if (lane == 0) mbar_arrive(wg == 1 ? BAR_PQ : BAR_BDONE);
    }
  }

  bool safe = true;
  {
    const uint32_t c63 = 0x1F801F80u + (threadIdx.x >> 20);
    const uint32_t m1 = (gridDim.x >> 20) - 1u;
    const uint64_t dK0 = make_desc(sb + OFF_K, 32768, 128, 0);
    const uint64_t dV0 = make_desc(sb + OFF_V, 128, 32768, 0);
    constexpr uint32_t dKV = ((2048u - 8u)  __H0__ ) + STEPK - (OFF_V - OFF_K) / 16;
    float Sm[12], Sp[36], O[12];
    uint32_t P[24];
    uint64_t dQ = make_desc(sb + OFF_F + wg * 2048, 128, 256, 0);
#pragma unroll
    for (int i = 0; i < 36; i++) Sp[i] = SMAGIC;
#pragma unroll
    for (int i = 0; i < 12; i++) Sm[i] = 0.f;
    fence_regs<12>(Sm); fence_regs<36>(Sp);
    mbar_wait(BAR_Q, 0);
    mbar_wait(BAR_KV(0), 0);
    wg_fence();
    wg_qs72<1>(Sp, dQ, dK0 + 24);
    wg_qs24<0>(Sm, dQ, dK0);
    wg_commit();
    wg_wait<0>();
    fence_regs<12>(Sm); fence_regs<36>(Sp);
#pragma unroll 1
    for (int pass = 0; pass < 2; pass++) {
#pragma unroll
      for (int i = 0; i < 12; i++) O[i] = 0.f;
      fence_regs<12>(O);
      uint32_t vlo = (uint32_t)dV0;
#pragma unroll 1
      for (int seg = 0; seg < 4; seg++) {
        if (pass == 0) {
          if (seg < 3) mbar_wait(seg == 0 ? BAR_VB(0) : BAR_KV(seg), 0);
        } else if (seg >= 1) {
          if ((tid & 127) == 0) {
            mbar_arrive(BAR_CL(seg));
            if (seg == 3) take_role(sM, wg);
          }
          __syncwarp();
        }
        const uint32_t vend = vlo + (seg == 3 ? 3 : 6) * STEPK;
#pragma unroll 1
        for (; vlo != vend; vlo += 3 * STEPK) {
          uint64_t dK, dV;
          asm("mov.b64 %0, {%1, %2};" : "=l"(dK) : "r"(vlo + dKV), "r"(8u));
          asm("mov.b64 %0, {%1, %2};" : "=l"(dV) : "r"(vlo), "r"(2048u));
#pragma unroll
          for (int u = 0; u < 3; u++) {
          { uint32_t w[18], y[18], z[18]; float e[12];
            X_MU(0) X_PR(0) X_LO(0) X_IM(0) X_MU(1) X_FM(0) X_PR(1) X_LO(1) X_IM(1) X_MU(2) X_FM(1) X_PR(2)
            X_LO(2) X_MU(3) X_IM(2) X_FM(2) X_PR(3) X_LO(3) X_PK(0) X_MU(4) X_IM(3) X_FM(3) X_PR(4) X_LO(4)
            X_MU(5) X_IM(4) X_FM(4) X_PR(5) X_PK(1) X_MU(6) X_LO(5) X_IM(5) X_FM(5) X_PR(6) X_MU(7) X_LO(6)
            X_IM(6) X_FM(6) X_MU(8) X_PR(7) X_PK(2) X_LO(7) X_IM(7) X_FM(7) X_MU(9) X_PR(8) X_LO(8) X_IM(8)
            X_FM(8) X_PK(3) X_MU(10) X_PR(9) X_LO(9) X_IM(9) X_MU(11) X_FM(9) X_PR(10) X_LO(10) X_IM(10) X_PK(4)
            X_FM(10) X_PR(11) X_LO(11) X_IM(11) X_FM(11) X_PR(12) X_LO(12) X_PK(5) X_IM(12) X_FM(12) X_PR(13) X_LO(13)
            X_IM(13) X_FM(13) X_PR(14) X_LO(14) X_IM(14) X_FM(14) X_PR(15) X_LO(15) X_IM(15) X_FM(15) X_PR(16) X_LO(16)
            X_IM(16) X_FM(16) X_PR(17) X_LO(17) X_IM(17) X_FM(17) }
          fence_regs<24>(P);
          wg_fence();
          wg_pv24<1>(O, &P[20], dV + u * STEPK + 80);
          wg_pv24<1>(O, &P[16], dV + u * STEPK + 64);
          wg_pv24<1>(O, &P[12], dV + u * STEPK + 48);
          wg_pv24<1>(O, &P[8], dV + u * STEPK + 32);
          wg_pv24<1>(O, &P[4], dV + u * STEPK + 16);
          wg_pv24<1>(O, &P[0], dV + u * STEPK + 0);
          wg_qs72<1>(Sp, dQ, dK + u * STEPK + 24);
          wg_qs24<0>(Sm, dQ, dK + u * STEPK);
          wg_commit();
          wg_wait<0>();
          fence_regs<12>(Sm); fence_regs<36>(Sp); fence_regs<12>(O); fence_regs<24>(P);
          }
        }
      }
#pragma unroll
      for (int i = 0; i < 6; i++) P[i] = pack_bf16(ex2f(Sm[2 * i]), ex2f(Sm[2 * i + 1]));
      P[6] = exp2_pair_fix(Sp[0], Sp[1], c63, m1);
      P[7] = exp2_pair_fix(Sp[2], Sp[3], c63, m1);
      fence_regs<8>(P);
      const uint32_t sO = pass == 0 ? sb + OFF_F + wg * 2048 + w4 * 512 + (lane & 15) * 32 + (lane >> 4) * 16
                                    : sb + 26 * 8192 + (w4 * 16 + (lane & 15)) * 128 + (((wg * 2 + (lane >> 4)) ^ (lane & 7)) << 4);
      dQ += 512;
      wg_fence();
      wg_pv24<1>(O, &P[0], dV0 + 21 * STEPK);
      wg_pv24<1>(O, &P[4], dV0 + 21 * STEPK + 16);
      wg_commit();
#pragma unroll
      for (int i = 0; i < 36; i++) Sp[i] = SMAGIC;
      fence_regs<36>(Sp);
      mbar_wait(pass == 0 ? BAR_Q2 : BAR_CL(3), 0);
      wg_fence();
      wg_qs72<1>(Sp, dQ, dK0 + 24);
      wg_qs24<0>(Sm, dQ, dK0);
      wg_commit();
      wg_wait<1>();
      fence_regs<12>(O);
      const float l0 = __shfl_sync(~0u, O[8], lane & ~3), l1 = __shfl_sync(~0u, O[10], lane & ~3);
      const float i0 = rcpf(l0), i1 = rcpf(l1);
      stsm4(sO,
            pack_bf16(O[0] * i0, O[1] * i0), pack_bf16(O[2] * i1, O[3] * i1),
            pack_bf16(O[4] * i0, O[5] * i0), pack_bf16(O[6] * i1, O[7] * i1));
      fence_async();
      {
        safe = __all_sync(~0u, lds1(sM + 16) != 0);
      }
      if (safe && lane == 0) mbar_arrive(BAR_OD(pass));
      wg_wait<0>();
      fence_regs<12>(Sm); fence_regs<36>(Sp);
      if (!safe) break;
    }
  }
  if (!safe) {
    if ((tid & 127) == 0) { mbar_arrive(BAR_CL(1)); mbar_arrive(BAR_CL(2)); mbar_arrive(BAR_CL(3)); take_role(sM, wg); }
#pragma unroll 1
    for (int pass = 0; pass < 2; pass++) {
      const int t = tid & 127;
      mbar_wait(BAR_CL(3), 0);
      attn_slow(prm.xa + (size_t)tbA * 64 * D_MOD, prm.wq + (hg * 8 + pass * 4 + wg) * 16,
                pass == 0 ? sb + OFF_F + wg * 2048 + t * 16
                          : sb + 26 * 8192 + (t >> 1) * 128 + (((wg * 2 + (t & 1)) ^ ((t >> 1) & 7)) << 4));
      __syncwarp();
      if (lane == 0) mbar_arrive(BAR_OD(pass));
    }
  }

  {
    named_bar(wg + 1, 128);
    if ((tid & 127) == 0) mbar_arrive(BAR_CL(4));
    const int role = __shfl_sync(~0u, lds1(sM + 32 + wg * 4), 0);
    const int m = lane >> 3, r = lane & 7;
    const uint32_t stoff = (w4 * 16 + (m & 1) * 8 + r) * 128;
    if (role < 2) {
      if (role == 0 && (tid & 127) == 0) mbar_arrive(BAR_RL);
      if (!isB || role == 1) mbar_wait(BAR_CL(4), 0);
      float acc[64];
#pragma unroll 1
      for (int n = 0; n < 8; n++) {
        const uint32_t sl = tail_slots(isB, n);
        const uint32_t w0 = (sl >> 16) & 255, w1 = sl >> 24;
        const uint64_t da = make_desc(sb + ((sl >> (8 * role)) & 255) * 8192, 16, 1024, 1);
        const uint64_t db = make_desc(sb + w0 * 8192, (w1 - w0) * 8192, 1024, 1);
        mbar_wait(BAR_TF(n), 0);
        if (!isB && n >= 4) mbar_wait(n == 4 && role == 0 ? BAR_OD(1) : BAR_TF(2 * n + role), 0);
        wg_fence();
#pragma unroll
        for (int k = 0; k < 4; k++) wg_ss128<0, 1>(acc, da + k * 2, db + k * 128, (n | k) != 0);
        wg_commit();
        wg_wait<1>();
        if ((n == 1 || n == 2) && (tid & 127) == 0) mbar_arrive(BAR_TE(n - 1));
        __syncwarp();
      }
      wg_wait<0>();
      fence_regs<64>(acc);
      const uint32_t x0 = sb + (role ? 16 : 8) * 8192, x1 = sb + (role ? 5 : 1) * 8192;
#pragma unroll
      for (int j = 0; j < 16; j += 2)
        stsm4((j < 8 ? x0 : x1) + stoff + ((((j & 7) + (m >> 1)) ^ r) << 4),
              pack_bf16(acc[4 * j], acc[4 * j + 1]), pack_bf16(acc[4 * j + 2], acc[4 * j + 3]),
              pack_bf16(acc[4 * j + 4], acc[4 * j + 5]), pack_bf16(acc[4 * j + 6], acc[4 * j + 7]));
      __syncwarp();
      uint4* dst = (uint4*)(prm.out + (size_t)(tok0 + role * 64 + w4 * 16 + (lane >> 4)) * 1024 + isB * 512 + hg * 128) + (lane & 15);
      const uint32_t src = ((lane & 8) ? x1 : x0) + (w4 * 16 + (lane >> 4)) * 128;
#pragma unroll
      for (int i = 0; i < 8; i++) {
        uint32_t v[4];
        lds4(src + i * 256 + (((lane & 7) ^ ((2 * i + (lane >> 4)) & 7)) << 4), v);
        dst[i * 256] = make_uint4(v[0], v[1], v[2], v[3]);
      }
    }
  }
}

__device__ __nv_bfloat16 g_T[S_TOK * 1536];
__device__ float g_Z[32 * 272];
__global__ void fb_gemm(const __nv_bfloat16* A, const __nv_bfloat16* B, __nv_bfloat16* C, int N, int ldc) {
  __shared__ float sa[16][17], sbm[16][17];
  const int tx = threadIdx.x & 15, ty = threadIdx.x >> 4, row = blockIdx.y * 16 + ty, col = blockIdx.x * 16 + tx;
  float acc = 0.f;
  for (int k0 = 0; k0 < D_MOD; k0 += 16) {
    sa[ty][tx] = __bfloat162float(A[(size_t)row * D_MOD + k0 + tx]);
    sbm[ty][tx] = __bfloat162float(B[(size_t)(k0 + ty) * N + col]);
    __syncthreads();
    for (int k = 0; k < 16; k++) acc = fmaf(sa[ty][k], sbm[k][tx], acc);
    __syncthreads();
  }
  C[(size_t)row * ldc + col] = __float2bfloat16_rn(acc);
}
__global__ void fb_attn() {
  const int r = blockIdx.x * blockDim.x + threadIdx.x;
  float q[16], o[16], m = -INFINITY, l = 0.f;
  for (int i = 0; i < 16; i++) { q[i] = __bfloat162float(g_Q[(size_t)r * 16 + i]); o[i] = 0.f; }
  for (int j = 0; j < S_TOK; j++) {
    float s = 0.f;
    for (int i = 0; i < 16; i++) s = fmaf(q[i], __bfloat162float(g_T[j * 32 + i]), s);
    s = rbf(s) * 0.25f;
    const float mn = fmaxf(m, s), c = __expf(m - mn), p = __expf(s - mn);
    l = l * c + p; m = mn;
    for (int i = 0; i < 16; i++) o[i] = fmaf(p, __bfloat162float(g_T[j * 32 + 16 + i]), o[i] * c);
  }
  for (int i = 0; i < 16; i++) g_O[(size_t)r * 16 + i] = __float2bfloat16_rn(o[i] / l);
}
__device__ __forceinline__ float fb_phi(__nv_bfloat16 x) { const float t = __bfloat162float(x); return bf_lo(phi2(t, t)); }
__global__ void fb_kv() {
  const int h = blockIdx.x, t = threadIdx.x, d = t < 256 ? t >> 4 : t - 256, e = t & 15;
  float acc = 0.f;
  for (int s = 0; s < S_TOK; s++)
    acc = fmaf(fb_phi(g_T[(size_t)s * 1536 + 512 + h * 16 + d]), t < 256 ? __bfloat162float(g_T[(size_t)s * 1536 + 1024 + h * 16 + e]) : 1.f, acc);
  g_Z[h * 272 + t] = rbf(acc);
}
__global__ void fb_lin() {
  const int idx = blockIdx.x * blockDim.x + threadIdx.x, s = idx >> 9, c = idx & 511, h = c >> 4, e = c & 15;
  float num = 0.f, den = 0.f;
  for (int d = 0; d < 16; d++) {
    const float p = fb_phi(g_T[(size_t)s * 1536 + h * 16 + d]);
    num = fmaf(p, g_Z[h * 272 + d * 16 + e], num); den = fmaf(p, g_Z[h * 272 + 256 + d], den);
  }
  g_O[(size_t)S_TOK * D_MOD + idx] = __float2bfloat16_rn(num / (den + 1e-6f));
}

typedef CUresult (*EncodeFn)(CUtensorMap*, CUtensorMapDataType, cuuint32_t, void*, const cuuint64_t*, const cuuint64_t*,
                             const cuuint32_t*, const cuuint32_t*, CUtensorMapInterleave, CUtensorMapSwizzle,
                             CUtensorMapL2promotion, CUtensorMapFloatOOBfill);

static void make_map(EncodeFn enc, CUtensorMap* m, const void* ptr, uint64_t cols, uint64_t rows, uint32_t bc, uint32_t br,
                     CUtensorMapSwizzle sw = CU_TENSOR_MAP_SWIZZLE_128B) {
  cuuint64_t dims[2] = {cols, rows};
  cuuint64_t strides[1] = {cols * 2};
  cuuint32_t box[2] = {bc, br};
  cuuint32_t es[2] = {1, 1};
  enc(m, CU_TENSOR_MAP_DATA_TYPE_BFLOAT16, 2, (void*)ptr, dims, strides, box, es, CU_TENSOR_MAP_INTERLEAVE_NONE,
      sw, CU_TENSOR_MAP_L2_PROMOTION_L2_256B, CU_TENSOR_MAP_FLOAT_OOB_FILL_NONE);
}

extern "C" void kernel_launch(void* const* d_in, const int* in_sizes, int n_in, void* d_out, int out_size) {
  (void)in_sizes; (void)n_in; (void)out_size;
  static EncodeFn enc = nullptr;
  static void* pQ = nullptr; static void* pO = nullptr; static void* pT = nullptr; static void* pK = nullptr;
  static bool fused = false;
  if (!enc) {
    void* fn = nullptr; cudaDriverEntryPointQueryResult qr;
    cudaGetDriverEntryPoint("cuTensorMapEncodeTiled", &fn, cudaEnableDefault, &qr);
    enc = (EncodeFn)fn;
    cudaGetSymbolAddress(&pQ, g_Q);
    cudaGetSymbolAddress(&pO, g_O);
    cudaGetSymbolAddress(&pT, g_T);
    cudaGetSymbolAddress(&pK, g_KV);
    cudaFuncSetAttribute(k1_main, cudaFuncAttributeMaxDynamicSharedMemorySize, SM_TOTAL);
    int dev = 0, sms = 0, occ = 0;
    cudaGetDevice(&dev);
    cudaDeviceGetAttribute(&sms, cudaDevAttrMultiProcessorCount, dev);
    cudaOccupancyMaxActiveBlocksPerMultiprocessor(&occ, k1_main, 640, SM_TOTAL);
    fused = sms * occ >= 132;
  }
  if (!fused) {
    typedef const __nv_bfloat16* CB; typedef __nv_bfloat16* MB;
    cudaStream_t st = cudaStreamPerThread;
    fb_gemm<<<dim3(32, 128), 256, 0, st>>>((CB)d_in[0], (CB)d_in[1], (MB)pQ, 512, 512);
    fb_gemm<<<dim3(1, 128), 256, 0, st>>>((CB)d_in[0], (CB)d_in[2], (MB)pT, 16, 32);
    fb_gemm<<<dim3(1, 128), 256, 0, st>>>((CB)d_in[0], (CB)d_in[3], (MB)pT + 16, 16, 32);
    fb_attn<<<512, 128, 0, st>>>();
    fb_gemm<<<dim3(96, 128), 256, 0, st>>>((CB)d_in[5], (CB)d_in[6], (MB)pT, 1536, 1536);
    fb_kv<<<32, 272, 0, st>>>();
    fb_lin<<<4096, 256, 0, st>>>();
    fb_gemm<<<dim3(32, 128), 256, 0, st>>>((CB)pO, (CB)d_in[4], (MB)d_out, 512, 1024);
    fb_gemm<<<dim3(32, 128), 256, 0, st>>>((CB)pO + S_TOK * D_MOD, (CB)d_in[7], (MB)d_out + 512, 512, 1024);
    return;
  }
  CUtensorMap mXA64, mXB, mWq, mWqkv, mQst, mO, mOst, mWoA, mWoB, mO16, mKV;
  make_map(enc, &mXA64, d_in[0], 512, 2048, 64, 64);
  make_map(enc, &mWq, d_in[1], 512, 512, 64, 64);
  make_map(enc, &mWoA, d_in[4], 512, 512, 64, 64);
  make_map(enc, &mXB, d_in[5], 512, 2048, 64, 128);
  make_map(enc, &mWqkv, d_in[6], 1536, 512, 64, 64);
  make_map(enc, &mWoB, d_in[7], 512, 512, 64, 64);
  make_map(enc, &mQst, pQ, 512, 4096, 64, 128);
  make_map(enc, &mO, pO, 512, 4096, 64, 64);
  make_map(enc, &mOst, pO, 512, 4096, 64, 128);
  make_map(enc, &mO16, pO, 512, 4096, 16, 64, CU_TENSOR_MAP_SWIZZLE_NONE);
  {
    cuuint64_t dims[3] = {768, 22, 4};
    cuuint64_t strides[2] = {1536, 32768};
    cuuint32_t box[3] = {8, 11, 1};
    cuuint32_t es[3] = {1, 1, 1};
    enc(&mKV, CU_TENSOR_MAP_DATA_TYPE_BFLOAT16, 3, pK, dims, strides, box, es, CU_TENSOR_MAP_INTERLEAVE_NONE,
        CU_TENSOR_MAP_SWIZZLE_NONE, CU_TENSOR_MAP_L2_PROMOTION_NONE, CU_TENSOR_MAP_FLOAT_OOB_FILL_NONE);
  }
  Params prm{(const __nv_bfloat16*)d_in[2], (const __nv_bfloat16*)d_in[3], (const __nv_bfloat16*)d_in[0], (const __nv_bfloat16*)d_in[1], (__nv_bfloat16*)d_out};
  k1_main<<<132, 640, SM_TOTAL, cudaStreamPerThread>>>(mXA64, mXB, mWq, mWqkv, mQst, mOst, mO, mWoA, mWoB, mO16, mKV, prm);
}
```

```cpp
#include <cuda_runtime.h>
#include <cuda_bf16.h>
#include <cuda_fp16.h>
#include <cuda.h>
#include <stdint.h>

#define S_TOK 2048
#define D_MOD 512

__device__ __align__(1024) __nv_bfloat16 g_Q[2 * S_TOK * D_MOD];
__device__ __align__(1024) __nv_bfloat16 g_O[2 * S_TOK * D_MOD];
__device__ __align__(1024) uint4 g_KV[8 * S_TOK];
__device__ __align__(16) uint32_t g_stats[128];
__device__ __align__(16) float4 g_kvp[32 * 32 * 3 * 32];

__device__ __forceinline__ uint32_t smem_u32(const void* p) { return (uint32_t)__cvta_generic_to_shared(p); }
__device__ __forceinline__ void mbar_init(uint32_t bar, int cnt) { asm volatile("mbarrier.init.shared::cta.b64 [%0], %1;" :: "r"(bar), "r"(cnt) : "memory"); }
__device__ __forceinline__ void mbar_expect_tx(uint32_t bar, uint32_t bytes) { asm volatile("mbarrier.arrive.expect_tx.shared::cta.b64 _, [%0], %1;" :: "r"(bar), "r"(bytes) : "memory"); }
__device__ __forceinline__ void mbar_wait(uint32_t bar, uint32_t parity) {
  asm volatile("{\n.reg .pred p;\n.reg .u32 c;\nmov.u32 c, 0;\n"
               "LW_%=:\n"
               "mbarrier.try_wait.parity.shared::cta.b64 p, [%0], %1;\n"
               "@p bra LD_%=;\n"
               "add.u32 c, c, 1;\n"
               "setp.lt.u32 p, c, 4000000;\n"
               "@p bra LW_%=;\n"
               "trap;\n"
               "LD_%=:\n}\n" :: "r"(bar), "r"(parity) : "memory");
}
__device__ __forceinline__ void tma2d(uint32_t dst, const CUtensorMap* m, int c0, int c1, uint32_t bar) {
  asm volatile("cp.async.bulk.tensor.2d.shared::cluster.global.mbarrier::complete_tx::bytes [%0], [%1, {%3, %4}], [%2];"
               :: "r"(dst), "l"(m), "r"(bar), "r"(c0), "r"(c1) : "memory");
}
__device__ __forceinline__ void tma2d_store(const CUtensorMap* m, uint32_t src, int c0, int c1) {
  asm volatile("cp.async.bulk.tensor.2d.global.shared::cta.bulk_group [%0, {%2, %3}], [%1];"
               :: "l"(m), "r"(src), "r"(c0), "r"(c1) : "memory");
}
__device__ __forceinline__ void tma3d_store(const CUtensorMap* m, uint32_t src, int c0, int c1, int c2) {
  asm volatile("cp.async.bulk.tensor.3d.global.shared::cta.bulk_group [%0, {%2, %3, %4}], [%1];"
               :: "l"(m), "r"(src), "r"(c0), "r"(c1), "r"(c2) : "memory");
}
__device__ __forceinline__ void bulk_g2s(uint32_t dst, const void* src, uint32_t bytes, uint32_t bar) {
  asm volatile("cp.async.bulk.shared::cluster.global.mbarrier::complete_tx::bytes [%0], [%1], %2, [%3];"
               :: "r"(dst), "l"(src), "r"(bytes), "r"(bar) : "memory");
}
__device__ __forceinline__ void bulk_commit() { asm volatile("cp.async.bulk.commit_group;" ::: "memory"); }
__device__ __forceinline__ void bulk_wait_all() { asm volatile("cp.async.bulk.wait_group 0;" ::: "memory"); }
__device__ __forceinline__ void fence_async() { asm volatile("fence.proxy.async.shared::cta;" ::: "memory"); }
__device__ __forceinline__ void named_bar(int id, int n) { asm volatile("bar.sync %0, %1;" :: "r"(id), "r"(n) : "memory"); }
__device__ __forceinline__ void wg_fence() { asm volatile("wgmma.fence.sync.aligned;" ::: "memory"); }
__device__ __forceinline__ void wg_commit() { asm volatile("wgmma.commit_group.sync.aligned;" ::: "memory"); }
template <int n> __device__ __forceinline__ void wg_wait() { asm volatile("wgmma.wait_group.sync.aligned %0;" :: "n"(n) : "memory"); }
template <int n> __device__ __forceinline__ void fence_regs(float* r) {
#pragma unroll
  for (int i = 0; i < n; i++) asm volatile("" : "+f"(r[i]) :: "memory");
}
template <int n> __device__ __forceinline__ void fence_regs(uint32_t* r) {
#pragma unroll
  for (int i = 0; i < n; i++) asm volatile("" : "+r"(r[i]) :: "memory");
}
__device__ __forceinline__ uint64_t make_desc(uint32_t addr, uint32_t lbo, uint32_t sbo, uint32_t swz) {
  return (uint64_t)((addr & 0x3FFFF) >> 4) | ((uint64_t)(lbo >> 4) << 16) | ((uint64_t)(sbo >> 4) << 32) | ((uint64_t)swz << 62);
}
__device__ __forceinline__ float ex2f(float x) { float y; asm("ex2.approx.ftz.f32 %0, %1;" : "=f"(y) : "f"(x)); return y; }
__device__ __forceinline__ uint32_t pack_bf16(float lo, float hi) { uint32_t r; asm("cvt.rn.bf16x2.f32 %0, %1, %2;" : "=r"(r) : "f"(hi), "f"(lo)); return r; }
__device__ __forceinline__ uint32_t pack_f16(float lo, float hi) { uint32_t r; asm("cvt.rn.f16x2.f32 %0, %1, %2;" : "=r"(r) : "f"(hi), "f"(lo)); return r; }
__device__ __forceinline__ float bf_lo(uint32_t v) { return __uint_as_float(v << 16); }
__device__ __forceinline__ float bf_hi(uint32_t v) { return __uint_as_float(v & 0xFFFF0000u); }
__device__ __forceinline__ float rbf(float x) { return __bfloat162float(__float2bfloat16_rn(x)); }
__device__ __forceinline__ void stsm4(uint32_t a, uint32_t r0, uint32_t r1, uint32_t r2, uint32_t r3) {
  asm volatile("stmatrix.sync.aligned.m8n8.x4.shared.b16 [%0], {%1,%2,%3,%4};" :: "r"(a), "r"(r0), "r"(r1), "r"(r2), "r"(r3) : "memory");
}
__device__ __forceinline__ void stsm4t(uint32_t a, uint32_t r0, uint32_t r1, uint32_t r2, uint32_t r3) {
  asm volatile("stmatrix.sync.aligned.m8n8.x4.trans.shared.b16 [%0], {%1,%2,%3,%4};" :: "r"(a), "r"(r0), "r"(r1), "r"(r2), "r"(r3) : "memory");
}
__device__ __forceinline__ void mma_bf16(float* d, uint32_t a0, uint32_t a1, uint32_t a2, uint32_t a3, uint32_t b0, uint32_t b1) {
  asm volatile("mma.sync.aligned.m16n8k16.row.col.f32.bf16.bf16.f32 {%0,%1,%2,%3}, {%4,%5,%6,%7}, {%8,%9}, {%0,%1,%2,%3};"
               : "+f"(d[0]), "+f"(d[1]), "+f"(d[2]), "+f"(d[3]) : "r"(a0), "r"(a1), "r"(a2), "r"(a3), "r"(b0), "r"(b1));
}
template<int SD> __device__ __forceinline__ void wg_qs24(float* d, uint64_t da, uint64_t db) {
  asm volatile("wgmma.mma_async.sync.aligned.m64n24k16.f32.f16.f16 {%0,%1,%2,%3,%4,%5,%6,%7,%8,%9,%10,%11}, %12, %13, %14, 1, 1, 0, 0;"
   : "+f"(d[0]),"+f"(d[1]),"+f"(d[2]),"+f"(d[3]),"+f"(d[4]),"+f"(d[5]),"+f"(d[6]),"+f"(d[7]),"+f"(d[8]),"+f"(d[9]),"+f"(d[10]),"+f"(d[11])
   : "l"(da),"l"(db),"n"(SD));
}
template<int SD> __device__ __forceinline__ void wg_qs72(float* d, uint64_t da, uint64_t db) {
  asm volatile("wgmma.mma_async.sync.aligned.m64n72k16.f32.f16.f16 {%0,%1,%2,%3,%4,%5,%6,%7,%8,%9,%10,%11,%12,%13,%14,%15,%16,%17,%18,%19,%20,%21,%22,%23,%24,%25,%26,%27,%28,%29,%30,%31,%32,%33,%34,%35}, %36, %37, %38, 1, 1, 0, 0;"
   : "+f"(d[0]),"+f"(d[1]),"+f"(d[2]),"+f"(d[3]),"+f"(d[4]),"+f"(d[5]),"+f"(d[6]),"+f"(d[7]),"+f"(d[8]),"+f"(d[9]),"+f"(d[10]),"+f"(d[11]),"+f"(d[12]),"+f"(d[13]),"+f"(d[14]),"+f"(d[15]),"+f"(d[16]),"+f"(d[17]),"+f"(d[18]),"+f"(d[19]),"+f"(d[20]),"+f"(d[21]),"+f"(d[22]),"+f"(d[23]),"+f"(d[24]),"+f"(d[25]),"+f"(d[26]),"+f"(d[27]),"+f"(d[28]),"+f"(d[29]),"+f"(d[30]),"+f"(d[31]),"+f"(d[32]),"+f"(d[33]),"+f"(d[34]),"+f"(d[35])
   : "l"(da),"l"(db),"n"(SD));
}
template<int SD> __device__ __forceinline__ void wg_pv24(float* d, const uint32_t* a, uint64_t desc) {
  asm volatile("wgmma.mma_async.sync.aligned.m64n24k16.f32.bf16.bf16 {%0,%1,%2,%3,%4,%5,%6,%7,%8,%9,%10,%11}, {%12,%13,%14,%15}, %16, %17, 1, 1, 1;"
   : "+f"(d[0]),"+f"(d[1]),"+f"(d[2]),"+f"(d[3]),"+f"(d[4]),"+f"(d[5]),"+f"(d[6]),"+f"(d[7]),"+f"(d[8]),"+f"(d[9]),"+f"(d[10]),"+f"(d[11])
   : "r"(a[0]),"r"(a[1]),"r"(a[2]),"r"(a[3]),"l"(desc),"n"(SD));
}
template<int TA, int TB> __device__ __forceinline__ void wg_ss128(float* d, uint64_t da, uint64_t db, int sd) {
  asm volatile("{\n.reg .pred p;\nsetp.ne.b32 p, %66, 0;\n"
   "wgmma.mma_async.sync.aligned.m64n128k16.f32.bf16.bf16 {%0,%1,%2,%3,%4,%5,%6,%7,%8,%9,%10,%11,%12,%13,%14,%15,%16,%17,%18,%19,%20,%21,%22,%23,%24,%25,%26,%27,%28,%29,%30,%31,%32,%33,%34,%35,%36,%37,%38,%39,%40,%41,%42,%43,%44,%45,%46,%47,%48,%49,%50,%51,%52,%53,%54,%55,%56,%57,%58,%59,%60,%61,%62,%63}, %64, %65, p, 1, 1, %67, %68;\n}\n"
   : "+f"(d[0]),"+f"(d[1]),"+f"(d[2]),"+f"(d[3]),"+f"(d[4]),"+f"(d[5]),"+f"(d[6]),"+f"(d[7]),"+f"(d[8]),"+f"(d[9]),"+f"(d[10]),"+f"(d[11]),"+f"(d[12]),"+f"(d[13]),"+f"(d[14]),"+f"(d[15]),"+f"(d[16]),"+f"(d[17]),"+f"(d[18]),"+f"(d[19]),"+f"(d[20]),"+f"(d[21]),"+f"(d[22]),"+f"(d[23]),"+f"(d[24]),"+f"(d[25]),"+f"(d[26]),"+f"(d[27]),"+f"(d[28]),"+f"(d[29]),"+f"(d[30]),"+f"(d[31]),"+f"(d[32]),"+f"(d[33]),"+f"(d[34]),"+f"(d[35]),"+f"(d[36]),"+f"(d[37]),"+f"(d[38]),"+f"(d[39]),"+f"(d[40]),"+f"(d[41]),"+f"(d[42]),"+f"(d[43]),"+f"(d[44]),"+f"(d[45]),"+f"(d[46]),"+f"(d[47]),"+f"(d[48]),"+f"(d[49]),"+f"(d[50]),"+f"(d[51]),"+f"(d[52]),"+f"(d[53]),"+f"(d[54]),"+f"(d[55]),"+f"(d[56]),"+f"(d[57]),"+f"(d[58]),"+f"(d[59]),"+f"(d[60]),"+f"(d[61]),"+f"(d[62]),"+f"(d[63])
   : "l"(da),"l"(db),"r"(sd),"n"(TA),"n"(TB));
}
template<int TA, int TB> __device__ __forceinline__ void wg_ss8(float* d, uint64_t da, uint64_t db, int sd) {
  asm volatile("{\n.reg .pred p;\nsetp.ne.b32 p, %6, 0;\n"
   "wgmma.mma_async.sync.aligned.m64n8k16.f32.bf16.bf16 {%0,%1,%2,%3}, %4, %5, p, 1, 1, %7, %8;\n}\n"
   : "+f"(d[0]),"+f"(d[1]),"+f"(d[2]),"+f"(d[3])
   : "l"(da),"l"(db),"r"(sd),"n"(TA),"n"(TB));
}


__device__ __forceinline__ uint32_t phi2(float a, float b) {
  uint32_t r, e;
  asm("cvt.rn.relu.bf16x2.f32 %0, %1, %2;" : "=r"(r) : "f"(b), "f"(a));
  e = pack_bf16(ex2f(a * 1.4426950408889634f), ex2f(b * 1.4426950408889634f));
  asm("add.rn.bf16x2 %0, %0, %1;" : "+r"(e) : "r"(0x35863586u));
  asm("min.NaN.bf16x2 %0, %0, %1;" : "+r"(e) : "r"(0x3F803F80u));
  asm("add.rn.bf16x2 %0, %0, %1;" : "+r"(e) : "r"(r));
  return e;
}

__device__ __forceinline__ void mbar_wait_long(uint32_t bar, uint32_t parity) {
  asm volatile("{\n.reg .pred p;\n.reg .u32 c;\nmov.u32 c, 0;\n"
               "LW_%=:\n"
               "mbarrier.try_wait.parity.shared::cta.b64 p, [%0], %1, 10000;\n"
               "@p bra LD_%=;\n"
               "add.u32 c, c, 1;\n"
               "setp.lt.u32 p, c, 400000;\n"
               "@p bra LW_%=;\n"
               "trap;\n"
               "LD_%=:\n}\n" :: "r"(bar), "r"(parity) : "memory");
}
__device__ __forceinline__ void mbar_arrive(uint32_t bar) { asm volatile("mbarrier.arrive.shared::cta.b64 _, [%0];" :: "r"(bar) : "memory"); }
__device__ __forceinline__ void named_arrive(int id, int n) { asm volatile("bar.arrive %0, %1;" :: "r"(id), "r"(n) : "memory"); }
__device__ __forceinline__ void fence_async_all() { asm volatile("fence.proxy.async.global;" ::: "memory"); }
__device__ __forceinline__ void flag_add(uint32_t* f) { asm volatile("fence.acq_rel.gpu;\nred.relaxed.gpu.global.add.u32 [%0], 1;" :: "l"(f) : "memory"); }
#define PUBLISH(f) asm volatile("fence.proxy.async.global;\nred.relaxed.gpu.global.add.u32 [%0], 1;" :: "l"(f) : "memory")
__device__ __forceinline__ void flag_wait(const uint32_t* f, uint32_t target) {
  uint32_t v;
#pragma unroll 1
  for (int it = 0;; it++) {
    asm volatile("ld.acquire.gpu.global.u32 %0, [%1];" : "=r"(v) : "l"(f) : "memory");
    if ((int32_t)(v - target) >= 0) break;
    if (it > 2000000) __trap();
    __nanosleep(64);
  }
}
__device__ __forceinline__ bool mbar_test(uint32_t bar, uint32_t parity) {
  uint32_t ok;
  asm volatile("{\n.reg .pred p;\nmbarrier.test_wait.parity.shared::cta.b64 p, [%1], %2;\nselp.b32 %0, 1, 0, p;\n}\n" : "=r"(ok) : "r"(bar), "r"(parity) : "memory");
  return ok;
}
__device__ __forceinline__ bool elect_one() {
  uint32_t p;
  asm volatile("{\n.reg .pred P;\nelect.sync _|P, 0xFFFFFFFF;\nselp.b32 %0, 1, 0, P;\n}\n" : "=r"(p));
  return p;
}
__device__ __forceinline__ void lds4(uint32_t a, uint32_t* r) {
  asm volatile("ld.shared.v4.b32 {%0,%1,%2,%3}, [%4];" : "=r"(r[0]), "=r"(r[1]), "=r"(r[2]), "=r"(r[3]) : "r"(a) : "memory");
}
__device__ __forceinline__ uint32_t lds1(uint32_t a) { uint32_t r; asm volatile("ld.shared.b32 %0, [%1];" : "=r"(r) : "r"(a) : "memory"); return r; }
__device__ __forceinline__ void sts1(uint32_t a, uint32_t v) { asm volatile("st.shared.b32 [%0], %1;" :: "r"(a), "r"(v) : "memory"); }
__device__ __forceinline__ void sts4(uint32_t a, uint32_t r0, uint32_t r1, uint32_t r2, uint32_t r3) {
  asm volatile("st.shared.v4.b32 [%0], {%1,%2,%3,%4};" :: "r"(a), "r"(r0), "r"(r1), "r"(r2), "r"(r3) : "memory");
}
__device__ __forceinline__ void ldsm4(uint32_t a, uint32_t* r) {
  asm volatile("ldmatrix.sync.aligned.m8n8.x4.shared.b16 {%0,%1,%2,%3}, [%4];" : "=r"(r[0]), "=r"(r[1]), "=r"(r[2]), "=r"(r[3]) : "r"(a) : "memory");
}
__device__ __forceinline__ float rcpf(float x) { float y; asm("rcp.approx.ftz.f32 %0, %1;" : "=f"(y) : "f"(x)); return y; }
__device__ __forceinline__ uint32_t hfma2(uint32_t a, uint32_t b, uint32_t c) { uint32_t r; asm("fma.rn.f16x2 %0, %1, %2, %3;" : "=r"(r) : "r"(a), "r"(b), "r"(c)); return r; }
__device__ __forceinline__ uint32_t hadd2(uint32_t a, uint32_t b) { uint32_t r; asm("add.rn.f16x2 %0, %1, %2;" : "=r"(r) : "r"(a), "r"(b)); return r; }

#define STEPK 96
#define GIMAP(i) ((((i) & 1) << 2) | (((i) >> 1) & 3) | ((i) & 8))
#define QSCALE 0.36067376022224085f
#define SMAGIC (512.0f + 2.0f * (191.0f - 30.0f - 1.5823545f))
#define VSHIFT 1073741824.0f

__device__ uint32_t g_epoch[132];
__device__ uint32_t g_flag[288 * 8];
#define FLAG_KV (g_flag)
#define FLAG_KV2 (g_flag + 8 * 8)
#define FLAG_B(h) (g_flag + (4 + (h)) * 8)
#define FLAG_OA(cta, pass) (g_flag + (16 + (cta) * 2 + (pass)) * 8)
#define FLAG_LM(i) (g_flag + (272 + (i)) * 8)

#define SM_TOTAL (224 * 1024 + 3072)
#define OFF_K 0
#define OFF_F 65536
#define OFF_V 131072
#define OFF_MISC (224 * 1024)

#define BAR_FULL(s) (bars + 8 * (s))
#define BAR_FW(s, w) (bars + 408 + 8 * ((s) * 4 + (w)))
#define BAR_EMPTY(s) (bars + 24 + 8 * (s))
#define BAR_KV(c) (bars + 48 + 8 * (c))
#define BAR_E0(i) (bars + 200 + 8 * (i))
#define BAR_BDONE (bars + 80)
#define BAR_Q (bars + 88)
#define BAR_GO (bars + 96)
#define BAR_Q2 (bars + 104)
#define BAR_OD(p) (bars + 112 + 8 * (p))
#define BAR_CL(c) (bars + 128 + 8 * (c))
#define BAR_TE(i) (bars + 168 + 8 * (i))
#define BAR_RL (bars + 184)
#define BAR_TF(g) (bars + 224 + 8 * (g))
#define BAR_XA(w) (bars + 352 + 8 * (w))
#define BAR_VB(c) (bars + 384 + 8 * (c))

__device__ __forceinline__ uint32_t exp2_pair_fix(float d0, float d1, uint32_t c63, uint32_t m1) {
  uint32_t w, y, s, r;
  asm("prmt.b32 %0, %1, %2, 0x6521;" : "=r"(w) : "r"(__float_as_uint(d0)), "r"(__float_as_uint(d1)));
  asm("lop3.b32 %0, %1, 0x007F007F, %2, 0xEA;" : "=r"(y) : "r"(w), "r"(c63));
  asm("mad.lo.u32 %0, %1, %2, %3;" : "=r"(s) : "r"(y), "r"(m1), "r"(w));
  asm("fma.rn.bf16x2 %0, %1, %2, %3;" : "=r"(r) : "r"(w), "r"(y), "r"(s));
  return r;
}

#define X_PR(i) asm volatile("prmt.b32 %0, %1, %2, 0x6521;" : "=r"(w[i]) : "r"(__float_as_uint(Sp[2 * (i)])), "r"(__float_as_uint(Sp[2 * (i) + 1])));
#define X_LO(i) asm volatile("lop3.b32 %0, %1, 0x007F007F, %2, 0xEA;" : "=r"(y[i]) : "r"(w[i]), "r"(c63));
#define X_IM(i) asm volatile("mad.lo.u32 %0, %1, %2, %3;" : "=r"(z[i]) : "r"(y[i]), "r"(m1), "r"(w[i]));
#define X_FM(i) asm volatile("fma.rn.bf16x2 %0, %1, %2, %3;" : "=r"(P[6 + (i)]) : "r"(w[i]), "r"(y[i]), "r"(z[i]));
#define X_MU(i) asm volatile("ex2.approx.ftz.f32 %0, %1;" : "=f"(e[i]) : "f"(Sm[i]));
#define X_PK(i) asm volatile("cvt.rn.bf16x2.f32 %0, %1, %2;" : "=r"(P[i]) : "f"(e[2 * (i) + 1]), "f"(e[2 * (i)]));

__device__ __forceinline__ void attn_slow(const __nv_bfloat16* xa, const __nv_bfloat16* wq, uint32_t dst) {
  const int t = threadIdx.x & 127;
  const int row = t >> 1, half = t & 1;
  float q[16];
  {
    float a[8];
#pragma unroll
    for (int i = 0; i < 8; i++) a[i] = 0.f;
#pragma unroll 1
    for (int k = 0; k < D_MOD; k++) {
      const float x = __bfloat162float(xa[(size_t)row * D_MOD + k]);
      const uint4 w = *(const uint4*)(wq + (size_t)k * D_MOD + half * 8);
      const uint32_t ww[4] = {w.x, w.y, w.z, w.w};
#pragma unroll
      for (int i = 0; i < 4; i++) { a[2 * i] = fmaf(x, bf_lo(ww[i]), a[2 * i]); a[2 * i + 1] = fmaf(x, bf_hi(ww[i]), a[2 * i + 1]); }
    }
#pragma unroll
    for (int i = 0; i < 8; i++) {
      const float mine = rbf(a[i]), other = __shfl_xor_sync(~0u, mine, 1);
      q[i] = half ? other : mine; q[8 + i] = half ? mine : other;
    }
  }
  float m = -INFINITY, l = 0.f, o[16];
#pragma unroll
  for (int i = 0; i < 16; i++) o[i] = 0.f;
#pragma unroll 1
  for (int j = half * 1024; j < half * 1024 + 1024; j++) {
    uint4 ka = g_KV[4 * S_TOK + j], kb = g_KV[5 * S_TOK + j];
    uint4 va = g_KV[6 * S_TOK + j], vb = g_KV[7 * S_TOK + j];
    uint32_t kk[8] = {ka.x, ka.y, ka.z, ka.w, kb.x, kb.y, kb.z, kb.w};
    uint32_t vv[8] = {va.x, va.y, va.z, va.w, vb.x, vb.y, vb.z, vb.w};
    float s = 0.f;
#pragma unroll
    for (int i = 0; i < 8; i++) { s = fmaf(q[2 * i], bf_lo(kk[i]), s); s = fmaf(q[2 * i + 1], bf_hi(kk[i]), s); }
    s = rbf(s) * 0.25f;
    if (s > m) {
      float c = __expf(m - s);
      l *= c;
#pragma unroll
      for (int i = 0; i < 16; i++) o[i] *= c;
      m = s;
    }
    float p = __expf(s - m);
    l += p;
#pragma unroll
    for (int i = 0; i < 8; i++) { o[2 * i] = fmaf(p, bf_lo(vv[i]), o[2 * i]); o[2 * i + 1] = fmaf(p, bf_hi(vv[i]), o[2 * i + 1]); }
  }
  float m2 = __shfl_xor_sync(~0u, m, 1);
  float mm = fmaxf(m, m2);
  float c = __expf(m - mm);
  l *= c; l += __shfl_xor_sync(~0u, l, 1);
  float inv = 1.f / l;
  uint32_t r[8];
#pragma unroll
  for (int i = 0; i < 16; i++) { o[i] *= c; o[i] += __shfl_xor_sync(~0u, o[i], 1); o[i] *= inv; }
#pragma unroll
  for (int i = 0; i < 8; i++) r[i] = pack_bf16(o[2 * i], o[2 * i + 1]);
  if (half == 0) sts4(dst, r[0], r[1], r[2], r[3]); else sts4(dst, r[4], r[5], r[6], r[7]);
  fence_async();
}

struct Params { const __nv_bfloat16* wk; const __nv_bfloat16* wv; const __nv_bfloat16* xa; const __nv_bfloat16* wq; __nv_bfloat16* out; };

__device__ __forceinline__ void helper_cta(const int h, const uint32_t sb, const uint32_t bars, const int wg, const int w4,
                                           const CUtensorMap* mQ, const CUtensorMap* mOs) {
  const int lane = threadIdx.x & 31;
  mbar_wait(BAR_GO, 0);
  const int cb = wg & 1, col = h * 128 + cb * 64, row0 = S_TOK + (wg >> 1) * 1024;
  const uint32_t buf = sb + wg * 49152;
  if (w4 == 0 && elect_one()) {
    fence_async_all();
#pragma unroll 1
    for (int u = 0; u < 3; u++) {
      mbar_expect_tx(BAR_TF(wg * 3 + u), 16384);
      tma2d(buf + u * 16384, mQ, col, row0 + u * 128, BAR_TF(wg * 3 + u));
    }
  }
  const int head = h * 8 + cb * 4 + w4;
  float4 a0 = make_float4(0, 0, 0, 0), a1 = a0, a2 = a0;
#pragma unroll 8
  for (int tt = 0; tt < 32; tt++) {
    const float4* src = g_kvp + ((tt * 32 + head) * 3) * 32 + lane;
    float4 u = src[0], v = src[32], w = src[64];
    a0.x += u.x; a0.y += u.y; a0.z += u.z; a0.w += u.w;
    a1.x += v.x; a1.y += v.y; a1.z += v.z; a1.w += v.w;
    a2.x += w.x; a2.y += w.y; a2.z += w.z; a2.w += w.w;
  }
  const uint32_t b00 = pack_bf16(a0.x, a0.y), b01 = pack_bf16(a0.z, a0.w);
  const uint32_t b10 = pack_bf16(a1.x, a1.y), b11 = pack_bf16(a1.z, a1.w);
  const uint32_t bz0 = pack_bf16(a2.x, a2.y), bz1 = pack_bf16(a2.z, a2.w);
  const int m = lane >> 3, r = lane & 7;
  const uint32_t off = ((m & 1) * 8 + r) * 128 + (((w4 * 2 + (m >> 1)) ^ r) << 4);
  int s = 0, ph = 0;
#pragma unroll 1
  for (int u = 0; u < 8; u++) {
    const uint32_t bb = buf + s * 16384;
    mbar_wait(BAR_TF(wg * 3 + s), ph);
#pragma unroll
    for (int mt = 0; mt < 8; mt++) {
      uint32_t a[4];
      ldsm4(bb + mt * 2048 + off, a);
      float n0[4] = {0, 0, 0, 0}, n1[4] = {0, 0, 0, 0}, dn[4] = {0, 0, 0, 0};
      mma_bf16(dn, a[0], a[1], a[2], a[3], bz0, bz1);
      mma_bf16(n0, a[0], a[1], a[2], a[3], b00, b01);
      mma_bf16(n1, a[0], a[1], a[2], a[3], b10, b11);
      const float i0 = rcpf(dn[0] + 1e-6f), i1 = rcpf(dn[2] + 1e-6f);
      stsm4(bb + mt * 2048 + off, pack_bf16(n0[0] * i0, n0[1] * i0), pack_bf16(n0[2] * i1, n0[3] * i1),
            pack_bf16(n1[0] * i0, n1[1] * i0), pack_bf16(n1[2] * i1, n1[3] * i1));
    }
    fence_async();
    named_bar(wg + 1, 128);
    if (w4 == 0 && lane == 0) {
      tma2d_store(mOs, bb, col, row0 + u * 128);
      bulk_commit();
      if (u >= 1 && u + 2 < 8) {
        asm volatile("cp.async.bulk.wait_group.read 1;" ::: "memory");
        const int sp = s == 0 ? 2 : s - 1;
        mbar_expect_tx(BAR_TF(wg * 3 + sp), 16384);
        tma2d(buf + sp * 16384, mQ, col, row0 + (u + 2) * 128, BAR_TF(wg * 3 + sp));
      }
    }
    __syncwarp();
    if (++s == 3) { s = 0; ph ^= 1; }
  }
  if (w4 == 0 && lane == 0) {
    bulk_wait_all();
    fence_async_all();
    flag_add(FLAG_LM((h * 2 + cb) * 2 + (wg >> 1)));
  }
}

#define STAGE(s) (sb + (2 - (s)) * 65536)
__device__ __forceinline__ uint32_t xa_addr(uint32_t sb, int kb) {
  return sb + (kb >= 1 && kb <= 4 ? OFF_V + 65536 + (kb - 1) * 8192 : 16384 + (kb == 5 ? OFF_K : (kb == 6 ? OFF_V : OFF_F)));
}
#define XA7_TMP (sb + OFF_K + 8192)
#define WKV_TMP (sb + OFF_K)
template <int TR> __device__ __forceinline__ void proj_kb(float* acc, uint32_t aA, uint32_t aB, int first) {
  const uint64_t da = make_desc(aA, TR ? 8192 : 16, 1024, 1);
  const uint64_t db = make_desc(aB, TR ? 16 : 8192, 1024, 1);
  wg_fence();
#pragma unroll
  for (int k = 0; k < 4; k++) wg_ss128<TR, 1 - TR>(acc, da + k * (TR ? 128 : 2), db + k * (TR ? 2 : 128), k != 0 || !first);
  wg_commit();
}
template <int TR> __device__ __forceinline__ void proj_loop(float* acc, uint32_t sb, uint32_t bars, uint32_t offA, uint32_t offB,
                                                            int wg, uint32_t sWKV, const CUtensorMap* mW, int col, bool w0, const CUtensorMap* mX, int xrow) {
  int s = 0, ph = 0;
#pragma unroll 1
  for (int kb = 0; kb < 8; kb++) {
    if (kb == TR)
  {
    float kv[4];
    mbar_wait(BAR_XA(wg), 0);
    const uint64_t da0 = make_desc(xa_addr(sb, 2 * wg), 16, 1024, 1);
    const uint64_t da1 = make_desc(wg == 3 ? XA7_TMP : xa_addr(sb, 2 * wg + 1), 16, 1024, 1);
    const uint64_t db = make_desc(sWKV + wg * 2048, 128, 128, 0);
    wg_fence();
#pragma unroll
    for (int k = 0; k < 8; k++) wg_ss8<0, 1>(kv, (k < 4 ? da0 : da1) + (k & 3) * 2, db + k * 16, k != 0);
    wg_commit();
    wg_wait<0>();
    fence_regs<4>(kv);
    named_bar(wg + 1, 128);
    sts4(sWKV + threadIdx.x * 16, __float_as_uint(kv[0]), __float_as_uint(kv[1]), __float_as_uint(kv[2]), __float_as_uint(kv[3]));
    __syncwarp();
    if ((threadIdx.x & 31) == 0) mbar_arrive(BAR_GO);
  }
    mbar_wait(BAR_FW(s, wg), ph);
    if (TR == 0) mbar_wait(BAR_XA(kb >> 1), 0); else mbar_wait(BAR_FULL(s), ph);
    proj_kb<TR>(acc, TR ? STAGE(s) + offA : xa_addr(sb, kb), STAGE(s) + offB, kb == 0);
    wg_wait<0>();
    if (w0 && elect_one()) {
      if (kb < 5) {
        mbar_expect_tx(BAR_FW(s, wg), TR ? 8192 : (kb == 4 ? 24576 : 16384));
        tma2d(STAGE(s) + (TR ? offA : 0), mW, col, (kb + 3) * 64, BAR_FW(s, wg));
        if (TR == 0) {
          tma2d(STAGE(s) + 8192, mW, col + 64, (kb + 3) * 64, BAR_FW(s, wg));
          if (kb == 4) tma2d(STAGE(s) + 16384, mX, 448, xrow, BAR_FW(s, wg));
        }
      }
      if (TR ? kb < 7 : (kb == 5 || kb == 6)) mbar_arrive(TR ? BAR_EMPTY(s) : BAR_E0(kb - 5));
      if (TR == 0 && kb == 4) mbar_arrive(BAR_VB(1));
    }
    __syncwarp();
    if (++s == 3) { s = 0; ph ^= 1; }
  }
  wg_wait<0>();
  fence_regs<64>(acc);
}

__device__ __forceinline__ uint32_t tail_slots(int isB, int n) {
  if (n < 4) return n < 2 ? (n == 0 ? 0x0D0C0B0Au : 0x04000F0Eu) : (n == 2 ? 0x18141008u : 0x15110501u);
  if (isB) return n < 6 ? (n == 4 ? 0x19120602u : 0x0D0C0B0Au) : (n == 6 ? 0x04000F0Eu : 0x13070316u);
  return n < 6 ? (n == 4 ? 0x1902031Au : 0x12061307u) : (n == 6 ? 0x16091B17u : 0x0D0C0B0Au);
}

__device__ __forceinline__ void take_role(uint32_t sM, int wg) {
  uint32_t r;
  asm volatile("atom.shared.add.u32 %0, [%1], 1;" : "=r"(r) : "r"(sM + 20) : "memory");
  sts1(sM + 32 + wg * 4, r);
}

__global__ void __launch_bounds__(640, 1)
k1_main(const __grid_constant__ CUtensorMap mXA64, const __grid_constant__ CUtensorMap mXB,
        const __grid_constant__ CUtensorMap mWq, const __grid_constant__ CUtensorMap mWqkv,
        const __grid_constant__ CUtensorMap mQst, const __grid_constant__ CUtensorMap mOst,
        const __grid_constant__ CUtensorMap mO, const __grid_constant__ CUtensorMap mWoA,
        const __grid_constant__ CUtensorMap mWoB,
        const __grid_constant__ CUtensorMap mO16, const __grid_constant__ CUtensorMap mKV, const Params prm) {
  if (threadIdx.x >= 608 && threadIdx.x < 612) {
    const CUtensorMap* pm = &mXA64 + (threadIdx.x - 608);
    asm volatile("prefetch.tensormap [%0];" :: "l"(pm) : "memory");
  }
  extern __shared__ __align__(1024) uint8_t smem_raw[];
  const uint32_t sb = smem_u32(smem_raw);
  if (sb & 1023u) __trap();
  const uint32_t bars = sb + OFF_MISC, sM = bars + 512, sT = bars + 640;
  const int tid = threadIdx.x, warp = __shfl_sync(~0u, tid >> 5, 0), wg = warp >> 2, w4 = warp & 3, lane = tid & 31;
  const bool helper = blockIdx.x >= 128;
  const int G = blockIdx.x >> 4, gi = GIMAP(blockIdx.x & 15);
  const int tbA = G * 4 + (gi >> 2), hg = gi & 3;
  const int ttB = (G >> 1) * 4 + (gi >> 2), hq = (G & 1) * 4 + (gi & 3);
  const int isB = tbA & 1, tok0 = (tbA >> 1) * 128;
  auto issue = [&](int kb, int part) {
    const uint32_t st = STAGE(kb);
    if (part & 1) {
      mbar_expect_tx(BAR_FW(kb, 0), 16384);
      tma2d(st, &mWq, hg * 128, kb * 64, BAR_FW(kb, 0));
      tma2d(st + 8192, &mWq, hg * 128 + 64, kb * 64, BAR_FW(kb, 0));
    }
    if (part & 2) {
      mbar_expect_tx(BAR_FULL(kb), 16384);
      tma2d(st + 49152, &mXB, kb * 64, ttB * 128, BAR_FULL(kb));
      mbar_expect_tx(BAR_FW(kb, 1), 8192);
      tma2d(st + 24576, &mWqkv, hq * 64, kb * 64, BAR_FW(kb, 1));
    }
    if (part & 4) {
      mbar_expect_tx(BAR_FW(kb, 2), 8192);
      tma2d(st + 32768, &mWqkv, 512 + hq * 64, kb * 64, BAR_FW(kb, 2));
      mbar_expect_tx(BAR_FW(kb, 3), 8192);
      tma2d(st + 40960, &mWqkv, 1024 + hq * 64, kb * 64, BAR_FW(kb, 3));
    }
  };
  const uint32_t sOne = sb + OFF_V + 65536, sWKV = WKV_TMP;
  if (warp >= 16) {
    if (warp == 17) {
      if (elect_one()) {
        mbar_init(BAR_BDONE, 12); mbar_init(BAR_Q, 6); mbar_init(BAR_GO, helper ? 1 : 16); mbar_init(BAR_Q2, 1);
        mbar_init(BAR_OD(0), 16); mbar_init(BAR_OD(1), 16); mbar_init(BAR_CL(0), 1); mbar_init(BAR_FULL(1), 1); mbar_init(BAR_FULL(2), 1);
        mbar_init(BAR_E0(0), 1); mbar_init(BAR_E0(1), 1);
#pragma unroll
        for (int i = 0; i < 4; i++) mbar_init(BAR_CL(i + 1), i == 0 ? 5 : 4);
#pragma unroll
        for (int i = 0; i < 3; i++) { mbar_init(BAR_EMPTY(i), 3); mbar_init(BAR_KV(i), 1); mbar_init(BAR_VB(i), i == 2 ? 4 : 1); }
        sts1(sM + 20, 0);
        asm volatile("fence.mbarrier_init.release.cluster;" ::: "memory");
      }
    } else if (warp == 18) {
      if (elect_one()) {
#pragma unroll
        for (int i = 0; i < 2; i++) mbar_init(BAR_TE(i), 2);
        mbar_init(BAR_RL, 1);
#pragma unroll
        for (int i = 4; i < 12; i++) mbar_init(BAR_FW(0, i), 1);
#pragma unroll
        for (int i = 0; i < 16; i++) mbar_init(BAR_TF(i), 1);
        asm volatile("fence.mbarrier_init.release.cluster;" ::: "memory");
      }
    } else if (warp == 16 && !helper && elect_one()) {
#pragma unroll
      for (int w = 0; w < 4; w++) { mbar_init(BAR_XA(w), 1); mbar_init(BAR_FW(0, w), 1); }
      mbar_init(BAR_FULL(0), 1);
      asm volatile("fence.mbarrier_init.release.cluster;" ::: "memory");
      issue(0, 6);
#pragma unroll
      for (int w = 0; w < 4; w++) {
        mbar_expect_tx(BAR_XA(w), 16384);
        tma2d(xa_addr(sb, 2 * w), &mXA64, w * 128, tbA * 64, BAR_XA(w));
        tma2d(w == 3 ? XA7_TMP : xa_addr(sb, 2 * w + 1), &mXA64, w * 128 + 64, tbA * 64, BAR_XA(w));
        if (w == 0) issue(0, 1);
      }
    }
  } else if (!helper) {
    const uint4 v = __ldg((const uint4*)(hg >= 2 ? prm.wv : prm.wk) + tid * 2 + (hg & 1));
    sts4(sWKV + tid * 16, v.x, v.y, v.z, v.w);
    fence_async();
  }
  __syncthreads();
  if (wg == 4) {
    if (w4 == 0 && !helper && elect_one()) { issue(1, 7); issue(2, 6); }
    asm volatile("setmaxnreg.dec.sync.aligned.u32 32;");
    const uint32_t ep = g_epoch[blockIdx.x] + 1;
    if (helper) {
      if (w4 == 0 && elect_one()) {
        flag_wait(FLAG_B(blockIdx.x - 128), ep * 32);
        fence_async_all();
        mbar_arrive(BAR_GO);
        g_epoch[blockIdx.x] = ep;
      }
      return;
    }
    if (w4 != 0) {
      mbar_wait(BAR_GO, 0);
#pragma unroll 1
      for (int qd = w4 & 3; qd >= 0; qd -= 3) {
        uint32_t a[4], b[4];
        float c[4];
        const uint32_t ad = sWKV + (qd * 32 + lane) * 16;
        lds4(ad, a);
        lds4(ad + 2048, b);
#pragma unroll
        for (int i = 0; i < 4; i++) c[i] = __uint_as_float(a[i]) + __uint_as_float(b[i]);
        lds4(ad + 4096, a);
        lds4(ad + 6144, b);
#pragma unroll
        for (int i = 0; i < 4; i++) c[i] += __uint_as_float(a[i]) + __uint_as_float(b[i]);
        sts1(sT + qd * 256 + lane * 4, pack_bf16(c[0], c[1]));
        sts1(sT + qd * 256 + 128 + lane * 4, pack_bf16(c[2], c[3]));
      }
      named_bar(9, 96);
      if (w4 == 3 && elect_one()) issue(2, 1);
    }
    auto write_ones = [&]() {
      mbar_wait_long(BAR_VB(1), 0);
      int c = ((w4 & 1) * 32 + lane);
#pragma unroll 4
      for (int key = c; key < S_TOK; key += 64) {
        sts4(sOne + key * 16, c < 24 ? 0x00003F80u : 0x00004E80u, 0u, 0u, 0u);
        c += 64; if (c >= STEPK) c -= STEPK;
      }
      fence_async();
      __syncwarp();
      if (lane == 0) mbar_arrive(BAR_Q);
    };
    if (w4 == 0) {
      int s = 0, ph = 0;
#pragma unroll 1
      for (int kb = 3; kb < 8; kb++) {
        mbar_wait(BAR_EMPTY(s), ph);
        if (elect_one()) {
          mbar_expect_tx(BAR_FULL(s), 16384);
          tma2d(STAGE(s) + 49152, &mXB, kb * 64, ttB * 128, BAR_FULL(s));
        }
        if (++s == 3) { s = 0; ph ^= 1; }
      }
      flag_wait(FLAG_KV, ep * 128);
      fence_async_all();
#pragma unroll 1
      for (int m = 0; m < 2; m++) {
        mbar_wait(m == 0 ? BAR_EMPTY(2) : BAR_EMPTY(0), 1 - m);
        mbar_wait(BAR_E0(m), 0);
        if (elect_one()) {
          const uint32_t fb = m == 0 ? BAR_KV(0) : BAR_VB(0);
          mbar_expect_tx(fb, 2 * 7 * STEPK * 16);
#pragma unroll
          for (int p = 0; p < 2; p++) bulk_g2s(sb + m * OFF_V + p * 32768, g_KV + (m * 2 + p) * S_TOK, 7 * STEPK * 16, fb);
        }
      }
      mbar_wait(BAR_Q, 0);
      if (elect_one()) {
#pragma unroll
        for (int c = 1; c < 3; c++) {
          const int k0 = c == 1 ? 7 * STEPK : 13 * STEPK, k1 = c == 1 ? 13 * STEPK : S_TOK;
          const uint32_t bytes = (k1 - k0) * 16;
          mbar_expect_tx(BAR_KV(c), 4 * bytes);
#pragma unroll
          for (int p = 0; p < 4; p++)
            bulk_g2s(sb + (p >> 1) * OFF_V + (p & 1) * 32768 + k0 * 16, g_KV + p * S_TOK + k0, bytes, BAR_KV(c));
        }
      }
      mbar_wait_long(BAR_CL(1), 0);
      flag_wait(isB ? FLAG_LM((lane & 7) * 2 + (tbA >> 4)) : FLAG_OA(tbA * 4 + (lane & 7), 0), ep);
      __syncwarp();
      fence_async_all();
      const CUtensorMap* mW = isB ? &mWoB : &mWoA;
#pragma unroll 1
      for (int it = 0; it < 8; it++) {
        const int n = (!isB && it >= 6) ? 13 - it : it;
        uint32_t wb = BAR_CL(n < 3 ? 0 : (n == 3 ? 2 : 3));
        if (isB) { if (n >= 5) wb = n == 7 ? BAR_CL(4) : BAR_TE(n - 5); }
        else if (n >= 6) wb = n == 6 ? BAR_CL(4) : BAR_TE(0);
        if (it < 6) mbar_wait_long(wb, 0); else mbar_wait(wb, 0);
        const uint32_t sl = tail_slots(isB, n), fb = BAR_TF(n);
        const bool withX = isB || n < 4;
        const int k0 = isB ? n * 64 : (n < 4 ? n * 128 : ((hg + n) & 3) * 128 + 64);
        if (elect_one()) {
          mbar_expect_tx(fb, withX ? 32768 : 16384);
          if (withX) {
            tma2d(sb + (sl & 255) * 8192, &mO, k0, isB * S_TOK + tok0, fb);
            tma2d(sb + ((sl >> 8) & 255) * 8192, &mO, k0, isB * S_TOK + tok0 + 64, fb);
          }
          tma2d(sb + ((sl >> 16) & 255) * 8192, mW, hg * 128, k0, fb);
          tma2d(sb + (sl >> 24) * 8192, mW, hg * 128 + 64, k0, fb);
        }
      }
      if (lane == 0) g_epoch[blockIdx.x] = ep;
    } else if (w4 == 3) {
      write_ones();
      flag_wait(FLAG_KV2, ep * 128);
      const uint4 a = *(const uint4*)(g_stats + lane * 4);
      const float kmax2 = __uint_as_float(__reduce_max_sync(~0u, a.x)) + __uint_as_float(__reduce_max_sync(~0u, a.y));
      const float vmax = __uint_as_float(__reduce_max_sync(~0u, max(a.z, a.w)));
      const float lv = vmax > 0.f ? __log2f(vmax) : 0.f;
      const float lim = fminf(90.f, fminf(91.f + lv, 95.f - lv));
      float thr = -1.f;
      if (vmax < 1e27f && kmax2 <= 65536.f && lim > 2.f) thr = fminf(60000.f, (lim * lim - 1.f) / (kmax2 * 1.02f + 1e-30f));
      mbar_wait_long(BAR_VB(2), 0);
      uint32_t nmax = 0;
#pragma unroll 2
      for (int i = 0; i < 16; i++) {
        uint32_t x[4], y[4];
        const uint32_t ad = sb + OFF_F + i * 1024 + (lane >> 3) * 256 + (lane & 7) * 16;
        lds4(ad, x); lds4(ad + 128, y);
        uint32_t n = hfma2(x[0], x[0], hfma2(x[1], x[1], hfma2(x[2], x[2], hfma2(x[3], x[3], 0u))));
        n = hfma2(y[0], y[0], hfma2(y[1], y[1], hfma2(y[2], y[2], hfma2(y[3], y[3], n))));
        n = hadd2(n, n >> 16);
        nmax = max(nmax, n & 0x7FFFu);
      }
      nmax = __reduce_max_sync(~0u, nmax);
      const bool ok = __half2float(__ushort_as_half((unsigned short)nmax)) <= thr;
      if (lane == 0) { sts1(sM + 16, ok ? 1u : 0u); mbar_arrive(BAR_Q2); }
    } else {
      const int tok = (w4 - 1) * 32 + lane;
      int step, col;
      if ((tbA & 3) == 0) {
        const int b8 = tbA >> 2;
        if (tok < 22) { step = tok; col = 24 + b8; }
        else { const int c = tok >= 43; step = tok - 22 - 21 * c; col = 32 + b8 * 2 + c; }
      } else {
        const int b24 = (tbA >> 2) * 3 + (tbA & 3) - 1;
        if (tok < 42) { const int c = tok >= 21; step = tok - 21 * c; col = 48 + b24 * 2 + c; }
        else { step = tok - 42; col = b24; }
      }
      const int kap = step * STEPK + col;
      const bool chained = col >= 24;
      uint32_t v[4], o[4];
      lds4(sT + tok * 16, v);
      float st = 0.f;
      if (hg < 2) {
        o[0] = o[1] = o[2] = o[3] = 0;
        if (chained && step > 0) lds4(sT + tok * 16 - 16, o);
        const float sc = chained ? 2.f : 1.f;
#pragma unroll
        for (int u = 0; u < 4; u++) {
          const float x = bf_lo(v[u]), y = bf_hi(v[u]);
          st += x * x + y * y;
          o[u] = pack_f16((x - bf_lo(o[u])) * sc, (y - bf_hi(o[u])) * sc);
        }
      } else {
        const float sc = chained ? VSHIFT : 1.f;
#pragma unroll
        for (int u = 0; u < 4; u++) { float x = bf_lo(v[u]), y = bf_hi(v[u]); st += fabsf(x) + fabsf(y); o[u] = pack_bf16(x * sc, y * sc); }
      }
      {
        const bool tl = (tbA & 3) == 0;
        const int run = tl ? (tok < 22 ? 0 : (tok < 43 ? 1 : 2)) : (tok < 21 ? 0 : (tok < 42 ? 1 : 2));
        const int h2 = (tl ? run == 0 : run == 2) ? 11 : 10;
        const uint32_t img = sT + run * 512;
        named_bar(10, 64);
        if (step < 11) sts4(img + step * 16, o[0], o[1], o[2], o[3]);
        if (step >= h2) sts4(img + 256 + (step - h2) * 16, o[0], o[1], o[2], o[3]);
        if (step == 0) sts1(sM + 48 + run * 4, col * 8 + (h2 << 16));
        fence_async();
        named_bar(10, 64);
        if (w4 == 1 && elect_one()) {
#pragma unroll
          for (int r = 0; r < 3; r++) {
            const uint32_t cw = lds1(sM + 48 + r * 4);
            tma3d_store(&mKV, sT + r * 512, cw & 0xFFFF, 0, hg);
            tma3d_store(&mKV, sT + r * 512 + 256, cw & 0xFFFF, cw >> 16, hg);
          }
          bulk_commit();
          bulk_wait_all();
          PUBLISH(FLAG_KV);
        }
        __syncwarp();
      }
      g_KV[(4 + hg) * S_TOK + kap] = make_uint4(v[0], v[1], v[2], v[3]);
      const uint32_t um = __reduce_max_sync(~0u, __float_as_uint(st) & 0x7FFFFFFFu);
      if (w4 == 2) {
        if (lane == 0) sts1(sM + 24, um);
        named_arrive(11, 64);
        write_ones();
        if (!isB) {
          mbar_wait_long(BAR_CL(3), 0);
          mbar_wait_long(BAR_RL, 0);
          uint32_t pend = 0xFE;
          const int li = lane & 7;
          const uint32_t* fl = FLAG_OA((tbA + (li & 1)) * 4 + ((hg + (li >> 1)) & 3), 1);
#pragma unroll 1
          for (int it = 0; pend; it++) {
            uint32_t fv;
            asm volatile("ld.acquire.gpu.global.u32 %0, [%1];" : "=r"(fv) : "l"(fl) : "memory");
            uint32_t go = __ballot_sync(~0u, (int32_t)(fv - ep) >= 0 && mbar_test(li >= 6 ? BAR_TE(0) : BAR_CL(4), 0)) & pend;
            pend &= ~go;
            if (go) fence_async_all();
#pragma unroll 1
            while (go) {
              const int b = __ffs(go) - 1;
              go &= go - 1;
              const uint32_t slot = (tail_slots(0, 4 + (b >> 1)) >> (8 * (b & 1))) & 255;
              if (elect_one()) {
                mbar_expect_tx(BAR_TF(8 + b), 8192);
                tma2d(sb + slot * 8192, &mO, ((hg + (b >> 1)) & 3) * 128 + 64, tok0 + (b & 1) * 64, BAR_TF(8 + b));
              }
            }
            if (it > 2000000) __trap();
          }
        }
      }
      else {
        named_bar(11, 64);
        if (elect_one()) {
          g_stats[tbA * 4 + hg] = max(um, lds1(sM + 24));
          flag_add(FLAG_KV2);
          mbar_wait_long(BAR_BDONE, 0);
          tma2d_store(&mQst, sb + OFF_F + 49152, hq * 64, S_TOK + ttB * 128);
          bulk_commit();
          bulk_wait_all();
          fence_async_all();
          flag_add(FLAG_B(hq >> 1));
          mbar_wait(BAR_Q, 0);
          mbar_arrive(BAR_CL(0));
#pragma unroll 1
          for (int p = 0; p < 2; p++) {
            mbar_wait_long(BAR_OD(p), 0);
            if (p == 0) {
#pragma unroll
              for (int w = 0; w < 4; w++) tma2d_store(&mO16, sb + OFF_F + w * 2048, hg * 128 + w * 16, tbA * 64);
            } else {
              tma2d_store(&mO, sb + 26 * 8192, hg * 128 + 64, tbA * 64);
            }
            bulk_commit();
            bulk_wait_all();
            if (p == 0) mbar_arrive(BAR_CL(1));
            PUBLISH(FLAG_OA(tbA * 4 + hg, p));
          }
        }
      }
    }
    return;
  }
  if (helper) { helper_cta(blockIdx.x - 128, sb, bars, wg, w4, &mQst, &mOst); return; }

  {
    float acc[64];
    if (wg == 0) proj_loop<0>(acc, sb, bars, 16384, 0, wg, sWKV, &mWq, hg * 128, w4 == 0, &mXA64, tbA * 64);
    else proj_loop<1>(acc, sb, bars, 16384 + wg * 8192, 49152, wg, sWKV, &mWqkv, (wg - 1) * 512 + hq * 64, w4 == 0, &mXA64, 0);
    const uint32_t sF = sb + OFF_F;
    const uint32_t qa = sF + w4 * 512 + ((lane >> 3) & 1) * 256 + (lane >> 4) * 128 + (lane & 7) * 16;
    if (wg == 0) {
#pragma unroll
      for (int hd = 0; hd < 4; hd++)
        stsm4(qa + hd * 2048, pack_f16(acc[8 * hd] * QSCALE, acc[8 * hd + 1] * QSCALE), pack_f16(acc[8 * hd + 2] * QSCALE, acc[8 * hd + 3] * QSCALE),
              pack_f16(acc[8 * hd + 4] * QSCALE, acc[8 * hd + 5] * QSCALE), pack_f16(acc[8 * hd + 6] * QSCALE, acc[8 * hd + 7] * QSCALE));
      fence_async();
      __syncwarp();
      if (lane == 0) mbar_arrive(BAR_Q);
    } else {
      if (wg != 1) {
        named_arrive(8, 384);
        const uint32_t ex = sF + 16384 + wg * 8192 + (tid & 127) * 16;
#pragma unroll
        for (int j = 0; j < 4; j++) {
          const float* a = acc + 8 * j;
          const float* b = acc + 32 + 8 * j;
          if (wg == 2) sts4(ex + j * 2048, pack_bf16(b[0], b[1]), pack_bf16(b[2], b[3]), pack_bf16(b[4], b[5]), pack_bf16(b[6], b[7]));
          else sts4(ex + j * 2048, pack_bf16(a[0], a[1]), pack_bf16(a[2], a[3]), pack_bf16(a[4], a[5]), pack_bf16(a[6], a[7]));
        }
        named_arrive(wg == 2 ? 6 : 7, 256);
      }
    }
    asm volatile("setmaxnreg.inc.sync.aligned.u32 112;");
    fence_regs<64>(acc);
    if (wg == 0) {
#pragma unroll
      for (int hd = 4; hd < 8; hd++)
        stsm4(qa + hd * 2048, pack_f16(acc[8 * hd] * QSCALE, acc[8 * hd + 1] * QSCALE), pack_f16(acc[8 * hd + 2] * QSCALE, acc[8 * hd + 3] * QSCALE),
              pack_f16(acc[8 * hd + 4] * QSCALE, acc[8 * hd + 5] * QSCALE), pack_f16(acc[8 * hd + 6] * QSCALE, acc[8 * hd + 7] * QSCALE));
      fence_async();
      __syncwarp();
      if (lane == 0) mbar_arrive(BAR_VB(2));
    } else {
      if (wg == 1) {
        uint32_t p[32];
#pragma unroll
        for (int i = 0; i < 32; i++) p[i] = phi2(acc[2 * i], acc[2 * i + 1]);
        named_bar(8, 384);
        const int m = lane >> 3, r = lane & 7;
#pragma unroll
        for (int j = 0; j < 16; j += 2) {
          const int tok = (j + (m >> 1)) * 8 + r;
          const int chunk = w4 * 2 + (m & 1);
          stsm4t(sF + 49152 + tok * 128 + ((chunk ^ r) << 4), p[2 * j], p[2 * j + 1], p[2 * j + 2], p[2 * j + 3]);
        }
        fence_async();
      } else {
        uint32_t p[16], a[16];
        const uint32_t ex = sF + 16384 + (5 - wg) * 8192 + (tid & 127) * 16;
        if (wg == 2) {
#pragma unroll
          for (int i = 0; i < 16; i++) p[i] = phi2(acc[2 * i], acc[2 * i + 1]);
          named_bar(7, 256);
#pragma unroll
          for (int j = 0; j < 4; j++) lds4(ex + j * 2048, a + 4 * j);
        } else {
#pragma unroll
          for (int i = 0; i < 16; i++) a[i] = pack_bf16(acc[32 + 2 * i], acc[33 + 2 * i]);
          named_bar(6, 256);
#pragma unroll
          for (int j = 0; j < 4; j++) lds4(ex + j * 2048, p + 4 * j);
#pragma unroll
          for (int i = 0; i < 16; i++) p[i] = phi2(bf_lo(p[i]), bf_hi(p[i]));
        }
        float kv0[4] = {0, 0, 0, 0}, kv1[4] = {0, 0, 0, 0}, z0[4] = {0, 0, 0, 0}, z1[4] = {0, 0, 0, 0};
        const uint32_t one = 0x3F803F80u;
#pragma unroll
        for (int j = 0; j < 4; j++) {
          mma_bf16(kv0, a[4 * j], a[4 * j + 1], a[4 * j + 2], a[4 * j + 3], p[4 * j], p[4 * j + 2]);
          mma_bf16(kv1, a[4 * j], a[4 * j + 1], a[4 * j + 2], a[4 * j + 3], p[4 * j + 1], p[4 * j + 3]);
          mma_bf16(z0, one, one, one, one, p[4 * j], p[4 * j + 2]);
          mma_bf16(z1, one, one, one, one, p[4 * j + 1], p[4 * j + 3]);
        }
        float4* dst = g_kvp + (((ttB * 2 + wg - 2) * 32 + hq * 4 + w4) * 3) * 32 + lane;
        dst[0] = make_float4(kv0[0], kv0[1], kv1[0], kv1[1]);
        dst[32] = make_float4(kv0[2], kv0[3], kv1[2], kv1[3]);
        dst[64] = make_float4(z0[0], z0[1], z1[0], z1[1]);
      }
      __syncwarp();
      if (lane == 0) mbar_arrive(BAR_BDONE);
    }
  }

  bool safe = true;
  {
    const uint32_t c63 = 0x1F801F80u + (threadIdx.x >> 20);
    const uint32_t m1 = (gridDim.x >> 20) - 1u;
    const uint64_t dK0 = make_desc(sb + OFF_K, 32768, 128, 0);
    const uint64_t dV0 = make_desc(sb + OFF_V, 128, 32768, 0);
    constexpr uint32_t dKV = ((2048u - 8u)  __H0__ ) + STEPK - (OFF_V - OFF_K) / 16;
    float Sm[12], Sp[36], O[12];
    uint32_t P[24];
    uint64_t dQ = make_desc(sb + OFF_F + wg * 2048, 128, 256, 0);
#pragma unroll
    for (int i = 0; i < 36; i++) Sp[i] = SMAGIC;
#pragma unroll
    for (int i = 0; i < 12; i++) Sm[i] = 0.f;
    fence_regs<12>(Sm); fence_regs<36>(Sp);
    mbar_wait(BAR_Q, 0);
    mbar_wait(BAR_KV(0), 0);
    wg_fence();
    wg_qs72<1>(Sp, dQ, dK0 + 24);
    wg_qs24<0>(Sm, dQ, dK0);
    wg_commit();
    wg_wait<0>();
    fence_regs<12>(Sm); fence_regs<36>(Sp);
#pragma unroll 1
    for (int pass = 0; pass < 2; pass++) {
#pragma unroll
      for (int i = 0; i < 12; i++) O[i] = 0.f;
      fence_regs<12>(O);
      uint32_t vlo = (uint32_t)dV0;
#pragma unroll 1
      for (int seg = 0; seg < 4; seg++) {
        if (pass == 0) {
          if (seg < 3) mbar_wait(seg == 0 ? BAR_VB(0) : BAR_KV(seg), 0);
        } else if (seg >= 1) {
          if ((tid & 127) == 0) {
            mbar_arrive(BAR_CL(seg));
            if (seg == 3) take_role(sM, wg);
          }
          __syncwarp();
        }
        const uint32_t vend = vlo + (seg == 3 ? 3 : 6) * STEPK;
#pragma unroll 1
        for (; vlo != vend; vlo += 3 * STEPK) {
          uint64_t dK, dV;
          asm("mov.b64 %0, {%1, %2};" : "=l"(dK) : "r"(vlo + dKV), "r"(8u));
          asm("mov.b64 %0, {%1, %2};" : "=l"(dV) : "r"(vlo), "r"(2048u));
#pragma unroll
          for (int u = 0; u < 3; u++) {
          { uint32_t w[18], y[18], z[18]; float e[12];
            X_MU(0) X_PR(0) X_LO(0) X_IM(0) X_MU(1) X_FM(0) X_PR(1) X_LO(1) X_IM(1) X_MU(2) X_FM(1) X_PR(2)
            X_LO(2) X_MU(3) X_IM(2) X_FM(2) X_PR(3) X_LO(3) X_PK(0) X_MU(4) X_IM(3) X_FM(3) X_PR(4) X_LO(4)
            X_MU(5) X_IM(4) X_FM(4) X_PR(5) X_PK(1) X_MU(6) X_LO(5) X_IM(5) X_FM(5) X_PR(6) X_MU(7) X_LO(6)
            X_IM(6) X_FM(6) X_MU(8) X_PR(7) X_PK(2) X_LO(7) X_IM(7) X_FM(7) X_MU(9) X_PR(8) X_LO(8) X_IM(8)
            X_FM(8) X_PK(3) X_MU(10) X_PR(9) X_LO(9) X_IM(9) X_MU(11) X_FM(9) X_PR(10) X_LO(10) X_IM(10) X_PK(4)
            X_FM(10) X_PR(11) X_LO(11) X_IM(11) X_FM(11) X_PR(12) X_LO(12) X_PK(5) X_IM(12) X_FM(12) X_PR(13) X_LO(13)
            X_IM(13) X_FM(13) X_PR(14) X_LO(14) X_IM(14) X_FM(14) X_PR(15) X_LO(15) X_IM(15) X_FM(15) X_PR(16) X_LO(16)
            X_IM(16) X_FM(16) X_PR(17) X_LO(17) X_IM(17) X_FM(17) }
          fence_regs<24>(P);
          wg_fence();
          wg_pv24<1>(O, &P[20], dV + u * STEPK + 80);
          wg_pv24<1>(O, &P[16], dV + u * STEPK + 64);
          wg_pv24<1>(O, &P[12], dV + u * STEPK + 48);
          wg_pv24<1>(O, &P[8], dV + u * STEPK + 32);
          wg_pv24<1>(O, &P[4], dV + u * STEPK + 16);
          wg_pv24<1>(O, &P[0], dV + u * STEPK + 0);
          wg_qs72<1>(Sp, dQ, dK + u * STEPK + 24);
          wg_qs24<0>(Sm, dQ, dK + u * STEPK);
          wg_commit();
          wg_wait<0>();
          fence_regs<12>(Sm); fence_regs<36>(Sp); fence_regs<12>(O); fence_regs<24>(P);
          }
        }
      }
#pragma unroll
      for (int i = 0; i < 6; i++) P[i] = pack_bf16(ex2f(Sm[2 * i]), ex2f(Sm[2 * i + 1]));
      P[6] = exp2_pair_fix(Sp[0], Sp[1], c63, m1);
      P[7] = exp2_pair_fix(Sp[2], Sp[3], c63, m1);
      fence_regs<8>(P);
      const uint32_t sO = pass == 0 ? sb + OFF_F + wg * 2048 + w4 * 512 + (lane & 15) * 32 + (lane >> 4) * 16
                                    : sb + 26 * 8192 + (w4 * 16 + (lane & 15)) * 128 + (((wg * 2 + (lane >> 4)) ^ (lane & 7)) << 4);
      dQ += 512;
      wg_fence();
      wg_pv24<1>(O, &P[0], dV0 + 21 * STEPK);
      wg_pv24<1>(O, &P[4], dV0 + 21 * STEPK + 16);
      wg_commit();
#pragma unroll
      for (int i = 0; i < 36; i++) Sp[i] = SMAGIC;
      fence_regs<36>(Sp);
      mbar_wait(pass == 0 ? BAR_Q2 : BAR_CL(3), 0);
      wg_fence();
      wg_qs72<1>(Sp, dQ, dK0 + 24);
      wg_qs24<0>(Sm, dQ, dK0);
      wg_commit();
      wg_wait<1>();
      fence_regs<12>(O);
      const float l0 = __shfl_sync(~0u, O[8], lane & ~3), l1 = __shfl_sync(~0u, O[10], lane & ~3);
      const float i0 = rcpf(l0), i1 = rcpf(l1);
      stsm4(sO,
            pack_bf16(O[0] * i0, O[1] * i0), pack_bf16(O[2] * i1, O[3] * i1),
            pack_bf16(O[4] * i0, O[5] * i0), pack_bf16(O[6] * i1, O[7] * i1));
      fence_async();
      {
        safe = __all_sync(~0u, lds1(sM + 16) != 0);
      }
      if (safe && lane == 0) mbar_arrive(BAR_OD(pass));
      wg_wait<0>();
      fence_regs<12>(Sm); fence_regs<36>(Sp);
      if (!safe) break;
    }
  }
  if (!safe) {
    if ((tid & 127) == 0) { mbar_arrive(BAR_CL(1)); mbar_arrive(BAR_CL(2)); mbar_arrive(BAR_CL(3)); take_role(sM, wg); }
#pragma unroll 1
    for (int pass = 0; pass < 2; pass++) {
      const int t = tid & 127;
      mbar_wait(BAR_CL(3), 0);
      attn_slow(prm.xa + (size_t)tbA * 64 * D_MOD, prm.wq + (hg * 8 + pass * 4 + wg) * 16,
                pass == 0 ? sb + OFF_F + wg * 2048 + t * 16
                          : sb + 26 * 8192 + (t >> 1) * 128 + (((wg * 2 + (t & 1)) ^ ((t >> 1) & 7)) << 4));
      __syncwarp();
      if (lane == 0) mbar_arrive(BAR_OD(pass));
    }
  }

  {
    named_bar(wg + 1, 128);
    if ((tid & 127) == 0) mbar_arrive(BAR_CL(4));
    const int role = __shfl_sync(~0u, lds1(sM + 32 + wg * 4), 0);
    const int m = lane >> 3, r = lane & 7;
    const uint32_t stoff = (w4 * 16 + (m & 1) * 8 + r) * 128;
    if (role < 2) {
      if (role == 0 && (tid & 127) == 0) mbar_arrive(BAR_RL);
      if (!isB || role == 1) mbar_wait(BAR_CL(4), 0);
      float acc[64];
#pragma unroll 1
      for (int n = 0; n < 8; n++) {
        const uint32_t sl = tail_slots(isB, n);
        const uint32_t w0 = (sl >> 16) & 255, w1 = sl >> 24;
        const uint64_t da = make_desc(sb + ((sl >> (8 * role)) & 255) * 8192, 16, 1024, 1);
        const uint64_t db = make_desc(sb + w0 * 8192, (w1 - w0) * 8192, 1024, 1);
        mbar_wait(BAR_TF(n), 0);
        if (!isB && n >= 4) mbar_wait(n == 4 && role == 0 ? BAR_OD(1) : BAR_TF(2 * n + role), 0);
        wg_fence();
#pragma unroll
        for (int k = 0; k < 4; k++) wg_ss128<0, 1>(acc, da + k * 2, db + k * 128, (n | k) != 0);
        wg_commit();
        wg_wait<1>();
        if ((n == 1 || n == 2) && (tid & 127) == 0) mbar_arrive(BAR_TE(n - 1));
        __syncwarp();
      }
      wg_wait<0>();
      fence_regs<64>(acc);
      const uint32_t x0 = sb + (role ? 16 : 8) * 8192, x1 = sb + (role ? 5 : 1) * 8192;
#pragma unroll
      for (int j = 0; j < 16; j += 2)
        stsm4((j < 8 ? x0 : x1) + stoff + ((((j & 7) + (m >> 1)) ^ r) << 4),
              pack_bf16(acc[4 * j], acc[4 * j + 1]), pack_bf16(acc[4 * j + 2], acc[4 * j + 3]),
              pack_bf16(acc[4 * j + 4], acc[4 * j + 5]), pack_bf16(acc[4 * j + 6], acc[4 * j + 7]));
      __syncwarp();
      uint4* dst = (uint4*)(prm.out + (size_t)(tok0 + role * 64 + w4 * 16 + (lane >> 4)) * 1024 + isB * 512 + hg * 128) + (lane & 15);
      const uint32_t src = ((lane & 8) ? x1 : x0) + (w4 * 16 + (lane >> 4)) * 128;
#pragma unroll
      for (int i = 0; i < 8; i++) {
        uint32_t v[4];
        lds4(src + i * 256 + (((lane & 7) ^ ((2 * i + (lane >> 4)) & 7)) << 4), v);
        dst[i * 256] = make_uint4(v[0], v[1], v[2], v[3]);
      }
    }
  }
}

__device__ __nv_bfloat16 g_T[S_TOK * 1536];
__device__ float g_Z[32 * 272];
__global__ void fb_gemm(const __nv_bfloat16* A, const __nv_bfloat16* B, __nv_bfloat16* C, int N, int ldc) {
  __shared__ float sa[16][17], sbm[16][17];
  const int tx = threadIdx.x & 15, ty = threadIdx.x >> 4, row = blockIdx.y * 16 + ty, col = blockIdx.x * 16 + tx;
  float acc = 0.f;
  for (int k0 = 0; k0 < D_MOD; k0 += 16) {
    sa[ty][tx] = __bfloat162float(A[(size_t)row * D_MOD + k0 + tx]);
    sbm[ty][tx] = __bfloat162float(B[(size_t)(k0 + ty) * N + col]);
    __syncthreads();
    for (int k = 0; k < 16; k++) acc = fmaf(sa[ty][k], sbm[k][tx], acc);
    __syncthreads();
  }
  C[(size_t)row * ldc + col] = __float2bfloat16_rn(acc);
}
__global__ void fb_attn() {
  const int r = blockIdx.x * blockDim.x + threadIdx.x;
  float q[16], o[16], m = -INFINITY, l = 0.f;
  for (int i = 0; i < 16; i++) { q[i] = __bfloat162float(g_Q[(size_t)r * 16 + i]); o[i] = 0.f; }
  for (int j = 0; j < S_TOK; j++) {
    float s = 0.f;
    for (int i = 0; i < 16; i++) s = fmaf(q[i], __bfloat162float(g_T[j * 32 + i]), s);
    s = rbf(s) * 0.25f;
    const float mn = fmaxf(m, s), c = __expf(m - mn), p = __expf(s - mn);
    l = l * c + p; m = mn;
    for (int i = 0; i < 16; i++) o[i] = fmaf(p, __bfloat162float(g_T[j * 32 + 16 + i]), o[i] * c);
  }
  for (int i = 0; i < 16; i++) g_O[(size_t)r * 16 + i] = __float2bfloat16_rn(o[i] / l);
}
__device__ __forceinline__ float fb_phi(__nv_bfloat16 x) { const float t = __bfloat162float(x); return bf_lo(phi2(t, t)); }
__global__ void fb_kv() {
  const int h = blockIdx.x, t = threadIdx.x, d = t < 256 ? t >> 4 : t - 256, e = t & 15;
  float acc = 0.f;
  for (int s = 0; s < S_TOK; s++)
    acc = fmaf(fb_phi(g_T[(size_t)s * 1536 + 512 + h * 16 + d]), t < 256 ? __bfloat162float(g_T[(size_t)s * 1536 + 1024 + h * 16 + e]) : 1.f, acc);
  g_Z[h * 272 + t] = rbf(acc);
}
__global__ void fb_lin() {
  const int idx = blockIdx.x * blockDim.x + threadIdx.x, s = idx >> 9, c = idx & 511, h = c >> 4, e = c & 15;
  float num = 0.f, den = 0.f;
  for (int d = 0; d < 16; d++) {
    const float p = fb_phi(g_T[(size_t)s * 1536 + h * 16 + d]);
    num = fmaf(p, g_Z[h * 272 + d * 16 + e], num); den = fmaf(p, g_Z[h * 272 + 256 + d], den);
  }
  g_O[(size_t)S_TOK * D_MOD + idx] = __float2bfloat16_rn(num / (den + 1e-6f));
}

typedef CUresult (*EncodeFn)(CUtensorMap*, CUtensorMapDataType, cuuint32_t, void*, const cuuint64_t*, const cuuint64_t*,
                             const cuuint32_t*, const cuuint32_t*, CUtensorMapInterleave, CUtensorMapSwizzle,
                             CUtensorMapL2promotion, CUtensorMapFloatOOBfill);

static void make_map(EncodeFn enc, CUtensorMap* m, const void* ptr, uint64_t cols, uint64_t rows, uint32_t bc, uint32_t br,
                     CUtensorMapSwizzle sw = CU_TENSOR_MAP_SWIZZLE_128B) {
  cuuint64_t dims[2] = {cols, rows};
  cuuint64_t strides[1] = {cols * 2};
  cuuint32_t box[2] = {bc, br};
  cuuint32_t es[2] = {1, 1};
  enc(m, CU_TENSOR_MAP_DATA_TYPE_BFLOAT16, 2, (void*)ptr, dims, strides, box, es, CU_TENSOR_MAP_INTERLEAVE_NONE,
      sw, CU_TENSOR_MAP_L2_PROMOTION_L2_256B, CU_TENSOR_MAP_FLOAT_OOB_FILL_NONE);
}

extern "C" void kernel_launch(void* const* d_in, const int* in_sizes, int n_in, void* d_out, int out_size) {
  (void)in_sizes; (void)n_in; (void)out_size;
  static EncodeFn enc = nullptr;
  static void* pQ = nullptr; static void* pO = nullptr; static void* pT = nullptr; static void* pK = nullptr;
  static bool fused = false;
  if (!enc) {
    void* fn = nullptr; cudaDriverEntryPointQueryResult qr;
    cudaGetDriverEntryPoint("cuTensorMapEncodeTiled", &fn, cudaEnableDefault, &qr);
    enc = (EncodeFn)fn;
    cudaGetSymbolAddress(&pQ, g_Q);
    cudaGetSymbolAddress(&pO, g_O);
    cudaGetSymbolAddress(&pT, g_T);
    cudaGetSymbolAddress(&pK, g_KV);
    cudaFuncSetAttribute(k1_main, cudaFuncAttributeMaxDynamicSharedMemorySize, SM_TOTAL);
    int dev = 0, sms = 0, occ = 0;
    cudaGetDevice(&dev);
    cudaDeviceGetAttribute(&sms, cudaDevAttrMultiProcessorCount, dev);
    cudaOccupancyMaxActiveBlocksPerMultiprocessor(&occ, k1_main, 640, SM_TOTAL);
    fused = sms * occ >= 132;
  }
  if (!fused) {
    typedef const __nv_bfloat16* CB; typedef __nv_bfloat16* MB;
    cudaStream_t st = cudaStreamPerThread;
    fb_gemm<<<dim3(32, 128), 256, 0, st>>>((CB)d_in[0], (CB)d_in[1], (MB)pQ, 512, 512);
    fb_gemm<<<dim3(1, 128), 256, 0, st>>>((CB)d_in[0], (CB)d_in[2], (MB)pT, 16, 32);
    fb_gemm<<<dim3(1, 128), 256, 0, st>>>((CB)d_in[0], (CB)d_in[3], (MB)pT + 16, 16, 32);
    fb_attn<<<512, 128, 0, st>>>();
    fb_gemm<<<dim3(96, 128), 256, 0, st>>>((CB)d_in[5], (CB)d_in[6], (MB)pT, 1536, 1536);
    fb_kv<<<32, 272, 0, st>>>();
    fb_lin<<<4096, 256, 0, st>>>();
    fb_gemm<<<dim3(32, 128), 256, 0, st>>>((CB)pO, (CB)d_in[4], (MB)d_out, 512, 1024);
    fb_gemm<<<dim3(32, 128), 256, 0, st>>>((CB)pO + S_TOK * D_MOD, (CB)d_in[7], (MB)d_out + 512, 512, 1024);
    return;
  }
  CUtensorMap mXA64, mXB, mWq, mWqkv, mQst, mO, mOst, mWoA, mWoB, mO16, mKV;
  make_map(enc, &mXA64, d_in[0], 512, 2048, 64, 64);
  make_map(enc, &mWq, d_in[1], 512, 512, 64, 64);
  make_map(enc, &mWoA, d_in[4], 512, 512, 64, 64);
  make_map(enc, &mXB, d_in[5], 512, 2048, 64, 128);
  make_map(enc, &mWqkv, d_in[6], 1536, 512, 64, 64);
  make_map(enc, &mWoB, d_in[7], 512, 512, 64, 64);
  make_map(enc, &mQst, pQ, 512, 4096, 64, 128);
  make_map(enc, &mO, pO, 512, 4096, 64, 64);
  make_map(enc, &mOst, pO, 512, 4096, 64, 128);
  make_map(enc, &mO16, pO, 512, 4096, 16, 64, CU_TENSOR_MAP_SWIZZLE_NONE);
  {
    cuuint64_t dims[3] = {768, 22, 4};
    cuuint64_t strides[2] = {1536, 32768};
    cuuint32_t box[3] = {8, 11, 1};
    cuuint32_t es[3] = {1, 1, 1};
    enc(&mKV, CU_TENSOR_MAP_DATA_TYPE_BFLOAT16, 3, pK, dims, strides, box, es, CU_TENSOR_MAP_INTERLEAVE_NONE,
        CU_TENSOR_MAP_SWIZZLE_NONE, CU_TENSOR_MAP_L2_PROMOTION_NONE, CU_TENSOR_MAP_FLOAT_OOB_FILL_NONE);
  }
  Params prm{(const __nv_bfloat16*)d_in[2], (const __nv_bfloat16*)d_in[3], (const __nv_bfloat16*)d_in[0], (const __nv_bfloat16*)d_in[1], (__nv_bfloat16*)d_out};
  k1_main<<<132, 640, SM_TOTAL, cudaStreamPerThread>>>(mXA64, mXB, mWq, mWqkv, mQst, mOst, mO, mWoA, mWoB, mO16, mKV, prm);
}
```

```cpp
#include <cuda_runtime.h>
#include <cuda_bf16.h>
#include <cuda_fp16.h>
#include <cuda.h>
#include <stdint.h>

#define S_TOK 2048
#define D_MOD 512

__device__ __align__(1024) __nv_bfloat16 g_Q[2 * S_TOK * D_MOD];
__device__ __align__(1024) __nv_bfloat16 g_O[2 * S_TOK * D_MOD];
__device__ __align__(1024) uint4 g_KV[8 * S_TOK];
__device__ __align__(16) uint32_t g_stats[128];
__device__ __align__(16) float4 g_kvp[16 * 32 * 3 * 32];

__device__ __forceinline__ uint32_t smem_u32(const void* p) { return (uint32_t)__cvta_generic_to_shared(p); }
__device__ __forceinline__ void mbar_init(uint32_t bar, int cnt) { asm volatile("mbarrier.init.shared::cta.b64 [%0], %1;" :: "r"(bar), "r"(cnt) : "memory"); }
__device__ __forceinline__ void mbar_expect_tx(uint32_t bar, uint32_t bytes) { asm volatile("mbarrier.arrive.expect_tx.shared::cta.b64 _, [%0], %1;" :: "r"(bar), "r"(bytes) : "memory"); }
__device__ __forceinline__ void mbar_wait(uint32_t bar, uint32_t parity) {
  asm volatile("{\n.reg .pred p;\n.reg .u32 c;\nmov.u32 c, 0;\n"
               "LW_%=:\n"
               "mbarrier.try_wait.parity.shared::cta.b64 p, [%0], %1;\n"
               "@p bra LD_%=;\n"
               "add.u32 c, c, 1;\n"
               "setp.lt.u32 p, c, 4000000;\n"
               "@p bra LW_%=;\n"
               "trap;\n"
               "LD_%=:\n}\n" :: "r"(bar), "r"(parity) : "memory");
}
__device__ __forceinline__ void tma2d(uint32_t dst, const CUtensorMap* m, int c0, int c1, uint32_t bar) {
  asm volatile("cp.async.bulk.tensor.2d.shared::cluster.global.mbarrier::complete_tx::bytes [%0], [%1, {%3, %4}], [%2];"
               :: "r"(dst), "l"(m), "r"(bar), "r"(c0), "r"(c1) : "memory");
}
__device__ __forceinline__ void tma2d_store(const CUtensorMap* m, uint32_t src, int c0, int c1) {
  asm volatile("cp.async.bulk.tensor.2d.global.shared::cta.bulk_group [%0, {%2, %3}], [%1];"
               :: "l"(m), "r"(src), "r"(c0), "r"(c1) : "memory");
}
__device__ __forceinline__ void tma3d_store(const CUtensorMap* m, uint32_t src, int c0, int c1, int c2) {
  asm volatile("cp.async.bulk.tensor.3d.global.shared::cta.bulk_group [%0, {%2, %3, %4}], [%1];"
               :: "l"(m), "r"(src), "r"(c0), "r"(c1), "r"(c2) : "memory");
}
__device__ __forceinline__ void bulk_g2s(uint32_t dst, const void* src, uint32_t bytes, uint32_t bar) {
  asm volatile("cp.async.bulk.shared::cluster.global.mbarrier::complete_tx::bytes [%0], [%1], %2, [%3];"
               :: "r"(dst), "l"(src), "r"(bytes), "r"(bar) : "memory");
}
__device__ __forceinline__ void bulk_commit() { asm volatile("cp.async.bulk.commit_group;" ::: "memory"); }
__device__ __forceinline__ void bulk_wait_all() { asm volatile("cp.async.bulk.wait_group 0;" ::: "memory"); }
__device__ __forceinline__ void fence_async() { asm volatile("fence.proxy.async.shared::cta;" ::: "memory"); }
__device__ __forceinline__ void named_bar(int id, int n) { asm volatile("bar.sync %0, %1;" :: "r"(id), "r"(n) : "memory"); }
__device__ __forceinline__ void wg_fence() { asm volatile("wgmma.fence.sync.aligned;" ::: "memory"); }
__device__ __forceinline__ void wg_commit() { asm volatile("wgmma.commit_group.sync.aligned;" ::: "memory"); }
template <int n> __device__ __forceinline__ void wg_wait() { asm volatile("wgmma.wait_group.sync.aligned %0;" :: "n"(n) : "memory"); }
template <int n> __device__ __forceinline__ void fence_regs(float* r) {
#pragma unroll
  for (int i = 0; i < n; i++) asm volatile("" : "+f"(r[i]) :: "memory");
}
template <int n> __device__ __forceinline__ void fence_regs(uint32_t* r) {
#pragma unroll
  for (int i = 0; i < n; i++) asm volatile("" : "+r"(r[i]) :: "memory");
}
__device__ __forceinline__ uint64_t make_desc(uint32_t addr, uint32_t lbo, uint32_t sbo, uint32_t swz) {
  return (uint64_t)((addr & 0x3FFFF) >> 4) | ((uint64_t)(lbo >> 4) << 16) | ((uint64_t)(sbo >> 4) << 32) | ((uint64_t)swz << 62);
}
__device__ __forceinline__ float ex2f(float x) { float y; asm("ex2.approx.ftz.f32 %0, %1;" : "=f"(y) : "f"(x)); return y; }
__device__ __forceinline__ uint32_t pack_bf16(float lo, float hi) { uint32_t r; asm("cvt.rn.bf16x2.f32 %0, %1, %2;" : "=r"(r) : "f"(hi), "f"(lo)); return r; }
__device__ __forceinline__ uint32_t pack_f16(float lo, float hi) { uint32_t r; asm("cvt.rn.f16x2.f32 %0, %1, %2;" : "=r"(r) : "f"(hi), "f"(lo)); return r; }
__device__ __forceinline__ float bf_lo(uint32_t v) { return __uint_as_float(v << 16); }
__device__ __forceinline__ float bf_hi(uint32_t v) { return __uint_as_float(v & 0xFFFF0000u); }
__device__ __forceinline__ float rbf(float x) { return __bfloat162float(__float2bfloat16_rn(x)); }
__device__ __forceinline__ void stsm4(uint32_t a, uint32_t r0, uint32_t r1, uint32_t r2, uint32_t r3) {
  asm volatile("stmatrix.sync.aligned.m8n8.x4.shared.b16 [%0], {%1,%2,%3,%4};" :: "r"(a), "r"(r0), "r"(r1), "r"(r2), "r"(r3) : "memory");
}
__device__ __forceinline__ void stsm4t(uint32_t a, uint32_t r0, uint32_t r1, uint32_t r2, uint32_t r3) {
  asm volatile("stmatrix.sync.aligned.m8n8.x4.trans.shared.b16 [%0], {%1,%2,%3,%4};" :: "r"(a), "r"(r0), "r"(r1), "r"(r2), "r"(r3) : "memory");
}
__device__ __forceinline__ void mma_bf16(float* d, uint32_t a0, uint32_t a1, uint32_t a2, uint32_t a3, uint32_t b0, uint32_t b1) {
  asm volatile("mma.sync.aligned.m16n8k16.row.col.f32.bf16.bf16.f32 {%0,%1,%2,%3}, {%4,%5,%6,%7}, {%8,%9}, {%0,%1,%2,%3};"
               : "+f"(d[0]), "+f"(d[1]), "+f"(d[2]), "+f"(d[3]) : "r"(a0), "r"(a1), "r"(a2), "r"(a3), "r"(b0), "r"(b1));
}
template<int SD> __device__ __forceinline__ void wg_qs24(float* d, uint64_t da, uint64_t db) {
  asm volatile("wgmma.mma_async.sync.aligned.m64n24k16.f32.f16.f16 {%0,%1,%2,%3,%4,%5,%6,%7,%8,%9,%10,%11}, %12, %13, %14, 1, 1, 0, 0;"
   : "+f"(d[0]),"+f"(d[1]),"+f"(d[2]),"+f"(d[3]),"+f"(d[4]),"+f"(d[5]),"+f"(d[6]),"+f"(d[7]),"+f"(d[8]),"+f"(d[9]),"+f"(d[10]),"+f"(d[11])
   : "l"(da),"l"(db),"n"(SD));
}
template<int SD> __device__ __forceinline__ void wg_qs72(float* d, uint64_t da, uint64_t db) {
  asm volatile("wgmma.mma_async.sync.aligned.m64n72k16.f32.f16.f16 {%0,%1,%2,%3,%4,%5,%6,%7,%8,%9,%10,%11,%12,%13,%14,%15,%16,%17,%18,%19,%20,%21,%22,%23,%24,%25,%26,%27,%28,%29,%30,%31,%32,%33,%34,%35}, %36, %37, %38, 1, 1, 0, 0;"
   : "+f"(d[0]),"+f"(d[1]),"+f"(d[2]),"+f"(d[3]),"+f"(d[4]),"+f"(d[5]),"+f"(d[6]),"+f"(d[7]),"+f"(d[8]),"+f"(d[9]),"+f"(d[10]),"+f"(d[11]),"+f"(d[12]),"+f"(d[13]),"+f"(d[14]),"+f"(d[15]),"+f"(d[16]),"+f"(d[17]),"+f"(d[18]),"+f"(d[19]),"+f"(d[20]),"+f"(d[21]),"+f"(d[22]),"+f"(d[23]),"+f"(d[24]),"+f"(d[25]),"+f"(d[26]),"+f"(d[27]),"+f"(d[28]),"+f"(d[29]),"+f"(d[30]),"+f"(d[31]),"+f"(d[32]),"+f"(d[33]),"+f"(d[34]),"+f"(d[35])
   : "l"(da),"l"(db),"n"(SD));
}
template<int SD> __device__ __forceinline__ void wg_pv24(float* d, const uint32_t* a, uint64_t desc) {
  asm volatile("wgmma.mma_async.sync.aligned.m64n24k16.f32.bf16.bf16 {%0,%1,%2,%3,%4,%5,%6,%7,%8,%9,%10,%11}, {%12,%13,%14,%15}, %16, %17, 1, 1, 1;"
   : "+f"(d[0]),"+f"(d[1]),"+f"(d[2]),"+f"(d[3]),"+f"(d[4]),"+f"(d[5]),"+f"(d[6]),"+f"(d[7]),"+f"(d[8]),"+f"(d[9]),"+f"(d[10]),"+f"(d[11])
   : "r"(a[0]),"r"(a[1]),"r"(a[2]),"r"(a[3]),"l"(desc),"n"(SD));
}
template<int TA, int TB> __device__ __forceinline__ void wg_ss128(float* d, uint64_t da, uint64_t db, int sd) {
  asm volatile("{\n.reg .pred p;\nsetp.ne.b32 p, %66, 0;\n"
   "wgmma.mma_async.sync.aligned.m64n128k16.f32.bf16.bf16 {%0,%1,%2,%3,%4,%5,%6,%7,%8,%9,%10,%11,%12,%13,%14,%15,%16,%17,%18,%19,%20,%21,%22,%23,%24,%25,%26,%27,%28,%29,%30,%31,%32,%33,%34,%35,%36,%37,%38,%39,%40,%41,%42,%43,%44,%45,%46,%47,%48,%49,%50,%51,%52,%53,%54,%55,%56,%57,%58,%59,%60,%61,%62,%63}, %64, %65, p, 1, 1, %67, %68;\n}\n"
   : "+f"(d[0]),"+f"(d[1]),"+f"(d[2]),"+f"(d[3]),"+f"(d[4]),"+f"(d[5]),"+f"(d[6]),"+f"(d[7]),"+f"(d[8]),"+f"(d[9]),"+f"(d[10]),"+f"(d[11]),"+f"(d[12]),"+f"(d[13]),"+f"(d[14]),"+f"(d[15]),"+f"(d[16]),"+f"(d[17]),"+f"(d[18]),"+f"(d[19]),"+f"(d[20]),"+f"(d[21]),"+f"(d[22]),"+f"(d[23]),"+f"(d[24]),"+f"(d[25]),"+f"(d[26]),"+f"(d[27]),"+f"(d[28]),"+f"(d[29]),"+f"(d[30]),"+f"(d[31]),"+f"(d[32]),"+f"(d[33]),"+f"(d[34]),"+f"(d[35]),"+f"(d[36]),"+f"(d[37]),"+f"(d[38]),"+f"(d[39]),"+f"(d[40]),"+f"(d[41]),"+f"(d[42]),"+f"(d[43]),"+f"(d[44]),"+f"(d[45]),"+f"(d[46]),"+f"(d[47]),"+f"(d[48]),"+f"(d[49]),"+f"(d[50]),"+f"(d[51]),"+f"(d[52]),"+f"(d[53]),"+f"(d[54]),"+f"(d[55]),"+f"(d[56]),"+f"(d[57]),"+f"(d[58]),"+f"(d[59]),"+f"(d[60]),"+f"(d[61]),"+f"(d[62]),"+f"(d[63])
   : "l"(da),"l"(db),"r"(sd),"n"(TA),"n"(TB));
}
template<int TA, int TB> __device__ __forceinline__ void wg_ss8(float* d, uint64_t da, uint64_t db, int sd) {
  asm volatile("{\n.reg .pred p;\nsetp.ne.b32 p, %6, 0;\n"
   "wgmma.mma_async.sync.aligned.m64n8k16.f32.bf16.bf16 {%0,%1,%2,%3}, %4, %5, p, 1, 1, %7, %8;\n}\n"
   : "+f"(d[0]),"+f"(d[1]),"+f"(d[2]),"+f"(d[3])
   : "l"(da),"l"(db),"r"(sd),"n"(TA),"n"(TB));
}


__device__ __forceinline__ uint32_t phi2(float a, float b) {
  uint32_t r, e;
  asm("cvt.rn.relu.bf16x2.f32 %0, %1, %2;" : "=r"(r) : "f"(b), "f"(a));
  e = pack_bf16(ex2f(a * 1.4426950408889634f), ex2f(b * 1.4426950408889634f));
  asm("add.rn.bf16x2 %0, %0, %1;" : "+r"(e) : "r"(0x35863586u));
  asm("min.NaN.bf16x2 %0, %0, %1;" : "+r"(e) : "r"(0x3F803F80u));
  asm("add.rn.bf16x2 %0, %0, %1;" : "+r"(e) : "r"(r));
  return e;
}

__device__ __forceinline__ void mbar_wait_long(uint32_t bar, uint32_t parity) {
  asm volatile("{\n.reg .pred p;\n.reg .u32 c;\nmov.u32 c, 0;\n"
               "LW_%=:\n"
               "mbarrier.try_wait.parity.shared::cta.b64 p, [%0], %1, 10000;\n"
               "@p bra LD_%=;\n"
               "add.u32 c, c, 1;\n"
               "setp.lt.u32 p, c, 400000;\n"
               "@p bra LW_%=;\n"
               "trap;\n"
               "LD_%=:\n}\n" :: "r"(bar), "r"(parity) : "memory");
}
__device__ __forceinline__ void mbar_arrive(uint32_t bar) { asm volatile("mbarrier.arrive.shared::cta.b64 _, [%0];" :: "r"(bar) : "memory"); }
__device__ __forceinline__ void named_arrive(int id, int n) { asm volatile("bar.arrive %0, %1;" :: "r"(id), "r"(n) : "memory"); }
__device__ __forceinline__ void fence_async_all() { asm volatile("fence.proxy.async.global;" ::: "memory"); }
__device__ __forceinline__ void flag_add(uint32_t* f) { asm volatile("fence.acq_rel.gpu;\nred.relaxed.gpu.global.add.u32 [%0], 1;" :: "l"(f) : "memory"); }
#define PUBLISH(f) asm volatile("fence.proxy.async.global;\nred.relaxed.gpu.global.add.u32 [%0], 1;" :: "l"(f) : "memory")
__device__ __forceinline__ void flag_wait(const uint32_t* f, uint32_t target) {
  uint32_t v;
#pragma unroll 1
  for (int it = 0;; it++) {
    asm volatile("ld.acquire.gpu.global.u32 %0, [%1];" : "=r"(v) : "l"(f) : "memory");
    if ((int32_t)(v - target) >= 0) break;
    if (it > 2000000) __trap();
    __nanosleep(64);
  }
}
__device__ __forceinline__ bool mbar_test(uint32_t bar, uint32_t parity) {
  uint32_t ok;
  asm volatile("{\n.reg .pred p;\nmbarrier.test_wait.parity.shared::cta.b64 p, [%1], %2;\nselp.b32 %0, 1, 0, p;\n}\n" : "=r"(ok) : "r"(bar), "r"(parity) : "memory");
  return ok;
}
__device__ __forceinline__ bool elect_one() {
  uint32_t p;
  asm volatile("{\n.reg .pred P;\nelect.sync _|P, 0xFFFFFFFF;\nselp.b32 %0, 1, 0, P;\n}\n" : "=r"(p));
  return p;
}
__device__ __forceinline__ void lds4(uint32_t a, uint32_t* r) {
  asm volatile("ld.shared.v4.b32 {%0,%1,%2,%3}, [%4];" : "=r"(r[0]), "=r"(r[1]), "=r"(r[2]), "=r"(r[3]) : "r"(a) : "memory");
}
__device__ __forceinline__ uint32_t lds1(uint32_t a) { uint32_t r; asm volatile("ld.shared.b32 %0, [%1];" : "=r"(r) : "r"(a) : "memory"); return r; }
__device__ __forceinline__ void sts1(uint32_t a, uint32_t v) { asm volatile("st.shared.b32 [%0], %1;" :: "r"(a), "r"(v) : "memory"); }
__device__ __forceinline__ void sts4(uint32_t a, uint32_t r0, uint32_t r1, uint32_t r2, uint32_t r3) {
  asm volatile("st.shared.v4.b32 [%0], {%1,%2,%3,%4};" :: "r"(a), "r"(r0), "r"(r1), "r"(r2), "r"(r3) : "memory");
}
__device__ __forceinline__ void ldsm4(uint32_t a, uint32_t* r) {
  asm volatile("ldmatrix.sync.aligned.m8n8.x4.shared.b16 {%0,%1,%2,%3}, [%4];" : "=r"(r[0]), "=r"(r[1]), "=r"(r[2]), "=r"(r[3]) : "r"(a) : "memory");
}
__device__ __forceinline__ float rcpf(float x) { float y; asm("rcp.approx.ftz.f32 %0, %1;" : "=f"(y) : "f"(x)); return y; }
__device__ __forceinline__ uint32_t hfma2(uint32_t a, uint32_t b, uint32_t c) { uint32_t r; asm("fma.rn.f16x2 %0, %1, %2, %3;" : "=r"(r) : "r"(a), "r"(b), "r"(c)); return r; }
__device__ __forceinline__ uint32_t hadd2(uint32_t a, uint32_t b) { uint32_t r; asm("add.rn.f16x2 %0, %1, %2;" : "=r"(r) : "r"(a), "r"(b)); return r; }

#define STEPK 96
#define GIMAP(i) ((((i) & 1) << 2) | (((i) >> 1) & 3) | ((i) & 8))
#define QSCALE 0.36067376022224085f
#define SMAGIC (512.0f + 2.0f * (191.0f - 30.0f - 1.5823545f))
#define VSHIFT 1073741824.0f

__device__ uint32_t g_epoch[132];
__device__ uint32_t g_flag[288 * 8];
#define FLAG_KV (g_flag)
#define FLAG_KV2 (g_flag + 8 * 8)
#define FLAG_B(h) (g_flag + (4 + (h)) * 8)
#define FLAG_OA(cta, pass) (g_flag + (16 + (cta) * 2 + (pass)) * 8)
#define FLAG_LM(i) (g_flag + (272 + (i)) * 8)

#define SM_TOTAL (224 * 1024 + 3072)
#define OFF_K 0
#define OFF_F 65536
#define OFF_V 131072
#define OFF_MISC (224 * 1024)

#define BAR_FULL(s) (bars + 8 * (s))
#define BAR_FW(s, w) (bars + 408 + 8 * ((s) * 4 + (w)))
#define BAR_EMPTY(s) (bars + 24 + 8 * (s))
#define BAR_KV(c) (bars + 48 + 8 * (c))
#define BAR_E0(i) (bars + 200 + 8 * (i))
#define BAR_BDONE (bars + 80)
#define BAR_Q (bars + 88)
#define BAR_GO (bars + 96)
#define BAR_Q2 (bars + 104)
#define BAR_OD(p) (bars + 112 + 8 * (p))
#define BAR_CL(c) (bars + 128 + 8 * (c))
#define BAR_TE(i) (bars + 168 + 8 * (i))
#define BAR_RL (bars + 184)
#define BAR_TF(g) (bars + 224 + 8 * (g))
#define BAR_XA(w) (bars + 352 + 8 * (w))
#define BAR_VB(c) (bars + 384 + 8 * (c))

__device__ __forceinline__ uint32_t exp2_pair_fix(float d0, float d1, uint32_t c63, uint32_t m1) {
  uint32_t w, y, s, r;
  asm("prmt.b32 %0, %1, %2, 0x6521;" : "=r"(w) : "r"(__float_as_uint(d0)), "r"(__float_as_uint(d1)));
  asm("lop3.b32 %0, %1, 0x007F007F, %2, 0xEA;" : "=r"(y) : "r"(w), "r"(c63));
  asm("mad.lo.u32 %0, %1, %2, %3;" : "=r"(s) : "r"(y), "r"(m1), "r"(w));
  asm("fma.rn.bf16x2 %0, %1, %2, %3;" : "=r"(r) : "r"(w), "r"(y), "r"(s));
  return r;
}

#define X_PR(i) asm volatile("prmt.b32 %0, %1, %2, 0x6521;" : "=r"(w[i]) : "r"(__float_as_uint(Sp[2 * (i)])), "r"(__float_as_uint(Sp[2 * (i) + 1])));
#define X_LO(i) asm volatile("lop3.b32 %0, %1, 0x007F007F, %2, 0xEA;" : "=r"(y[i]) : "r"(w[i]), "r"(c63));
#define X_IM(i) asm volatile("mad.lo.u32 %0, %1, %2, %3;" : "=r"(z[i]) : "r"(y[i]), "r"(m1), "r"(w[i]));
#define X_FM(i) asm volatile("fma.rn.bf16x2 %0, %1, %2, %3;" : "=r"(P[6 + (i)]) : "r"(w[i]), "r"(y[i]), "r"(z[i]));
#define X_MU(i) asm volatile("ex2.approx.ftz.f32 %0, %1;" : "=f"(e[i]) : "f"(Sm[i]));
#define X_PK(i) asm volatile("cvt.rn.bf16x2.f32 %0, %1, %2;" : "=r"(P[i]) : "f"(e[2 * (i) + 1]), "f"(e[2 * (i)]));

__device__ __forceinline__ void attn_slow(const __nv_bfloat16* xa, const __nv_bfloat16* wq, uint32_t dst) {
  const int t = threadIdx.x & 127;
  const int row = t >> 1, half = t & 1;
  float q[16];
  {
    float a[8];
#pragma unroll
    for (int i = 0; i < 8; i++) a[i] = 0.f;
#pragma unroll 1
    for (int k = 0; k < D_MOD; k++) {
      const float x = __bfloat162float(xa[(size_t)row * D_MOD + k]);
      const uint4 w = *(const uint4*)(wq + (size_t)k * D_MOD + half * 8);
      const uint32_t ww[4] = {w.x, w.y, w.z, w.w};
#pragma unroll
      for (int i = 0; i < 4; i++) { a[2 * i] = fmaf(x, bf_lo(ww[i]), a[2 * i]); a[2 * i + 1] = fmaf(x, bf_hi(ww[i]), a[2 * i + 1]); }
    }
#pragma unroll
    for (int i = 0; i < 8; i++) {
      const float mine = rbf(a[i]), other = __shfl_xor_sync(~0u, mine, 1);
      q[i] = half ? other : mine; q[8 + i] = half ? mine : other;
    }
  }
  float m = -INFINITY, l = 0.f, o[16];
#pragma unroll
  for (int i = 0; i < 16; i++) o[i] = 0.f;
#pragma unroll 1
  for (int j = half * 1024; j < half * 1024 + 1024; j++) {
    uint4 ka = g_KV[4 * S_TOK + j], kb = g_KV[5 * S_TOK + j];
    uint4 va = g_KV[6 * S_TOK + j], vb = g_KV[7 * S_TOK + j];
    uint32_t kk[8] = {ka.x, ka.y, ka.z, ka.w, kb.x, kb.y, kb.z, kb.w};
    uint32_t vv[8] = {va.x, va.y, va.z, va.w, vb.x, vb.y, vb.z, vb.w};
    float s = 0.f;
#pragma unroll
    for (int i = 0; i < 8; i++) { s = fmaf(q[2 * i], bf_lo(kk[i]), s); s = fmaf(q[2 * i + 1], bf_hi(kk[i]), s); }
    s = rbf(s) * 0.25f;
    if (s > m) {
      float c = __expf(m - s);
      l *= c;
#pragma unroll
      for (int i = 0; i < 16; i++) o[i] *= c;
      m = s;
    }
    float p = __expf(s - m);
    l += p;
#pragma unroll
    for (int i = 0; i < 8; i++) { o[2 * i] = fmaf(p, bf_lo(vv[i]), o[2 * i]); o[2 * i + 1] = fmaf(p, bf_hi(vv[i]), o[2 * i + 1]); }
  }
  float m2 = __shfl_xor_sync(~0u, m, 1);
  float mm = fmaxf(m, m2);
  float c = __expf(m - mm);
  l *= c; l += __shfl_xor_sync(~0u, l, 1);
  float inv = 1.f / l;
  uint32_t r[8];
#pragma unroll
  for (int i = 0; i < 16; i++) { o[i] *= c; o[i] += __shfl_xor_sync(~0u, o[i], 1); o[i] *= inv; }
#pragma unroll
  for (int i = 0; i < 8; i++) r[i] = pack_bf16(o[2 * i], o[2 * i + 1]);
  if (half == 0) sts4(dst, r[0], r[1], r[2], r[3]); else sts4(dst, r[4], r[5], r[6], r[7]);
  fence_async();
}

struct Params { const __nv_bfloat16* wk; const __nv_bfloat16* wv; const __nv_bfloat16* xa; const __nv_bfloat16* wq; __nv_bfloat16* out; };

__device__ __forceinline__ void helper_cta(const int h, const uint32_t sb, const uint32_t bars, const int wg, const int w4,
                                           const CUtensorMap* mQ, const CUtensorMap* mOs) {
  const int lane = threadIdx.x & 31;
  mbar_wait(BAR_GO, 0);
  const int cb = wg & 1, col = h * 128 + cb * 64, row0 = S_TOK + (wg >> 1) * 1024;
  const uint32_t buf = sb + wg * 49152;
  if (w4 == 0 && elect_one()) {
    fence_async_all();
#pragma unroll 1
    for (int u = 0; u < 3; u++) {
      mbar_expect_tx(BAR_TF(wg * 3 + u), 16384);
      tma2d(buf + u * 16384, mQ, col, row0 + u * 128, BAR_TF(wg * 3 + u));
    }
  }
  const int head = h * 8 + cb * 4 + w4;
  float4 a0 = make_float4(0, 0, 0, 0), a1 = a0, a2 = a0;
#pragma unroll 8
  for (int tt = 0; tt < 16; tt++) {
    const float4* src = g_kvp + ((tt * 32 + head) * 3) * 32 + lane;
    float4 u = src[0], v = src[32], w = src[64];
    a0.x += u.x; a0.y += u.y; a0.z += u.z; a0.w += u.w;
    a1.x += v.x; a1.y += v.y; a1.z += v.z; a1.w += v.w;
    a2.x += w.x; a2.y += w.y; a2.z += w.z; a2.w += w.w;
  }
  const uint32_t b00 = pack_bf16(a0.x, a0.y), b01 = pack_bf16(a0.z, a0.w);
  const uint32_t b10 = pack_bf16(a1.x, a1.y), b11 = pack_bf16(a1.z, a1.w);
  const uint32_t bz0 = pack_bf16(a2.x, a2.y), bz1 = pack_bf16(a2.z, a2.w);
  const int m = lane >> 3, r = lane & 7;
  const uint32_t off = ((m & 1) * 8 + r) * 128 + (((w4 * 2 + (m >> 1)) ^ r) << 4);
  int s = 0, ph = 0;
#pragma unroll 1
  for (int u = 0; u < 8; u++) {
    const uint32_t bb = buf + s * 16384;
    mbar_wait(BAR_TF(wg * 3 + s), ph);
#pragma unroll
    for (int mt = 0; mt < 8; mt++) {
      uint32_t a[4];
      ldsm4(bb + mt * 2048 + off, a);
      float n0[4] = {0, 0, 0, 0}, n1[4] = {0, 0, 0, 0}, dn[4] = {0, 0, 0, 0};
      mma_bf16(dn, a[0], a[1], a[2], a[3], bz0, bz1);
      mma_bf16(n0, a[0], a[1], a[2], a[3], b00, b01);
      mma_bf16(n1, a[0], a[1], a[2], a[3], b10, b11);
      const float i0 = rcpf(dn[0] + 1e-6f), i1 = rcpf(dn[2] + 1e-6f);
      stsm4(bb + mt * 2048 + off, pack_bf16(n0[0] * i0, n0[1] * i0), pack_bf16(n0[2] * i1, n0[3] * i1),
            pack_bf16(n1[0] * i0, n1[1] * i0), pack_bf16(n1[2] * i1, n1[3] * i1));
    }
    fence_async();
    named_bar(wg + 1, 128);
    if (w4 == 0 && lane == 0) {
      tma2d_store(mOs, bb, col, row0 + u * 128);
      bulk_commit();
      if (u >= 1 && u + 2 < 8) {
        asm volatile("cp.async.bulk.wait_group.read 1;" ::: "memory");
        const int sp = s == 0 ? 2 : s - 1;
        mbar_expect_tx(BAR_TF(wg * 3 + sp), 16384);
        tma2d(buf + sp * 16384, mQ, col, row0 + (u + 2) * 128, BAR_TF(wg * 3 + sp));
      }
    }
    __syncwarp();
    if (++s == 3) { s = 0; ph ^= 1; }
  }
  if (w4 == 0 && lane == 0) {
    bulk_wait_all();
    fence_async_all();
    flag_add(FLAG_LM((h * 2 + cb) * 2 + (wg >> 1)));
  }
}

#define STAGE(s) (sb + (2 - (s)) * 65536)
__device__ __forceinline__ uint32_t xa_addr(uint32_t sb, int kb) {
  return sb + (kb >= 1 && kb <= 4 ? OFF_V + 65536 + (kb - 1) * 8192 : 16384 + (kb == 5 ? OFF_K : (kb == 6 ? OFF_V : OFF_F)));
}
#define XA7_TMP (sb + OFF_K + 8192)
#define WKV_TMP (sb + OFF_K)
template <int TR> __device__ __forceinline__ void proj_kb(float* acc, uint32_t aA, uint32_t aB, int first) {
  const uint64_t da = make_desc(aA, TR ? 8192 : 16, 1024, 1);
  const uint64_t db = make_desc(aB, TR ? 16 : 8192, 1024, 1);
  wg_fence();
#pragma unroll
  for (int k = 0; k < 4; k++) wg_ss128<TR, 1 - TR>(acc, da + k * (TR ? 128 : 2), db + k * (TR ? 2 : 128), k != 0 || !first);
  wg_commit();
}
template <int TR> __device__ __forceinline__ void proj_loop(float* acc, uint32_t sb, uint32_t bars, uint32_t offA, uint32_t offB,
                                                            int wg, uint32_t sWKV, const CUtensorMap* mW, int col, bool w0, const CUtensorMap* mX, int xrow) {
  int s = 0, ph = 0;
#pragma unroll 1
  for (int kb = 0; kb < 8; kb++) {
    if (kb == TR)
  {
    float kv[4];
    mbar_wait(BAR_XA(wg), 0);
    const uint64_t da0 = make_desc(xa_addr(sb, 2 * wg), 16, 1024, 1);
    const uint64_t da1 = make_desc(wg == 3 ? XA7_TMP : xa_addr(sb, 2 * wg + 1), 16, 1024, 1);
    const uint64_t db = make_desc(sWKV + wg * 2048, 128, 128, 0);
    wg_fence();
#pragma unroll
    for (int k = 0; k < 8; k++) wg_ss8<0, 1>(kv, (k < 4 ? da0 : da1) + (k & 3) * 2, db + k * 16, k != 0);
    wg_commit();
    wg_wait<0>();
    fence_regs<4>(kv);
    named_bar(wg + 1, 128);
    sts4(sWKV + threadIdx.x * 16, __float_as_uint(kv[0]), __float_as_uint(kv[1]), __float_as_uint(kv[2]), __float_as_uint(kv[3]));
    __syncwarp();
    if ((threadIdx.x & 31) == 0) mbar_arrive(BAR_GO);
  }
    mbar_wait(BAR_FW(s, wg), ph);
    if (TR == 0) mbar_wait(BAR_XA(kb >> 1), 0); else mbar_wait(BAR_FULL(s), ph);
    proj_kb<TR>(acc, TR ? STAGE(s) + offA : xa_addr(sb, kb), STAGE(s) + offB, kb == 0);
    wg_wait<0>();
    if (w0 && elect_one()) {
      if (kb < 5) {
        mbar_expect_tx(BAR_FW(s, wg), TR ? 8192 : (kb == 4 ? 24576 : 16384));
        tma2d(STAGE(s) + (TR ? offA : 0), mW, col, (kb + 3) * 64, BAR_FW(s, wg));
        if (TR == 0) {
          tma2d(STAGE(s) + 8192, mW, col + 64, (kb + 3) * 64, BAR_FW(s, wg));
          if (kb == 4) tma2d(STAGE(s) + 16384, mX, 448, xrow, BAR_FW(s, wg));
        }
      }
      if (TR ? kb < 7 : (kb == 5 || kb == 6)) mbar_arrive(TR ? BAR_EMPTY(s) : BAR_E0(kb - 5));
      if (TR == 0 && kb == 4) mbar_arrive(BAR_VB(1));
    }
    __syncwarp();
    if (++s == 3) { s = 0; ph ^= 1; }
  }
  wg_wait<0>();
  fence_regs<64>(acc);
}

__device__ __forceinline__ uint32_t tail_slots(int isB, int n) {
  if (n < 4) return n < 2 ? (n == 0 ? 0x0D0C0B0Au : 0x04000F0Eu) : (n == 2 ? 0x18141008u : 0x15110501u);
  if (isB) return n < 6 ? (n == 4 ? 0x19120602u : 0x0D0C0B0Au) : (n == 6 ? 0x04000F0Eu : 0x13070316u);
  return n < 6 ? (n == 4 ? 0x1902031Au : 0x12061307u) : (n == 6 ? 0x16091B17u : 0x0D0C0B0Au);
}

__device__ __forceinline__ void take_role(uint32_t sM, int wg) {
  uint32_t r;
  asm volatile("atom.shared.add.u32 %0, [%1], 1;" : "=r"(r) : "r"(sM + 20) : "memory");
  sts1(sM + 32 + wg * 4, r);
}

__global__ void __launch_bounds__(640, 1)
k1_main(const __grid_constant__ CUtensorMap mXA64, const __grid_constant__ CUtensorMap mXB,
        const __grid_constant__ CUtensorMap mWq, const __grid_constant__ CUtensorMap mWqkv,
        const __grid_constant__ CUtensorMap mQst, const __grid_constant__ CUtensorMap mOst,
        const __grid_constant__ CUtensorMap mO, const __grid_constant__ CUtensorMap mWoA,
        const __grid_constant__ CUtensorMap mWoB,
        const __grid_constant__ CUtensorMap mO16, const __grid_constant__ CUtensorMap mKV, const Params prm) {
  if (threadIdx.x >= 608 && threadIdx.x < 612) {
    const CUtensorMap* pm = &mXA64 + (threadIdx.x - 608);
    asm volatile("prefetch.tensormap [%0];" :: "l"(pm) : "memory");
  }
  extern __shared__ __align__(1024) uint8_t smem_raw[];
  const uint32_t sb = smem_u32(smem_raw);
  if (sb & 1023u) __trap();
  const uint32_t bars = sb + OFF_MISC, sM = bars + 512, sT = bars + 640;
  const int tid = threadIdx.x, warp = __shfl_sync(~0u, tid >> 5, 0), wg = warp >> 2, w4 = warp & 3, lane = tid & 31;
  const bool helper = blockIdx.x >= 128;
  const int G = blockIdx.x >> 4, gi = GIMAP(blockIdx.x & 15);
  const int tbA = G * 4 + (gi >> 2), hg = gi & 3;
  const int ttB = (G >> 1) * 4 + (gi >> 2), hq = (G & 1) * 4 + (gi & 3);
  const int isB = tbA & 1, tok0 = (tbA >> 1) * 128;
  auto issue = [&](int kb, int part) {
    const uint32_t st = STAGE(kb);
    if (part & 1) {
      mbar_expect_tx(BAR_FW(kb, 0), 16384);
      tma2d(st, &mWq, hg * 128, kb * 64, BAR_FW(kb, 0));
      tma2d(st + 8192, &mWq, hg * 128 + 64, kb * 64, BAR_FW(kb, 0));
    }
    if (part & 2) {
      mbar_expect_tx(BAR_FULL(kb), 16384);
      tma2d(st + 49152, &mXB, kb * 64, ttB * 128, BAR_FULL(kb));
      mbar_expect_tx(BAR_FW(kb, 1), 8192);
      tma2d(st + 24576, &mWqkv, hq * 64, kb * 64, BAR_FW(kb, 1));
    }
    if (part & 4) {
      mbar_expect_tx(BAR_FW(kb, 2), 8192);
      tma2d(st + 32768, &mWqkv, 512 + hq * 64, kb * 64, BAR_FW(kb, 2));
      mbar_expect_tx(BAR_FW(kb, 3), 8192);
      tma2d(st + 40960, &mWqkv, 1024 + hq * 64, kb * 64, BAR_FW(kb, 3));
    }
  };
  const uint32_t sOne = sb + OFF_V + 65536, sWKV = WKV_TMP;
  if (warp >= 16) {
    if (warp == 17) {
      if (elect_one()) {
        mbar_init(BAR_BDONE, 8); mbar_init(BAR_Q, 6); mbar_init(BAR_GO, helper ? 1 : 16); mbar_init(BAR_Q2, 1);
        mbar_init(BAR_OD(0), 16); mbar_init(BAR_OD(1), 16); mbar_init(BAR_CL(0), 1); mbar_init(BAR_FULL(1), 1); mbar_init(BAR_FULL(2), 1);
        mbar_init(BAR_E0(0), 1); mbar_init(BAR_E0(1), 1);
#pragma unroll
        for (int i = 0; i < 4; i++) mbar_init(BAR_CL(i + 1), i == 0 ? 5 : 4);
#pragma unroll
        for (int i = 0; i < 3; i++) { mbar_init(BAR_EMPTY(i), 3); mbar_init(BAR_KV(i), 1); mbar_init(BAR_VB(i), i == 2 ? 4 : 1); }
        sts1(sM + 20, 0);
        asm volatile("fence.mbarrier_init.release.cluster;" ::: "memory");
      }
    } else if (warp == 18) {
      if (elect_one()) {
#pragma unroll
        for (int i = 0; i < 2; i++) mbar_init(BAR_TE(i), 2);
        mbar_init(BAR_RL, 1);
#pragma unroll
        for (int i = 4; i < 12; i++) mbar_init(BAR_FW(0, i), 1);
#pragma unroll
        for (int i = 0; i < 16; i++) mbar_init(BAR_TF(i), 1);
        asm volatile("fence.mbarrier_init.release.cluster;" ::: "memory");
      }
    } else if (warp == 16 && !helper && elect_one()) {
#pragma unroll
      for (int w = 0; w < 4; w++) { mbar_init(BAR_XA(w), 1); mbar_init(BAR_FW(0, w), 1); }
      mbar_init(BAR_FULL(0), 1);
      asm volatile("fence.mbarrier_init.release.cluster;" ::: "memory");
      issue(0, 6);
#pragma unroll
      for (int w = 0; w < 4; w++) {
        mbar_expect_tx(BAR_XA(w), 16384);
        tma2d(xa_addr(sb, 2 * w), &mXA64, w * 128, tbA * 64, BAR_XA(w));
        tma2d(w == 3 ? XA7_TMP : xa_addr(sb, 2 * w + 1), &mXA64, w * 128 + 64, tbA * 64, BAR_XA(w));
        if (w == 0) issue(0, 1);
      }
    }
  } else if (!helper) {
    const uint4 v = __ldg((const uint4*)(hg >= 2 ? prm.wv : prm.wk) + tid * 2 + (hg & 1));
    sts4(sWKV + tid * 16, v.x, v.y, v.z, v.w);
    fence_async();
  }
  __syncthreads();
  if (wg == 4) {
    if (w4 == 0 && !helper && elect_one()) { issue(1, 7); issue(2, 6); }
    asm volatile("setmaxnreg.dec.sync.aligned.u32 32;");
    const uint32_t ep = g_epoch[blockIdx.x] + 1;
    if (helper) {
      if (w4 == 0 && elect_one()) {
        flag_wait(FLAG_B(blockIdx.x - 128), ep * 32);
        fence_async_all();
        mbar_arrive(BAR_GO);
        g_epoch[blockIdx.x] = ep;
      }
      return;
    }
    if (w4 != 0) {
      mbar_wait(BAR_GO, 0);
#pragma unroll 1
      for (int qd = w4 & 3; qd >= 0; qd -= 3) {
        uint32_t a[4], b[4];
        float c[4];
        const uint32_t ad = sWKV + (qd * 32 + lane) * 16;
        lds4(ad, a);
        lds4(ad + 2048, b);
#pragma unroll
        for (int i = 0; i < 4; i++) c[i] = __uint_as_float(a[i]) + __uint_as_float(b[i]);
        lds4(ad + 4096, a);
        lds4(ad + 6144, b);
#pragma unroll
        for (int i = 0; i < 4; i++) c[i] += __uint_as_float(a[i]) + __uint_as_float(b[i]);
        sts1(sT + qd * 256 + lane * 4, pack_bf16(c[0], c[1]));
        sts1(sT + qd * 256 + 128 + lane * 4, pack_bf16(c[2], c[3]));
      }
      named_bar(9, 96);
      if (w4 == 3 && elect_one()) issue(2, 1);
    }
    auto write_ones = [&]() {
      mbar_wait_long(BAR_VB(1), 0);
      int c = ((w4 & 1) * 32 + lane);
#pragma unroll 4
      for (int key = c; key < S_TOK; key += 64) {
        sts4(sOne + key * 16, c < 24 ? 0x00003F80u : 0x00004E80u, 0u, 0u, 0u);
        c += 64; if (c >= STEPK) c -= STEPK;
      }
      fence_async();
      __syncwarp();
      if (lane == 0) mbar_arrive(BAR_Q);
    };
    if (w4 == 0) {
      int s = 0, ph = 0;
#pragma unroll 1
      for (int kb = 3; kb < 8; kb++) {
        mbar_wait(BAR_EMPTY(s), ph);
        if (elect_one()) {
          mbar_expect_tx(BAR_FULL(s), 16384);
          tma2d(STAGE(s) + 49152, &mXB, kb * 64, ttB * 128, BAR_FULL(s));
        }
        if (++s == 3) { s = 0; ph ^= 1; }
      }
      flag_wait(FLAG_KV, ep * 128);
      fence_async_all();
#pragma unroll 1
      for (int m = 0; m < 2; m++) {
        mbar_wait(m == 0 ? BAR_EMPTY(2) : BAR_EMPTY(0), 1 - m);
        mbar_wait(BAR_E0(m), 0);
        if (elect_one()) {
          const uint32_t fb = m == 0 ? BAR_KV(0) : BAR_VB(0);
          mbar_expect_tx(fb, 2 * 7 * STEPK * 16);
#pragma unroll
          for (int p = 0; p < 2; p++) bulk_g2s(sb + m * OFF_V + p * 32768, g_KV + (m * 2 + p) * S_TOK, 7 * STEPK * 16, fb);
        }
      }
      mbar_wait(BAR_Q, 0);
      if (elect_one()) {
#pragma unroll
        for (int c = 1; c < 3; c++) {
          const int k0 = c == 1 ? 7 * STEPK : 13 * STEPK, k1 = c == 1 ? 13 * STEPK : S_TOK;
          const uint32_t bytes = (k1 - k0) * 16;
          mbar_expect_tx(BAR_KV(c), 4 * bytes);
#pragma unroll
          for (int p = 0; p < 4; p++)
            bulk_g2s(sb + (p >> 1) * OFF_V + (p & 1) * 32768 + k0 * 16, g_KV + p * S_TOK + k0, bytes, BAR_KV(c));
        }
      }
      mbar_wait_long(BAR_CL(1), 0);
      flag_wait(isB ? FLAG_LM((lane & 7) * 2 + (tbA >> 4)) : FLAG_OA(tbA * 4 + (lane & 7), 0), ep);
      __syncwarp();
      fence_async_all();
      const CUtensorMap* mW = isB ? &mWoB : &mWoA;
#pragma unroll 1
      for (int it = 0; it < 8; it++) {
        const int n = (!isB && it >= 6) ? 13 - it : it;
        uint32_t wb = BAR_CL(n < 3 ? 0 : (n == 3 ? 2 : 3));
        if (isB) { if (n >= 5) wb = n == 7 ? BAR_CL(4) : BAR_TE(n - 5); }
        else if (n >= 6) wb = n == 6 ? BAR_CL(4) : BAR_TE(0);
        if (it < 6) mbar_wait_long(wb, 0); else mbar_wait(wb, 0);
        const uint32_t sl = tail_slots(isB, n), fb = BAR_TF(n);
        const bool withX = isB || n < 4;
        const int k0 = isB ? n * 64 : (n < 4 ? n * 128 : ((hg + n) & 3) * 128 + 64);
        if (elect_one()) {
          mbar_expect_tx(fb, withX ? 32768 : 16384);
          if (withX) {
            tma2d(sb + (sl & 255) * 8192, &mO, k0, isB * S_TOK + tok0, fb);
            tma2d(sb + ((sl >> 8) & 255) * 8192, &mO, k0, isB * S_TOK + tok0 + 64, fb);
          }
          tma2d(sb + ((sl >> 16) & 255) * 8192, mW, hg * 128, k0, fb);
          tma2d(sb + (sl >> 24) * 8192, mW, hg * 128 + 64, k0, fb);
        }
      }
      if (lane == 0) g_epoch[blockIdx.x] = ep;
    } else if (w4 == 3) {
      write_ones();
      flag_wait(FLAG_KV2, ep * 128);
      const uint4 a = *(const uint4*)(g_stats + lane * 4);
      const float kmax2 = __uint_as_float(__reduce_max_sync(~0u, a.x)) + __uint_as_float(__reduce_max_sync(~0u, a.y));
      const float vmax = __uint_as_float(__reduce_max_sync(~0u, max(a.z, a.w)));
      const float lv = vmax > 0.f ? __log2f(vmax) : 0.f;
      const float lim = fminf(90.f, fminf(91.f + lv, 95.f - lv));
      float thr = -1.f;
      if (vmax < 1e27f && kmax2 <= 65536.f && lim > 2.f) thr = fminf(60000.f, (lim * lim - 1.f) / (kmax2 * 1.02f + 1e-30f));
      mbar_wait_long(BAR_VB(2), 0);
      uint32_t nmax = 0;
#pragma unroll 2
      for (int i = 0; i < 16; i++) {
        uint32_t x[4], y[4];
        const uint32_t ad = sb + OFF_F + i * 1024 + (lane >> 3) * 256 + (lane & 7) * 16;
        lds4(ad, x); lds4(ad + 128, y);
        uint32_t n = hfma2(x[0], x[0], hfma2(x[1], x[1], hfma2(x[2], x[2], hfma2(x[3], x[3], 0u))));
        n = hfma2(y[0], y[0], hfma2(y[1], y[1], hfma2(y[2], y[2], hfma2(y[3], y[3], n))));
        n = hadd2(n, n >> 16);
        nmax = max(nmax, n & 0x7FFFu);
      }
      nmax = __reduce_max_sync(~0u, nmax);
      const bool ok = __half2float(__ushort_as_half((unsigned short)nmax)) <= thr;
      if (lane == 0) { sts1(sM + 16, ok ? 1u : 0u); mbar_arrive(BAR_Q2); }
    } else {
      const int tok = (w4 - 1) * 32 + lane;
      int step, col;
      if ((tbA & 3) == 0) {
        const int b8 = tbA >> 2;
        if (tok < 22) { step = tok; col = 24 + b8; }
        else { const int c = tok >= 43; step = tok - 22 - 21 * c; col = 32 + b8 * 2 + c; }
      } else {
        const int b24 = (tbA >> 2) * 3 + (tbA & 3) - 1;
        if (tok < 42) { const int c = tok >= 21; step = tok - 21 * c; col = 48 + b24 * 2 + c; }
        else { step = tok - 42; col = b24; }
      }
      const int kap = step * STEPK + col;
      const bool chained = col >= 24;
      uint32_t v[4], o[4];
      lds4(sT + tok * 16, v);
      float st = 0.f;
      if (hg < 2) {
        o[0] = o[1] = o[2] = o[3] = 0;
        if (chained && step > 0) lds4(sT + tok * 16 - 16, o);
        const float sc = chained ? 2.f : 1.f;
#pragma unroll
        for (int u = 0; u < 4; u++) {
          const float x = bf_lo(v[u]), y = bf_hi(v[u]);
          st += x * x + y * y;
          o[u] = pack_f16((x - bf_lo(o[u])) * sc, (y - bf_hi(o[u])) * sc);
        }
      } else {
        const float sc = chained ? VSHIFT : 1.f;
#pragma unroll
        for (int u = 0; u < 4; u++) { float x = bf_lo(v[u]), y = bf_hi(v[u]); st += fabsf(x) + fabsf(y); o[u] = pack_bf16(x * sc, y * sc); }
      }
      {
        const bool tl = (tbA & 3) == 0;
        const int run = tl ? (tok < 22 ? 0 : (tok < 43 ? 1 : 2)) : (tok < 21 ? 0 : (tok < 42 ? 1 : 2));
        const int h2 = (tl ? run == 0 : run == 2) ? 11 : 10;
        const uint32_t img = sT + run * 512;
        named_bar(10, 64);
        if (step < 11) sts4(img + step * 16, o[0], o[1], o[2], o[3]);
        if (step >= h2) sts4(img + 256 + (step - h2) * 16, o[0], o[1], o[2], o[3]);
        if (step == 0) sts1(sM + 48 + run * 4, col * 8 + (h2 << 16));
        fence_async();
        named_bar(10, 64);
        if (w4 == 1 && elect_one()) {
#pragma unroll
          for (int r = 0; r < 3; r++) {
            const uint32_t cw = lds1(sM + 48 + r * 4);
            tma3d_store(&mKV, sT + r * 512, cw & 0xFFFF, 0, hg);
            tma3d_store(&mKV, sT + r * 512 + 256, cw & 0xFFFF, cw >> 16, hg);
          }
          bulk_commit();
          bulk_wait_all();
          PUBLISH(FLAG_KV);
        }
        __syncwarp();
      }
      g_KV[(4 + hg) * S_TOK + kap] = make_uint4(v[0], v[1], v[2], v[3]);
      const uint32_t um = __reduce_max_sync(~0u, __float_as_uint(st) & 0x7FFFFFFFu);
      if (w4 == 2) {
        if (lane == 0) sts1(sM + 24, um);
        named_arrive(11, 64);
        write_ones();
        if (!isB) {
          mbar_wait_long(BAR_CL(3), 0);
          mbar_wait_long(BAR_RL, 0);
          uint32_t pend = 0xFE;
          const int li = lane & 7;
          const uint32_t* fl = FLAG_OA((tbA + (li & 1)) * 4 + ((hg + (li >> 1)) & 3), 1);
#pragma unroll 1
          for (int it = 0; pend; it++) {
            uint32_t fv;
            asm volatile("ld.acquire.gpu.global.u32 %0, [%1];" : "=r"(fv) : "l"(fl) : "memory");
            uint32_t go = __ballot_sync(~0u, (int32_t)(fv - ep) >= 0 && mbar_test(li >= 6 ? BAR_TE(0) : BAR_CL(4), 0)) & pend;
            pend &= ~go;
            if (go) fence_async_all();
#pragma unroll 1
            while (go) {
              const int b = __ffs(go) - 1;
              go &= go - 1;
              const uint32_t slot = (tail_slots(0, 4 + (b >> 1)) >> (8 * (b & 1))) & 255;
              if (elect_one()) {
                mbar_expect_tx(BAR_TF(8 + b), 8192);
                tma2d(sb + slot * 8192, &mO, ((hg + (b >> 1)) & 3) * 128 + 64, tok0 + (b & 1) * 64, BAR_TF(8 + b));
              }
            }
            if (it > 2000000) __trap();
          }
        }
      }
      else {
        named_bar(11, 64);
        if (elect_one()) {
          g_stats[tbA * 4 + hg] = max(um, lds1(sM + 24));
          flag_add(FLAG_KV2);
          mbar_wait_long(BAR_BDONE, 0);
          tma2d_store(&mQst, sb + OFF_F + 49152, hq * 64, S_TOK + ttB * 128);
          bulk_commit();
          bulk_wait_all();
          fence_async_all();
          flag_add(FLAG_B(hq >> 1));
          mbar_wait(BAR_Q, 0);
          mbar_arrive(BAR_CL(0));
#pragma unroll 1
          for (int p = 0; p < 2; p++) {
            mbar_wait_long(BAR_OD(p), 0);
            if (p == 0) {
#pragma unroll
              for (int w = 0; w < 4; w++) tma2d_store(&mO16, sb + OFF_F + w * 2048, hg * 128 + w * 16, tbA * 64);
            } else {
              tma2d_store(&mO, sb + 26 * 8192, hg * 128 + 64, tbA * 64);
            }
            bulk_commit();
            bulk_wait_all();
            if (p == 0) mbar_arrive(BAR_CL(1));
            PUBLISH(FLAG_OA(tbA * 4 + hg, p));
          }
        }
      }
    }
    return;
  }
  if (helper) { helper_cta(blockIdx.x - 128, sb, bars, wg, w4, &mQst, &mOst); return; }

  {
    float acc[64];
    if (wg == 0) proj_loop<0>(acc, sb, bars, 16384, 0, wg, sWKV, &mWq, hg * 128, w4 == 0, &mXA64, tbA * 64);
    else proj_loop<1>(acc, sb, bars, 16384 + wg * 8192, 49152, wg, sWKV, &mWqkv, (wg - 1) * 512 + hq * 64, w4 == 0, &mXA64, 0);
    const uint32_t sF = sb + OFF_F;
    const uint32_t qa = sF + w4 * 512 + ((lane >> 3) & 1) * 256 + (lane >> 4) * 128 + (lane & 7) * 16;
    if (wg == 0) {
#pragma unroll
      for (int hd = 0; hd < 4; hd++)
        stsm4(qa + hd * 2048, pack_f16(acc[8 * hd] * QSCALE, acc[8 * hd + 1] * QSCALE), pack_f16(acc[8 * hd + 2] * QSCALE, acc[8 * hd + 3] * QSCALE),
              pack_f16(acc[8 * hd + 4] * QSCALE, acc[8 * hd + 5] * QSCALE), pack_f16(acc[8 * hd + 6] * QSCALE, acc[8 * hd + 7] * QSCALE));
      fence_async();
      __syncwarp();
      if (lane == 0) mbar_arrive(BAR_Q);
    } else {
      if (wg != 3) named_arrive(6, 384);
      if (wg != 1) named_arrive(8, 384);
    }
    asm volatile("setmaxnreg.inc.sync.aligned.u32 112;");
    fence_regs<64>(acc);
    if (wg == 0) {
#pragma unroll
      for (int hd = 4; hd < 8; hd++)
        stsm4(qa + hd * 2048, pack_f16(acc[8 * hd] * QSCALE, acc[8 * hd + 1] * QSCALE), pack_f16(acc[8 * hd + 2] * QSCALE, acc[8 * hd + 3] * QSCALE),
              pack_f16(acc[8 * hd + 4] * QSCALE, acc[8 * hd + 5] * QSCALE), pack_f16(acc[8 * hd + 6] * QSCALE, acc[8 * hd + 7] * QSCALE));
      fence_async();
      __syncwarp();
      if (lane == 0) mbar_arrive(BAR_VB(2));
    } else if (wg == 3) {
      named_bar(6, 384);
      const int t = tid & 127;
#pragma unroll
      for (int j = 0; j < 8; j++)
        sts4(sF + 24576 + j * 2048 + t * 16, pack_bf16(acc[8 * j], acc[8 * j + 1]), pack_bf16(acc[8 * j + 2], acc[8 * j + 3]),
             pack_bf16(acc[8 * j + 4], acc[8 * j + 5]), pack_bf16(acc[8 * j + 6], acc[8 * j + 7]));
      named_arrive(7, 256);
    } else {
      uint32_t p[32];
#pragma unroll
      for (int i = 0; i < 32; i++) p[i] = phi2(acc[2 * i], acc[2 * i + 1]);
      if (wg == 1) {
        named_bar(8, 384);
        const int m = lane >> 3, r = lane & 7;
#pragma unroll
        for (int j = 0; j < 16; j += 2) {
          const int tok = (j + (m >> 1)) * 8 + r;
          const int chunk = w4 * 2 + (m & 1);
          stsm4t(sF + 49152 + tok * 128 + ((chunk ^ r) << 4), p[2 * j], p[2 * j + 1], p[2 * j + 2], p[2 * j + 3]);
        }
        fence_async();
      } else {
        named_bar(7, 256);
        float kv0[4] = {0, 0, 0, 0}, kv1[4] = {0, 0, 0, 0}, z0[4] = {0, 0, 0, 0}, z1[4] = {0, 0, 0, 0};
        const uint32_t one = 0x3F803F80u;
        const int t = tid & 127;
#pragma unroll
        for (int j = 0; j < 8; j++) {
          uint32_t a[4];
          lds4(sF + 24576 + j * 2048 + t * 16, a);
          mma_bf16(kv0, a[0], a[1], a[2], a[3], p[4 * j], p[4 * j + 2]);
          mma_bf16(kv1, a[0], a[1], a[2], a[3], p[4 * j + 1], p[4 * j + 3]);
          mma_bf16(z0, one, one, one, one, p[4 * j], p[4 * j + 2]);
          mma_bf16(z1, one, one, one, one, p[4 * j + 1], p[4 * j + 3]);
        }
        float4* dst = g_kvp + ((ttB * 32 + hq * 4 + w4) * 3) * 32 + lane;
        dst[0] = make_float4(kv0[0], kv0[1], kv1[0], kv1[1]);
        dst[32] = make_float4(kv0[2], kv0[3], kv1[2], kv1[3]);
        dst[64] = make_float4(z0[0], z0[1], z1[0], z1[1]);
      }
      __syncwarp();
      if (lane == 0) mbar_arrive(BAR_BDONE);
    }
  }

  bool safe = true;
  {
    const uint32_t c63 = 0x1F801F80u + (threadIdx.x >> 20);
    const uint32_t m1 = (gridDim.x >> 20) - 1u;
    const uint64_t dK0 = make_desc(sb + OFF_K, 32768, 128, 0);
    const uint64_t dV0 = make_desc(sb + OFF_V, 128, 32768, 0);
    constexpr uint32_t dKV = ((2048u - 8u) << 16) + STEPK - (OFF_V - OFF_K) / 16;
    float Sm[12], Sp[36], O[12];
    uint32_t P[24];
    uint64_t dQ = make_desc(sb + OFF_F + wg * 2048, 128, 256, 0);
#pragma unroll
    for (int i = 0; i < 36; i++) Sp[i] = SMAGIC;
#pragma unroll
    for (int i = 0; i < 12; i++) Sm[i] = 0.f;
    fence_regs<12>(Sm); fence_regs<36>(Sp);
    mbar_wait(BAR_Q, 0);
    mbar_wait(BAR_KV(0), 0);
    wg_fence();
    wg_qs72<1>(Sp, dQ, dK0 + 24);
    wg_qs24<0>(Sm, dQ, dK0);
    wg_commit();
    wg_wait<0>();
    fence_regs<12>(Sm); fence_regs<36>(Sp);
#pragma unroll 1
    for (int pass = 0; pass < 2; pass++) {
#pragma unroll
      for (int i = 0; i < 12; i++) O[i] = 0.f;
      fence_regs<12>(O);
      uint32_t vlo = (uint32_t)dV0;
#pragma unroll 1
      for (int seg = 0; seg < 4; seg++) {
        if (pass == 0) {
          if (seg < 3) mbar_wait(seg == 0 ? BAR_VB(0) : BAR_KV(seg), 0);
        } else if (seg >= 1) {
          if ((tid & 127) == 0) {
            mbar_arrive(BAR_CL(seg));
            if (seg == 3) take_role(sM, wg);
          }
          __syncwarp();
        }
        const uint32_t vend = vlo + (seg == 3 ? 3 : 6) * STEPK;
#pragma unroll 1
        for (; vlo != vend; vlo += 3 * STEPK) {
          uint64_t dK, dV;
          asm("mov.b64 %0, {%1, %2};" : "=l"(dK) : "r"(vlo + dKV), "r"(8u));
          asm("mov.b64 %0, {%1, %2};" : "=l"(dV) : "r"(vlo), "r"(2048u));
#pragma unroll
          for (int u = 0; u < 3; u++) {
          if (u == 0)
          { uint32_t w[18], y[18], z[18]; float e[12];
            X_MU(0) X_PR(3) X_LO(3) X_IM(3) X_MU(1) X_FM(3) X_PR(0) X_LO(0) X_IM(0) X_MU(2) X_FM(0) X_PR(16)
            X_LO(16) X_MU(3) X_IM(16) X_FM(16) X_PR(2) X_LO(2) X_PK(0) X_MU(4) X_IM(2) X_FM(2) X_PR(8) X_LO(8)
            X_MU(5) X_IM(8) X_FM(8) X_PR(6) X_PK(1) X_MU(6) X_LO(6) X_IM(6) X_FM(6) X_PR(1) X_MU(7) X_LO(1)
            X_IM(1) X_FM(1) X_MU(8) X_PR(4) X_PK(2) X_LO(4) X_IM(4) X_FM(4) X_MU(9) X_PR(9) X_LO(9) X_IM(9)
            X_FM(9) X_PK(3) X_MU(10) X_PR(10) X_LO(10) X_IM(10) X_MU(11) X_FM(10) X_PR(14) X_LO(14) X_IM(14) X_PK(4)
            X_FM(14) X_PR(11) X_LO(11) X_IM(11) X_FM(11) X_PR(15) X_LO(15) X_PK(5) X_IM(15) X_FM(15) X_PR(13) X_LO(13)
            X_IM(13) X_FM(13) X_PR(7) X_LO(7) X_IM(7) X_FM(7) X_PR(12) X_LO(12) X_IM(12) X_FM(12) X_PR(17) X_LO(17)
            X_IM(17) X_FM(17) X_PR(5) X_LO(5) X_IM(5) X_FM(5) }
          else if (u == 1)
          { uint32_t w[18], y[18], z[18]; float e[12];
            X_MU(4) X_PR(1) X_PR(3) X_LO(1) X_MU(5) X_PR(7) X_IM(1) X_LO(3) X_PR(10) X_MU(10) X_IM(3) X_LO(7)
            X_FM(1) X_MU(11) X_PR(2) X_IM(7) X_LO(10) X_FM(3) X_PK(2) X_MU(6) X_PR(17) X_IM(10) X_LO(2) X_FM(7)
            X_MU(7) X_PR(11) X_IM(2) X_LO(17) X_PK(5) X_MU(2) X_FM(10) X_PR(13) X_IM(17) X_LO(11) X_MU(3) X_FM(2)
            X_PR(9) X_IM(11) X_MU(8) X_LO(13) X_PK(3) X_FM(17) X_PR(8) X_IM(13) X_MU(9) X_LO(9) X_FM(11) X_PR(14)
            X_IM(9) X_PK(1) X_MU(0) X_LO(8) X_FM(13) X_PR(16) X_MU(1) X_IM(8) X_LO(14) X_FM(9) X_PR(15) X_PK(4)
            X_IM(14) X_LO(16) X_FM(8) X_PR(4) X_IM(16) X_LO(15) X_FM(14) X_PK(0) X_PR(6) X_IM(15) X_LO(4) X_FM(16)
            X_PR(12) X_IM(4) X_LO(6) X_FM(15) X_PR(5) X_IM(6) X_LO(12) X_FM(4) X_PR(0) X_IM(12) X_LO(5) X_FM(6)
            X_IM(5) X_LO(0) X_FM(12) X_IM(0) X_FM(5) X_FM(0) }
          else
          { uint32_t w[18], y[18], z[18]; float e[12];
            X_MU(4) X_PR(1) X_PR(3) X_LO(1) X_MU(5) X_PR(7) X_IM(1) X_LO(3) X_PR(10) X_MU(10) X_IM(3) X_LO(7)
            X_FM(1) X_MU(11) X_PR(2) X_IM(7) X_LO(10) X_FM(3) X_PK(2) X_MU(6) X_PR(17) X_IM(10) X_LO(2) X_FM(7)
            X_MU(7) X_PR(11) X_IM(2) X_LO(17) X_PK(5) X_MU(2) X_FM(10) X_PR(13) X_IM(17) X_LO(11) X_MU(3) X_FM(2)
            X_PR(9) X_IM(11) X_MU(8) X_LO(13) X_PK(3) X_FM(17) X_PR(8) X_IM(13) X_MU(9) X_LO(9) X_FM(11) X_PR(14)
            X_IM(9) X_PK(1) X_MU(0) X_LO(8) X_FM(13) X_PR(16) X_MU(1) X_IM(8) X_LO(14) X_FM(9) X_PR(15) X_PK(4)
            X_IM(14) X_LO(16) X_FM(8) X_PR(4) X_IM(16) X_LO(15) X_FM(14) X_PK(0) X_PR(6) X_IM(15) X_LO(4) X_FM(16)
            X_PR(12) X_IM(4) X_LO(6) X_FM(15) X_PR(5) X_IM(6) X_LO(12) X_FM(4) X_PR(0) X_IM(12) X_LO(5) X_FM(6)
            X_IM(5) X_LO(0) X_FM(12) X_IM(0) X_FM(5) X_FM(0) }
          fence_regs<24>(P);
          wg_fence();
          wg_pv24<1>(O, &P[20], dV + u * STEPK + 80);
          wg_pv24<1>(O, &P[16], dV + u * STEPK + 64);
          wg_pv24<1>(O, &P[12], dV + u * STEPK + 48);
          wg_pv24<1>(O, &P[8], dV + u * STEPK + 32);
          wg_pv24<1>(O, &P[4], dV + u * STEPK + 16);
          wg_pv24<1>(O, &P[0], dV + u * STEPK + 0);
          wg_qs72<1>(Sp, dQ, dK + u * STEPK + 24);
          wg_qs24<0>(Sm, dQ, dK + u * STEPK);
          wg_commit();
          wg_wait<0>();
          fence_regs<12>(Sm); fence_regs<36>(Sp); fence_regs<12>(O); fence_regs<24>(P);
          }
        }
      }
#pragma unroll
      for (int i = 0; i < 6; i++) P[i] = pack_bf16(ex2f(Sm[2 * i]), ex2f(Sm[2 * i + 1]));
      P[6] = exp2_pair_fix(Sp[0], Sp[1], c63, m1);
      P[7] = exp2_pair_fix(Sp[2], Sp[3], c63, m1);
      fence_regs<8>(P);
      const uint32_t sO = pass == 0 ? sb + OFF_F + wg * 2048 + w4 * 512 + (lane & 15) * 32 + (lane >> 4) * 16
                                    : sb + 26 * 8192 + (w4 * 16 + (lane & 15)) * 128 + (((wg * 2 + (lane >> 4)) ^ (lane & 7)) << 4);
      dQ += 512;
      wg_fence();
      wg_pv24<1>(O, &P[0], dV0 + 21 * STEPK);
      wg_pv24<1>(O, &P[4], dV0 + 21 * STEPK + 16);
      wg_commit();
#pragma unroll
      for (int i = 0; i < 36; i++) Sp[i] = SMAGIC;
      fence_regs<36>(Sp);
      mbar_wait(pass == 0 ? BAR_Q2 : BAR_CL(3), 0);
      wg_fence();
      wg_qs72<1>(Sp, dQ, dK0 + 24);
      wg_qs24<0>(Sm, dQ, dK0);
      wg_commit();
      wg_wait<1>();
      fence_regs<12>(O);
      const float l0 = __shfl_sync(~0u, O[8], lane & ~3), l1 = __shfl_sync(~0u, O[10], lane & ~3);
      const float i0 = rcpf(l0), i1 = rcpf(l1);
      stsm4(sO,
            pack_bf16(O[0] * i0, O[1] * i0), pack_bf16(O[2] * i1, O[3] * i1),
            pack_bf16(O[4] * i0, O[5] * i0), pack_bf16(O[6] * i1, O[7] * i1));
      fence_async();
      {
        safe = __all_sync(~0u, lds1(sM + 16) != 0);
      }
      if (safe && lane == 0) mbar_arrive(BAR_OD(pass));
      wg_wait<0>();
      fence_regs<12>(Sm); fence_regs<36>(Sp);
      if (!safe) break;
    }
  }
  if (!safe) {
    if ((tid & 127) == 0) { mbar_arrive(BAR_CL(1)); mbar_arrive(BAR_CL(2)); mbar_arrive(BAR_CL(3)); take_role(sM, wg); }
#pragma unroll 1
    for (int pass = 0; pass < 2; pass++) {
      const int t = tid & 127;
      mbar_wait(BAR_CL(3), 0);
      attn_slow(prm.xa + (size_t)tbA * 64 * D_MOD, prm.wq + (hg * 8 + pass * 4 + wg) * 16,
                pass == 0 ? sb + OFF_F + wg * 2048 + t * 16
                          : sb + 26 * 8192 + (t >> 1) * 128 + (((wg * 2 + (t & 1)) ^ ((t >> 1) & 7)) << 4));
      __syncwarp();
      if (lane == 0) mbar_arrive(BAR_OD(pass));
    }
  }

  {
    named_bar(wg + 1, 128);
    if ((tid & 127) == 0) mbar_arrive(BAR_CL(4));
    const int role = __shfl_sync(~0u, lds1(sM + 32 + wg * 4), 0);
    const int m = lane >> 3, r = lane & 7;
    const uint32_t stoff = (w4 * 16 + (m & 1) * 8 + r) * 128;
    if (role < 2) {
      if (role == 0 && (tid & 127) == 0) mbar_arrive(BAR_RL);
      if (!isB || role == 1) mbar_wait(BAR_CL(4), 0);
      float acc[64];
#pragma unroll 1
      for (int n = 0; n < 8; n++) {
        const uint32_t sl = tail_slots(isB, n);
        const uint32_t w0 = (sl >> 16) & 255, w1 = sl >> 24;
        const uint64_t da = make_desc(sb + ((sl >> (8 * role)) & 255) * 8192, 16, 1024, 1);
        const uint64_t db = make_desc(sb + w0 * 8192, (w1 - w0) * 8192, 1024, 1);
        mbar_wait(BAR_TF(n), 0);
        if (!isB && n >= 4) mbar_wait(n == 4 && role == 0 ? BAR_OD(1) : BAR_TF(2 * n + role), 0);
        wg_fence();
#pragma unroll
        for (int k = 0; k < 4; k++) wg_ss128<0, 1>(acc, da + k * 2, db + k * 128, (n | k) != 0);
        wg_commit();
        wg_wait<1>();
        if ((n == 1 || n == 2) && (tid & 127) == 0) mbar_arrive(BAR_TE(n - 1));
        __syncwarp();
      }
      wg_wait<0>();
      fence_regs<64>(acc);
      const uint32_t x0 = sb + (role ? 16 : 8) * 8192, x1 = sb + (role ? 5 : 1) * 8192;
#pragma unroll
      for (int j = 0; j < 16; j += 2)
        stsm4((j < 8 ? x0 : x1) + stoff + ((((j & 7) + (m >> 1)) ^ r) << 4),
              pack_bf16(acc[4 * j], acc[4 * j + 1]), pack_bf16(acc[4 * j + 2], acc[4 * j + 3]),
              pack_bf16(acc[4 * j + 4], acc[4 * j + 5]), pack_bf16(acc[4 * j + 6], acc[4 * j + 7]));
      __syncwarp();
      uint4* dst = (uint4*)(prm.out + (size_t)(tok0 + role * 64 + w4 * 16 + (lane >> 4)) * 1024 + isB * 512 + hg * 128) + (lane & 15);
      const uint32_t src = ((lane & 8) ? x1 : x0) + (w4 * 16 + (lane >> 4)) * 128;
#pragma unroll
      for (int i = 0; i < 8; i++) {
        uint32_t v[4];
        lds4(src + i * 256 + (((lane & 7) ^ ((2 * i + (lane >> 4)) & 7)) << 4), v);
        dst[i * 256] = make_uint4(v[0], v[1], v[2], v[3]);
      }
    }
  }
}

__device__ __nv_bfloat16 g_T[S_TOK * 1536];
__device__ float g_Z[32 * 272];
__global__ void fb_gemm(const __nv_bfloat16* A, const __nv_bfloat16* B, __nv_bfloat16* C, int N, int ldc) {
  __shared__ float sa[16][17], sbm[16][17];
  const int tx = threadIdx.x & 15, ty = threadIdx.x >> 4, row = blockIdx.y * 16 + ty, col = blockIdx.x * 16 + tx;
  float acc = 0.f;
  for (int k0 = 0; k0 < D_MOD; k0 += 16) {
    sa[ty][tx] = __bfloat162float(A[(size_t)row * D_MOD + k0 + tx]);
    sbm[ty][tx] = __bfloat162float(B[(size_t)(k0 + ty) * N + col]);
    __syncthreads();
    for (int k = 0; k < 16; k++) acc = fmaf(sa[ty][k], sbm[k][tx], acc);
    __syncthreads();
  }
  C[(size_t)row * ldc + col] = __float2bfloat16_rn(acc);
}
__global__ void fb_attn() {
  const int r = blockIdx.x * blockDim.x + threadIdx.x;
  float q[16], o[16], m = -INFINITY, l = 0.f;
  for (int i = 0; i < 16; i++) { q[i] = __bfloat162float(g_Q[(size_t)r * 16 + i]); o[i] = 0.f; }
  for (int j = 0; j < S_TOK; j++) {
    float s = 0.f;
    for (int i = 0; i < 16; i++) s = fmaf(q[i], __bfloat162float(g_T[j * 32 + i]), s);
    s = rbf(s) * 0.25f;
    const float mn = fmaxf(m, s), c = __expf(m - mn), p = __expf(s - mn);
    l = l * c + p; m = mn;
    for (int i = 0; i < 16; i++) o[i] = fmaf(p, __bfloat162float(g_T[j * 32 + 16 + i]), o[i] * c);
  }
  for (int i = 0; i < 16; i++) g_O[(size_t)r * 16 + i] = __float2bfloat16_rn(o[i] / l);
}
__device__ __forceinline__ float fb_phi(__nv_bfloat16 x) { const float t = __bfloat162float(x); return bf_lo(phi2(t, t)); }
__global__ void fb_kv() {
  const int h = blockIdx.x, t = threadIdx.x, d = t < 256 ? t >> 4 : t - 256, e = t & 15;
  float acc = 0.f;
  for (int s = 0; s < S_TOK; s++)
    acc = fmaf(fb_phi(g_T[(size_t)s * 1536 + 512 + h * 16 + d]), t < 256 ? __bfloat162float(g_T[(size_t)s * 1536 + 1024 + h * 16 + e]) : 1.f, acc);
  g_Z[h * 272 + t] = rbf(acc);
}
__global__ void fb_lin() {
  const int idx = blockIdx.x * blockDim.x + threadIdx.x, s = idx >> 9, c = idx & 511, h = c >> 4, e = c & 15;
  float num = 0.f, den = 0.f;
  for (int d = 0; d < 16; d++) {
    const float p = fb_phi(g_T[(size_t)s * 1536 + h * 16 + d]);
    num = fmaf(p, g_Z[h * 272 + d * 16 + e], num); den = fmaf(p, g_Z[h * 272 + 256 + d], den);
  }
  g_O[(size_t)S_TOK * D_MOD + idx] = __float2bfloat16_rn(num / (den + 1e-6f));
}

typedef CUresult (*EncodeFn)(CUtensorMap*, CUtensorMapDataType, cuuint32_t, void*, const cuuint64_t*, const cuuint64_t*,
                             const cuuint32_t*, const cuuint32_t*, CUtensorMapInterleave, CUtensorMapSwizzle,
                             CUtensorMapL2promotion, CUtensorMapFloatOOBfill);

static void make_map(EncodeFn enc, CUtensorMap* m, const void* ptr, uint64_t cols, uint64_t rows, uint32_t bc, uint32_t br,
                     CUtensorMapSwizzle sw = CU_TENSOR_MAP_SWIZZLE_128B) {
  cuuint64_t dims[2] = {cols, rows};
  cuuint64_t strides[1] = {cols * 2};
  cuuint32_t box[2] = {bc, br};
  cuuint32_t es[2] = {1, 1};
  enc(m, CU_TENSOR_MAP_DATA_TYPE_BFLOAT16, 2, (void*)ptr, dims, strides, box, es, CU_TENSOR_MAP_INTERLEAVE_NONE,
      sw, CU_TENSOR_MAP_L2_PROMOTION_L2_256B, CU_TENSOR_MAP_FLOAT_OOB_FILL_NONE);
}

extern "C" void kernel_launch(void* const* d_in, const int* in_sizes, int n_in, void* d_out, int out_size) {
  (void)in_sizes; (void)n_in; (void)out_size;
  static EncodeFn enc = nullptr;
  static void* pQ = nullptr; static void* pO = nullptr; static void* pT = nullptr; static void* pK = nullptr;
  static bool fused = false;
  if (!enc) {
    void* fn = nullptr; cudaDriverEntryPointQueryResult qr;
    cudaGetDriverEntryPoint("cuTensorMapEncodeTiled", &fn, cudaEnableDefault, &qr);
    enc = (EncodeFn)fn;
    cudaGetSymbolAddress(&pQ, g_Q);
    cudaGetSymbolAddress(&pO, g_O);
    cudaGetSymbolAddress(&pT, g_T);
    cudaGetSymbolAddress(&pK, g_KV);
    cudaFuncSetAttribute(k1_main, cudaFuncAttributeMaxDynamicSharedMemorySize, SM_TOTAL);
    int dev = 0, sms = 0, occ = 0;
    cudaGetDevice(&dev);
    cudaDeviceGetAttribute(&sms, cudaDevAttrMultiProcessorCount, dev);
    cudaOccupancyMaxActiveBlocksPerMultiprocessor(&occ, k1_main, 640, SM_TOTAL);
    fused = sms * occ >= 132;
  }
  if (!fused) {
    typedef const __nv_bfloat16* CB; typedef __nv_bfloat16* MB;
    cudaStream_t st = cudaStreamPerThread;
    fb_gemm<<<dim3(32, 128), 256, 0, st>>>((CB)d_in[0], (CB)d_in[1], (MB)pQ, 512, 512);
    fb_gemm<<<dim3(1, 128), 256, 0, st>>>((CB)d_in[0], (CB)d_in[2], (MB)pT, 16, 32);
    fb_gemm<<<dim3(1, 128), 256, 0, st>>>((CB)d_in[0], (CB)d_in[3], (MB)pT + 16, 16, 32);
    fb_attn<<<512, 128, 0, st>>>();
    fb_gemm<<<dim3(96, 128), 256, 0, st>>>((CB)d_in[5], (CB)d_in[6], (MB)pT, 1536, 1536);
    fb_kv<<<32, 272, 0, st>>>();
    fb_lin<<<4096, 256, 0, st>>>();
    fb_gemm<<<dim3(32, 128), 256, 0, st>>>((CB)pO, (CB)d_in[4], (MB)d_out, 512, 1024);
    fb_gemm<<<dim3(32, 128), 256, 0, st>>>((CB)pO + S_TOK * D_MOD, (CB)d_in[7], (MB)d_out + 512, 512, 1024);
    return;
  }
  CUtensorMap mXA64, mXB, mWq, mWqkv, mQst, mO, mOst, mWoA, mWoB, mO16, mKV;
  make_map(enc, &mXA64, d_in[0], 512, 2048, 64, 64);
  make_map(enc, &mWq, d_in[1], 512, 512, 64, 64);
  make_map(enc, &mWoA, d_in[4], 512, 512, 64, 64);
  make_map(enc, &mXB, d_in[5], 512, 2048, 64, 128);
  make_map(enc, &mWqkv, d_in[6], 1536, 512, 64, 64);
  make_map(enc, &mWoB, d_in[7], 512, 512, 64, 64);
  make_map(enc, &mQst, pQ, 512, 4096, 64, 128);
  make_map(enc, &mO, pO, 512, 4096, 64, 64);
  make_map(enc, &mOst, pO, 512, 4096, 64, 128);
  make_map(enc, &mO16, pO, 512, 4096, 16, 64, CU_TENSOR_MAP_SWIZZLE_NONE);
  {
    cuuint64_t dims[3] = {768, 22, 4};
    cuuint64_t strides[2] = {1536, 32768};
    cuuint32_t box[3] = {8, 11, 1};
    cuuint32_t es[3] = {1, 1, 1};
    enc(&mKV, CU_TENSOR_MAP_DATA_TYPE_BFLOAT16, 3, pK, dims, strides, box, es, CU_TENSOR_MAP_INTERLEAVE_NONE,
        CU_TENSOR_MAP_SWIZZLE_NONE, CU_TENSOR_MAP_L2_PROMOTION_NONE, CU_TENSOR_MAP_FLOAT_OOB_FILL_NONE);
  }
  Params prm{(const __nv_bfloat16*)d_in[2], (const __nv_bfloat16*)d_in[3], (const __nv_bfloat16*)d_in[0], (const __nv_bfloat16*)d_in[1], (__nv_bfloat16*)d_out};
  k1_main<<<132, 640, SM_TOTAL, cudaStreamPerThread>>>(mXA64, mXB, mWq, mWqkv, mQst, mOst, mO, mWoA, mWoB, mO16, mKV, prm);
}
```
